```python
import torch

def _softmax(x, axis=-1):
    return torch.softmax(x, dim=axis)

def _gelu(x):
    return torch.nn.functional.gelu(x, approximate='tanh')

def _silu(x):
    return torch.nn.functional.silu(x)

def _sigmoid(x):
    return torch.sigmoid(x)

def _layernorm(x, axis=-1, eps=1e-05):
    m = x.mean(dim=axis, keepdim=True)
    v = x.var(dim=axis, keepdim=True, unbiased=False)
    return (x - m) / torch.sqrt(v + eps)

def _scatter_add(tgt, idx, src, axis=0):
    return tgt.clone().index_add_(axis, idx, src)

def _segment_sum(src, seg, n):
    out = torch.zeros((n,) + src.shape[1:], dtype=src.dtype)
    return out.index_add_(0, seg, src)

def _pad(x, pw):
    flat = tuple((v for pair in reversed(pw) for v in pair))
    return torch.nn.functional.pad(x, flat)
kernel_name = 'concat_heads__memory_aug_recurrent_mem_tr__sliding_local_dilated__prompt'

def setup_inputs():

    _w = lambda a: (lambda t: t.to(torch.bfloat16) if t.is_floating_point() else t)(torch.as_tensor(a))

    def _A_setup():
        B, S, Dm = (1, 2048, 1024)
        H, Dh = (32, 128)
        M, seg = (8, 32)
        seg = min(seg, S)
        S = S // seg * seg
        return {'x': _w((lambda *s: torch.randn(*s, dtype=torch.bfloat16) * 0.05)(B, S, Dm)), 'mem0': _w((lambda *s: torch.randn(*s, dtype=torch.bfloat16) * 1.6)(B, M, Dm)), 'Wq': _w((lambda *s: torch.randn(*s, dtype=torch.bfloat16) * 0.8)(Dm, H, Dh) * Dm ** (-0.5)), 'Wk': _w((lambda *s: torch.randn(*s, dtype=torch.bfloat16) * 0.8)(Dm, H, Dh) * Dm ** (-0.5)), 'Wv': _w((lambda *s: torch.randn(*s, dtype=torch.bfloat16) * 1.6)(Dm, H, Dh) * Dm ** (-0.5)), 'Wo': _w((lambda *s: torch.randn(*s, dtype=torch.bfloat16) * 1.6)(H, Dh, Dm) * (H * Dh) ** (-0.5)), 'seg_len': seg}
    _A_in = _A_setup()

    def _B_setup():
        B, S, D = (1, 2048, 1024)
        return {'x': _w((lambda *s: torch.randn(*s, dtype=torch.bfloat16) * 0.2)(B, S, D)), 'wqkv': _w((lambda *s: torch.randn(*s, dtype=torch.bfloat16) * 0.2)(D, 3 * D)), 'wo': _w((lambda *s: torch.randn(*s, dtype=torch.bfloat16) * 0.05)(D, D))}
    _B_in = _B_setup()
    return {'A_x': _A_in['x'], 'A_mem0': _A_in['mem0'], 'A_Wq': _A_in['Wq'], 'A_Wk': _A_in['Wk'], 'A_Wv': _A_in['Wv'], 'A_Wo': _A_in['Wo'], 'A_seg_len': _A_in['seg_len'], 'B_x': _B_in['x'], 'B_wqkv': _B_in['wqkv'], 'B_wo': _B_in['wo']}

def reference(A_x, A_mem0, A_Wq, A_Wk, A_Wv, A_Wo, A_seg_len, B_x, B_wqkv, B_wo):

    def _A_ref(x, mem0, Wq, Wk, Wv, Wo, seg_len):
        B, S, Dm = x.shape
        H, Dh = (Wq.shape[1], Wq.shape[2])
        M = mem0.shape[1]
        scale = Dh ** (-0.5)
        n_seg = S // seg_len
        L = M + seg_len
        idx = torch.arange(L)
        mask = (idx[:, None] < M) | (idx[:, None] >= idx[None, :])
        mem = mem0
        outs = []
        for s in range(n_seg):
            xs = x[:, s * seg_len:(s + 1) * seg_len, :].clone()
            h = torch.concatenate([mem, xs], axis=1)
            q = torch.einsum('btd,dhe->bhte', h, Wq)
            k = torch.einsum('btd,dhe->bhte', h, Wk)
            v = torch.einsum('btd,dhe->bhte', h, Wv)
            scores = torch.einsum('bhqe,bhke->bhqk', q, k) * scale
            scores = torch.where(mask[None, None], scores, -1000000000.0)
            p = _softmax(scores, axis=-1)
            o = torch.einsum('bhqk,bhke->bhqe', p, v)
            o = torch.einsum('bhte,hed->btd', o, Wo)
            mem = o[:, :M, :].clone()
            outs.append(o[:, M:, :])
        return torch.concatenate(outs, axis=1)

    def _B_ref(x, wqkv, wo):
        B, S, D = x.shape
        H = 32
        Dh = D // H
        W, dil = (8, 2)
        qkv = (lambda x, *d: x.permute(*d))((x @ wqkv).reshape(B, S, 3, H, Dh), 2, 0, 3, 1, 4)
        q, k, v = (qkv[0], qkv[1], qkv[2])
        scale = Dh ** (-0.5)
        pos = torch.arange(S)
        off = torch.arange(W) * dil
        idx = pos[:, None] - off[None, :]
        mask = idx >= 0
        idx_c = torch.where(mask, idx, 0).reshape(-1)
        kg = k[:, :, idx_c, :].reshape(B, H, S, W, Dh)
        vg = v[:, :, idx_c, :].reshape(B, H, S, W, Dh)
        logits = torch.einsum('bhsd,bhswd->bhsw', q, kg) * scale
        logits = torch.where(mask[None, None, :, :], logits, -1000000000.0)
        attn = _softmax(logits, axis=-1)
        o = torch.einsum('bhsw,bhswd->bhsd', attn, vg)
        return (lambda x, *d: x.permute(*d))(o, 0, 2, 1, 3).reshape(B, S, D) @ wo
    a = _A_ref(A_x, A_mem0, A_Wq, A_Wk, A_Wv, A_Wo, A_seg_len)
    b = _B_ref(B_x, B_wqkv, B_wo)
    return torch.concatenate([a, b], axis=-1)
```

```cpp
#include <cuda_runtime.h>
#include <cuda_bf16.h>
#include <cuda.h>
#include <stdint.h>

namespace {

constexpr int S_TOK = 2048;
constexpr int DM = 1024;
constexpr int NH = 32;
constexpr int DH = 128;
constexpr int HD = NH * DH;
constexpr int NSEG = 64;
constexpr int SEG = 32;
constexpr int MROWS = 8;
constexpr uint32_t SENT = 0xFFFFFFFFu;
constexpr uint32_t SPIN_LIMIT = 1u << 24;

__device__ __align__(1024) __nv_bfloat16 g_qkv_tok[3ull * NSEG * NH * SEG * DH];
__device__ __align__(1024) __nv_bfloat16 g_kv_mem[2ull * NSEG * NH * MROWS * DH];
__device__ __align__(1024) __nv_bfloat16 g_o_tok[(size_t)S_TOK * HD];
__device__ __align__(1024) __nv_bfloat16 g_qkv_b[(size_t)S_TOK * 3 * DM];
__device__ __align__(1024) __nv_bfloat16 g_o_b[(size_t)S_TOK * DM];
constexpr int PUB_BYTES = 32768;
constexpr int XCHG_SLOT = 1 << 20;
constexpr int XCHG_PUB = 0, XCHG_INBOX = 2 * PUB_BYTES;
constexpr int INBOX_MAX = 80;
constexpr int XCHG_BYTES = 2 * XCHG_SLOT;
__device__ __align__(8192) uint8_t g_xchg[2 * XCHG_BYTES];
__device__ int g_ctacolor[96];
enum { F_QUEUE3 = 3, F_QUEUE4 = 4, F_SIDEQ = 8, F_TAILQ = 16, F_OUTBQ = 24, F_PROGRESS = 32, F_QKVB = 96, F_OB = 112, F_OA = 128, F_COUNT = 144 };
__device__ uint32_t g_flags[F_COUNT];
__device__ uint32_t g_arrivals;

#define STAMP(k) do {} while (0)
#define STAMPD(k, x) do {} while (0)
#define PSTAMP(k) do {} while (0)
#define KENTER(k) do {} while (0)
#define APROF(k) do {} while (0)
#define KEXIT(k) do {} while (0)

__device__ __forceinline__ uint32_t class_off(uint64_t a, uint32_t c) {
    return ((__popc((uint32_t)a & 0xB3000u) ^ c) & 1u) << 12;
}
__device__ __forceinline__ uint32_t smem_u32(const void* p) { return (uint32_t)__cvta_generic_to_shared(p); }
__device__ __forceinline__ uint32_t pack_bf16(float lo, float hi) {
    uint32_t r;
    asm("cvt.rn.bf16x2.f32 %0, %1, %2;" : "=r"(r) : "f"(hi), "f"(lo));
    return r;
}
__device__ __forceinline__ float ex2(float x) {
    float y;
    asm("ex2.approx.ftz.f32 %0, %1;" : "=f"(y) : "f"(x));
    return y;
}
__device__ __forceinline__ float rcp(float x) {
    float y;
    asm("rcp.approx.ftz.f32 %0, %1;" : "=f"(y) : "f"(x));
    return y;
}
__device__ __forceinline__ uint32_t clock32() {
    uint32_t t;
    asm volatile("mov.u32 %0, %%clock;" : "=r"(t));
    return t;
}
__device__ __forceinline__ void spin_clks(uint32_t n) {
    const uint32_t t0 = clock32();
    while (clock32() - t0 < n) {}
}
__device__ __forceinline__ void spin_until(uint32_t t) {
    while ((int)(clock32() - t) < 0) {}
}
__device__ __forceinline__ uint32_t clock_after(uint32_t x) {
    uint32_t t;
    asm volatile("{\n.reg .pred p;\nsetp.eq.u32 p, %1, 0x12345678;\n@p exit;\nmov.u32 %0, %%clock;\n}" : "=r"(t) : "r"(x) : "memory");
    return t;
}
__device__ __forceinline__ uint32_t opaque(uint32_t x) { return __shfl_sync(~0u, x, threadIdx.x & 31); }
__device__ __forceinline__ float bf16_lo(uint32_t w) { return __uint_as_float(w << 16); }
__device__ __forceinline__ float bf16_hi(uint32_t w) { return __uint_as_float(w & 0xFFFF0000u); }

__device__ __forceinline__ void mbar_init(uint32_t bar, uint32_t cnt) {
    asm volatile("mbarrier.init.shared::cta.b64 [%0], %1;" ::"r"(bar), "r"(cnt) : "memory");
}
__device__ __forceinline__ void mbar_arrive(uint32_t bar) {
    asm volatile("mbarrier.arrive.shared::cta.b64 _, [%0];" ::"r"(bar) : "memory");
}
__device__ __forceinline__ void mbar_arrive_expect_tx(uint32_t bar, uint32_t bytes) {
    asm volatile("mbarrier.arrive.expect_tx.shared::cta.b64 _, [%0], %1;" ::"r"(bar), "r"(bytes) : "memory");
}
__device__ __forceinline__ bool mbar_try_wait(uint32_t bar, uint32_t parity) {
    uint32_t ok;
    asm volatile(
        "{\n.reg .pred p;\n"
        "mbarrier.try_wait.parity.shared::cta.b64 p, [%1], %2;\n"
        "selp.u32 %0, 1, 0, p;\n}"
        : "=r"(ok) : "r"(bar), "r"(parity) : "memory");
    return ok != 0;
}
__device__ __forceinline__ void mbar_wait(uint32_t bar, uint32_t parity) {
    uint32_t n = 0;
    while (!mbar_try_wait(bar, parity)) {
        if (++n > SPIN_LIMIT) __trap();
    }
}
__device__ __forceinline__ void mbar_wait_bounded(uint32_t bar, uint32_t parity) {
    for (uint32_t n = 0; n < (1u << 20) && !mbar_try_wait(bar, parity); n++) {}
}
__device__ __forceinline__ bool elect_one() {
    uint32_t ok;
    asm volatile("{\n.reg .pred p;\nelect.sync _|p, 0xFFFFFFFF;\nselp.u32 %0, 1, 0, p;\n}" : "=r"(ok));
    return ok != 0;
}
__device__ __forceinline__ void named_bar_sync(int id, int nthreads) {
    asm volatile("bar.sync %0, %1;" ::"r"(id), "r"(nthreads) : "memory");
}
__device__ __forceinline__ void named_bar_arrive(int id, int nthreads) {
    asm volatile("bar.arrive %0, %1;" ::"r"(id), "r"(nthreads) : "memory");
}
__device__ __forceinline__ void cluster_sync() {
    asm volatile("barrier.cluster.arrive.release.aligned;\nbarrier.cluster.wait.acquire.aligned;" ::: "memory");
}
__device__ __forceinline__ uint32_t mapa(uint32_t addr, uint32_t rank) {
    uint32_t r;
    asm volatile("mapa.shared::cluster.u32 %0, %1, %2;" : "=r"(r) : "r"(addr), "r"(rank));
    return r;
}

__device__ __forceinline__ void tma_load_2d(uint32_t dst, const CUtensorMap* tm, int c0, int c1, uint32_t bar) {
    asm volatile(
        "cp.async.bulk.tensor.2d.shared::cluster.global.mbarrier::complete_tx::bytes [%0], [%1, {%3, %4}], [%2];"
        ::"r"(dst), "l"(tm), "r"(bar), "r"(c0), "r"(c1) : "memory");
}
__device__ __forceinline__ void tma_load_3d(uint32_t dst, const CUtensorMap* tm, int c0, int c1, int c2, uint32_t bar) {
    asm volatile(
        "cp.async.bulk.tensor.3d.shared::cluster.global.mbarrier::complete_tx::bytes [%0], [%1, {%3, %4, %5}], [%2];"
        ::"r"(dst), "l"(tm), "r"(bar), "r"(c0), "r"(c1), "r"(c2) : "memory");
}
__device__ __forceinline__ void tma_load_3d_mc(uint32_t dst, const CUtensorMap* tm, int c0, int c1, int c2, uint32_t bar, uint16_t mask) {
    asm volatile(
        "cp.async.bulk.tensor.3d.shared::cluster.global.mbarrier::complete_tx::bytes.multicast::cluster [%0], [%1, {%3, %4, %5}], [%2], %6;"
        ::"r"(dst), "l"(tm), "r"(bar), "r"(c0), "r"(c1), "r"(c2), "h"(mask) : "memory");
}
__device__ __forceinline__ void tma_store_2d(const CUtensorMap* tm, uint32_t src, int c0, int c1) {
    asm volatile("cp.async.bulk.tensor.2d.global.shared::cta.bulk_group [%0, {%2, %3}], [%1];"
                 ::"l"(tm), "r"(src), "r"(c0), "r"(c1) : "memory");
}
__device__ __forceinline__ void bulk_store(void* dst, uint32_t src, uint32_t bytes) {
    asm volatile("cp.async.bulk.global.shared::cta.bulk_group [%0], [%1], %2;" ::"l"(dst), "r"(src), "r"(bytes) : "memory");
}
__device__ __forceinline__ void bulk_commit() { asm volatile("cp.async.bulk.commit_group;" ::: "memory"); }
__device__ __forceinline__ void bulk_wait_read_all() { asm volatile("cp.async.bulk.wait_group.read 0;" ::: "memory"); }
__device__ __forceinline__ void bulk_wait_all() { asm volatile("cp.async.bulk.wait_group 0;" ::: "memory"); }
__device__ __forceinline__ void bulk_load(uint32_t dst, const void* src, uint32_t bytes, uint32_t bar) {
    asm volatile("cp.async.bulk.shared::cluster.global.mbarrier::complete_tx::bytes [%0], [%1], %2, [%3];"
                 ::"r"(dst), "l"(src), "r"(bytes), "r"(bar) : "memory");
}
__device__ __forceinline__ void bulk_load_mc(uint32_t dst, const void* src, uint32_t bytes, uint32_t bar, uint16_t mask) {
    asm volatile(
        "cp.async.bulk.shared::cluster.global.mbarrier::complete_tx::bytes.multicast::cluster [%0], [%1], %2, [%3], %4;"
        ::"r"(dst), "l"(src), "r"(bytes), "r"(bar), "h"(mask) : "memory");
}
__device__ __forceinline__ void cp_async16(uint32_t dst, const void* src) {
    asm volatile("cp.async.cg.shared.global [%0], [%1], 16;" ::"r"(dst), "l"(src) : "memory");
}
__device__ __forceinline__ void cp_async_commit() { asm volatile("cp.async.commit_group;" ::: "memory"); }
template <int N> __device__ __forceinline__ void cp_async_wait() {
    asm volatile("cp.async.wait_group %0;" ::"n"(N) : "memory");
}

__device__ __forceinline__ void ldsm_x4(uint32_t addr, uint32_t& r0, uint32_t& r1, uint32_t& r2, uint32_t& r3) {
    asm volatile("ldmatrix.sync.aligned.m8n8.x4.shared.b16 {%0,%1,%2,%3}, [%4];"
                 : "=r"(r0), "=r"(r1), "=r"(r2), "=r"(r3) : "r"(addr) : "memory");
}
__device__ __forceinline__ void ldsm_x4_t(uint32_t addr, uint32_t& r0, uint32_t& r1, uint32_t& r2, uint32_t& r3) {
    asm volatile("ldmatrix.sync.aligned.m8n8.x4.trans.shared.b16 {%0,%1,%2,%3}, [%4];"
                 : "=r"(r0), "=r"(r1), "=r"(r2), "=r"(r3) : "r"(addr) : "memory");
}
__device__ __forceinline__ void stsm_x4(uint32_t addr, uint32_t r0, uint32_t r1, uint32_t r2, uint32_t r3) {
    asm volatile("stmatrix.sync.aligned.m8n8.x4.shared.b16 [%0], {%1,%2,%3,%4};"
                 ::"r"(addr), "r"(r0), "r"(r1), "r"(r2), "r"(r3) : "memory");
}
__device__ __forceinline__ uint32_t movmat(uint32_t a) {
    uint32_t d;
    asm volatile("movmatrix.sync.aligned.m8n8.trans.b16 %0, %1;" : "=r"(d) : "r"(a));
    return d;
}
__device__ __forceinline__ void mma16816(float* d, uint32_t a0, uint32_t a1, uint32_t a2, uint32_t a3,
                                         uint32_t b0, uint32_t b1) {
    asm volatile(
        "mma.sync.aligned.m16n8k16.row.col.f32.bf16.bf16.f32 {%0,%1,%2,%3}, {%4,%5,%6,%7}, {%8,%9}, {%0,%1,%2,%3};"
        : "+f"(d[0]), "+f"(d[1]), "+f"(d[2]), "+f"(d[3])
        : "r"(a0), "r"(a1), "r"(a2), "r"(a3), "r"(b0), "r"(b1));
}
__device__ __forceinline__ void mma1688(float* d, uint32_t a0, uint32_t a1, uint32_t b0) {
    asm volatile("mma.sync.aligned.m16n8k8.row.col.f32.bf16.bf16.f32 {%0,%1,%2,%3}, {%4,%5}, {%6}, {%0,%1,%2,%3};"
                 : "+f"(d[0]), "+f"(d[1]), "+f"(d[2]), "+f"(d[3]) : "r"(a0), "r"(a1), "r"(b0));
}
__device__ __forceinline__ uint32_t any_reg() {
    uint32_t r;
    asm volatile("" : "=r"(r));
    return r;
}
__device__ __forceinline__ uint2 lds64(uint32_t addr) {
    uint2 v;
    asm volatile("ld.volatile.shared.v2.b32 {%0,%1}, [%2];" : "=r"(v.x), "=r"(v.y) : "r"(addr) : "memory");
    return v;
}
__device__ __forceinline__ uint4 lds128(uint32_t addr) {
    uint4 v;
    asm volatile("ld.volatile.shared.v4.b32 {%0,%1,%2,%3}, [%4];" : "=r"(v.x), "=r"(v.y), "=r"(v.z), "=r"(v.w) : "r"(addr) : "memory");
    return v;
}
__device__ __forceinline__ void sts32(uint32_t addr, uint32_t x) {
    asm volatile("st.volatile.shared.b32 [%0], %1;" ::"r"(addr), "r"(x) : "memory");
}
__device__ __forceinline__ void sts64(uint32_t addr, uint32_t x, uint32_t y) {
    asm volatile("st.volatile.shared.v2.b32 [%0], {%1,%2};" ::"r"(addr), "r"(x), "r"(y) : "memory");
}
__device__ __forceinline__ void sts128(uint32_t addr, uint32_t x, uint32_t y, uint32_t z, uint32_t w) {
    asm volatile("st.volatile.shared.v4.b32 [%0], {%1,%2,%3,%4};" ::"r"(addr), "r"(x), "r"(y), "r"(z), "r"(w) : "memory");
}
__device__ __forceinline__ void st_async_v2(uint32_t addr, uint32_t x, uint32_t y, uint32_t bar) {
    asm volatile("st.async.weak.shared::cluster.mbarrier::complete_tx::bytes.v2.b32 [%0], {%1,%2}, [%3];"
                 ::"r"(addr), "r"(x), "r"(y), "r"(bar) : "memory");
}
__device__ __forceinline__ uint2 ld_relaxed_v2(const void* p) {
    uint2 v;
    asm volatile("ld.relaxed.gpu.global.v2.b32 {%0,%1}, [%2];" : "=r"(v.x), "=r"(v.y) : "l"(p) : "memory");
    return v;
}
__device__ __forceinline__ void st_relaxed_v2(void* p, uint32_t x, uint32_t y) {
    asm volatile("st.relaxed.gpu.global.v2.b32 [%0], {%1,%2};" ::"l"(p), "r"(x), "r"(y) : "memory");
}
__device__ __forceinline__ void st_relaxed_v4(void* p, uint32_t x) {
    asm volatile("st.relaxed.gpu.global.v4.b32 [%0], {%1,%1,%1,%1};" ::"l"(p), "r"(x) : "memory");
}
__device__ __forceinline__ uint32_t ld_relaxed_b32(const void* p) {
    uint32_t v;
    asm volatile("ld.relaxed.gpu.global.b32 %0, [%1];" : "=r"(v) : "l"(p) : "memory");
    return v;
}
__device__ __forceinline__ uint32_t lds32_volatile(uint32_t addr) {
    uint32_t v;
    asm volatile("ld.volatile.shared.b32 %0, [%1];" : "=r"(v) : "r"(addr) : "memory");
    return v;
}
__device__ __forceinline__ void st_relaxed_b32(void* p, uint32_t x) {
    asm volatile("st.relaxed.gpu.global.b32 [%0], %1;" ::"l"(p), "r"(x) : "memory");
}

__device__ __forceinline__ uint32_t ld_acquire_b32(const void* p) {
    uint32_t v;
    asm volatile("ld.acquire.gpu.global.b32 %0, [%1];" : "=r"(v) : "l"(p) : "memory");
    return v;
}
__device__ __forceinline__ void wait_flag(const uint32_t* p, uint32_t target) {
    uint32_t n = 0;
    while (ld_acquire_b32(p) < target) {
        __nanosleep(64);
        if (++n > SPIN_LIMIT) __trap();
    }
}
__device__ __forceinline__ void signal_flag(uint32_t* p) {
    asm volatile("red.release.gpu.global.add.u32 [%0], 1;" ::"l"(p) : "memory");
}
__device__ __forceinline__ void pdl_launch_dependents() { asm volatile("griddepcontrol.launch_dependents;" ::: "memory"); }

constexpr int BM = 128, BK = 64;
constexpr int A_STAGE = BM * BK * 2;
template <int BN> struct GemmCfg {
    static constexpr int STAGES = BN == 256 ? 3 : 6;
    static constexpr int STAGE = A_STAGE + BK * BN * 2;
    static constexpr int EPI_WARP = 16 * BN * 2;
    static constexpr int SMEM = STAGES * STAGE + 8 * EPI_WARP + 1024 + 512;
};

struct SideProb {
    CUtensorMap tmA, tmB, tmB2, tmC;
    int n_split;
    int n_tiles, k_blocks, c_col0;
    const uint32_t* dep;
    uint32_t dep_target;
    uint32_t* sig;
    __nv_bfloat16* blocked;
};
struct SideSeg { int prob, m0, m1; };
constexpr int SIDE_MAX_SEG = 6;
struct SideParams {
    SideProb prob[5];
    SideSeg seg[SIDE_MAX_SEG];
    int nseg;
    uint32_t* queue;
};
static_assert(sizeof(SideParams) <= 4096, "kernel parameter limit");

__device__ __forceinline__ uint64_t make_desc(uint32_t addr, uint32_t lbo, uint32_t sbo) {
    return (uint64_t)((addr & 0x3FFFF) >> 4) | ((uint64_t)(lbo >> 4) << 16) | ((uint64_t)(sbo >> 4) << 32) | (1ull << 62);
}

__device__ __forceinline__ void wgmma_m64n256k16(float (&d)[128], uint64_t da, uint64_t db, int scale_d) {
    asm volatile(
        "{\n.reg .pred p;\nsetp.ne.b32 p, %130, 0;\n"
        "wgmma.mma_async.sync.aligned.m64n256k16.f32.bf16.bf16 "
        "{%0,%1,%2,%3,%4,%5,%6,%7,%8,%9,%10,%11,%12,%13,%14,%15,"
        "%16,%17,%18,%19,%20,%21,%22,%23,%24,%25,%26,%27,%28,%29,%30,%31,"
        "%32,%33,%34,%35,%36,%37,%38,%39,%40,%41,%42,%43,%44,%45,%46,%47,"
        "%48,%49,%50,%51,%52,%53,%54,%55,%56,%57,%58,%59,%60,%61,%62,%63,"
        "%64,%65,%66,%67,%68,%69,%70,%71,%72,%73,%74,%75,%76,%77,%78,%79,"
        "%80,%81,%82,%83,%84,%85,%86,%87,%88,%89,%90,%91,%92,%93,%94,%95,"
        "%96,%97,%98,%99,%100,%101,%102,%103,%104,%105,%106,%107,%108,%109,%110,%111,"
        "%112,%113,%114,%115,%116,%117,%118,%119,%120,%121,%122,%123,%124,%125,%126,%127},"
        " %128, %129, p, 1, 1, 0, 1;\n}\n"
        : "+f"(d[0]), "+f"(d[1]), "+f"(d[2]), "+f"(d[3]), "+f"(d[4]), "+f"(d[5]), "+f"(d[6]), "+f"(d[7]),
          "+f"(d[8]), "+f"(d[9]), "+f"(d[10]), "+f"(d[11]), "+f"(d[12]), "+f"(d[13]), "+f"(d[14]), "+f"(d[15]),
          "+f"(d[16]), "+f"(d[17]), "+f"(d[18]), "+f"(d[19]), "+f"(d[20]), "+f"(d[21]), "+f"(d[22]), "+f"(d[23]),
          "+f"(d[24]), "+f"(d[25]), "+f"(d[26]), "+f"(d[27]), "+f"(d[28]), "+f"(d[29]), "+f"(d[30]), "+f"(d[31]),
          "+f"(d[32]), "+f"(d[33]), "+f"(d[34]), "+f"(d[35]), "+f"(d[36]), "+f"(d[37]), "+f"(d[38]), "+f"(d[39]),
          "+f"(d[40]), "+f"(d[41]), "+f"(d[42]), "+f"(d[43]), "+f"(d[44]), "+f"(d[45]), "+f"(d[46]), "+f"(d[47]),
          "+f"(d[48]), "+f"(d[49]), "+f"(d[50]), "+f"(d[51]), "+f"(d[52]), "+f"(d[53]), "+f"(d[54]), "+f"(d[55]),
          "+f"(d[56]), "+f"(d[57]), "+f"(d[58]), "+f"(d[59]), "+f"(d[60]), "+f"(d[61]), "+f"(d[62]), "+f"(d[63]),
          "+f"(d[64]), "+f"(d[65]), "+f"(d[66]), "+f"(d[67]), "+f"(d[68]), "+f"(d[69]), "+f"(d[70]), "+f"(d[71]),
          "+f"(d[72]), "+f"(d[73]), "+f"(d[74]), "+f"(d[75]), "+f"(d[76]), "+f"(d[77]), "+f"(d[78]), "+f"(d[79]),
          "+f"(d[80]), "+f"(d[81]), "+f"(d[82]), "+f"(d[83]), "+f"(d[84]), "+f"(d[85]), "+f"(d[86]), "+f"(d[87]),
          "+f"(d[88]), "+f"(d[89]), "+f"(d[90]), "+f"(d[91]), "+f"(d[92]), "+f"(d[93]), "+f"(d[94]), "+f"(d[95]),
          "+f"(d[96]), "+f"(d[97]), "+f"(d[98]), "+f"(d[99]), "+f"(d[100]), "+f"(d[101]), "+f"(d[102]), "+f"(d[103]),
          "+f"(d[104]), "+f"(d[105]), "+f"(d[106]), "+f"(d[107]), "+f"(d[108]), "+f"(d[109]), "+f"(d[110]), "+f"(d[111]),
          "+f"(d[112]), "+f"(d[113]), "+f"(d[114]), "+f"(d[115]), "+f"(d[116]), "+f"(d[117]), "+f"(d[118]), "+f"(d[119]),
          "+f"(d[120]), "+f"(d[121]), "+f"(d[122]), "+f"(d[123]), "+f"(d[124]), "+f"(d[125]), "+f"(d[126]), "+f"(d[127])
        : "l"(da), "l"(db), "r"(scale_d));
}

__device__ __forceinline__ void wgmma_m64n128k16(float (&d)[64], uint64_t da, uint64_t db, int scale_d) {
    asm volatile(
        "{\n.reg .pred p;\nsetp.ne.b32 p, %66, 0;\n"
        "wgmma.mma_async.sync.aligned.m64n128k16.f32.bf16.bf16 "
        "{%0,%1,%2,%3,%4,%5,%6,%7,%8,%9,%10,%11,%12,%13,%14,%15,"
        "%16,%17,%18,%19,%20,%21,%22,%23,%24,%25,%26,%27,%28,%29,%30,%31,"
        "%32,%33,%34,%35,%36,%37,%38,%39,%40,%41,%42,%43,%44,%45,%46,%47,"
        "%48,%49,%50,%51,%52,%53,%54,%55,%56,%57,%58,%59,%60,%61,%62,%63},"
        " %64, %65, p, 1, 1, 0, 1;\n}\n"
        : "+f"(d[0]), "+f"(d[1]), "+f"(d[2]), "+f"(d[3]), "+f"(d[4]), "+f"(d[5]), "+f"(d[6]), "+f"(d[7]),
          "+f"(d[8]), "+f"(d[9]), "+f"(d[10]), "+f"(d[11]), "+f"(d[12]), "+f"(d[13]), "+f"(d[14]), "+f"(d[15]),
          "+f"(d[16]), "+f"(d[17]), "+f"(d[18]), "+f"(d[19]), "+f"(d[20]), "+f"(d[21]), "+f"(d[22]), "+f"(d[23]),
          "+f"(d[24]), "+f"(d[25]), "+f"(d[26]), "+f"(d[27]), "+f"(d[28]), "+f"(d[29]), "+f"(d[30]), "+f"(d[31]),
          "+f"(d[32]), "+f"(d[33]), "+f"(d[34]), "+f"(d[35]), "+f"(d[36]), "+f"(d[37]), "+f"(d[38]), "+f"(d[39]),
          "+f"(d[40]), "+f"(d[41]), "+f"(d[42]), "+f"(d[43]), "+f"(d[44]), "+f"(d[45]), "+f"(d[46]), "+f"(d[47]),
          "+f"(d[48]), "+f"(d[49]), "+f"(d[50]), "+f"(d[51]), "+f"(d[52]), "+f"(d[53]), "+f"(d[54]), "+f"(d[55]),
          "+f"(d[56]), "+f"(d[57]), "+f"(d[58]), "+f"(d[59]), "+f"(d[60]), "+f"(d[61]), "+f"(d[62]), "+f"(d[63])
        : "l"(da), "l"(db), "r"(scale_d));
}
template <int BN> struct WgmmaOp;
template <> struct WgmmaOp<256> {
    static __device__ __forceinline__ void run(float (&d)[128], uint64_t a, uint64_t b, int sc) { wgmma_m64n256k16(d, a, b, sc); }
};
template <> struct WgmmaOp<128> {
    static __device__ __forceinline__ void run(float (&d)[64], uint64_t a, uint64_t b, int sc) { wgmma_m64n128k16(d, a, b, sc); }
};

struct StoreRec {
    uint64_t dst;
    uint64_t flag;
    int kind;
    int pad;
};
struct EpiCtx { uint32_t buf, rec, st_full, st_empty; uint32_t it; int lane; };
template <int N>
__device__ __forceinline__ void epi_hand_over(const float (&acc)[N], EpiCtx& e, uint64_t dst, uint64_t flag, int kind) {
    mbar_wait(e.st_empty, (e.it & 1) ^ 1);
    const int mi = e.lane >> 3, row = (mi & 1) * 8 + (e.lane & 7);
    #pragma unroll
    for (int j = 0; j < N / 4; j += 2) {
        const int chunk = (j & 7) + (mi >> 1);
        stsm_x4(e.buf + (j >> 3) * 2048 + row * 128 + ((chunk ^ (row & 7)) << 4),
                pack_bf16(acc[4 * j], acc[4 * j + 1]), pack_bf16(acc[4 * j + 2], acc[4 * j + 3]),
                pack_bf16(acc[4 * j + 4], acc[4 * j + 5]), pack_bf16(acc[4 * j + 6], acc[4 * j + 7]));
    }
    if (e.lane == 0) {
        asm volatile("st.shared.v2.b64 [%0], {%1, %2};" ::"r"(e.rec), "l"(dst), "l"(flag) : "memory");
        asm volatile("st.shared.b32 [%0], %1;" ::"r"(e.rec + 16), "r"(kind) : "memory");
    }
    asm volatile("fence.proxy.async.shared::cta;" ::: "memory");
    __syncwarp();
    if (e.lane == 0) mbar_arrive(e.st_full);
    e.it++;
}
__device__ __forceinline__ void epi_exit(EpiCtx& e) {
    mbar_wait(e.st_empty, (e.it & 1) ^ 1);
    if (e.lane == 0) {
        asm volatile("st.shared.b32 [%0], %1;" ::"r"(e.rec + 16), "r"(-1) : "memory");
        mbar_arrive(e.st_full);
    }
}
template <int BN, bool PAIR = false>
__device__ __forceinline__ void gemm_mainloop(float (&acc)[BN / 2], int k_blocks, uint32_t sbase, uint32_t bar_base, int cw,
                                              bool elected, int& stage, uint32_t& phase, uint32_t peer = 0) {
    using C = GemmCfg<BN>;
    auto release = [&](int st) {
        const uint32_t bar = bar_base + 8 * (C::STAGES + st);
        mbar_arrive(bar);
        if (PAIR) asm volatile("mbarrier.arrive.shared::cluster.b64 _, [%0];" ::"r"(mapa(bar, peer)) : "memory");
    };
    int prev_stage = -1;
    for (int kb = 0; kb < k_blocks; kb++) {
        mbar_wait(bar_base + 8 * stage, phase);
        const uint32_t sa = sbase + stage * C::STAGE + cw * (64 * 128);
        const uint32_t sb = sbase + stage * C::STAGE + A_STAGE;
        asm volatile("wgmma.fence.sync.aligned;" ::: "memory");
        #pragma unroll
        for (int kk = 0; kk < BK / 16; kk++)
            WgmmaOp<BN>::run(acc, make_desc(sa + kk * 32, 16, 1024), make_desc(sb + kk * 2048, 8192, 1024), (kb | kk) != 0);
        asm volatile("wgmma.commit_group.sync.aligned;" ::: "memory");
        asm volatile("wgmma.wait_group.sync.aligned 1;" ::: "memory");
        if (prev_stage >= 0 && elected) release(prev_stage);
        prev_stage = stage;
        if (++stage == C::STAGES) { stage = 0; phase ^= 1; }
    }
    asm volatile("wgmma.wait_group.sync.aligned 0;" ::: "memory");
    if (elected) release(prev_stage);
}
template <int BN>
__device__ __forceinline__ void store_warp(uint32_t epi_base, uint32_t rec_base, uint32_t st_full, uint32_t st_empty, int lane,
                                           const uint8_t* tmaps, int tstride) {
    for (uint32_t it = 0;; it++) {
        mbar_wait(st_full, it & 1);
        uint64_t dst = 0, flag = 0;
        int kind = -1;
        if (lane < 8) {
            const uint32_t rec = rec_base + lane * 32;
            asm volatile("ld.volatile.shared.v2.b64 {%0, %1}, [%2];" : "=l"(dst), "=l"(flag) : "r"(rec) : "memory");
            kind = (int)lds32_volatile(rec + 16);
        }
        if (__shfl_sync(~0u, kind, 0) < 0) break;
        if (lane < 8) {
            const uint32_t buf = epi_base + lane * GemmCfg<BN>::EPI_WARP;
            #pragma unroll
            for (int q = 0; q < BN / 64; q++) {
                if (kind == 0) bulk_store(reinterpret_cast<__nv_bfloat16*>(dst) + q * (SEG * 64), buf + q * 2048, 2048);
                else tma_store_2d(reinterpret_cast<const CUtensorMap*>(tmaps + (kind - 1) * tstride), buf + q * 2048,
                                  (int)(uint32_t)dst + q * 64, (int)(dst >> 32));
            }
            bulk_commit();
            bulk_wait_read_all();
            mbar_arrive(st_empty);
            if (flag) {
                bulk_wait_all();
                asm volatile("fence.proxy.async;" ::: "memory");
                signal_flag(reinterpret_cast<uint32_t*>(flag));
            }
        }
        __syncwarp();
    }
    if (lane < 8) bulk_wait_all();
}

template <int BN>
__global__ void __launch_bounds__(384, 1) side_gemm_kernel(const __grid_constant__ SideParams p) {
    using C = GemmCfg<BN>;
    extern __shared__ uint8_t smem_raw[];
    const uint32_t sbase = (smem_u32(smem_raw) + 1023) & ~1023u;
    const uint32_t epi_base = sbase + C::STAGES * C::STAGE;
    const uint32_t bar_base = epi_base + 8 * C::EPI_WARP;
    const uint32_t tfull = bar_base + 16 * C::STAGES, tempty = tfull + 16, tslot = tempty + 16;
    const uint32_t st_full = bar_base + 192, st_empty = st_full + 8, rec_base = bar_base + 256;
    const int tid = threadIdx.x, wg = tid >> 7;
    if (tid == 0) {
        for (int s = 0; s < C::STAGES; s++) { mbar_init(bar_base + 8 * s, 1); mbar_init(bar_base + 8 * (C::STAGES + s), 2); }
        for (int s = 0; s < 2; s++) { mbar_init(tfull + 8 * s, 1); mbar_init(tempty + 8 * s, 2); }
        mbar_init(st_full, 8);
        mbar_init(st_empty, 8);
        asm volatile("fence.mbarrier_init.release.cluster;" ::: "memory");
        pdl_launch_dependents();
    }
    __syncthreads();
    KENTER(BN == 256 ? (p.nseg == 1 ? 6 : 2) : 4);

    if (wg == 0) {
        asm volatile("setmaxnreg.dec.sync.aligned.u32 40;");
        if (tid == 0) {
            int stage = 0; uint32_t phase = 1;
            for (uint32_t it = 0;; it++) {
                int pr = -1, mt = 0, nt = 0;
                for (uint32_t tries = 0;; tries++) {
                    uint32_t head[SIDE_MAX_SEG], ready[SIDE_MAX_SEG];
                    #pragma unroll
                    for (int g = 0; g < SIDE_MAX_SEG; g++) head[g] = g < p.nseg ? ld_relaxed_b32(p.queue + g) : 0xFFFFFFFFu;
                    bool left = false;
                    #pragma unroll
                    for (int g = 0; g < SIDE_MAX_SEG; g++) {
                        ready[g] = 0;
                        if (g < p.nseg) {
                            const SideProb& q = p.prob[p.seg[g].prob];
                            if (head[g] < (uint32_t)((p.seg[g].m1 - p.seg[g].m0) * q.n_tiles)) {
                                left = true;
                                ready[g] = q.dep ? ld_relaxed_b32(q.dep + p.seg[g].m0 + head[g] / q.n_tiles) >= q.dep_target : 1u;
                            }
                        }
                    }
                    if (!left) break;
                    #pragma unroll
                    for (int g = 0; g < SIDE_MAX_SEG; g++) {
                        if (pr < 0 && ready[g]) {
                            const int nts = p.prob[p.seg[g].prob].n_tiles;
                            const uint32_t idx = atomicAdd(p.queue + g, 1u);
                            if (idx < (uint32_t)((p.seg[g].m1 - p.seg[g].m0) * nts)) {
                                pr = p.seg[g].prob; mt = p.seg[g].m0 + idx / nts; nt = idx % nts;
                            }
                        }
                    }
                    if (pr >= 0) break;
                    __nanosleep(200);
                    if (tries > SPIN_LIMIT) __trap();
                }
                mbar_wait(tempty + 8 * (it & 1), ((it >> 1) & 1) ^ 1);
                asm volatile("st.shared.b32 [%0], %1;" ::"r"(tslot + 4 * (it & 1)), "r"(pr < 0 ? -1 : (pr << 16) | (mt << 8) | nt) : "memory");
                mbar_arrive(tfull + 8 * (it & 1));
                if (pr < 0) break;
                const SideProb& q = p.prob[pr];
                if (q.dep) {
                    wait_flag(q.dep + mt, q.dep_target);
                    asm volatile("fence.proxy.async;" ::: "memory");
                }
                for (int kb = 0; kb < q.k_blocks; kb++) {
                    mbar_wait(bar_base + 8 * (C::STAGES + stage), phase);
                    const uint32_t sa = sbase + stage * C::STAGE, fb = bar_base + 8 * stage;
                    mbar_arrive_expect_tx(fb, C::STAGE);
                    tma_load_2d(sa, &q.tmA, kb * BK, mt * BM, fb);
                    tma_load_3d(sa + A_STAGE, nt < q.n_split ? &q.tmB : &q.tmB2, 0, kb * BK,
                                (nt < q.n_split ? nt : nt - q.n_split) * (BN / 64), fb);
                    if (++stage == C::STAGES) { stage = 0; phase ^= 1; }
                }
            }
        } else if (tid >= 32 && tid < 64) {
            store_warp<BN>(epi_base, rec_base, st_full, st_empty, tid & 31, reinterpret_cast<const uint8_t*>(&p.prob[0].tmC),
                           (int)sizeof(SideProb));
        }
    } else {
        asm volatile("setmaxnreg.inc.sync.aligned.u32 232;");
        const int cw = wg - 1, lane = tid & 31, wi = (tid >> 5) & 3;
        const bool elected = (tid & 127) == 0;
        int stage = 0; uint32_t phase = 0;
        float acc[BN / 2];
        EpiCtx ectx = {epi_base + (cw * 4 + wi) * C::EPI_WARP, rec_base + (cw * 4 + wi) * 32, st_full, st_empty, 0, lane};
        for (uint32_t it = 0;; it++) {
            mbar_wait(tfull + 8 * (it & 1), (it >> 1) & 1);
            const int code = (int)lds32_volatile(tslot + 4 * (it & 1));
            named_bar_sync(1 + cw, 128);
            if (elected) mbar_arrive(tempty + 8 * (it & 1));
            if (code < 0) break;
            const SideProb& q = p.prob[code >> 16];
            const int mt = (code >> 8) & 255, nt = code & 255;
            gemm_mainloop<BN>(acc, q.k_blocks, sbase, bar_base, cw, elected, stage, phase);
            const int row0 = mt * BM + cw * 64 + wi * 16;
            uint64_t dst;
            if (q.blocked) {
                const int col = nt * BN;
                dst = (uint64_t)(q.blocked + (((size_t)(col / HD) * NSEG + row0 / SEG) * NH + (col % HD) / DH) * (SEG * DH) +
                                 (row0 % SEG) * 64);
            } else {
                dst = ((uint64_t)row0 << 32) | (uint32_t)(q.c_col0 + nt * BN);
            }
            epi_hand_over(acc, ectx, dst, q.sig ? (uint64_t)(q.sig + mt) : 0, q.blocked ? 0 : 1 + (code >> 16));
        }
        epi_exit(ectx);
        if (elected) KEXIT(BN == 256 ? (p.nseg == 1 ? 6 : 2) : 4);
    }
}

#define FIN_SPLIT 8
constexpr int FIN_STAGES = 5, FIN_STAGE = A_STAGE + BK * 128 * 2, FIN_RED = FIN_STAGES * FIN_STAGE;
constexpr int FIN_NACC = 64 / FIN_SPLIT;
constexpr int FIN_SLOT = 256 * FIN_NACC * 4;
constexpr int FIN_BAR = FIN_RED + (FIN_SPLIT - 1) * FIN_SLOT, FIN_SMEM = FIN_BAR + 256 + 1024;
struct FinalParams {
    CUtensorMap tmA, tmB;
    __nv_bfloat16* out;
    const uint32_t* dep;
    uint32_t dep_target;
    int mt;
};
__global__ void __launch_bounds__(384, 1) final_gemm_kernel(const __grid_constant__ FinalParams p) {
    extern __shared__ uint8_t smem_raw[];
    const uint32_t sbase = (smem_u32(smem_raw) + 1023) & ~1023u;
    const uint32_t bar_base = sbase + FIN_BAR, bar_red = bar_base + 16 * FIN_STAGES;
    const int tid = threadIdx.x, wg = tid >> 7;
    const int rank = blockIdx.x % FIN_SPLIT, nt = blockIdx.x / FIN_SPLIT;
    constexpr int KB = HD / BK / FIN_SPLIT;
    KENTER(5);
    if (tid == 0) {
        for (int s = 0; s < FIN_STAGES; s++) { mbar_init(bar_base + 8 * s, 1); mbar_init(bar_base + 8 * (FIN_STAGES + s), 2); }
        mbar_init(bar_red, 1);
        asm volatile("fence.mbarrier_init.release.cluster;" ::: "memory");
        mbar_arrive_expect_tx(bar_red, (FIN_SPLIT - 1) * FIN_SLOT);
        pdl_launch_dependents();
    }
    __syncthreads();
    cluster_sync();
    if (wg == 0) {
        if (tid == 0) {
            for (int kb = 0; kb < FIN_STAGES; kb++) {
                mbar_arrive_expect_tx(bar_base + 8 * kb, FIN_STAGE);
                tma_load_3d(sbase + kb * FIN_STAGE + A_STAGE, &p.tmB, 0, (rank * KB + kb) * BK, nt * 2, bar_base + 8 * kb);
            }
            uint32_t n = 0;
            while (ld_acquire_b32(p.dep) < p.dep_target) { if (++n > SPIN_LIMIT) __trap(); }
            asm volatile("fence.proxy.async;" ::: "memory");
            for (int kb = 0; kb < FIN_STAGES; kb++)
                tma_load_2d(sbase + kb * FIN_STAGE, &p.tmA, (rank * KB + kb) * BK, p.mt * BM, bar_base + 8 * kb);
            int stage = 0; uint32_t phase = 0;
            for (int kb = FIN_STAGES; kb < KB; kb++) {
                mbar_wait(bar_base + 8 * (FIN_STAGES + stage), phase);
                const uint32_t sa = sbase + stage * FIN_STAGE, fb = bar_base + 8 * stage;
                mbar_arrive_expect_tx(fb, FIN_STAGE);
                tma_load_3d(sa + A_STAGE, &p.tmB, 0, (rank * KB + kb) * BK, nt * 2, fb);
                tma_load_2d(sa, &p.tmA, (rank * KB + kb) * BK, p.mt * BM, fb);
                if (++stage == FIN_STAGES) { stage = 0; phase ^= 1; }
            }
        }
    } else {
        const int cw = wg - 1, lane = tid & 31, wi = (tid >> 5) & 3, t128 = tid & 127;
        const bool elected = t128 == 0;
        float acc[64];
        int stage = 0; uint32_t phase = 0;
        int prev_stage = -1;
        for (int kb = 0; kb < KB; kb++) {
            mbar_wait(bar_base + 8 * stage, phase);
            const uint32_t sa = sbase + stage * FIN_STAGE + cw * (64 * 128), sb = sbase + stage * FIN_STAGE + A_STAGE;
            asm volatile("wgmma.fence.sync.aligned;" ::: "memory");
            #pragma unroll
            for (int kk = 0; kk < BK / 16; kk++)
                wgmma_m64n128k16(acc, make_desc(sa + kk * 32, 16, 1024), make_desc(sb + kk * 2048, 8192, 1024), (kb | kk) != 0);
            asm volatile("wgmma.commit_group.sync.aligned;" ::: "memory");
            asm volatile("wgmma.wait_group.sync.aligned 1;" ::: "memory");
            if (prev_stage >= 0 && elected) mbar_arrive(bar_base + 8 * (FIN_STAGES + prev_stage));
            prev_stage = stage;
            if (++stage == FIN_STAGES) { stage = 0; phase ^= 1; }
        }
        asm volatile("wgmma.wait_group.sync.aligned 0;" ::: "memory");
        #pragma unroll
        for (int q = 0; q < FIN_SPLIT; q++) {
            if (q != rank) {
                const int slot = rank - (rank > q ? 1 : 0);
                const uint32_t dst = mapa(sbase + FIN_RED + slot * FIN_SLOT + cw * (FIN_SLOT / 2) + t128 * 16, q), rb = mapa(bar_red, q);
                #pragma unroll
                for (int j = 0; j < FIN_NACC / 4; j++)
                    asm volatile("st.async.weak.shared::cluster.mbarrier::complete_tx::bytes.v4.f32 [%0], {%1,%2,%3,%4}, [%5];"
                                 ::"r"(dst + j * 2048), "f"(acc[FIN_NACC * q + 4 * j]), "f"(acc[FIN_NACC * q + 4 * j + 1]),
                                   "f"(acc[FIN_NACC * q + 4 * j + 2]), "f"(acc[FIN_NACC * q + 4 * j + 3]), "r"(rb) : "memory");
            }
        }
        float o[FIN_NACC];
        #pragma unroll
        for (int q = 0; q < FIN_SPLIT; q++)
            if (q == rank) {
                #pragma unroll
                for (int e = 0; e < FIN_NACC; e++) o[e] = acc[FIN_NACC * q + e];
            }
        mbar_wait(bar_red, 0);
        #pragma unroll
        for (int sl = 0; sl < FIN_SPLIT - 1; sl++) {
            #pragma unroll
            for (int j = 0; j < FIN_NACC / 4; j++) {
                const uint4 v = lds128(sbase + FIN_RED + sl * FIN_SLOT + cw * (FIN_SLOT / 2) + j * 2048 + t128 * 16);
                o[4 * j] += __uint_as_float(v.x); o[4 * j + 1] += __uint_as_float(v.y);
                o[4 * j + 2] += __uint_as_float(v.z); o[4 * j + 3] += __uint_as_float(v.w);
            }
        }
        __nv_bfloat16* dst = p.out + (size_t)(p.mt * BM + cw * 64 + wi * 16 + (lane >> 2)) * (2 * DM) + nt * 128 +
                             rank * (128 / FIN_SPLIT) + (lane & 3) * 2;
        #pragma unroll
        for (int j = 0; j < FIN_NACC / 4; j++) {
            *reinterpret_cast<uint32_t*>(dst + j * 8) = pack_bf16(o[4 * j], o[4 * j + 1]);
            *reinterpret_cast<uint32_t*>(dst + (size_t)8 * (2 * DM) + j * 8) = pack_bf16(o[4 * j + 2], o[4 * j + 3]);
        }
    }
    __syncthreads();
    cluster_sync();
    if (tid == 0) KEXIT(5);
}

#define POLL_DELAY 10
#define FETCH_DELAY 2
#define WO_PF0 0
#define WO_PF1 12
#define WO_AHEAD 6
constexpr int REC_THREADS = 256;
constexpr uint32_t POLL_LIMIT = 1u << 16;
constexpr int NREG = 24;
__host__ __device__ constexpr int reg_idx(int j) { return ((j & 3) - 1) * 8 + (j >> 2); }
constexpr int SM_WQ = 0;
constexpr int SM_WO = 65536;
constexpr int SM_X = SM_WO + 11 * 8192;
constexpr int SM_PARK = SM_X;
constexpr int SM_MEM = SM_X + 4 * 4096;
constexpr int SM_RED = SM_X + 8 * 4096;
constexpr int SM_V = SM_X + 12 * 4096;
constexpr int SM_K = SM_X + 14 * 4096;
constexpr int SM_QS = SM_X + 15 * 4096;
constexpr int SM_QK = SM_X + 65536;
constexpr int SM_SP = SM_QK + 2048;
constexpr int SM_VM = SM_SP + 2560;
constexpr int SM_O = SM_VM + 2048;
constexpr int SM_SUM = SM_O + 2048;
constexpr int SM_TBL = SM_SUM + 128;
constexpr int SM_BAR = SM_TBL + 512;
constexpr int SM_STAMP = SM_BAR + 192;
constexpr int REC_SMEM = SM_STAMP;
static_assert(REC_SMEM <= 232448, "shared memory");
enum { BAR_V = 0, BAR_X = 8, BAR_P0 = 16, BAR_WQ = 40, BAR_WO = 48, BAR_XG = 56, BAR_F0 = 88, BAR_F3 = 96, BAR_VF = 104,
       BAR_M = 112, BAR_SELF = 144, BAR_MIN = 152 };

template <int V> struct IntC { static constexpr int value = V; };
template <int I, int N, typename F> __device__ __forceinline__ void sfor(F&& f) {
    if constexpr (I < N) { f(IntC<I>{}); sfor<I + 1, N>(f); }
}

struct RecParams {
    CUtensorMap tmW[3];
    CUtensorMap tmWo;
    CUtensorMap tmX;
    const __nv_bfloat16* mem0;
    __nv_bfloat16* qkv_tok;
    __nv_bfloat16* kv_mem;
    uint8_t* xchg;
    int* ctacolor;
    uint32_t* flags;
    uint32_t one[2];
    uint32_t* arrivals;
};

__device__ __forceinline__ void mma_a(float* d, const uint32_t* a, uint32_t b0, uint32_t b1) {
    mma16816(d, a[0], a[1], a[2], a[3], b0, b1);
}
__device__ __forceinline__ void ldsm4_sel(uint32_t sel, uint32_t a0, uint32_t a1, uint32_t* r) {
    if (sel == 0) ldsm_x4(a0, r[0], r[1], r[2], r[3]); else ldsm_x4_t(a1, r[0], r[1], r[2], r[3]);
}
__device__ __forceinline__ void ldsm4t(uint32_t addr, uint32_t* r) { ldsm_x4_t(addr, r[0], r[1], r[2], r[3]); }
template <int OFF> __device__ __forceinline__ void poll_v2(uint2& v, const uint8_t* p) {
    asm volatile("ld.relaxed.gpu.global.v2.b32 {%0,%1}, [%2+%3];" : "=r"(v.x), "=r"(v.y) : "l"(p), "n"(OFF) : "memory");
}
__device__ __forceinline__ uint32_t max3(uint32_t a, uint32_t b, uint32_t c) { return max(max(a, b), c); }
__device__ __forceinline__ uint32_t pub_slot(int s) { return (s & 1) * XCHG_SLOT + ((s >> 1) & 1) * PUB_BYTES; }

__device__ __forceinline__ uint8_t* xaddr(uint32_t lo, uint32_t hi) {
    uint64_t a;
    asm("mov.b64 %0, {%1, %2};" : "=l"(a) : "r"(lo), "r"(hi));
    return reinterpret_cast<uint8_t*>(a);
}
template <int N> __device__ __forceinline__ uint32_t delay_zero(uint32_t a) {
    uint32_t x = a;
    #pragma unroll
    for (int i = 0; i < N; i++) x = lds32_volatile(x);
    return x - a;
}
__device__ __forceinline__ uint32_t fresh(uint32_t x) { asm volatile("" : "+r"(x)); return x; }

template <int NT> __device__ __forceinline__ uint32_t wo_addr(uint32_t ao, uint32_t a3, int n) {
    return (n % NT == 2 ? a3 : ao + (n % NT) * 32768) + (n / NT) * 1024;
}
template <int NT, int PF>
__device__ __forceinline__ void wo_phase(uint32_t (&st)[8 * NT][4], uint32_t ao, uint32_t a3, uint32_t l16, uint32_t tbl, uint32_t sums,
                                         uint32_t slot, uint32_t xhi, bool third) {
    constexpr int AHEAD = PF > WO_AHEAD ? PF - NT : WO_AHEAD;
    uint32_t of[4][4], pl[3];
    float i0, i1;
    ldsm4t(l16 + SM_O, of[0]);
    #pragma unroll
    for (int n = PF; n < AHEAD; n++) ldsm4t(wo_addr<NT>(ao, a3, n), st[n]);
    float acc[NT][4];
    #pragma unroll
    for (int i = 0; i < NT; i++) { acc[i][0] = acc[i][1] = acc[i][2] = acc[i][3] = 0.f; }
    #pragma unroll
    for (int kk = 0; kk < 8; kk++) {
        if ((kk & 1) == 0 && kk + 2 < 8) ldsm4t(l16 + SM_O + ((kk >> 1) + 1) * 512, of[(kk >> 1) + 1]);
        if (kk == 4) {
            const uint32_t x = fresh(l16);
            const uint4 sa = lds128(sums + ((x << 1) & 0x60)), sc = lds128(sums + ((x << 1) & 0x60) + 16);
            i0 = rcp((__uint_as_float(sa.x) + __uint_as_float(sa.y)) + (__uint_as_float(sa.z) + __uint_as_float(sa.w)));
            i1 = rcp((__uint_as_float(sc.x) + __uint_as_float(sc.y)) + (__uint_as_float(sc.z) + __uint_as_float(sc.w)));
            const uint4 t = lds128(tbl + ((x >> 3) & 0x30));
            const uint32_t d = slot + ((x >> 1) & 0x38);
            pl[0] = t.x + d; pl[1] = t.y + d; pl[2] = t.z + d;
            __syncwarp();
        }
        #pragma unroll
        for (int i = 0; i < NT; i++) {
            const int n = kk * NT + i;
            mma_a(acc[i], st[n], of[kk >> 1][(kk & 1) * 2], of[kk >> 1][(kk & 1) * 2 + 1]);
            if (n + AHEAD >= PF && n + AHEAD < 8 * NT) ldsm4t(wo_addr<NT>(ao, a3, n + AHEAD), st[n + AHEAD]);
        }
    }
    #pragma unroll
    for (int i = 0; i < NT; i++)
        if (i < 2 || third)
            st_relaxed_v2(xaddr(pl[i], xhi), pack_bf16(acc[i][0] * i0, acc[i][1] * i1), pack_bf16(acc[i][2] * i0, acc[i][3] * i1));
}

constexpr uint32_t SMEM_ORIGIN = 1024;
constexpr uint64_t DESC_BASE = (1ull << 16) | (0x40000040ull << 32);
template <int OFFB, int SCALE_D>
__device__ __forceinline__ void wgmma_n32_rs(float (&d)[16], const uint32_t* a, uint32_t one) {
    asm volatile(
        "{\n.reg .b64 db;\nmad.wide.u32 db, %20, %21, %22;\n"
        "wgmma.mma_async.sync.aligned.m64n32k16.f32.bf16.bf16 {%0,%1,%2,%3,%4,%5,%6,%7,%8,%9,%10,%11,%12,%13,%14,%15}, "
        "{%16,%17,%18,%19}, db, %23, 1, 1, 0;\n}"
        : "+f"(d[0]), "+f"(d[1]), "+f"(d[2]), "+f"(d[3]), "+f"(d[4]), "+f"(d[5]), "+f"(d[6]), "+f"(d[7]),
          "+f"(d[8]), "+f"(d[9]), "+f"(d[10]), "+f"(d[11]), "+f"(d[12]), "+f"(d[13]), "+f"(d[14]), "+f"(d[15])
        : "r"(a[0]), "r"(a[1]), "r"(a[2]), "r"(a[3]), "r"(one), "n"((SMEM_ORIGIN + OFFB) >> 4), "l"(DESC_BASE), "n"(SCALE_D));
}
template <int OFFA, int OFFB, int SCALE_D>
__device__ __forceinline__ void wgmma_n32_ss(float (&d)[16], uint32_t one) {
    asm volatile(
        "{\n.reg .b64 da, db;\nmad.wide.u32 da, %16, %17, %19;\nmad.wide.u32 db, %16, %18, %19;\n"
        "wgmma.mma_async.sync.aligned.m64n32k16.f32.bf16.bf16 {%0,%1,%2,%3,%4,%5,%6,%7,%8,%9,%10,%11,%12,%13,%14,%15}, "
        "da, db, %20, 1, 1, 1, 0;\n}"
        : "+f"(d[0]), "+f"(d[1]), "+f"(d[2]), "+f"(d[3]), "+f"(d[4]), "+f"(d[5]), "+f"(d[6]), "+f"(d[7]),
          "+f"(d[8]), "+f"(d[9]), "+f"(d[10]), "+f"(d[11]), "+f"(d[12]), "+f"(d[13]), "+f"(d[14]), "+f"(d[15])
        : "r"(one), "n"((SMEM_ORIGIN + OFFA) >> 4), "n"((SMEM_ORIGIN + OFFB) >> 4), "l"(DESC_BASE), "n"(SCALE_D));
}
template <int WG, int J0, int J1, int I0, int I1, bool ACC>
__device__ __forceinline__ void token_mma(float (&ta)[2][16], const uint32_t (&wr)[NREG][2][4], uint32_t one) {
    asm volatile("wgmma.fence.sync.aligned;" ::: "memory");
    sfor<J0, J1>([&](auto J) {
        constexpr int j = J.value, offb = SM_X + WG * 32768 + (j >> 2) * 4096 + (j & 3) * 32, sc = (ACC || j != J0) ? 1 : 0;
        sfor<I0, I1>([&](auto I) {
            constexpr int i = I.value;
            if constexpr ((j & 3) != 0) wgmma_n32_rs<offb, sc>(ta[i], wr[reg_idx(j)][i], one);
            else wgmma_n32_ss<SM_WQ + WG * 32768 + i * 16384 + (j >> 2) * 2048, offb, sc>(ta[i], one);
        });
    });
    asm volatile("wgmma.commit_group.sync.aligned;" ::: "memory");
}
__device__ __forceinline__ void remote_arrive(uint32_t bar, uint32_t rank) {
    asm volatile("mbarrier.arrive.relaxed.cluster.shared::cluster.b64 _, [%0];" ::"r"(mapa(bar, rank)) : "memory");
}
__device__ __forceinline__ void x_load(const RecParams& p, uint32_t sb, int sg, int g) {
    tma_load_3d_mc(sb + SM_X + g * 16384, &p.tmX, 0, sg * SEG, g * 4, sb + SM_BAR + BAR_XG + 8 * g, (uint16_t)7);
}

__device__ __forceinline__ void rec_steps(const RecParams& p, const uint32_t (&wr)[NREG][2][4], const uint32_t sb, const int warp,
                                          const int cta, const int head, const int rank) {
    const int wq = warp & 3, wg = warp >> 2;
    const uint32_t bar = sb + SM_BAR;
    const uint32_t xhi = (uint32_t)((uint64_t)p.xchg >> 32);
    const float sl2 = 0.08838834764831845f * 1.4426950408889634f;
    const bool has_unit = warp >= 5 && (warp < 7 || cta < 64);
    const bool qk = rank < 2;
    const uint32_t pa = rank == 2 ? 0 : rank + 1, pb = rank == 0 ? 2 : rank - 1;
    const uint32_t tbl = sb + SM_TBL + warp * 64;

    uint32_t l16, xa, aq, ao;
    {
        const int lane = threadIdx.x & 31, mi = lane >> 3, r8 = lane & 7, r16 = (mi >> 1) * 8 + r8;
        l16 = opaque(sb + lane * 16);
        xa = opaque(sb + lane * 8 + warp * 256 + (qk ? SM_SP + rank * 1280 : SM_VM));
        aq = opaque(sb + SM_WQ + wg * 32768 + r16 * 128 + (((wq * 2 + (mi & 1)) ^ r8) << 4));
        ao = opaque(sb + SM_WO + (warp >> 1) * 8192 + r16 * 64 + ((((warp & 1) * 2 + (mi & 1)) ^ ((r8 >> 1) & 3)) << 4));
    }

    uint32_t mphase = 0;
    #pragma unroll 1
    for (int s = 0; s < NSEG; s++) {
        const uint32_t par = s & 1;
        uint32_t at[4][4];
        auto at_prefetch = [&]() {
            #pragma unroll
            for (int i = 0; i < 4; i++) ldsm4t(aq + (i & 1) * 16384 + (i >> 1) * 2048, at[i]);
        };
        if (wg == 0) {
            float ta[2][16];
            mbar_wait_bounded(bar + BAR_XG, par);
            STAMP(6);
            token_mma<0, 0, 16, 0, 2, false>(ta, wr, p.one[0]);
            mbar_wait_bounded(bar + BAR_XG + 8, par);
            token_mma<0, 16, 32, 0, 2, true>(ta, wr, p.one[0]);
            named_bar_arrive(8, REC_THREADS);
            const uint32_t srcl = lds32_volatile(tbl + 44) + pub_slot(s);
            asm volatile("wgmma.wait_group.sync.aligned 0;" ::: "memory");
            named_bar_sync(10, 128);
            auto park = [&](int i) {
                #pragma unroll
                for (int j = 0; j < 4; j++)
                    sts128(l16 + SM_PARK + (i * 4 + j) * 2048 + wq * 512, __float_as_uint(ta[i][4 * j]), __float_as_uint(ta[i][4 * j + 1]),
                           __float_as_uint(ta[i][4 * j + 2]), __float_as_uint(ta[i][4 * j + 3]));
            };
            park(0);
            named_bar_arrive(12, REC_THREADS);
            park(1);
            named_bar_arrive(13, REC_THREADS);
            at_prefetch();
            STAMP(9);
            const uint32_t x = fresh(l16) - sb;
            const uint32_t ca = sb + SM_MEM + wq * 4096 + x * 2 + ((x >> 4) & 0x1C);
            named_bar_sync(7, REC_THREADS - 32);
            const uint8_t* src = xaddr(__shfl_sync(~0u, srcl + delay_zero<FETCH_DELAY>(bar + BAR_SELF), 0), xhi);
            STAMP(12);
            #pragma unroll 1
            for (uint32_t n = 0; n < POLL_LIMIT; n++) {
                if (elect_one()) {
                    mbar_arrive_expect_tx(bar + BAR_M + 8 * wq, 4096);
                    bulk_load(sb + SM_MEM + wq * 4096, src, 4096, bar + BAR_M + 8 * wq);
                }
                mbar_wait_bounded(bar + BAR_M + 8 * wq, mphase);
                mphase ^= 1;
                const uint32_t c0 = lds32_volatile(ca), c1 = lds32_volatile(ca + 1024), c2 = lds32_volatile(ca + 2048), c3 = lds32_volatile(ca + 3072);
                if (!__any_sync(~0u, max(max3(c0, c1, c2), c3) == SENT)) break;
            }
            STAMP(0);
            named_bar_sync(0, REC_THREADS);
            if (warp < 2 && elect_one()) remote_arrive(bar + (warp == 0 ? BAR_VF : BAR_F0), warp == 0 ? 2 : 0);
        } else {
            if (s > 0) {
                if (has_unit) {
                    const uint32_t ln = (fresh(l16) >> 4) & 31;
                    const uint32_t ibl = lds32_volatile(tbl + 12) + (par ^ 1) * XCHG_SLOT + ln * 8;
                    const uint32_t publ = lds32_volatile(tbl + 28) + pub_slot(s) + (ln & 16) * 256 + (ln & 8) * 16 + (ln & 7) * 4;
                    const bool odd = ln & 8;
                    const uint8_t* ib = xaddr(ibl + delay_zero<POLL_DELAY>(bar + BAR_SELF), xhi);
                    STAMP(8);
                    uint2 v[8];
                    #pragma unroll 1
                    for (uint32_t n = 0; n < POLL_LIMIT; n++) {
                        sfor<0, 8>([&](auto I) { poll_v2<I.value * 256>(v[I.value], ib); });
                        const uint32_t mx = max(max3(v[0].y, v[1].y, v[2].y), max3(max3(v[3].y, v[4].y, v[5].y), v[6].y, v[7].y));
                        if (!__any_sync(~0u, mx == SENT)) break;
                    }
                    float a0 = ((bf16_lo(v[0].x) + bf16_lo(v[1].x)) + (bf16_lo(v[2].x) + bf16_lo(v[3].x))) +
                               ((bf16_lo(v[4].x) + bf16_lo(v[5].x)) + (bf16_lo(v[6].x) + bf16_lo(v[7].x)));
                    float a1 = ((bf16_hi(v[0].x) + bf16_hi(v[1].x)) + (bf16_hi(v[2].x) + bf16_hi(v[3].x))) +
                               ((bf16_hi(v[4].x) + bf16_hi(v[5].x)) + (bf16_hi(v[6].x) + bf16_hi(v[7].x)));
                    float a2 = ((bf16_lo(v[0].y) + bf16_lo(v[1].y)) + (bf16_lo(v[2].y) + bf16_lo(v[3].y))) +
                               ((bf16_lo(v[4].y) + bf16_lo(v[5].y)) + (bf16_lo(v[6].y) + bf16_lo(v[7].y)));
                    float a3 = ((bf16_hi(v[0].y) + bf16_hi(v[1].y)) + (bf16_hi(v[2].y) + bf16_hi(v[3].y))) +
                               ((bf16_hi(v[4].y) + bf16_hi(v[5].y)) + (bf16_hi(v[6].y) + bf16_hi(v[7].y)));
                    float k0 = odd ? a2 : a0, k1 = odd ? a3 : a1;
                    k0 += __shfl_xor_sync(~0u, odd ? a0 : a2, 8);
                    k1 += __shfl_xor_sync(~0u, odd ? a1 : a3, 8);
                    k0 += __shfl_xor_sync(~0u, k0, 16);
                    k1 += __shfl_xor_sync(~0u, k1, 16);
                    st_relaxed_b32(xaddr(publ, xhi), pack_bf16(k0, k1));
                    STAMP(11);
                } else if (warp == 4) {
                    if (elect_one()) {
                        remote_arrive(bar + BAR_F3, 2);
                        if (!qk) {
                            mbar_wait_bounded(bar + BAR_F3, par ^ 1);
                            x_load(p, sb, s, 3);
                        }
                        bulk_wait_all();
                        signal_flag(p.flags + F_PROGRESS + s - 1);
                    }
                    __syncwarp();
                    STAMP(10);
                }
            }
            float ta[2][16];
            uint32_t w[2][8];
            if (warp != 4) named_bar_arrive(7, REC_THREADS - 32);
            mbar_wait_bounded(bar + BAR_XG + 16, par);
            named_bar_sync(8, REC_THREADS);
            STAMP(6);
            token_mma<1, 0, 16, 0, 1, false>(ta, wr, p.one[0]);
            mbar_wait_bounded(bar + BAR_XG + 24, par);
            named_bar_sync(12, REC_THREADS);
            uint4 pk[4];
            #pragma unroll
            for (int j = 0; j < 4; j++) pk[j] = lds128(l16 + SM_PARK + j * 2048 + wq * 512);
            token_mma<1, 16, 32, 0, 1, true>(ta, wr, p.one[0]);
            #pragma unroll
            for (int j = 0; j < 4; j++) {
                ta[1][4 * j] = __uint_as_float(pk[j].x); ta[1][4 * j + 1] = __uint_as_float(pk[j].y);
                ta[1][4 * j + 2] = __uint_as_float(pk[j].z); ta[1][4 * j + 3] = __uint_as_float(pk[j].w);
            }
            named_bar_sync(13, REC_THREADS);
            #pragma unroll
            for (int j = 0; j < 4; j++) pk[j] = lds128(l16 + SM_PARK + (4 + j) * 2048 + wq * 512);
            token_mma<1, 0, 32, 1, 2, true>(ta, wr, p.one[1]);
            asm volatile("wgmma.wait_group.sync.aligned 1;" ::: "memory");
            #pragma unroll
            for (int e = 0; e < 16; e++) asm volatile("" : "+f"(ta[0][e]));
            #pragma unroll
            for (int j = 0; j < 4; j++) {
                w[0][2 * j] = pack_bf16(ta[0][4 * j] + __uint_as_float(pk[j].x), ta[0][4 * j + 1] + __uint_as_float(pk[j].y));
                w[0][2 * j + 1] = pack_bf16(ta[0][4 * j + 2] + __uint_as_float(pk[j].z), ta[0][4 * j + 3] + __uint_as_float(pk[j].w));
            }
            at_prefetch();
            const uint32_t d1 = aq - (SM_WQ + 32768) + (qk ? SM_K : SM_V + 4096), d0 = aq - (SM_WQ + 32768) + (qk ? SM_QS : SM_V);
            asm volatile("wgmma.wait_group.sync.aligned 0;" ::: "memory");
            #pragma unroll
            for (int e = 0; e < 16; e++) asm volatile("" : "+f"(ta[1][e]));
            #pragma unroll
            for (int j = 0; j < 8; j++) w[1][j] = pack_bf16(ta[1][2 * j], ta[1][2 * j + 1]);
            STAMP(0);
            named_bar_sync(0, REC_THREADS);
            #pragma unroll
            for (int i = 0; i < 4; i++) {
                const uint32_t* q = &w[i >> 1][(i & 1) * 4];
                asm volatile("stmatrix.sync.aligned.m8n8.x4.trans.shared.b16 [%0], {%1,%2,%3,%4};"
                             ::"r"((i < 2 ? d1 : d0) + (i & 1) * 2048), "r"(q[0]), "r"(q[1]), "r"(q[2]), "r"(q[3]) : "memory");
            }
            if (!qk) {
                asm volatile("fence.proxy.async.shared::cta;" ::: "memory");
                if (warp != 4) {
                    named_bar_arrive(11, 128);
                } else {
                    named_bar_sync(11, 128);
                    if (elect_one()) {
                        mbar_wait_bounded(bar + BAR_VF, par);
                        #pragma unroll
                        for (int r = 0; r < 2; r++)
                            asm volatile("cp.async.bulk.shared::cluster.shared::cta.mbarrier::complete_tx::bytes [%0], [%1], %2, [%3];"
                                         ::"r"(mapa(sb + SM_V, r)), "r"(sb + SM_V), "r"(8192), "r"(mapa(bar + BAR_V, r)) : "memory");
                    }
                    __syncwarp();
                }
            }
            STAMP(14);
        }
        const uint32_t mb = l16 + SM_MEM + wg * 8192;
        float acc[2][2][4];
        {
            uint32_t b[2][4];
            ldsm4t(mb, b[0]);
            ldsm4t(mb + 512, b[1]);
            STAMPD(1, b[0][0]);
            #pragma unroll
            for (int i = 0; i < 4; i++) { for (int e = 0; e < 4; e++) acc[i >> 1][i & 1][e] = 0.f; }
            #pragma unroll
            for (int u = 0; u < 16; u++) {
                #pragma unroll
                for (int h = 0; h < 2; h++) {
                    const int j = 2 * u + h;
                    #pragma unroll
                    for (int m = 0; m < 2; m++) {
                        if ((j & 3) == 0) mma_a(acc[h][m], at[((j >> 2) & 1) * 2 + m], b[u & 1][2 * h], b[u & 1][2 * h + 1]);
                        else mma_a(acc[h][m], wr[reg_idx(j)][m], b[u & 1][2 * h], b[u & 1][2 * h + 1]);
                    }
                }
                if (u + 2 < 16) ldsm4t(mb + (u + 2) * 512, b[u & 1]);
                if (u < 12) ldsm4t(aq + (u & 1) * 16384 + ((u >> 1) + 2) * 2048, at[((u >> 1) & 1) * 2 + (u & 1)]);
            }
        }
        sts128(l16 + SM_RED + warp * 512, __float_as_uint(acc[0][1][0] + acc[1][1][0]), __float_as_uint(acc[0][1][1] + acc[1][1][1]),
               __float_as_uint(acc[0][1][2] + acc[1][1][2]), __float_as_uint(acc[0][1][3] + acc[1][1][3]));
        #pragma unroll
        for (int e = 0; e < 4; e++) acc[0][0][e] += acc[1][0][e];
        const uint32_t x16 = fresh(l16);
        const uint32_t ast = x16 + (x16 & (wg == 0 ? 0x80 : 0)) + SM_QK + (wg == 0 ? (wq >> 1) * 512 + (wq & 1) * 128 : 1024 + wq * 256);
        const uint32_t ak = sb + SM_K + wq * 1024 + (x16 & 0x70) * 8 + ((((x16 >> 3) & 0x30) ^ x16) & 0x70);
        const uint32_t xra = mapa(xa, pa), xrb = mapa(xa, pb), bra = mapa(bar + BAR_X, pa), brb = mapa(bar + BAR_X, pb);
        STAMP(2);
        named_bar_sync(1 + wq, 64);
        uint32_t p0, p1;
        {
            const uint4 v = lds128(l16 + SM_RED + (warp ^ 4) * 512);
            p0 = pack_bf16(acc[0][0][0] + __uint_as_float(v.x), acc[0][0][1] + __uint_as_float(v.y));
            p1 = pack_bf16(acc[0][0][2] + __uint_as_float(v.z), acc[0][0][3] + __uint_as_float(v.w));
        }
        {
            uint32_t y0 = p0, y1 = p1;
            if (qk) {
                asm volatile("stmatrix.sync.aligned.m8n8.x2.shared.b16 [%0], {%1,%2};" ::"r"(ast), "r"(p0), "r"(p1) : "memory");
                named_bar_sync(5, REC_THREADS);
                if (warp <= 4) {
                    uint32_t qa[2][4], kf[2][4];
                    ldsm4t(l16 + SM_QK, qa[0]);
                    ldsm4_sel(wg, ak, l16 + SM_QK + 1024, kf[0]);
                    ldsm4t(l16 + SM_QK + 512, qa[1]);
                    ldsm4_sel(wg, ak ^ 64, l16 + SM_QK + 1536, kf[1]);
                    float se[4] = {0.f, 0.f, 0.f, 0.f}, so[4] = {0.f, 0.f, 0.f, 0.f};
                    #pragma unroll
                    for (int u = 0; u < 2; u++) {
                        mma_a(se, qa[u], kf[u][0], kf[u][1]);
                        mma_a(so, qa[u], kf[u][2], kf[u][3]);
                    }
                    y0 = __float_as_uint(se[0] + so[2]); y1 = __float_as_uint(se[1] + so[3]);
                }
            }
            if (!qk || warp <= 4) {
                st_async_v2(xra, y0, y1, bra);
                st_async_v2(xrb, y0, y1, brb);
                sts64(xa, y0, y1);
                __syncwarp();
                if (elect_one()) mbar_arrive_expect_tx(bar + BAR_X, warp != 0 ? 0 : qk ? 1280 + 2048 : 2560);
            }
            if (!qk) named_bar_sync(5, REC_THREADS);
        }
        STAMP(3);
        const uint32_t lane = (fresh(l16) >> 4) & 31;
        if (!qk || wg == 1) {
            uint32_t* dst = reinterpret_cast<uint32_t*>(p.kv_mem + (((size_t)(rank >> 1) * NSEG + s) * NH + head) * (MROWS * DH)) +
                            (qk ? rank * 4 + wq : warp) * 64 + lane;
            dst[0] = p0;
            dst[32] = p1;
        }
        if (wg == 1) {
            asm volatile("fence.proxy.async.shared::cta;" ::: "memory");
            if (warp != 4) {
                named_bar_arrive(14, 128);
            } else {
                named_bar_sync(14, 128);
                if (elect_one()) {
                    __nv_bfloat16* dst = p.qkv_tok + ((size_t)s * NH + head) * (SEG * DH);
                    constexpr size_t MAT = (size_t)NSEG * NH * SEG * DH;
                    bulk_store(dst + (qk ? rank * (SEG * 64) : 2 * MAT), sb + (qk ? SM_QS : SM_V), 4096);
                    bulk_store(dst + (qk ? MAT + rank * (SEG * 64) : 2 * MAT + SEG * 64), sb + (qk ? SM_K : SM_V + 4096), 4096);
                    bulk_commit();
                }
                __syncwarp();
            }
        } else if (warp == 0 && qk) {
            if (elect_one()) mbar_arrive_expect_tx(bar + BAR_V, 8192);
        }
        if (s == NSEG - 1) break;
        const uint32_t slot = par * XCHG_SLOT;
        if ((warp & 6) == 2) {
            if (qk) mbar_wait_bounded(bar + BAR_V, par);
            uint32_t vt[2][4][4];
            {
                const uint32_t r8 = lane & 7, mi = lane >> 3;
                const uint32_t a = sb + SM_V + (warp & 1) * 4096 + ((mi >> 1) * 8 + r8) * 128 + (((mi & 1) ^ r8) << 4);
                #pragma unroll
                for (int i = 0; i < 8; i++) ldsm4t((a ^ ((i & 3) << 5)) + (i >> 2) * 2048, vt[i >> 2][i & 3]);
            }
            const uint32_t l8 = sb + lane * 8;
            mbar_wait_bounded(bar + BAR_X, par);
            STAMP(4);
            float sv[10];
            #pragma unroll
            for (int j = 0; j < 5; j++) {
                const uint2 a = lds64(l8 + SM_SP + j * 256), b = lds64(l8 + SM_SP + 1280 + j * 256);
                sv[2 * j] = __uint_as_float(a.x) + __uint_as_float(b.x);
                sv[2 * j + 1] = __uint_as_float(a.y) + __uint_as_float(b.y);
            }
            float mx = fmaxf(fmaxf(fmaxf(sv[0], sv[1]), fmaxf(sv[2], sv[3])), fmaxf(fmaxf(sv[4], sv[5]), fmaxf(sv[6], sv[7])));
            mx = fmaxf(mx, fmaxf(sv[8], sv[9]));
            const float m1 = __shfl_xor_sync(~0u, mx, 1), m2 = __shfl_xor_sync(~0u, mx, 2), m3 = __shfl_xor_sync(~0u, mx, 3);
            mx = fmaxf(fmaxf(mx, m1), fmaxf(m2, m3));
            const float mo = mx * sl2;
            #pragma unroll
            for (int j = 0; j < 10; j++) sv[j] = ex2(fmaf(sv[j], sl2, -mo));
            const uint32_t e0 = pack_bf16(sv[0], sv[1]), e1 = pack_bf16(sv[2], sv[3]);
            const uint32_t e2 = pack_bf16(sv[4], sv[5]), e3 = pack_bf16(sv[6], sv[7]), em = pack_bf16(sv[8], sv[9]);
            float o[4][4];
            #pragma unroll
            for (int i = 0; i < 4; i++) {
                o[i][0] = o[i][1] = o[i][2] = o[i][3] = 0.f;
                mma_a(o[i], vt[0][i], e0, e1);
            }
            sts32(sb + SM_SUM + lane * 4,
                  __float_as_uint((((sv[0] + sv[1]) + (sv[2] + sv[3])) + ((sv[4] + sv[5]) + (sv[6] + sv[7]))) + (sv[8] + sv[9])));
            uint2 vm[4];
            #pragma unroll
            for (int i = 0; i < 4; i++) {
                vm[i] = lds64(l8 + SM_VM + (warp & 1) * 1024 + i * 256);
                mma_a(o[i], vt[1][i], e2, e3);
            }
            #pragma unroll
            for (int i = 0; i < 4; i++) mma1688(o[i], vm[i].x, vm[i].y, em);
            #pragma unroll
            for (int i = 0; i < 4; i += 2)
                stsm_x4(l16 + SM_O + (warp & 1) * 1024 + i * 256, pack_bf16(o[i][0], o[i][1]), pack_bf16(o[i][2], o[i][3]),
                        pack_bf16(o[i + 1][0], o[i + 1][1]), pack_bf16(o[i + 1][2], o[i + 1][3]));
            STAMP(5);
            uint32_t st[16][4];
            #pragma unroll
            for (int n = 0; n < WO_PF0; n++) ldsm4t(wo_addr<2>(ao, 0, n), st[n]);
            named_bar_sync(6, REC_THREADS);
            wo_phase<2, WO_PF0>(st, ao, 0, l16, tbl, sb + SM_SUM, slot, xhi, false);
        } else {
            if (has_unit) {
                uint8_t* ib = xaddr(lds32_volatile(tbl + 12) + (par ^ 1) * XCHG_SLOT + lane * 16, xhi);
                #pragma unroll
                for (int i = 0; i < 4; i++) st_relaxed_v4(ib + i * 512, SENT);
                st_relaxed_b32(xaddr(lds32_volatile(tbl + 28) + pub_slot(s + 3) + (lane & 16) * 256 + (lane & 8) * 16 + (lane & 7) * 4, xhi), SENT);
            }
            const uint32_t a3 = fresh(ao) + (wg == 0 ? 10 : 6) * 8192;
            uint32_t st[24][4];
            #pragma unroll
            for (int n = 0; n < WO_PF1; n++) ldsm4t(wo_addr<3>(ao, a3, n), st[n]);
            if (warp == 1) {
                if (elect_one()) {
                    #pragma unroll
                    for (int g = 0; g < 4; g++) mbar_arrive_expect_tx(bar + BAR_XG + 8 * g, 16384);
                    mbar_wait_bounded(bar + (rank == 0 ? BAR_F0 : BAR_X), par);
                    x_load(p, sb, s + 1, rank);
                    if (s + 2 < NSEG && cta < 4)
                        asm volatile("cp.async.bulk.prefetch.tensor.3d.L2.global [%0, {%1, %2, %3}];"
                                     ::"l"(&p.tmX), "r"(0), "r"((s + 2) * SEG), "r"(cta * 4) : "memory");
                }
                __syncwarp();
            } else if (warp == 4) {
                if (elect_one()) bulk_wait_read_all();
                __syncwarp();
            }
            named_bar_sync(6, REC_THREADS);
            wo_phase<3, WO_PF1>(st, ao, a3, l16, tbl, sb + SM_SUM, slot, xhi, warp != 1 || rank == 0);
        }
        STAMP(7);
        if (wg == 0) named_bar_sync(9, REC_THREADS); else named_bar_arrive(9, REC_THREADS);
    }
    mbar_wait(bar + BAR_X, 1);
    if (qk) mbar_wait(bar + BAR_V, 1);
    named_bar_sync(0, REC_THREADS);
    if (warp == 4 && elect_one()) {
        bulk_wait_all();
        signal_flag(p.flags + F_PROGRESS + NSEG - 1);
    }
}

__global__ void __launch_bounds__(REC_THREADS, 1) rec_kernel(const __grid_constant__ RecParams p) {
    extern __shared__ __align__(1024) uint8_t smem_raw[];
    const uint32_t sb = smem_u32(smem_raw);
    const int tid = threadIdx.x, lane = tid & 31;
    const int warp = __shfl_sync(~0u, tid >> 5, 0);
    const int cta = blockIdx.x, head = cta / 3, rank = cta % 3;
    const int wg = warp >> 2, wq = warp & 3;
    const int t0 = (rank * 64 + 2) / 3;
    const uint32_t bar = sb + SM_BAR;
    uint8_t* const xb = p.xchg;
    const uint32_t xlo = (uint32_t)(uint64_t)xb;
    if ((sb & 0x3FFFF) != SMEM_ORIGIN) __trap();
    KENTER(1);
    auto w_box = [&](int part, int g, int i, uint32_t dst, uint32_t mb) {
        const int m = i ^ g;
        const CUtensorMap* tm = &p.tmW[rank == 2 ? 2 : m];
        const int col = head * DH + (rank == 2 ? m : rank) * 64, row = ((part + 1) & 3) * 16;
        if (mb) tma_load_3d(dst, tm, col, row, g * 8, mb);
        else asm volatile("cp.async.bulk.prefetch.tensor.3d.L2.global [%0, {%1, %2, %3}];" ::"l"(tm), "r"(col), "r"(row), "r"(g * 8) : "memory");
    };
    auto wo_box = [&](int b, uint32_t mb) {
        if (mb) tma_load_2d(sb + SM_WO + b * 8192, &p.tmWo, t0 * 16 + b * 32, head * DH, mb);
        else asm volatile("cp.async.bulk.prefetch.tensor.2d.L2.global [%0, {%1, %2}];" ::"l"(&p.tmWo), "r"(t0 * 16 + b * 32), "r"(head * DH) : "memory");
    };
    if (tid == 0) {
        mbar_init(bar + BAR_V, 1);
        for (int i = 0; i < 4; i++) { mbar_init(bar + BAR_XG + 8 * i, 1); mbar_init(bar + BAR_M + 8 * i, 1); }
        mbar_init(bar + BAR_F0, 3);
        mbar_init(bar + BAR_F3, 3);
        mbar_init(bar + BAR_VF, 3);
        sts64(bar + BAR_MIN, ~0u, ~0u);
        mbar_init(bar + BAR_X, rank < 2 ? 5 : 8);
        for (int i = 0; i < 3; i++) mbar_init(bar + BAR_P0 + 8 * i, 1);
        mbar_init(bar + BAR_WQ, 1);
        mbar_init(bar + BAR_WO, 2);
        sts32(bar + BAR_SELF, bar + BAR_SELF);
        asm volatile("fence.mbarrier_init.release.cluster;" ::: "memory");
        for (int part = 0; part < 3; part++) {
            mbar_arrive_expect_tx(bar + BAR_P0 + 8 * part, 65536);
            for (int u = 0; u < 4; u++) w_box(part, u >> 1, u & 1, sb + part * 65536 + u * 16384, bar + BAR_P0 + 8 * part);
        }
        for (int u = 0; u < 4; u++) w_box(3, u >> 1, u & 1, 0, 0);
        if (cta < 8)
            asm volatile("cp.async.bulk.prefetch.tensor.3d.L2.global [%0, {%1, %2, %3}];"
                         ::"l"(&p.tmX), "r"(0), "r"((cta >> 2) * SEG), "r"((cta & 3) * 4) : "memory");
        for (int b = 0; b < 11; b++) wo_box(b, 0);
    }
    __syncthreads();
    if (cta == 0 && tid < F_COUNT) {
        p.flags[tid] = 0;
        __threadfence();
    }
    {
        uint8_t* pr = xb + cta * 8192;
        const uint32_t c0 = class_off(xlo + cta * 8192, 0);
        if (lane < 12) *reinterpret_cast<uint4*>(pr + (((lane >> 1) & 1) << 12) + (warp * 4 + (lane >> 2)) * 128 + (lane & 1) * 16) = make_uint4(0, 0, 0, 0);
        __syncwarp();
        if (lane == 0) {
            uint32_t x = 0;
            for (int k = 0; k < 6; k++) {
                const uint32_t t0 = clock_after(x);
                x = atomicAdd(reinterpret_cast<uint32_t*>(pr + (c0 ^ ((k & 1) << 12)) + (warp * 4 + (k >> 1)) * 128 + x), 1u);
                const uint32_t lat = clock_after(x) - t0;
                asm volatile("red.shared.min.u32 [%0], %1;" ::"r"(bar + BAR_MIN + 4 * (k & 1)), "r"(lat) : "memory");
            }
        }
    }
    __syncthreads();
    if (tid == 0) {
        pdl_launch_dependents();
        p.ctacolor[cta] = lds32_volatile(bar + BAR_MIN) > lds32_volatile(bar + BAR_MIN + 4) ? 1 : 0;
    }
    for (int pair = cta; pair < XCHG_BYTES / 8192; pair += 96) {
        uint4 v = make_uint4(SENT, SENT, SENT, SENT);
        if (pair < 4) {
            const unsigned short* m = reinterpret_cast<const unsigned short*>(p.mem0) + pair * 256 + tid;
            uint32_t w[4];
            #pragma unroll
            for (int i = 0; i < 4; i++) {
                w[i] = (uint32_t)__ldg(m + 2 * i * DM) | ((uint32_t)__ldg(m + (2 * i + 1) * DM) << 16);
                if (w[i] == SENT) w[i] = 0x7FFF7FFFu;
            }
            v = make_uint4(w[0], w[1], w[2], w[3]);
        }
        reinterpret_cast<uint4*>(xb + pair * 8192)[tid] = v;
        reinterpret_cast<uint4*>(xb + pair * 8192 + 4096)[tid] = v;
    }
    __syncthreads();
    if (tid == 224) signal_flag(p.arrivals);
    PSTAMP(4);
    uint32_t wr[NREG][2][4];
    {
        const int mi = lane >> 3, r8 = lane & 7;
        const uint32_t a0 = sb + wg * 32768 + ((mi >> 1) * 8 + r8) * 128 + (((wq * 2 + (mi & 1)) ^ r8) << 4);
        #pragma unroll
        for (int part = 0; part < 3; part++) {
            mbar_wait(bar + BAR_P0 + 8 * part, 0);
            #pragma unroll
            for (int j = 0; j < 8; j++) {
                #pragma unroll
                for (int i = 0; i < 2; i++) ldsm4t(a0 + part * 65536 + i * 16384 + j * 2048, wr[part * 8 + j][i]);
            }
            asm volatile("fence.proxy.async.shared::cta;" ::: "memory");
            __syncthreads();
            if (tid == 0) {
                if (part == 0) {
                    mbar_arrive_expect_tx(bar + BAR_WQ, 65536);
                    for (int u = 0; u < 4; u++) w_box(3, u >> 1, u & 1, sb + SM_WQ + u * 16384, bar + BAR_WQ);
                } else {
                    mbar_arrive_expect_tx(bar + BAR_WO, (part == 1 ? 8 : 3) * 8192);
                    for (int b = part == 1 ? 0 : 8; b < (part == 1 ? 8 : 11); b++) wo_box(b, bar + BAR_WO);
                }
            }
        }
    }
    PSTAMP(5);
    cluster_sync();
    if (tid == 0) {
        for (int g = 0; g < 4; g++) mbar_arrive_expect_tx(bar + BAR_XG + 8 * g, 16384);
        x_load(p, sb, 0, rank);
        if (rank == 0) x_load(p, sb, 0, 3);
    }
    PSTAMP(8);
    if (tid == 0) wait_flag(p.arrivals, 96);
    PSTAMP(9);
    __syncthreads();
    {
        uint32_t cm[3];
        #pragma unroll
        for (int i = 0; i < 3; i++) cm[i] = __ballot_sync(~0u, __ldcg(p.ctacolor + i * 32 + lane) != 0);
        auto color_of = [&](int o) { return ((o < 32 ? cm[0] : o < 64 ? cm[1] : cm[2]) >> (o & 31)) & 1u; };
        auto inbox = [&](int o, int byte) {
            uint32_t c = color_of(o);
            int ones = 0;
            #pragma unroll
            for (int i = 0; i < 3; i++) ones += __popc(o >= i * 32 + 32 ? cm[i] : (o > i * 32 ? cm[i] & ((1u << (o - i * 32)) - 1) : 0u));
            int idx = c ? ones : o - ones;
            if (idx >= INBOX_MAX) { idx = 2 * INBOX_MAX - 1 - idx; c ^= 1; }
            const uint32_t lin = idx * 6144 + byte, q = XCHG_INBOX + (lin >> 12) * 8192;
            return q + class_off(xlo + q, c) + (lin & 4095);
        };
        uint32_t off = 0;
        const int grp = (warp + 3) & 3;
        if (lane < 12) {
            const int i = lane >> 2, lt0 = rank == 0 ? 0 : (rank == 1 ? 6 : 11);
            const int o = i < 2 ? rank * 32 + warp * 4 + (lane & 3) : (lt0 + ((warp + 4) & 7)) * 4 + (lane & 3);
            off = inbox(min(o, 95), i * 2048 + head * 64);
        } else if (lane == 12) {
            off = inbox(cta, (grp % 3) * 2048);
        } else if (lane == 13) {
            int T;
            if (grp < 2) {
                T = ((cta >> 5) * 64 + 2) / 3 + 8 * grp + ((cta & 31) >> 2);
            } else {
                const int tl = (cta & 63) >> 2;
                T = tl < 6 ? 16 + tl : (tl < 11 ? 22 + 16 + (tl - 6) : 43 + 16 + (tl - 11));
            }
            off = XCHG_PUB + (T >> 4) * 8192 + (T & 15) * 256 + (cta & 3) * 32;
        } else if (lane == 14) {
            const uint32_t q = XCHG_PUB + wq * 8192;
            off = q + class_off(xlo + q, color_of(cta));
        }
        if (lane < 16) asm volatile("st.shared.b32 [%0], %1;" ::"r"(sb + SM_TBL + warp * 64 + (lane & 3) * 16 + (lane >> 2) * 4), "r"(xlo + off) : "memory");
    }
    mbar_wait(bar + BAR_WQ, 0);
    mbar_wait(bar + BAR_WO, 0);
    __syncthreads();

    rec_steps(p, wr, sb, warp, cta, head, rank);
    if (cta == 0 && tid == 0) *p.arrivals = 0;
    cluster_sync();
    if (tid == 0) KEXIT(1);
}

constexpr int ATT_A_BYTES = 3 * 8192 + 2 * 2048;
constexpr int ATT_TASKW = 4 * ATT_A_BYTES;
constexpr int ATT_SMEM = ATT_TASKW + 16;
struct AttnParams {
    const __nv_bfloat16* qkv_tok;
    const __nv_bfloat16* kv_mem;
    __nv_bfloat16* o_tok;
    const __nv_bfloat16* qkv_b;
    __nv_bfloat16* o_b;
    uint32_t* flags;
};

__device__ __forceinline__ void tok_attn_warp(uint32_t base, int hh, int mh, int lane, __nv_bfloat16* obase) {
    const uint32_t sq = base + hh * 8192, sk = sq + 32768, sv = sq + 65536, skm = base + 98304 + hh * 4096, svm = skm + 2048;
    const int g = lane >> 2, c = lane & 3, mi = lane >> 3, r8 = lane & 7;
    const int ntile = mh ? 5 : 3;
    float sc[5][4];
    #pragma unroll
    for (int j = 0; j < 5; j++) { sc[j][0] = sc[j][1] = sc[j][2] = sc[j][3] = 0.f; }
    #pragma unroll
    for (int t2 = 0; t2 < 4; t2++) {
        uint32_t a[2][4];
        #pragma unroll
        for (int h = 0; h < 2; h++) {
            const int row = mh * 16 + (mi & 1) * 8 + r8, ch16 = 4 * t2 + 2 * h + (mi >> 1);
            ldsm_x4(sq + (ch16 >> 3) * 4096 + row * 128 + (((ch16 & 7) ^ r8) << 4), a[h][0], a[h][1], a[h][2], a[h][3]);
        }
        const int ch16 = 4 * t2 + mi;
        uint32_t b[5][4];
        #pragma unroll
        for (int j = 0; j < 5; j++) {
            if (j < ntile) {
                if (j == 0) ldsm_x4_t(skm + t2 * 512 + lane * 16, b[j][0], b[j][1], b[j][2], b[j][3]);
                else ldsm_x4(sk + (ch16 >> 3) * 4096 + ((j - 1) * 8 + r8) * 128 + (((ch16 & 7) ^ r8) << 4), b[j][0], b[j][1], b[j][2], b[j][3]);
            }
        }
        #pragma unroll
        for (int h = 0; h < 2; h++) {
            #pragma unroll
            for (int j = 0; j < 5; j++)
                if (j < ntile) mma16816(sc[j], a[h][0], a[h][1], a[h][2], a[h][3], b[j][2 * h], b[j][2 * h + 1]);
        }
    }
    APROF(10);
    const float sl2 = 0.08838834764831845f * 1.4426950408889634f;
    uint32_t pf[2][5];
    float inv[2];
    #pragma unroll
    for (int q = 0; q < 2; q++) {
        const int tok = mh * 16 + q * 8 + g;
        float v[10];
        #pragma unroll
        for (int j = 0; j < 5; j++) {
            #pragma unroll
            for (int e = 0; e < 2; e++) {
                const int key = (j - 1) * 8 + 2 * c + e;
                v[2 * j + e] = (j == 0 || key <= tok) ? sc[j][2 * q + e] : -INFINITY;
            }
        }
        float mx = v[0];
        #pragma unroll
        for (int j = 1; j < 10; j++) mx = fmaxf(mx, v[j]);
        mx = fmaxf(mx, __shfl_xor_sync(~0u, mx, 1));
        mx = fmaxf(mx, __shfl_xor_sync(~0u, mx, 2));
        const float mo = mx * sl2;
        float sum = 0.f;
        #pragma unroll
        for (int j = 0; j < 10; j++) { v[j] = ex2(fmaf(v[j], sl2, -mo)); sum += v[j]; }
        sum += __shfl_xor_sync(~0u, sum, 1);
        sum += __shfl_xor_sync(~0u, sum, 2);
        inv[q] = rcp(sum);
        #pragma unroll
        for (int j = 0; j < 5; j++) pf[q][j] = pack_bf16(v[2 * j], v[2 * j + 1]);
    }
    APROF(11);
    auto load_v = [&](int n4, uint32_t (&vm)[4], uint32_t (&vt)[4][4]) {
        ldsm_x4(svm + n4 * 512 + lane * 16, vm[0], vm[1], vm[2], vm[3]);
        #pragma unroll
        for (int u = 0; u < 4; u++) {
            const int nt = 4 * n4 + u;
            ldsm_x4_t(sv + (nt >> 3) * 4096 + lane * 128 + (((nt & 7) ^ r8) << 4), vt[u][0], vt[u][1], vt[u][2], vt[u][3]);
        }
    };
    uint32_t vm[2][4], vt[2][4][4];
    load_v(0, vm[0], vt[0]);
    #pragma unroll
    for (int n4 = 0; n4 < 4; n4++) {
        const int cur = n4 & 1;
        if (n4 + 1 < 4) load_v(n4 + 1, vm[cur ^ 1], vt[cur ^ 1]);
        float o[4][4];
        #pragma unroll
        for (int u = 0; u < 4; u++) {
            o[u][0] = o[u][1] = o[u][2] = o[u][3] = 0.f;
            mma16816(o[u], pf[0][1], pf[1][1], pf[0][2], pf[1][2], vt[cur][u][0], vt[cur][u][1]);
        }
        if (mh) {
            #pragma unroll
            for (int u = 0; u < 4; u++) mma16816(o[u], pf[0][3], pf[1][3], pf[0][4], pf[1][4], vt[cur][u][2], vt[cur][u][3]);
        }
        #pragma unroll
        for (int u = 0; u < 4; u++) mma1688(o[u], pf[0][0], pf[1][0], vm[cur][u]);
        #pragma unroll
        for (int u = 0; u < 4; u += 2) {
            const int row = mh * 16 + (mi & 1) * 8 + r8, nt = 4 * n4 + u + (mi >> 1);
            stsm_x4(sq + (nt >> 3) * 4096 + row * 128 + (((nt & 7) ^ r8) << 4),
                    pack_bf16(o[u][0] * inv[0], o[u][1] * inv[0]), pack_bf16(o[u][2] * inv[1], o[u][3] * inv[1]),
                    pack_bf16(o[u + 1][0] * inv[0], o[u + 1][1] * inv[0]), pack_bf16(o[u + 1][2] * inv[1], o[u + 1][3] * inv[1]));
        }
    }
    __syncwarp();
    APROF(12);
    #pragma unroll
    for (int i = 0; i < 8; i++) {
        const int row = 2 * i + (lane >> 4), ch = lane & 15;
        const uint4 v = lds128(sq + (ch >> 3) * 4096 + (mh * 16 + row) * 128 + (((ch & 7) ^ (row & 7)) << 4));
        *reinterpret_cast<uint4*>(obase + (size_t)row * HD + ch * 8) = v;
    }
}

__device__ __forceinline__ void b_attn_warp(uint32_t base, int hl, int half, int tok0, int lane, __nv_bfloat16* obase) {
    const uint32_t sq = base, sk = base + 128 * 256, sv = base + (128 + 144) * 256;
    const int g = lane >> 2, c = lane & 3;
    auto addr = [&](uint32_t t, int row, int ch) { return t + row * 256 + ((ch ^ ((row >> 1) & 7)) << 4); };
    const float sl2 = 0.17677669529663687f * 1.4426950408889634f;
    #pragma unroll 2
    for (int blk = half * 4; blk < half * 4 + 4; blk++) {
        const int r0 = (blk >> 1) * 32 + (blk & 1);
        float sc[3][4];
        #pragma unroll
        for (int j = 0; j < 3; j++) { sc[j][0] = sc[j][1] = sc[j][2] = sc[j][3] = 0.f; }
        #pragma unroll
        for (int t = 0; t < 2; t++) {
            uint32_t a0, a1, a2, a3, b0, b1, b2, b3, d0, d1, d2, d3;
            const int mi = lane >> 3, r = lane & 7;
            ldsm_x4(addr(sq, r0 + 2 * ((mi & 1) * 8 + r), hl * 4 + 2 * t + (mi >> 1)), a0, a1, a2, a3);
            ldsm_x4(addr(sk, r0 + 2 + 2 * ((mi >> 1) * 8 + r), hl * 4 + 2 * t + (mi & 1)), b0, b1, b2, b3);
            ldsm_x4(addr(sk, min(r0 + 2 + 2 * (16 + r), 143), hl * 4 + 2 * t + (mi & 1)), d0, d1, d2, d3);
            mma16816(sc[0], a0, a1, a2, a3, b0, b1);
            mma16816(sc[1], a0, a1, a2, a3, b2, b3);
            mma16816(sc[2], a0, a1, a2, a3, d0, d1);
        }
        uint32_t pf[2][3];
        float inv[2];
        #pragma unroll
        for (int r = 0; r < 2; r++) {
            const int u = r * 8 + g;
            float v[6];
            #pragma unroll
            for (int j = 0; j < 3; j++) {
                #pragma unroll
                for (int e = 0; e < 2; e++) {
                    const int key = j * 8 + 2 * c + e;
                    const bool ok = key >= u && key <= u + 7 && tok0 + r0 - 14 + 2 * key >= 0;
                    v[2 * j + e] = ok ? sc[j][2 * r + e] : -INFINITY;
                }
            }
            float mx = fmaxf(fmaxf(fmaxf(v[0], v[1]), fmaxf(v[2], v[3])), fmaxf(v[4], v[5]));
            mx = fmaxf(mx, __shfl_xor_sync(~0u, mx, 1));
            mx = fmaxf(mx, __shfl_xor_sync(~0u, mx, 2));
            const float mo = mx * sl2;
            float sum = 0.f;
            #pragma unroll
            for (int j = 0; j < 6; j++) { v[j] = ex2(fmaf(v[j], sl2, -mo)); sum += v[j]; }
            sum += __shfl_xor_sync(~0u, sum, 1);
            sum += __shfl_xor_sync(~0u, sum, 2);
            inv[r] = rcp(sum);
            #pragma unroll
            for (int j = 0; j < 3; j++) pf[r][j] = pack_bf16(v[2 * j], v[2 * j + 1]);
        }
        uint32_t ow[4][2];
        {
            const int mi = lane >> 3, r = lane & 7;
            uint32_t vv[4][4];
            #pragma unroll
            for (int nt = 0; nt < 4; nt++)
                ldsm_x4_t(addr(sv, min(r0 + 2 + 2 * (min(mi, 2) * 8 + r), 143), hl * 4 + nt), vv[nt][0], vv[nt][1], vv[nt][2], vv[nt][3]);
            float o[4][4];
            #pragma unroll
            for (int nt = 0; nt < 4; nt++) {
                o[nt][0] = o[nt][1] = o[nt][2] = o[nt][3] = 0.f;
                mma16816(o[nt], pf[0][0], pf[1][0], pf[0][1], pf[1][1], vv[nt][0], vv[nt][1]);
            }
            #pragma unroll
            for (int nt = 0; nt < 4; nt++) mma1688(o[nt], pf[0][2], pf[1][2], vv[nt][2]);
            #pragma unroll
            for (int nt = 0; nt < 4; nt++) {
                ow[nt][0] = pack_bf16(o[nt][0] * inv[0], o[nt][1] * inv[0]);
                ow[nt][1] = pack_bf16(o[nt][2] * inv[1], o[nt][3] * inv[1]);
            }
        }
        #pragma unroll
        for (int u = 0; u < 4; u += 2) {
            const int mi = lane >> 3, r = lane & 7;
            stsm_x4(addr(sq, r0 + 2 * ((mi & 1) * 8 + r), hl * 4 + u + (mi >> 1)), ow[u][0], ow[u][1], ow[u + 1][0], ow[u + 1][1]);
        }
    }
    __syncwarp();
    #pragma unroll
    for (int i = 0; i < 8; i++) {
        const int row = half * 64 + i * 8 + (lane >> 2);
        const uint4 v = lds128(addr(sq, row, hl * 4 + (lane & 3)));
        *reinterpret_cast<uint4*>(obase + (size_t)row * DM + (lane & 3) * 8) = v;
    }
}

constexpr uint32_t QKVB_TARGET = 12 * 8;
constexpr uint32_t PROGRESS_TARGET = 96;
constexpr int ATT_A_TASKS = NSEG * 8;
constexpr int ATT_B_TASKS = 16 * 8;
constexpr uint32_t ATT_B_BIT = 0x10000u, ATT_DONE = 0xFFFFFFFFu;

constexpr uint32_t ATT_RETRY = 0xFFFFFFFEu;
__device__ __forceinline__ uint32_t attn_pick(uint32_t* flags) {
    const uint32_t ha = ld_relaxed_b32(flags + F_QUEUE3), hb = ld_relaxed_b32(flags + F_QUEUE4);
    const bool left_a = ha < ATT_A_TASKS, left_b = hb < ATT_B_TASKS;
    if (!left_a && !left_b) return ATT_DONE;
    uint32_t pa = left_a ? ld_relaxed_b32(flags + F_PROGRESS + (ha >> 3)) : 0u;
    const uint32_t pb = left_b ? ld_relaxed_b32(flags + F_QKVB + (hb >> 3)) : 0u;
    if (pa >= PROGRESS_TARGET || !left_b) {
        const uint32_t t = atomicAdd(flags + F_QUEUE3, 1u);
        if (t < ATT_A_TASKS) return t;
        if (!left_b) return ATT_DONE;
    }
    if (pb >= QKVB_TARGET) {
        const uint32_t t = atomicAdd(flags + F_QUEUE4, 1u);
        if (t < ATT_B_TASKS) return t | ATT_B_BIT;
    }
    return ATT_RETRY;
}

constexpr int ATT_THREADS = 288;
__global__ void __launch_bounds__(ATT_THREADS, 2) attn_kernel(const AttnParams p) {
    extern __shared__ uint8_t smem_raw[];
    const uint32_t sb = smem_u32(smem_raw), taskw = sb + ATT_TASKW;
    const int tid = threadIdx.x, warp = tid >> 5, lane = tid & 31;
    const uint32_t bar_ld = taskw + 8;
    if (tid == 0) {
        pdl_launch_dependents();
        mbar_init(bar_ld, 1);
        asm volatile("fence.mbarrier_init.release.cluster;" ::: "memory");
    }
    KENTER(3);
    __syncthreads();
    if (warp == 8) {
        auto pick = [&]() {
            uint32_t t, n = 0;
            while ((t = attn_pick(p.flags)) == ATT_RETRY) {
                __nanosleep(50);
                if (++n > SPIN_LIMIT) __trap();
            }
            return t;
        };
        uint32_t task = 0;
        if (lane == 0) task = pick();
        uint32_t* pending = nullptr;
        while (true) {
            if (lane == 0) asm volatile("st.shared.b32 [%0], %1;" ::"r"(taskw), "r"(task) : "memory");
            __syncwarp();
            named_bar_sync(1, ATT_THREADS);
            task = __shfl_sync(~0u, task, 0);
            if (lane == 0 && task != ATT_DONE && !(task & ATT_B_BIT)) {
                {
                    const uint32_t* fq = p.flags + F_PROGRESS + (task >> 3);
                    if (ld_acquire_b32(fq) < PROGRESS_TARGET) {
                        if (pending) { signal_flag(pending); pending = nullptr; }
                        wait_flag(fq, PROGRESS_TARGET);
                    }
                    asm volatile("fence.proxy.async;" ::: "memory");
                }
                asm volatile("fence.proxy.async.shared::cta;" ::: "memory");
                mbar_arrive_expect_tx(bar_ld, 3 * 32768);
                #pragma unroll
                for (int w = 0; w < 3; w++)
                    bulk_load(sb + w * 32768, p.qkv_tok + (((size_t)w * NSEG + (task >> 3)) * NH + (task & 7) * 4) * (SEG * DH), 32768, bar_ld);
            }
            if (task == ATT_DONE) {
                if (lane == 0 && pending) signal_flag(pending);
                break;
            }
            uint32_t* mine = nullptr;
            if (lane == 0) {
                const bool isb = task & ATT_B_BIT;
                const int mt = (task & 0xFFFF) >> 3;
                const uint32_t* dep = isb ? p.flags + F_QKVB + mt : p.flags + F_PROGRESS + mt;
                const uint32_t target = isb ? QKVB_TARGET : PROGRESS_TARGET;
                if (ld_acquire_b32(dep) < target) {
                    if (pending) { signal_flag(pending); pending = nullptr; }
                    wait_flag(dep, target);
                }
                if (isb && mt > 0) wait_flag(dep - 1, QKVB_TARGET);
                mine = isb ? p.flags + F_OB + mt : p.flags + F_OA + (mt >> 2);
            }
            __syncwarp();
            named_bar_sync(2, ATT_THREADS);
            if (lane == 0) {
                if (pending) signal_flag(pending);
                pending = mine;
            }
            uint32_t nxt = ATT_RETRY;
            if (lane == 0) nxt = attn_pick(p.flags);
            __syncwarp();
            named_bar_sync(3, ATT_THREADS);
            if (lane == 0) {
                if (nxt == ATT_RETRY) {
                    signal_flag(pending);
                    pending = nullptr;
                    nxt = pick();
                }
                task = nxt;
            }
        }
    } else {
        uint32_t ld_phase = 0;
        while (true) {
            named_bar_sync(1, ATT_THREADS);
            APROF(1);
            const uint32_t task = lds32_volatile(taskw);
            if (task == ATT_DONE) break;
            if (task & ATT_B_BIT) {
                const int mt = (task & 0xFFFF) >> 3, hg = task & 7, tok0 = mt * 128;
                named_bar_sync(2, ATT_THREADS);
                #pragma unroll 2
                for (int i = tid; i < 416 * 16; i += 256) {
                    const int row = i >> 4, ch = i & 15;
                    const int which = row < 128 ? 0 : (row < 272 ? 1 : 2);
                    const int r = row < 128 ? row : (row < 272 ? row - 128 : row - 272);
                    const int tok = which == 0 ? tok0 + r : max(tok0 - 16 + r, 0);
                    cp_async16(sb + row * 256 + ((ch ^ ((r >> 1) & 7)) << 4),
                               p.qkv_b + (size_t)tok * (3 * DM) + which * DM + hg * 128 + ch * 8);
                }
                cp_async_commit();
                cp_async_wait<0>();
                named_bar_sync(4, 256);
                APROF(8);
                b_attn_warp(sb, warp & 3, warp >> 2, tok0, lane, p.o_b + (size_t)tok0 * DM + hg * 128 + (warp & 3) * 32);
                APROF(9);
            } else {
                const int seg = task >> 3, hq = task & 7;
                APROF(2);
                named_bar_sync(2, ATT_THREADS);
                APROF(3);
                #pragma unroll
                for (int w = 0; w < 2; w++) {
                    const uint8_t* src = reinterpret_cast<const uint8_t*>(p.kv_mem + (((size_t)w * NSEG + seg) * NH + hq * 4) * (MROWS * DH));
                    #pragma unroll
                    for (int u = 0; u < 2; u++) {
                        const int e = u * 256 + tid;
                        cp_async16(sb + 98304 + (e >> 7) * 4096 + w * 2048 + (e & 127) * 16, src + e * 16);
                    }
                }
                cp_async_commit();
                cp_async_wait<0>();
                mbar_wait(bar_ld, ld_phase);
                ld_phase ^= 1;
                named_bar_sync(4, 256);
                APROF(4);
                const int hh = warp >> 1, mh = warp & 1;
                tok_attn_warp(sb, hh, mh, lane,
                              p.o_tok + (size_t)(seg * SEG + mh * 16) * HD + (hq * 4 + hh) * DH);
                APROF(7);
            }
            named_bar_sync(3, ATT_THREADS);
            APROF(0);
        }
    }
    if (tid == 256) KEXIT(3);
}

typedef CUresult (*EncodeFn)(CUtensorMap*, CUtensorMapDataType, cuuint32_t, void*, const cuuint64_t*, const cuuint64_t*,
                             const cuuint32_t*, const cuuint32_t*, CUtensorMapInterleave, CUtensorMapSwizzle,
                             CUtensorMapL2promotion, CUtensorMapFloatOOBfill);

void make_map_2d(EncodeFn enc, CUtensorMap* m, const void* ptr, uint64_t rows, uint64_t cols, uint32_t box_rows, uint32_t box_cols = 64) {
    cuuint64_t dims[2] = {cols, rows};
    cuuint64_t strides[1] = {cols * 2};
    cuuint32_t box[2] = {box_cols, box_rows};
    cuuint32_t es[2] = {1, 1};
    enc(m, CU_TENSOR_MAP_DATA_TYPE_BFLOAT16, 2, const_cast<void*>(ptr), dims, strides, box, es,
        CU_TENSOR_MAP_INTERLEAVE_NONE, box_cols == 64 ? CU_TENSOR_MAP_SWIZZLE_128B : CU_TENSOR_MAP_SWIZZLE_64B, CU_TENSOR_MAP_L2_PROMOTION_L2_256B,
        CU_TENSOR_MAP_FLOAT_OOB_FILL_NONE);
}
void make_map_b(EncodeFn enc, CUtensorMap* m, const void* ptr, uint64_t k, uint64_t n, uint32_t nblk, uint32_t box_rows = 64) {
    cuuint64_t dims[3] = {64, k, n / 64};
    cuuint64_t strides[2] = {n * 2, 128};
    cuuint32_t box[3] = {64, box_rows, nblk};
    cuuint32_t es[3] = {1, 1, 1};
    enc(m, CU_TENSOR_MAP_DATA_TYPE_BFLOAT16, 3, const_cast<void*>(ptr), dims, strides, box, es,
        CU_TENSOR_MAP_INTERLEAVE_NONE, CU_TENSOR_MAP_SWIZZLE_128B, CU_TENSOR_MAP_L2_PROMOTION_L2_256B,
        CU_TENSOR_MAP_FLOAT_OOB_FILL_NONE);
}

void make_map_w(EncodeFn enc, CUtensorMap* m, const void* ptr) {
    cuuint64_t dims[3] = {HD, 64, DM / 64};
    cuuint64_t strides[2] = {HD * 2, 64 * HD * 2};
    cuuint32_t box[3] = {64, 16, 8};
    cuuint32_t es[3] = {1, 1, 1};
    enc(m, CU_TENSOR_MAP_DATA_TYPE_BFLOAT16, 3, const_cast<void*>(ptr), dims, strides, box, es,
        CU_TENSOR_MAP_INTERLEAVE_NONE, CU_TENSOR_MAP_SWIZZLE_128B, CU_TENSOR_MAP_L2_PROMOTION_L2_256B,
        CU_TENSOR_MAP_FLOAT_OOB_FILL_NONE);
}

#define OUTB_SIDE_BLOCKS 8
#define SIDE_ORDER 0
#define N_POST_CTAS 0
#define N_POST_ATT 0
#define N_SIDE_CTAS 26
#define N_ATT_CTAS 20
#define TAIL_BLOCK0 12

struct HostState {
    bool ready;
    bool overlap;
    int n_side, n_att, n_sm;
    SideParams seq_a, seq_b;
    const void* key[11];
    RecParams rec;
    SideParams side, tail, outb;
    FinalParams fin;
    AttnParams attn;
    __nv_bfloat16 *qkv_tok, *kv_mem, *o_tok, *qkv_b, *o_b;
    uint8_t* xchg;
};
HostState g_host;

void setup(void* const* d_in, void* d_out) {
    HostState& h = g_host;
    void* fn = nullptr;
    cudaDriverEntryPointQueryResult qr;
    cudaGetDriverEntryPoint("cuTensorMapEncodeTiled", &fn, cudaEnableDefault, &qr);
    EncodeFn enc = reinterpret_cast<EncodeFn>(fn);
    void* ptr;
    cudaGetSymbolAddress(&ptr, g_qkv_tok); h.qkv_tok = (__nv_bfloat16*)ptr;
    cudaGetSymbolAddress(&ptr, g_kv_mem);  h.kv_mem = (__nv_bfloat16*)ptr;
    cudaGetSymbolAddress(&ptr, g_o_tok);   h.o_tok = (__nv_bfloat16*)ptr;
    cudaGetSymbolAddress(&ptr, g_qkv_b);   h.qkv_b = (__nv_bfloat16*)ptr;
    cudaGetSymbolAddress(&ptr, g_o_b);     h.o_b = (__nv_bfloat16*)ptr;
    cudaGetSymbolAddress(&ptr, g_xchg);    h.xchg = (uint8_t*)(((uint64_t)ptr + XCHG_BYTES - 1) & ~(uint64_t)(XCHG_BYTES - 1));
    cudaGetSymbolAddress(&ptr, g_ctacolor); int* ctacolor = (int*)ptr;
    cudaGetSymbolAddress(&ptr, g_flags);   uint32_t* flags = (uint32_t*)ptr;
    cudaGetSymbolAddress(&ptr, g_arrivals); uint32_t* arrivals = (uint32_t*)ptr;

    const void *xa = d_in[0], *mem0 = d_in[1], *wq = d_in[2], *wk = d_in[3], *wv = d_in[4], *wo = d_in[5];
    const void *xb = d_in[7], *wqkv = d_in[8], *wob = d_in[9];

    RecParams& r = h.rec;
    make_map_w(enc, &r.tmW[0], wq);
    make_map_w(enc, &r.tmW[1], wk);
    make_map_w(enc, &r.tmW[2], wv);
    make_map_2d(enc, &r.tmWo, wo, HD, DM, 128, 32);
    r.mem0 = (const __nv_bfloat16*)mem0;
    r.qkv_tok = h.qkv_tok; r.kv_mem = h.kv_mem; r.xchg = h.xchg; r.ctacolor = ctacolor;
    r.flags = flags; r.arrivals = arrivals; r.one[0] = r.one[1] = 1;
    make_map_b(enc, &r.tmX, xa, S_TOK, DM, 4, SEG);

    SideParams& sd = h.side;
    SideProb& p0 = sd.prob[0];
    make_map_2d(enc, &p0.tmA, xb, S_TOK, DM, BM);
    make_map_b(enc, &p0.tmB, wqkv, DM, 3 * DM, 4);
    make_map_2d(enc, &p0.tmC, h.qkv_b, S_TOK, 3 * DM, 16);
    p0.n_tiles = 3 * DM / 256; p0.k_blocks = DM / BK; p0.c_col0 = 0; p0.dep = nullptr; p0.dep_target = 0; p0.sig = flags + F_QKVB;
    SideProb& p1 = sd.prob[1];
    make_map_2d(enc, &p1.tmA, h.o_tok, S_TOK, HD, BM);
    make_map_b(enc, &p1.tmB, wo, HD, DM, 4);
    make_map_2d(enc, &p1.tmC, d_out, S_TOK, 2 * DM, 16);
    p1.n_tiles = DM / 256; p1.k_blocks = HD / BK; p1.c_col0 = 0; p1.dep = flags + F_OA; p1.dep_target = 32; p1.sig = nullptr;
    SideProb& p2 = sd.prob[2];
    make_map_2d(enc, &p2.tmA, h.o_b, S_TOK, DM, BM);
    make_map_b(enc, &p2.tmB, wob, DM, DM, 4);
    p2.tmC = p1.tmC;
    p2.n_tiles = DM / 256; p2.k_blocks = DM / BK; p2.c_col0 = DM; p2.dep = flags + F_OB; p2.dep_target = 8; p2.sig = nullptr;
    p0.tmB2 = p0.tmB; p1.tmB2 = p1.tmB; p2.tmB2 = p2.tmB;
    p0.n_split = p1.n_split = p2.n_split = 1 << 20;
    p0.blocked = p1.blocked = p2.blocked = nullptr;
    if (SIDE_ORDER == 0) { sd.seg[0] = {0, 0, 16}; sd.seg[1] = {1, 0, TAIL_BLOCK0}; }
    else { sd.seg[0] = {1, 0, TAIL_BLOCK0}; sd.seg[1] = {0, 0, 16}; }
    sd.seg[2] = {2, 0, OUTB_SIDE_BLOCKS};
    sd.nseg = 3; sd.queue = flags + F_SIDEQ;
    h.outb = sd;
    h.outb.seg[0] = {2, OUTB_SIDE_BLOCKS, 16};
    h.outb.nseg = 1; h.outb.queue = flags + F_OUTBQ;

    SideParams& tl = h.tail;
    tl.prob[0] = p1;
    make_map_b(enc, &tl.prob[0].tmB, wo, HD, DM, 2);
    tl.prob[0].n_tiles = DM / 128;
    tl.prob[0].tmB2 = tl.prob[0].tmB;
    tl.prob[1] = tl.prob[2] = tl.prob[3] = tl.prob[4] = tl.prob[0];
    tl.seg[0] = {0, TAIL_BLOCK0, 15};
    tl.nseg = 1; tl.queue = flags + F_TAILQ;

    h.fin.tmA = p1.tmA; h.fin.tmB = tl.prob[0].tmB; h.fin.out = (__nv_bfloat16*)d_out;
    h.fin.dep = flags + F_OA + 15; h.fin.dep_target = 32; h.fin.mt = 15;

    h.attn = {h.qkv_tok, h.kv_mem, h.o_tok, h.qkv_b, h.o_b, flags};

    int dev = 0, nsm = 0;
    cudaGetDevice(&dev);
    cudaDeviceGetAttribute(&nsm, cudaDevAttrMultiProcessorCount, dev);
    h.n_sm = nsm;
    h.overlap = nsm - 96 >= N_SIDE_CTAS + (N_ATT_CTAS + 1) / 2;
    h.n_side = N_SIDE_CTAS; h.n_att = N_ATT_CTAS;
    h.seq_a = sd;
    h.seq_a.seg[0] = {0, 0, 16};
    h.seq_a.seg[1] = {0, 16, 16};
    h.seq_a.nseg = 2;
    h.seq_b = sd;
    h.seq_b.seg[0] = {1, 0, 16};
    h.seq_b.seg[1] = {2, 0, 16};
    h.seq_b.nseg = 2; h.seq_b.queue = flags + F_TAILQ;

    cudaFuncSetAttribute(side_gemm_kernel<256>, cudaFuncAttributeMaxDynamicSharedMemorySize, GemmCfg<256>::SMEM);
    cudaFuncSetAttribute(side_gemm_kernel<128>, cudaFuncAttributeMaxDynamicSharedMemorySize, GemmCfg<128>::SMEM);
    cudaFuncSetAttribute(final_gemm_kernel, cudaFuncAttributeMaxDynamicSharedMemorySize, FIN_SMEM);
    cudaFuncSetAttribute(rec_kernel, cudaFuncAttributeMaxDynamicSharedMemorySize, REC_SMEM);
    cudaFuncSetAttribute(attn_kernel, cudaFuncAttributeMaxDynamicSharedMemorySize, ATT_SMEM);
    for (int i = 0; i < 10; i++) h.key[i] = d_in[i];
    h.key[10] = d_out;
    h.ready = true;
}

template <typename K, typename P>
void launch(K kernel, int grid, int block, int smem, cudaStream_t st, const P& prm, int cluster, bool pdl) {
    cudaLaunchConfig_t cfg = {};
    cfg.gridDim = dim3(grid); cfg.blockDim = dim3(block); cfg.dynamicSmemBytes = smem; cfg.stream = st;
    cudaLaunchAttribute at[2];
    int n = 0;
    if (cluster > 1) {
        at[n].id = cudaLaunchAttributeClusterDimension;
        at[n].val.clusterDim.x = cluster; at[n].val.clusterDim.y = 1; at[n].val.clusterDim.z = 1;
        n++;
    }
    if (pdl) {
        at[n].id = cudaLaunchAttributeProgrammaticStreamSerialization;
        at[n].val.programmaticStreamSerializationAllowed = 1;
        n++;
    }
    cfg.attrs = at; cfg.numAttrs = n;
    cudaLaunchKernelEx(&cfg, kernel, prm);
}

}

extern "C" void kernel_launch(void* const* d_in, const int* in_sizes, int n_in, void* d_out, int out_size) {
    HostState& h = g_host;
    bool same = h.ready;
    for (int i = 0; same && i < 10; i++) same = h.key[i] == d_in[i];
    if (!same || h.key[10] != d_out) setup(d_in, d_out);
    cudaStream_t st = cudaStreamPerThread;

    launch(rec_kernel, 96, REC_THREADS, REC_SMEM, st, h.rec, 3, false);
    {
        if (!h.overlap) {
            launch(side_gemm_kernel<256>, h.n_sm, 384, GemmCfg<256>::SMEM, st, h.seq_a, 1, false);
            launch(attn_kernel, 2 * h.n_sm, ATT_THREADS, ATT_SMEM, st, h.attn, 1, false);
            launch(side_gemm_kernel<256>, h.n_sm, 384, GemmCfg<256>::SMEM, st, h.seq_b, 1, false);
            return;
        }
    }
    launch(side_gemm_kernel<256>, h.n_side, 384, GemmCfg<256>::SMEM, st, h.side, 1, true);
    launch(attn_kernel, h.n_att, ATT_THREADS, ATT_SMEM, st, h.attn, 1, true);
    if (N_POST_ATT > 0) launch(attn_kernel, N_POST_ATT, ATT_THREADS, ATT_SMEM, st, h.attn, 1, true);
    if (N_POST_CTAS > 0) launch(side_gemm_kernel<256>, N_POST_CTAS, 384, GemmCfg<256>::SMEM, st, h.side, 1, true);
    launch(side_gemm_kernel<128>, (15 - TAIL_BLOCK0) * 8, 384, GemmCfg<128>::SMEM, st, h.tail, 1, true);
    launch(final_gemm_kernel, 8 * FIN_SPLIT, 384, FIN_SMEM, st, h.fin, FIN_SPLIT, true);
    if (OUTB_SIDE_BLOCKS < 16)
        launch(side_gemm_kernel<256>, (16 - OUTB_SIDE_BLOCKS) * 4, 384, GemmCfg<256>::SMEM, st, h.outb, 1, true);
}
```

```cpp
#include <cuda_runtime.h>
#include <cuda_bf16.h>
#include <cuda.h>
#include <stdint.h>

namespace {

constexpr int S_TOK = 2048;
constexpr int DM = 1024;
constexpr int NH = 32;
constexpr int DH = 128;
constexpr int HD = NH * DH;
constexpr int NSEG = 64;
constexpr int SEG = 32;
constexpr int MROWS = 8;
constexpr uint32_t SENT = 0xFFFFFFFFu;
constexpr uint32_t SPIN_LIMIT = 1u << 24;

__device__ __align__(1024) __nv_bfloat16 g_qkv_tok[3ull * NSEG * NH * SEG * DH];
__device__ __align__(1024) __nv_bfloat16 g_kv_mem[2ull * NSEG * NH * MROWS * DH];
__device__ __align__(1024) __nv_bfloat16 g_o_tok[(size_t)S_TOK * HD];
__device__ __align__(1024) __nv_bfloat16 g_qkv_b[(size_t)S_TOK * 3 * DM];
__device__ __align__(1024) __nv_bfloat16 g_o_b[(size_t)S_TOK * DM];
constexpr int PUB_BYTES = 32768;
constexpr int XCHG_SLOT = 1 << 20;
constexpr int XCHG_PUB = 0, XCHG_INBOX = 2 * PUB_BYTES;
constexpr int INBOX_MAX = 80;
constexpr int XCHG_BYTES = 2 * XCHG_SLOT;
__device__ __align__(8192) uint8_t g_xchg[2 * XCHG_BYTES];
__device__ int g_ctacolor[96];
enum { F_QUEUE3 = 3, F_QUEUE4 = 4, F_SIDEQ = 8, F_TAILQ = 16, F_OUTBQ = 24, F_PROGRESS = 32, F_QKVB = 96, F_OB = 112, F_OA = 128, F_COUNT = 144 };
__device__ uint32_t g_flags[F_COUNT];
__device__ uint32_t g_arrivals;

#define STAMP(k) do {} while (0)
#define STAMPD(k, x) do {} while (0)
#define PSTAMP(k) do {} while (0)
#define KENTER(k) do {} while (0)
#define APROF(k) do {} while (0)
#define KEXIT(k) do {} while (0)

__device__ __forceinline__ uint32_t class_off(uint64_t a, uint32_t c) {
    return ((__popc((uint32_t)a & 0xB3000u) ^ c) & 1u) << 12;
}
__device__ __forceinline__ uint32_t smem_u32(const void* p) { return (uint32_t)__cvta_generic_to_shared(p); }
__device__ __forceinline__ uint32_t pack_bf16(float lo, float hi) {
    uint32_t r;
    asm("cvt.rn.bf16x2.f32 %0, %1, %2;" : "=r"(r) : "f"(hi), "f"(lo));
    return r;
}
__device__ __forceinline__ float ex2(float x) {
    float y;
    asm("ex2.approx.ftz.f32 %0, %1;" : "=f"(y) : "f"(x));
    return y;
}
__device__ __forceinline__ float rcp(float x) {
    float y;
    asm("rcp.approx.ftz.f32 %0, %1;" : "=f"(y) : "f"(x));
    return y;
}
__device__ __forceinline__ uint32_t clock32() {
    uint32_t t;
    asm volatile("mov.u32 %0, %%clock;" : "=r"(t));
    return t;
}
__device__ __forceinline__ void spin_clks(uint32_t n) {
    if (n == 0) return;
    const uint32_t t0 = clock32();
    while (clock32() - t0 < n) {}
}
__device__ __forceinline__ void spin_until(uint32_t t) {
    while ((int)(clock32() - t) < 0) {}
}
__device__ __forceinline__ uint32_t clock_after(uint32_t x) {
    uint32_t t;
    asm volatile("{\n.reg .pred p;\nsetp.eq.u32 p, %1, 0x12345678;\n@p exit;\nmov.u32 %0, %%clock;\n}" : "=r"(t) : "r"(x) : "memory");
    return t;
}
__device__ __forceinline__ uint32_t opaque(uint32_t x) { return __shfl_sync(~0u, x, threadIdx.x & 31); }
__device__ __forceinline__ uint32_t uniform(uint32_t x) { return __shfl_sync(~0u, x + (threadIdx.x & 31), 0); }
__device__ __forceinline__ float bf16_lo(uint32_t w) { return __uint_as_float(w << 16); }
__device__ __forceinline__ float bf16_hi(uint32_t w) { return __uint_as_float(w & 0xFFFF0000u); }

__device__ __forceinline__ void mbar_init(uint32_t bar, uint32_t cnt) {
    asm volatile("mbarrier.init.shared::cta.b64 [%0], %1;" ::"r"(bar), "r"(cnt) : "memory");
}
__device__ __forceinline__ void mbar_arrive(uint32_t bar) {
    asm volatile("mbarrier.arrive.shared::cta.b64 _, [%0];" ::"r"(bar) : "memory");
}
__device__ __forceinline__ void mbar_arrive_expect_tx(uint32_t bar, uint32_t bytes) {
    asm volatile("mbarrier.arrive.expect_tx.shared::cta.b64 _, [%0], %1;" ::"r"(bar), "r"(bytes) : "memory");
}
__device__ __forceinline__ bool mbar_try_wait(uint32_t bar, uint32_t parity) {
    uint32_t ok;
    asm volatile(
        "{\n.reg .pred p;\n"
        "mbarrier.try_wait.parity.shared::cta.b64 p, [%1], %2;\n"
        "selp.u32 %0, 1, 0, p;\n}"
        : "=r"(ok) : "r"(bar), "r"(parity) : "memory");
    return ok != 0;
}
__device__ __forceinline__ void mbar_wait(uint32_t bar, uint32_t parity) {
    uint32_t n = 0;
    while (!mbar_try_wait(bar, parity)) {
        if (++n > SPIN_LIMIT) __trap();
    }
}
__device__ __forceinline__ void mbar_wait_bounded(uint32_t bar, uint32_t parity) {
    for (uint32_t n = 0; n < (1u << 20) && !mbar_try_wait(bar, parity); n++) {}
}
__device__ __forceinline__ bool elect_one() {
    uint32_t ok;
    asm volatile("{\n.reg .pred p;\nelect.sync _|p, 0xFFFFFFFF;\nselp.u32 %0, 1, 0, p;\n}" : "=r"(ok));
    return ok != 0;
}
__device__ __forceinline__ void named_bar_sync(int id, int nthreads) {
    asm volatile("bar.sync %0, %1;" ::"r"(id), "r"(nthreads) : "memory");
}
__device__ __forceinline__ void named_bar_arrive(int id, int nthreads) {
    asm volatile("bar.arrive %0, %1;" ::"r"(id), "r"(nthreads) : "memory");
}
__device__ __forceinline__ void cluster_sync() {
    asm volatile("barrier.cluster.arrive.release.aligned;\nbarrier.cluster.wait.acquire.aligned;" ::: "memory");
}
__device__ __forceinline__ uint32_t mapa(uint32_t addr, uint32_t rank) {
    uint32_t r;
    asm volatile("mapa.shared::cluster.u32 %0, %1, %2;" : "=r"(r) : "r"(addr), "r"(rank));
    return r;
}

__device__ __forceinline__ void tma_load_2d(uint32_t dst, const CUtensorMap* tm, int c0, int c1, uint32_t bar) {
    asm volatile(
        "cp.async.bulk.tensor.2d.shared::cluster.global.mbarrier::complete_tx::bytes [%0], [%1, {%3, %4}], [%2];"
        ::"r"(dst), "l"(tm), "r"(bar), "r"(c0), "r"(c1) : "memory");
}
__device__ __forceinline__ void tma_load_3d(uint32_t dst, const CUtensorMap* tm, int c0, int c1, int c2, uint32_t bar) {
    asm volatile(
        "cp.async.bulk.tensor.3d.shared::cluster.global.mbarrier::complete_tx::bytes [%0], [%1, {%3, %4, %5}], [%2];"
        ::"r"(dst), "l"(tm), "r"(bar), "r"(c0), "r"(c1), "r"(c2) : "memory");
}
__device__ __forceinline__ void tma_load_3d_mc(uint32_t dst, const CUtensorMap* tm, int c0, int c1, int c2, uint32_t bar, uint16_t mask) {
    asm volatile(
        "cp.async.bulk.tensor.3d.shared::cluster.global.mbarrier::complete_tx::bytes.multicast::cluster [%0], [%1, {%3, %4, %5}], [%2], %6;"
        ::"r"(dst), "l"(tm), "r"(bar), "r"(c0), "r"(c1), "r"(c2), "h"(mask) : "memory");
}
__device__ __forceinline__ void tma_store_2d(const CUtensorMap* tm, uint32_t src, int c0, int c1) {
    asm volatile("cp.async.bulk.tensor.2d.global.shared::cta.bulk_group [%0, {%2, %3}], [%1];"
                 ::"l"(tm), "r"(src), "r"(c0), "r"(c1) : "memory");
}
__device__ __forceinline__ void bulk_store(void* dst, uint32_t src, uint32_t bytes) {
    asm volatile("cp.async.bulk.global.shared::cta.bulk_group [%0], [%1], %2;" ::"l"(dst), "r"(src), "r"(bytes) : "memory");
}
__device__ __forceinline__ void bulk_commit() { asm volatile("cp.async.bulk.commit_group;" ::: "memory"); }
__device__ __forceinline__ void bulk_wait_read_all() { asm volatile("cp.async.bulk.wait_group.read 0;" ::: "memory"); }
__device__ __forceinline__ void bulk_wait_all() { asm volatile("cp.async.bulk.wait_group 0;" ::: "memory"); }
__device__ __forceinline__ void bulk_load(uint32_t dst, const void* src, uint32_t bytes, uint32_t bar) {
    asm volatile("cp.async.bulk.shared::cluster.global.mbarrier::complete_tx::bytes [%0], [%1], %2, [%3];"
                 ::"r"(dst), "l"(src), "r"(bytes), "r"(bar) : "memory");
}
__device__ __forceinline__ void bulk_load_mc(uint32_t dst, const void* src, uint32_t bytes, uint32_t bar, uint16_t mask) {
    asm volatile(
        "cp.async.bulk.shared::cluster.global.mbarrier::complete_tx::bytes.multicast::cluster [%0], [%1], %2, [%3], %4;"
        ::"r"(dst), "l"(src), "r"(bytes), "r"(bar), "h"(mask) : "memory");
}
__device__ __forceinline__ void cp_async16(uint32_t dst, const void* src) {
    asm volatile("cp.async.cg.shared.global [%0], [%1], 16;" ::"r"(dst), "l"(src) : "memory");
}
__device__ __forceinline__ void cp_async_commit() { asm volatile("cp.async.commit_group;" ::: "memory"); }
template <int N> __device__ __forceinline__ void cp_async_wait() {
    asm volatile("cp.async.wait_group %0;" ::"n"(N) : "memory");
}

__device__ __forceinline__ void ldsm_x4(uint32_t addr, uint32_t& r0, uint32_t& r1, uint32_t& r2, uint32_t& r3) {
    asm volatile("ldmatrix.sync.aligned.m8n8.x4.shared.b16 {%0,%1,%2,%3}, [%4];"
                 : "=r"(r0), "=r"(r1), "=r"(r2), "=r"(r3) : "r"(addr) : "memory");
}
__device__ __forceinline__ void ldsm_x4_t(uint32_t addr, uint32_t& r0, uint32_t& r1, uint32_t& r2, uint32_t& r3) {
    asm volatile("ldmatrix.sync.aligned.m8n8.x4.trans.shared.b16 {%0,%1,%2,%3}, [%4];"
                 : "=r"(r0), "=r"(r1), "=r"(r2), "=r"(r3) : "r"(addr) : "memory");
}
__device__ __forceinline__ void stsm_x4(uint32_t addr, uint32_t r0, uint32_t r1, uint32_t r2, uint32_t r3) {
    asm volatile("stmatrix.sync.aligned.m8n8.x4.shared.b16 [%0], {%1,%2,%3,%4};"
                 ::"r"(addr), "r"(r0), "r"(r1), "r"(r2), "r"(r3) : "memory");
}
__device__ __forceinline__ uint32_t movmat(uint32_t a) {
    uint32_t d;
    asm volatile("movmatrix.sync.aligned.m8n8.trans.b16 %0, %1;" : "=r"(d) : "r"(a));
    return d;
}
__device__ __forceinline__ void mma16816(float* d, uint32_t a0, uint32_t a1, uint32_t a2, uint32_t a3,
                                         uint32_t b0, uint32_t b1) {
    asm volatile(
        "mma.sync.aligned.m16n8k16.row.col.f32.bf16.bf16.f32 {%0,%1,%2,%3}, {%4,%5,%6,%7}, {%8,%9}, {%0,%1,%2,%3};"
        : "+f"(d[0]), "+f"(d[1]), "+f"(d[2]), "+f"(d[3])
        : "r"(a0), "r"(a1), "r"(a2), "r"(a3), "r"(b0), "r"(b1));
}
__device__ __forceinline__ void mma1688(float* d, uint32_t a0, uint32_t a1, uint32_t b0) {
    asm volatile("mma.sync.aligned.m16n8k8.row.col.f32.bf16.bf16.f32 {%0,%1,%2,%3}, {%4,%5}, {%6}, {%0,%1,%2,%3};"
                 : "+f"(d[0]), "+f"(d[1]), "+f"(d[2]), "+f"(d[3]) : "r"(a0), "r"(a1), "r"(b0));
}
__device__ __forceinline__ uint32_t any_reg() {
    uint32_t r;
    asm volatile("" : "=r"(r));
    return r;
}
__device__ __forceinline__ uint2 lds64(uint32_t addr) {
    uint2 v;
    asm volatile("ld.volatile.shared.v2.b32 {%0,%1}, [%2];" : "=r"(v.x), "=r"(v.y) : "r"(addr) : "memory");
    return v;
}
__device__ __forceinline__ uint4 lds128(uint32_t addr) {
    uint4 v;
    asm volatile("ld.volatile.shared.v4.b32 {%0,%1,%2,%3}, [%4];" : "=r"(v.x), "=r"(v.y), "=r"(v.z), "=r"(v.w) : "r"(addr) : "memory");
    return v;
}
__device__ __forceinline__ void sts32(uint32_t addr, uint32_t x) {
    asm volatile("st.volatile.shared.b32 [%0], %1;" ::"r"(addr), "r"(x) : "memory");
}
__device__ __forceinline__ void sts64(uint32_t addr, uint32_t x, uint32_t y) {
    asm volatile("st.volatile.shared.v2.b32 [%0], {%1,%2};" ::"r"(addr), "r"(x), "r"(y) : "memory");
}
__device__ __forceinline__ void sts128(uint32_t addr, uint32_t x, uint32_t y, uint32_t z, uint32_t w) {
    asm volatile("st.volatile.shared.v4.b32 [%0], {%1,%2,%3,%4};" ::"r"(addr), "r"(x), "r"(y), "r"(z), "r"(w) : "memory");
}
__device__ __forceinline__ void st_async_v2(uint32_t addr, uint32_t x, uint32_t y, uint32_t bar) {
    asm volatile("st.async.weak.shared::cluster.mbarrier::complete_tx::bytes.v2.b32 [%0], {%1,%2}, [%3];"
                 ::"r"(addr), "r"(x), "r"(y), "r"(bar) : "memory");
}
__device__ __forceinline__ uint2 ld_relaxed_v2(const void* p) {
    uint2 v;
    asm volatile("ld.relaxed.gpu.global.v2.b32 {%0,%1}, [%2];" : "=r"(v.x), "=r"(v.y) : "l"(p) : "memory");
    return v;
}
__device__ __forceinline__ void st_relaxed_v2(void* p, uint32_t x, uint32_t y) {
    asm volatile("st.relaxed.gpu.global.v2.b32 [%0], {%1,%2};" ::"l"(p), "r"(x), "r"(y) : "memory");
}
__device__ __forceinline__ void st_relaxed_v4(void* p, uint32_t x) {
    asm volatile("st.relaxed.gpu.global.v4.b32 [%0], {%1,%1,%1,%1};" ::"l"(p), "r"(x) : "memory");
}
__device__ __forceinline__ uint32_t ld_relaxed_b32(const void* p) {
    uint32_t v;
    asm volatile("ld.relaxed.gpu.global.b32 %0, [%1];" : "=r"(v) : "l"(p) : "memory");
    return v;
}
__device__ __forceinline__ uint32_t lds32_volatile(uint32_t addr) {
    uint32_t v;
    asm volatile("ld.volatile.shared.b32 %0, [%1];" : "=r"(v) : "r"(addr) : "memory");
    return v;
}
__device__ __forceinline__ void st_relaxed_b32(void* p, uint32_t x) {
    asm volatile("st.relaxed.gpu.global.b32 [%0], %1;" ::"l"(p), "r"(x) : "memory");
}

__device__ __forceinline__ uint32_t ld_acquire_b32(const void* p) {
    uint32_t v;
    asm volatile("ld.acquire.gpu.global.b32 %0, [%1];" : "=r"(v) : "l"(p) : "memory");
    return v;
}
__device__ __forceinline__ void wait_flag(const uint32_t* p, uint32_t target) {
    uint32_t n = 0;
    while (ld_acquire_b32(p) < target) {
        __nanosleep(64);
        if (++n > SPIN_LIMIT) __trap();
    }
}
__device__ __forceinline__ void signal_flag(uint32_t* p) {
    asm volatile("red.release.gpu.global.add.u32 [%0], 1;" ::"l"(p) : "memory");
}
__device__ __forceinline__ void pdl_launch_dependents() { asm volatile("griddepcontrol.launch_dependents;" ::: "memory"); }

constexpr int BM = 128, BK = 64;
constexpr int A_STAGE = BM * BK * 2;
template <int BN> struct GemmCfg {
    static constexpr int STAGES = BN == 256 ? 3 : 6;
    static constexpr int STAGE = A_STAGE + BK * BN * 2;
    static constexpr int EPI_WARP = 16 * BN * 2;
    static constexpr int SMEM = STAGES * STAGE + 8 * EPI_WARP + 1024 + 512;
};

struct SideProb {
    CUtensorMap tmA, tmB, tmB2, tmC;
    int n_split;
    int n_tiles, k_blocks, c_col0;
    const uint32_t* dep;
    uint32_t dep_target;
    uint32_t* sig;
    __nv_bfloat16* blocked;
};
struct SideSeg { int prob, m0, m1; };
constexpr int SIDE_MAX_SEG = 6;
struct SideParams {
    SideProb prob[5];
    SideSeg seg[SIDE_MAX_SEG];
    int nseg;
    uint32_t* queue;
};
static_assert(sizeof(SideParams) <= 4096, "kernel parameter limit");

__device__ __forceinline__ uint64_t make_desc(uint32_t addr, uint32_t lbo, uint32_t sbo) {
    return (uint64_t)((addr & 0x3FFFF) >> 4) | ((uint64_t)(lbo >> 4) << 16) | ((uint64_t)(sbo >> 4) << 32) | (1ull << 62);
}

__device__ __forceinline__ void wgmma_m64n256k16(float (&d)[128], uint64_t da, uint64_t db, int scale_d) {
    asm volatile(
        "{\n.reg .pred p;\nsetp.ne.b32 p, %130, 0;\n"
        "wgmma.mma_async.sync.aligned.m64n256k16.f32.bf16.bf16 "
        "{%0,%1,%2,%3,%4,%5,%6,%7,%8,%9,%10,%11,%12,%13,%14,%15,"
        "%16,%17,%18,%19,%20,%21,%22,%23,%24,%25,%26,%27,%28,%29,%30,%31,"
        "%32,%33,%34,%35,%36,%37,%38,%39,%40,%41,%42,%43,%44,%45,%46,%47,"
        "%48,%49,%50,%51,%52,%53,%54,%55,%56,%57,%58,%59,%60,%61,%62,%63,"
        "%64,%65,%66,%67,%68,%69,%70,%71,%72,%73,%74,%75,%76,%77,%78,%79,"
        "%80,%81,%82,%83,%84,%85,%86,%87,%88,%89,%90,%91,%92,%93,%94,%95,"
        "%96,%97,%98,%99,%100,%101,%102,%103,%104,%105,%106,%107,%108,%109,%110,%111,"
        "%112,%113,%114,%115,%116,%117,%118,%119,%120,%121,%122,%123,%124,%125,%126,%127},"
        " %128, %129, p, 1, 1, 0, 1;\n}\n"
        : "+f"(d[0]), "+f"(d[1]), "+f"(d[2]), "+f"(d[3]), "+f"(d[4]), "+f"(d[5]), "+f"(d[6]), "+f"(d[7]),
          "+f"(d[8]), "+f"(d[9]), "+f"(d[10]), "+f"(d[11]), "+f"(d[12]), "+f"(d[13]), "+f"(d[14]), "+f"(d[15]),
          "+f"(d[16]), "+f"(d[17]), "+f"(d[18]), "+f"(d[19]), "+f"(d[20]), "+f"(d[21]), "+f"(d[22]), "+f"(d[23]),
          "+f"(d[24]), "+f"(d[25]), "+f"(d[26]), "+f"(d[27]), "+f"(d[28]), "+f"(d[29]), "+f"(d[30]), "+f"(d[31]),
          "+f"(d[32]), "+f"(d[33]), "+f"(d[34]), "+f"(d[35]), "+f"(d[36]), "+f"(d[37]), "+f"(d[38]), "+f"(d[39]),
          "+f"(d[40]), "+f"(d[41]), "+f"(d[42]), "+f"(d[43]), "+f"(d[44]), "+f"(d[45]), "+f"(d[46]), "+f"(d[47]),
          "+f"(d[48]), "+f"(d[49]), "+f"(d[50]), "+f"(d[51]), "+f"(d[52]), "+f"(d[53]), "+f"(d[54]), "+f"(d[55]),
          "+f"(d[56]), "+f"(d[57]), "+f"(d[58]), "+f"(d[59]), "+f"(d[60]), "+f"(d[61]), "+f"(d[62]), "+f"(d[63]),
          "+f"(d[64]), "+f"(d[65]), "+f"(d[66]), "+f"(d[67]), "+f"(d[68]), "+f"(d[69]), "+f"(d[70]), "+f"(d[71]),
          "+f"(d[72]), "+f"(d[73]), "+f"(d[74]), "+f"(d[75]), "+f"(d[76]), "+f"(d[77]), "+f"(d[78]), "+f"(d[79]),
          "+f"(d[80]), "+f"(d[81]), "+f"(d[82]), "+f"(d[83]), "+f"(d[84]), "+f"(d[85]), "+f"(d[86]), "+f"(d[87]),
          "+f"(d[88]), "+f"(d[89]), "+f"(d[90]), "+f"(d[91]), "+f"(d[92]), "+f"(d[93]), "+f"(d[94]), "+f"(d[95]),
          "+f"(d[96]), "+f"(d[97]), "+f"(d[98]), "+f"(d[99]), "+f"(d[100]), "+f"(d[101]), "+f"(d[102]), "+f"(d[103]),
          "+f"(d[104]), "+f"(d[105]), "+f"(d[106]), "+f"(d[107]), "+f"(d[108]), "+f"(d[109]), "+f"(d[110]), "+f"(d[111]),
          "+f"(d[112]), "+f"(d[113]), "+f"(d[114]), "+f"(d[115]), "+f"(d[116]), "+f"(d[117]), "+f"(d[118]), "+f"(d[119]),
          "+f"(d[120]), "+f"(d[121]), "+f"(d[122]), "+f"(d[123]), "+f"(d[124]), "+f"(d[125]), "+f"(d[126]), "+f"(d[127])
        : "l"(da), "l"(db), "r"(scale_d));
}

__device__ __forceinline__ void wgmma_m64n128k16(float (&d)[64], uint64_t da, uint64_t db, int scale_d) {
    asm volatile(
        "{\n.reg .pred p;\nsetp.ne.b32 p, %66, 0;\n"
        "wgmma.mma_async.sync.aligned.m64n128k16.f32.bf16.bf16 "
        "{%0,%1,%2,%3,%4,%5,%6,%7,%8,%9,%10,%11,%12,%13,%14,%15,"
        "%16,%17,%18,%19,%20,%21,%22,%23,%24,%25,%26,%27,%28,%29,%30,%31,"
        "%32,%33,%34,%35,%36,%37,%38,%39,%40,%41,%42,%43,%44,%45,%46,%47,"
        "%48,%49,%50,%51,%52,%53,%54,%55,%56,%57,%58,%59,%60,%61,%62,%63},"
        " %64, %65, p, 1, 1, 0, 1;\n}\n"
        : "+f"(d[0]), "+f"(d[1]), "+f"(d[2]), "+f"(d[3]), "+f"(d[4]), "+f"(d[5]), "+f"(d[6]), "+f"(d[7]),
          "+f"(d[8]), "+f"(d[9]), "+f"(d[10]), "+f"(d[11]), "+f"(d[12]), "+f"(d[13]), "+f"(d[14]), "+f"(d[15]),
          "+f"(d[16]), "+f"(d[17]), "+f"(d[18]), "+f"(d[19]), "+f"(d[20]), "+f"(d[21]), "+f"(d[22]), "+f"(d[23]),
          "+f"(d[24]), "+f"(d[25]), "+f"(d[26]), "+f"(d[27]), "+f"(d[28]), "+f"(d[29]), "+f"(d[30]), "+f"(d[31]),
          "+f"(d[32]), "+f"(d[33]), "+f"(d[34]), "+f"(d[35]), "+f"(d[36]), "+f"(d[37]), "+f"(d[38]), "+f"(d[39]),
          "+f"(d[40]), "+f"(d[41]), "+f"(d[42]), "+f"(d[43]), "+f"(d[44]), "+f"(d[45]), "+f"(d[46]), "+f"(d[47]),
          "+f"(d[48]), "+f"(d[49]), "+f"(d[50]), "+f"(d[51]), "+f"(d[52]), "+f"(d[53]), "+f"(d[54]), "+f"(d[55]),
          "+f"(d[56]), "+f"(d[57]), "+f"(d[58]), "+f"(d[59]), "+f"(d[60]), "+f"(d[61]), "+f"(d[62]), "+f"(d[63])
        : "l"(da), "l"(db), "r"(scale_d));
}
template <int BN> struct WgmmaOp;
template <> struct WgmmaOp<256> {
    static __device__ __forceinline__ void run(float (&d)[128], uint64_t a, uint64_t b, int sc) { wgmma_m64n256k16(d, a, b, sc); }
};
template <> struct WgmmaOp<128> {
    static __device__ __forceinline__ void run(float (&d)[64], uint64_t a, uint64_t b, int sc) { wgmma_m64n128k16(d, a, b, sc); }
};

struct StoreRec {
    uint64_t dst;
    uint64_t flag;
    int kind;
    int pad;
};
struct EpiCtx { uint32_t buf, rec, st_full, st_empty; uint32_t it; int lane; };
template <int N>
__device__ __forceinline__ void epi_hand_over(const float (&acc)[N], EpiCtx& e, uint64_t dst, uint64_t flag, int kind) {
    mbar_wait(e.st_empty, (e.it & 1) ^ 1);
    const int mi = e.lane >> 3, row = (mi & 1) * 8 + (e.lane & 7);
    #pragma unroll
    for (int j = 0; j < N / 4; j += 2) {
        const int chunk = (j & 7) + (mi >> 1);
        stsm_x4(e.buf + (j >> 3) * 2048 + row * 128 + ((chunk ^ (row & 7)) << 4),
                pack_bf16(acc[4 * j], acc[4 * j + 1]), pack_bf16(acc[4 * j + 2], acc[4 * j + 3]),
                pack_bf16(acc[4 * j + 4], acc[4 * j + 5]), pack_bf16(acc[4 * j + 6], acc[4 * j + 7]));
    }
    if (e.lane == 0) {
        asm volatile("st.shared.v2.b64 [%0], {%1, %2};" ::"r"(e.rec), "l"(dst), "l"(flag) : "memory");
        asm volatile("st.shared.b32 [%0], %1;" ::"r"(e.rec + 16), "r"(kind) : "memory");
    }
    asm volatile("fence.proxy.async.shared::cta;" ::: "memory");
    __syncwarp();
    if (e.lane == 0) mbar_arrive(e.st_full);
    e.it++;
}
__device__ __forceinline__ void epi_exit(EpiCtx& e) {
    mbar_wait(e.st_empty, (e.it & 1) ^ 1);
    if (e.lane == 0) {
        asm volatile("st.shared.b32 [%0], %1;" ::"r"(e.rec + 16), "r"(-1) : "memory");
        mbar_arrive(e.st_full);
    }
}
template <int BN, bool PAIR = false>
__device__ __forceinline__ void gemm_mainloop(float (&acc)[BN / 2], int k_blocks, uint32_t sbase, uint32_t bar_base, int cw,
                                              bool elected, int& stage, uint32_t& phase, uint32_t peer = 0) {
    using C = GemmCfg<BN>;
    auto release = [&](int st) {
        const uint32_t bar = bar_base + 8 * (C::STAGES + st);
        mbar_arrive(bar);
        if (PAIR) asm volatile("mbarrier.arrive.shared::cluster.b64 _, [%0];" ::"r"(mapa(bar, peer)) : "memory");
    };
    int prev_stage = -1;
    for (int kb = 0; kb < k_blocks; kb++) {
        mbar_wait(bar_base + 8 * stage, phase);
        const uint32_t sa = sbase + stage * C::STAGE + cw * (64 * 128);
        const uint32_t sb = sbase + stage * C::STAGE + A_STAGE;
        asm volatile("wgmma.fence.sync.aligned;" ::: "memory");
        #pragma unroll
        for (int kk = 0; kk < BK / 16; kk++)
            WgmmaOp<BN>::run(acc, make_desc(sa + kk * 32, 16, 1024), make_desc(sb + kk * 2048, 8192, 1024), (kb | kk) != 0);
        asm volatile("wgmma.commit_group.sync.aligned;" ::: "memory");
        asm volatile("wgmma.wait_group.sync.aligned 1;" ::: "memory");
        if (prev_stage >= 0 && elected) release(prev_stage);
        prev_stage = stage;
        if (++stage == C::STAGES) { stage = 0; phase ^= 1; }
    }
    asm volatile("wgmma.wait_group.sync.aligned 0;" ::: "memory");
    if (elected) release(prev_stage);
}
template <int BN>
__device__ __forceinline__ void store_warp(uint32_t epi_base, uint32_t rec_base, uint32_t st_full, uint32_t st_empty, int lane,
                                           const uint8_t* tmaps, int tstride) {
    for (uint32_t it = 0;; it++) {
        mbar_wait(st_full, it & 1);
        uint64_t dst = 0, flag = 0;
        int kind = -1;
        if (lane < 8) {
            const uint32_t rec = rec_base + lane * 32;
            asm volatile("ld.volatile.shared.v2.b64 {%0, %1}, [%2];" : "=l"(dst), "=l"(flag) : "r"(rec) : "memory");
            kind = (int)lds32_volatile(rec + 16);
        }
        if (__shfl_sync(~0u, kind, 0) < 0) break;
        if (lane < 8) {
            const uint32_t buf = epi_base + lane * GemmCfg<BN>::EPI_WARP;
            #pragma unroll
            for (int q = 0; q < BN / 64; q++) {
                if (kind == 0) bulk_store(reinterpret_cast<__nv_bfloat16*>(dst) + q * (SEG * 64), buf + q * 2048, 2048);
                else tma_store_2d(reinterpret_cast<const CUtensorMap*>(tmaps + (kind - 1) * tstride), buf + q * 2048,
                                  (int)(uint32_t)dst + q * 64, (int)(dst >> 32));
            }
            bulk_commit();
            bulk_wait_read_all();
            mbar_arrive(st_empty);
            if (flag) {
                bulk_wait_all();
                asm volatile("fence.proxy.async;" ::: "memory");
                signal_flag(reinterpret_cast<uint32_t*>(flag));
            }
        }
        __syncwarp();
    }
    if (lane < 8) bulk_wait_all();
}

template <int BN>
__global__ void __launch_bounds__(384, 1) side_gemm_kernel(const __grid_constant__ SideParams p) {
    using C = GemmCfg<BN>;
    extern __shared__ uint8_t smem_raw[];
    const uint32_t sbase = (smem_u32(smem_raw) + 1023) & ~1023u;
    const uint32_t epi_base = sbase + C::STAGES * C::STAGE;
    const uint32_t bar_base = epi_base + 8 * C::EPI_WARP;
    const uint32_t tfull = bar_base + 16 * C::STAGES, tempty = tfull + 16, tslot = tempty + 16;
    const uint32_t st_full = bar_base + 192, st_empty = st_full + 8, rec_base = bar_base + 256;
    const int tid = threadIdx.x, wg = tid >> 7;
    if (tid == 0) {
        for (int s = 0; s < C::STAGES; s++) { mbar_init(bar_base + 8 * s, 1); mbar_init(bar_base + 8 * (C::STAGES + s), 2); }
        for (int s = 0; s < 2; s++) { mbar_init(tfull + 8 * s, 1); mbar_init(tempty + 8 * s, 2); }
        mbar_init(st_full, 8);
        mbar_init(st_empty, 8);
        asm volatile("fence.mbarrier_init.release.cluster;" ::: "memory");
        pdl_launch_dependents();
    }
    __syncthreads();
    KENTER(BN == 256 ? (p.nseg == 1 ? 6 : 2) : 4);

    if (wg == 0) {
        asm volatile("setmaxnreg.dec.sync.aligned.u32 40;");
        if (tid == 0) {
            int stage = 0; uint32_t phase = 1;
            for (uint32_t it = 0;; it++) {
                int pr = -1, mt = 0, nt = 0;
                for (uint32_t tries = 0;; tries++) {
                    uint32_t head[SIDE_MAX_SEG], ready[SIDE_MAX_SEG];
                    #pragma unroll
                    for (int g = 0; g < SIDE_MAX_SEG; g++) head[g] = g < p.nseg ? ld_relaxed_b32(p.queue + g) : 0xFFFFFFFFu;
                    bool left = false;
                    #pragma unroll
                    for (int g = 0; g < SIDE_MAX_SEG; g++) {
                        ready[g] = 0;
                        if (g < p.nseg) {
                            const SideProb& q = p.prob[p.seg[g].prob];
                            if (head[g] < (uint32_t)((p.seg[g].m1 - p.seg[g].m0) * q.n_tiles)) {
                                left = true;
                                ready[g] = q.dep ? ld_relaxed_b32(q.dep + p.seg[g].m0 + head[g] / q.n_tiles) >= q.dep_target : 1u;
                            }
                        }
                    }
                    if (!left) break;
                    #pragma unroll
                    for (int g = 0; g < SIDE_MAX_SEG; g++) {
                        if (pr < 0 && ready[g]) {
                            const int nts = p.prob[p.seg[g].prob].n_tiles;
                            const uint32_t idx = atomicAdd(p.queue + g, 1u);
                            if (idx < (uint32_t)((p.seg[g].m1 - p.seg[g].m0) * nts)) {
                                pr = p.seg[g].prob; mt = p.seg[g].m0 + idx / nts; nt = idx % nts;
                            }
                        }
                    }
                    if (pr >= 0) break;
                    __nanosleep(200);
                    if (tries > SPIN_LIMIT) __trap();
                }
                mbar_wait(tempty + 8 * (it & 1), ((it >> 1) & 1) ^ 1);
                asm volatile("st.shared.b32 [%0], %1;" ::"r"(tslot + 4 * (it & 1)), "r"(pr < 0 ? -1 : (pr << 16) | (mt << 8) | nt) : "memory");
                mbar_arrive(tfull + 8 * (it & 1));
                if (pr < 0) break;
                const SideProb& q = p.prob[pr];
                if (q.dep) {
                    wait_flag(q.dep + mt, q.dep_target);
                    asm volatile("fence.proxy.async;" ::: "memory");
                }
                for (int kb = 0; kb < q.k_blocks; kb++) {
                    mbar_wait(bar_base + 8 * (C::STAGES + stage), phase);
                    const uint32_t sa = sbase + stage * C::STAGE, fb = bar_base + 8 * stage;
                    mbar_arrive_expect_tx(fb, C::STAGE);
                    tma_load_2d(sa, &q.tmA, kb * BK, mt * BM, fb);
                    tma_load_3d(sa + A_STAGE, nt < q.n_split ? &q.tmB : &q.tmB2, 0, kb * BK,
                                (nt < q.n_split ? nt : nt - q.n_split) * (BN / 64), fb);
                    if (++stage == C::STAGES) { stage = 0; phase ^= 1; }
                }
            }
        } else if (tid >= 32 && tid < 64) {
            store_warp<BN>(epi_base, rec_base, st_full, st_empty, tid & 31, reinterpret_cast<const uint8_t*>(&p.prob[0].tmC),
                           (int)sizeof(SideProb));
        }
    } else {
        asm volatile("setmaxnreg.inc.sync.aligned.u32 232;");
        const int cw = wg - 1, lane = tid & 31, wi = (tid >> 5) & 3;
        const bool elected = (tid & 127) == 0;
        int stage = 0; uint32_t phase = 0;
        float acc[BN / 2];
        EpiCtx ectx = {epi_base + (cw * 4 + wi) * C::EPI_WARP, rec_base + (cw * 4 + wi) * 32, st_full, st_empty, 0, lane};
        for (uint32_t it = 0;; it++) {
            mbar_wait(tfull + 8 * (it & 1), (it >> 1) & 1);
            const int code = (int)lds32_volatile(tslot + 4 * (it & 1));
            named_bar_sync(1 + cw, 128);
            if (elected) mbar_arrive(tempty + 8 * (it & 1));
            if (code < 0) break;
            const SideProb& q = p.prob[code >> 16];
            const int mt = (code >> 8) & 255, nt = code & 255;
            gemm_mainloop<BN>(acc, q.k_blocks, sbase, bar_base, cw, elected, stage, phase);
            const int row0 = mt * BM + cw * 64 + wi * 16;
            uint64_t dst;
            if (q.blocked) {
                const int col = nt * BN;
                dst = (uint64_t)(q.blocked + (((size_t)(col / HD) * NSEG + row0 / SEG) * NH + (col % HD) / DH) * (SEG * DH) +
                                 (row0 % SEG) * 64);
            } else {
                dst = ((uint64_t)row0 << 32) | (uint32_t)(q.c_col0 + nt * BN);
            }
            epi_hand_over(acc, ectx, dst, q.sig ? (uint64_t)(q.sig + mt) : 0, q.blocked ? 0 : 1 + (code >> 16));
        }
        epi_exit(ectx);
        if (elected) KEXIT(BN == 256 ? (p.nseg == 1 ? 6 : 2) : 4);
    }
}

#define FIN_SPLIT 8
constexpr int FIN_STAGES = 5, FIN_STAGE = A_STAGE + BK * 128 * 2, FIN_RED = FIN_STAGES * FIN_STAGE;
constexpr int FIN_NACC = 64 / FIN_SPLIT;
constexpr int FIN_SLOT = 256 * FIN_NACC * 4;
constexpr int FIN_BAR = FIN_RED + (FIN_SPLIT - 1) * FIN_SLOT, FIN_SMEM = FIN_BAR + 256 + 1024;
struct FinalParams {
    CUtensorMap tmA, tmB;
    __nv_bfloat16* out;
    const uint32_t* dep;
    uint32_t dep_target;
    int mt;
};
__global__ void __launch_bounds__(384, 1) final_gemm_kernel(const __grid_constant__ FinalParams p) {
    extern __shared__ uint8_t smem_raw[];
    const uint32_t sbase = (smem_u32(smem_raw) + 1023) & ~1023u;
    const uint32_t bar_base = sbase + FIN_BAR, bar_red = bar_base + 16 * FIN_STAGES;
    const int tid = threadIdx.x, wg = tid >> 7;
    const int rank = blockIdx.x % FIN_SPLIT, nt = blockIdx.x / FIN_SPLIT;
    constexpr int KB = HD / BK / FIN_SPLIT;
    KENTER(5);
    if (tid == 0) {
        for (int s = 0; s < FIN_STAGES; s++) { mbar_init(bar_base + 8 * s, 1); mbar_init(bar_base + 8 * (FIN_STAGES + s), 2); }
        mbar_init(bar_red, 1);
        asm volatile("fence.mbarrier_init.release.cluster;" ::: "memory");
        mbar_arrive_expect_tx(bar_red, (FIN_SPLIT - 1) * FIN_SLOT);
        pdl_launch_dependents();
    }
    __syncthreads();
    cluster_sync();
    if (wg == 0) {
        if (tid == 0) {
            for (int kb = 0; kb < FIN_STAGES; kb++) {
                mbar_arrive_expect_tx(bar_base + 8 * kb, FIN_STAGE);
                tma_load_3d(sbase + kb * FIN_STAGE + A_STAGE, &p.tmB, 0, (rank * KB + kb) * BK, nt * 2, bar_base + 8 * kb);
            }
            uint32_t n = 0;
            while (ld_acquire_b32(p.dep) < p.dep_target) { if (++n > SPIN_LIMIT) __trap(); }
            asm volatile("fence.proxy.async;" ::: "memory");
            for (int kb = 0; kb < FIN_STAGES; kb++)
                tma_load_2d(sbase + kb * FIN_STAGE, &p.tmA, (rank * KB + kb) * BK, p.mt * BM, bar_base + 8 * kb);
            int stage = 0; uint32_t phase = 0;
            for (int kb = FIN_STAGES; kb < KB; kb++) {
                mbar_wait(bar_base + 8 * (FIN_STAGES + stage), phase);
                const uint32_t sa = sbase + stage * FIN_STAGE, fb = bar_base + 8 * stage;
                mbar_arrive_expect_tx(fb, FIN_STAGE);
                tma_load_3d(sa + A_STAGE, &p.tmB, 0, (rank * KB + kb) * BK, nt * 2, fb);
                tma_load_2d(sa, &p.tmA, (rank * KB + kb) * BK, p.mt * BM, fb);
                if (++stage == FIN_STAGES) { stage = 0; phase ^= 1; }
            }
        }
    } else {
        const int cw = wg - 1, lane = tid & 31, wi = (tid >> 5) & 3, t128 = tid & 127;
        const bool elected = t128 == 0;
        float acc[64];
        int stage = 0; uint32_t phase = 0;
        int prev_stage = -1;
        for (int kb = 0; kb < KB; kb++) {
            mbar_wait(bar_base + 8 * stage, phase);
            const uint32_t sa = sbase + stage * FIN_STAGE + cw * (64 * 128), sb = sbase + stage * FIN_STAGE + A_STAGE;
            asm volatile("wgmma.fence.sync.aligned;" ::: "memory");
            #pragma unroll
            for (int kk = 0; kk < BK / 16; kk++)
                wgmma_m64n128k16(acc, make_desc(sa + kk * 32, 16, 1024), make_desc(sb + kk * 2048, 8192, 1024), (kb | kk) != 0);
            asm volatile("wgmma.commit_group.sync.aligned;" ::: "memory");
            asm volatile("wgmma.wait_group.sync.aligned 1;" ::: "memory");
            if (prev_stage >= 0 && elected) mbar_arrive(bar_base + 8 * (FIN_STAGES + prev_stage));
            prev_stage = stage;
            if (++stage == FIN_STAGES) { stage = 0; phase ^= 1; }
        }
        asm volatile("wgmma.wait_group.sync.aligned 0;" ::: "memory");
        #pragma unroll
        for (int q = 0; q < FIN_SPLIT; q++) {
            if (q != rank) {
                const int slot = rank - (rank > q ? 1 : 0);
                const uint32_t dst = mapa(sbase + FIN_RED + slot * FIN_SLOT + cw * (FIN_SLOT / 2) + t128 * 16, q), rb = mapa(bar_red, q);
                #pragma unroll
                for (int j = 0; j < FIN_NACC / 4; j++)
                    asm volatile("st.async.weak.shared::cluster.mbarrier::complete_tx::bytes.v4.f32 [%0], {%1,%2,%3,%4}, [%5];"
                                 ::"r"(dst + j * 2048), "f"(acc[FIN_NACC * q + 4 * j]), "f"(acc[FIN_NACC * q + 4 * j + 1]),
                                   "f"(acc[FIN_NACC * q + 4 * j + 2]), "f"(acc[FIN_NACC * q + 4 * j + 3]), "r"(rb) : "memory");
            }
        }
        float o[FIN_NACC];
        #pragma unroll
        for (int q = 0; q < FIN_SPLIT; q++)
            if (q == rank) {
                #pragma unroll
                for (int e = 0; e < FIN_NACC; e++) o[e] = acc[FIN_NACC * q + e];
            }
        mbar_wait(bar_red, 0);
        #pragma unroll
        for (int sl = 0; sl < FIN_SPLIT - 1; sl++) {
            #pragma unroll
            for (int j = 0; j < FIN_NACC / 4; j++) {
                const uint4 v = lds128(sbase + FIN_RED + sl * FIN_SLOT + cw * (FIN_SLOT / 2) + j * 2048 + t128 * 16);
                o[4 * j] += __uint_as_float(v.x); o[4 * j + 1] += __uint_as_float(v.y);
                o[4 * j + 2] += __uint_as_float(v.z); o[4 * j + 3] += __uint_as_float(v.w);
            }
        }
        __nv_bfloat16* dst = p.out + (size_t)(p.mt * BM + cw * 64 + wi * 16 + (lane >> 2)) * (2 * DM) + nt * 128 +
                             rank * (128 / FIN_SPLIT) + (lane & 3) * 2;
        #pragma unroll
        for (int j = 0; j < FIN_NACC / 4; j++) {
            *reinterpret_cast<uint32_t*>(dst + j * 8) = pack_bf16(o[4 * j], o[4 * j + 1]);
            *reinterpret_cast<uint32_t*>(dst + (size_t)8 * (2 * DM) + j * 8) = pack_bf16(o[4 * j + 2], o[4 * j + 3]);
        }
    }
    __syncthreads();
    cluster_sync();
    if (tid == 0) KEXIT(5);
}

#define POLL_DELAY 4
#define FETCH_DELAY 200
#define AT_PF 6
#define AT_AHEAD 4
#define TOK_GO 12
#define WO_PFA 7
#define WO_PFB_DELAY 60
#define NO_COMM 0
#define TOK_MOVED 4
#define XB_DELAY 50
#define WO_PF0 0
#define WO_PF1 11
#define WO_AHEAD 6
constexpr int REC_THREADS = 256;
constexpr uint32_t POLL_LIMIT = 1u << 16;
constexpr int NREG = 24;
__host__ __device__ constexpr int reg_idx(int j) { return ((j & 3) - 1) * 8 + (j >> 2); }
constexpr int SM_WQ = 0;
constexpr int SM_WO = 65536;
constexpr int SM_X = SM_WO + 11 * 8192;
constexpr int SM_PARK1 = SM_X;
constexpr int SM_MEM = SM_X + 4 * 4096;
constexpr int SM_RED = SM_X + 8 * 4096;
constexpr int SM_V = SM_X + 12 * 4096;
constexpr int SM_K = SM_X + 14 * 4096;
constexpr int SM_QS = SM_X + 15 * 4096;
constexpr int SM_QK = SM_X + 65536;
constexpr int SM_SP = SM_QK + 2048;
constexpr int SM_VM = SM_SP + 2560;
constexpr int SM_O = SM_VM + 2048;
constexpr int SM_PARK0 = SM_QK;
constexpr int SM_SUM = SM_O + 2048;
constexpr int SM_TBL = SM_SUM + 128;
constexpr int SM_BAR = SM_TBL + 512;
constexpr int SM_STAMP = SM_BAR + 192;
constexpr int REC_SMEM = SM_STAMP;
static_assert(REC_SMEM <= 232448, "shared memory");
enum { BAR_V = 0, BAR_X = 8, BAR_P0 = 16, BAR_WQ = 40, BAR_WO = 48, BAR_XG = 56, BAR_F0 = 88, BAR_F3 = 96, BAR_VF = 104,
       BAR_M = 112, BAR_GO = 144, BAR_PK = 152, BAR_OUT = 168, BAR_VM = 160, BAR_SELF = 176, BAR_MIN = 184 };

template <int V> struct IntC { static constexpr int value = V; };
template <int I, int N, typename F> __device__ __forceinline__ void sfor(F&& f) {
    if constexpr (I < N) { f(IntC<I>{}); sfor<I + 1, N>(f); }
}

struct RecParams {
    CUtensorMap tmW[3];
    CUtensorMap tmWo;
    CUtensorMap tmX;
    const __nv_bfloat16* mem0;
    __nv_bfloat16* qkv_tok;
    __nv_bfloat16* kv_mem;
    uint8_t* xchg;
    int* ctacolor;
    uint32_t* flags;
    uint32_t one[2];
    uint32_t* arrivals;
};

__device__ __forceinline__ void mma_a(float* d, const uint32_t* a, uint32_t b0, uint32_t b1) {
    mma16816(d, a[0], a[1], a[2], a[3], b0, b1);
}
__device__ __forceinline__ void ldsm4(uint32_t addr, uint32_t* r) { ldsm_x4(addr, r[0], r[1], r[2], r[3]); }
__device__ __forceinline__ void ldsm4t(uint32_t addr, uint32_t* r) { ldsm_x4_t(addr, r[0], r[1], r[2], r[3]); }
template <int OFF> __device__ __forceinline__ void poll_v2(uint2& v, const uint8_t* p) {
    asm volatile("ld.relaxed.gpu.global.v2.b32 {%0,%1}, [%2+%3];" : "=r"(v.x), "=r"(v.y) : "l"(p), "n"(OFF) : "memory");
}
__device__ __forceinline__ uint32_t max3(uint32_t a, uint32_t b, uint32_t c) { return max(max(a, b), c); }
__device__ __forceinline__ uint32_t pub_slot(int s) { return (s & 1) * XCHG_SLOT + ((s >> 1) & 1) * PUB_BYTES; }

__device__ __forceinline__ uint8_t* xaddr(uint32_t lo, uint32_t hi) {
    uint64_t a;
    asm("mov.b64 %0, {%1, %2};" : "=l"(a) : "r"(lo), "r"(hi));
    return reinterpret_cast<uint8_t*>(a);
}
template <int N> __device__ __forceinline__ uint32_t delay_zero(uint32_t a) {
    uint32_t x = a;
    #pragma unroll
    for (int i = 0; i < N; i++) x = lds32_volatile(x);
    return x - a;
}
__device__ __forceinline__ uint32_t fresh(uint32_t x) { asm volatile("" : "+r"(x)); return x; }

template <int NT> __device__ __forceinline__ uint32_t wo_addr(uint32_t ao, uint32_t a3, int n) {
    return (n % NT == 2 ? a3 : ao + (n % NT) * 32768) + (n / NT) * 1024;
}
template <int NT, int PF>
__device__ __forceinline__ void wo_phase(uint32_t (&st)[8 * NT][4], uint32_t ao, uint32_t a3, uint32_t l16, uint32_t tbl, uint32_t sums,
                                         uint32_t slot, uint32_t xhi, uint32_t third) {
    constexpr int AHEAD = PF > WO_AHEAD ? PF - NT : WO_AHEAD;
    uint32_t of[4][4], pl[3];
    float i0, i1;
    ldsm4t(l16 + SM_O, of[0]);
    #pragma unroll
    for (int n = PF; n < AHEAD; n++) ldsm4t(wo_addr<NT>(ao, a3, n), st[n]);
    float acc[NT][4];
    #pragma unroll
    for (int i = 0; i < NT; i++) { acc[i][0] = acc[i][1] = acc[i][2] = acc[i][3] = 0.f; }
    #pragma unroll
    for (int kk = 0; kk < 8; kk++) {
        if ((kk & 1) == 0 && kk + 2 < 8) ldsm4t(l16 + SM_O + ((kk >> 1) + 1) * 512, of[(kk >> 1) + 1]);
        if (kk == 4) {
            const uint32_t x = fresh(l16);
            const uint4 sa = lds128(sums + ((x << 1) & 0x60)), sc = lds128(sums + ((x << 1) & 0x60) + 16);
            i0 = rcp((__uint_as_float(sa.x) + __uint_as_float(sa.y)) + (__uint_as_float(sa.z) + __uint_as_float(sa.w)));
            i1 = rcp((__uint_as_float(sc.x) + __uint_as_float(sc.y)) + (__uint_as_float(sc.z) + __uint_as_float(sc.w)));
            const uint4 t = lds128(tbl + ((x >> 3) & 0x30));
            const uint32_t d = slot + ((x >> 1) & 0x38);
            pl[0] = t.x + d; pl[1] = t.y + d; pl[2] = t.z + d;
            __syncwarp();
        }
        #pragma unroll
        for (int i = 0; i < NT; i++) {
            const int n = kk * NT + i;
            mma_a(acc[i], st[n], of[kk >> 1][(kk & 1) * 2], of[kk >> 1][(kk & 1) * 2 + 1]);
            if (n + AHEAD >= PF && n + AHEAD < 8 * NT) ldsm4t(wo_addr<NT>(ao, a3, n + AHEAD), st[n + AHEAD]);
        }
    }
    #pragma unroll
    for (int i = 0; i < NT; i++)
        asm volatile("{\n.reg .pred p;\nsetp.ne.u32 p, %3, 0;\n@p st.relaxed.gpu.global.v2.b32 [%0], {%1,%2};\n}"
                     ::"l"(xaddr(pl[i], xhi)), "r"(pack_bf16(acc[i][0] * i0, acc[i][1] * i1)), "r"(pack_bf16(acc[i][2] * i0, acc[i][3] * i1)),
                       "r"(i < 2 ? 1u : third) : "memory");
}

constexpr uint32_t SMEM_ORIGIN = 1024;
constexpr uint64_t DESC_BASE = (1ull << 16) | (0x40000040ull << 32);
template <int OFFB, int SCALE_D>
__device__ __forceinline__ void wgmma_n32_rs(float (&d)[16], const uint32_t* a, uint32_t one) {
    asm volatile(
        "{\n.reg .b64 db;\nmad.wide.u32 db, %20, %21, %22;\n"
        "wgmma.mma_async.sync.aligned.m64n32k16.f32.bf16.bf16 {%0,%1,%2,%3,%4,%5,%6,%7,%8,%9,%10,%11,%12,%13,%14,%15}, "
        "{%16,%17,%18,%19}, db, %23, 1, 1, 0;\n}"
        : "+f"(d[0]), "+f"(d[1]), "+f"(d[2]), "+f"(d[3]), "+f"(d[4]), "+f"(d[5]), "+f"(d[6]), "+f"(d[7]),
          "+f"(d[8]), "+f"(d[9]), "+f"(d[10]), "+f"(d[11]), "+f"(d[12]), "+f"(d[13]), "+f"(d[14]), "+f"(d[15])
        : "r"(a[0]), "r"(a[1]), "r"(a[2]), "r"(a[3]), "r"(one), "n"((SMEM_ORIGIN + OFFB) >> 4), "l"(DESC_BASE), "n"(SCALE_D));
}
template <int OFFA, int OFFB, int SCALE_D>
__device__ __forceinline__ void wgmma_n32_ss(float (&d)[16], uint32_t one) {
    asm volatile(
        "{\n.reg .b64 da, db;\nmad.wide.u32 da, %16, %17, %19;\nmad.wide.u32 db, %16, %18, %19;\n"
        "wgmma.mma_async.sync.aligned.m64n32k16.f32.bf16.bf16 {%0,%1,%2,%3,%4,%5,%6,%7,%8,%9,%10,%11,%12,%13,%14,%15}, "
        "da, db, %20, 1, 1, 1, 0;\n}"
        : "+f"(d[0]), "+f"(d[1]), "+f"(d[2]), "+f"(d[3]), "+f"(d[4]), "+f"(d[5]), "+f"(d[6]), "+f"(d[7]),
          "+f"(d[8]), "+f"(d[9]), "+f"(d[10]), "+f"(d[11]), "+f"(d[12]), "+f"(d[13]), "+f"(d[14]), "+f"(d[15])
        : "r"(one), "n"((SMEM_ORIGIN + OFFA) >> 4), "n"((SMEM_ORIGIN + OFFB) >> 4), "l"(DESC_BASE), "n"(SCALE_D));
}
template <int WG, int J0, int J1, int I0, int I1, bool ACC, bool FENCE = true>
__device__ __forceinline__ void token_mma(float (&ta)[2][16], const uint32_t (&wr)[NREG][2][4], uint32_t one) {
    if (FENCE) asm volatile("wgmma.fence.sync.aligned;" ::: "memory");
    sfor<J0, J1>([&](auto J) {
        constexpr int j = J.value, offb = SM_X + WG * 32768 + (j >> 2) * 4096 + (j & 3) * 32, sc = (ACC || j != J0) ? 1 : 0;
        sfor<I0, I1>([&](auto I) {
            constexpr int i = I.value;
            if constexpr ((j & 3) != 0) wgmma_n32_rs<offb, sc>(ta[i], wr[reg_idx(j)][i], one);
            else if constexpr (WG == 0 || (j >> 2) >= TOK_MOVED) wgmma_n32_ss<SM_WQ + WG * 32768 + i * 16384 + (j >> 2) * 2048, offb, sc>(ta[i], one);
            constexpr int c = (j >> 2) - (8 - TOK_MOVED);
            if constexpr (WG == 0 && (j & 3) == 2 && c >= 0)
                wgmma_n32_ss<SM_WQ + 32768 + (1 - i) * 16384 + c * 2048, SM_X + 32768 + c * 4096, 1>(ta[i], one);
        });
    });
    asm volatile("wgmma.commit_group.sync.aligned;" ::: "memory");
}
__device__ __forceinline__ void warp_arrive(uint32_t bar) {
    __syncwarp();
    if (elect_one()) mbar_arrive(bar);
}
__device__ __forceinline__ void remote_arrive(uint32_t bar, uint32_t rank) {
    asm volatile("mbarrier.arrive.relaxed.cluster.shared::cluster.b64 _, [%0];" ::"r"(mapa(bar, rank)) : "memory");
}
__device__ __forceinline__ void x_load(const RecParams& p, uint32_t sb, int sg, int g) {
    tma_load_3d_mc(sb + SM_X + g * 16384, &p.tmX, 0, sg * SEG, g * 4, sb + SM_BAR + BAR_XG + 8 * g, (uint16_t)7);
}

__device__ __forceinline__ void rec_steps(const RecParams& p, const uint32_t (&wr)[NREG][2][4], const uint32_t sb, const int warp,
                                          const int cta, const int head, const int rank) {
    const int wq = warp & 3, wg = warp >> 2;
    const uint32_t bar = sb + SM_BAR;
    const uint32_t xhi = (uint32_t)((uint64_t)p.xchg >> 32);
    const float sl2 = 0.08838834764831845f * 1.4426950408889634f;
    const bool has_unit = warp >= 5 && (warp < 7 || cta < 64);
    const bool qk = rank < 2;
    const uint32_t pa = rank == 2 ? 0 : rank + 1, pb = rank == 0 ? 2 : rank - 1;
    const uint32_t tbl = sb + SM_TBL + warp * 64;
    const bool att = (warp & 6) == 2;
    const int stile = warp < 5 ? warp : warp - 3;

    const uint32_t u_st = uniform(SM_QK - SM_WQ - wg * (32768 - 1024)), u_stmask = uniform(wg == 0 ? 0x30 : 0);
    const uint32_t u_key = uniform(!qk || att || warp == 7 ? 0 : sb + (warp == 4 ? SM_QK + 1024 : SM_K + stile * 1024));
    const uint32_t u_bx = uniform(bar + (qk ? BAR_X : BAR_VM)), u_bra = uniform(mapa(u_bx, pa)), u_brb = uniform(mapa(u_bx, pb));
    const uint32_t u_src = uniform(lds32_volatile(tbl + 44));
    const uint32_t u_kv = uniform(qk && wg == 0 ? ~0u : (((rank >> 1) * NSEG * NH + head) * 8 + (qk ? rank * 4 + wq : warp)) * 64);
    const uint32_t u_free = uniform(warp == 5 ? mapa(bar + BAR_VF, 2) : warp == 6 ? mapa(bar + BAR_F0, 0) : 0);
    const uint32_t u_role = uniform((has_unit ? 1 : 0) | (att ? 2 : 0) | (warp != 1 || rank == 0 ? 4 : 0) | (!qk && warp == 0 ? 8 : 0) | (rank != 0 && warp == 1 ? 16 : 0));
    uint32_t l16, xa, aq, ao;
    {
        const int lane = threadIdx.x & 31, mi = lane >> 3, r8 = lane & 7, r16 = (mi >> 1) * 8 + r8;
        l16 = opaque(sb + lane * 16);
        xa = opaque(sb + lane * 8 + (qk ? SM_SP + rank * 1280 + stile * 256 : SM_VM + warp * 256));
        aq = opaque(sb + SM_WQ + wg * 32768 + r16 * 128 + (((wq * 2 + (mi & 1)) ^ r8) << 4));
        ao = opaque(sb + SM_WO + (warp >> 1) * 8192 + r16 * 64 + ((((warp & 1) * 2 + (mi & 1)) ^ ((r8 >> 1) & 3)) << 4));
    }

    uint32_t mphase = 0;
    #pragma unroll 1
    for (int s = 0; s < NSEG; s++) {
        const uint32_t par = s & 1;
        uint32_t at[16][4];
        auto at_early = [](int i) { return i < 2 || ((i & 1) == 0 && (i >> 1) <= AT_PF - 2); };
        auto at_prefetch = [&](int i0, int i1) {
            #pragma unroll
            for (int i = i0; i < i1; i++)
                if (at_early(i)) ldsm4t(aq + (i & 1) * 16384 + (i >> 1) * 2048, at[i]);
        };
        if (wg == 0) {
            float ta[2][16];
            mbar_wait_bounded(bar + BAR_XG, par);
            STAMP(6);
            auto park = [&](int i, uint32_t dst) {
                #pragma unroll
                for (int e = 0; e < 16; e++) asm volatile("" : "+f"(ta[i][e]));
                #pragma unroll
                for (int j = 0; j < 4; j++)
                    sts128(l16 + dst + j * 2048 + wq * 512, __float_as_uint(ta[i][4 * j]), __float_as_uint(ta[i][4 * j + 1]),
                           __float_as_uint(ta[i][4 * j + 2]), __float_as_uint(ta[i][4 * j + 3]));
            };
            token_mma<0, 0, 16, 0, 1, false>(ta, wr, 1);
            mbar_wait_bounded(bar + BAR_XG + 8, par);
            if (TOK_MOVED > 0) mbar_wait_bounded(bar + BAR_XG + 16, par);
            token_mma<0, 16, 32, 0, 1, true>(ta, wr, p.one[0]);
            token_mma<0, 0, TOK_GO, 1, 2, false, false>(ta, wr, p.one[1]);
            token_mma<0, TOK_GO, 32, 1, 2, true, false>(ta, wr, p.one[1]);
            if (TOK_MOVED == 0) mbar_wait_bounded(bar + BAR_XG + 16, par);
            asm volatile("wgmma.wait_group.sync.aligned 1;" ::: "memory");
            park(0, SM_PARK0);
            warp_arrive(bar + BAR_GO);
            asm volatile("wgmma.wait_group.sync.aligned 0;" ::: "memory");
            named_bar_sync(10, 128);
            park(1, SM_PARK1);
            mbar_wait_bounded(bar + BAR_XG + 24, par);
            warp_arrive(bar + BAR_PK);
            const uint8_t* src = xaddr(u_src + pub_slot(s), xhi);
            auto fetch = [&]() {
                if (elect_one()) {
                    mbar_arrive_expect_tx(bar + BAR_M + 8 * wq, 4096);
                    bulk_load(sb + SM_MEM + wq * 4096, src, 4096, bar + BAR_M + 8 * wq);
                }
            };
            named_bar_sync(7, REC_THREADS - 32);
            spin_clks(FETCH_DELAY);
            fetch();
            STAMP(12);
            if (warp == 0 && elect_one()) {
                if (qk) mbar_arrive_expect_tx(bar + BAR_V, 8192);
                mbar_arrive_expect_tx(bar + BAR_X, qk ? 1280 : 2560);
                mbar_arrive_expect_tx(bar + BAR_VM, qk ? 2048 : 0);
            }
            at_prefetch(0, 16);
            const uint32_t x = fresh(l16) - sb;
            const uint32_t ca = sb + SM_MEM + wq * 4096 + x * 2 + ((x >> 4) & 0x1C);
            #pragma unroll 1
            for (uint32_t n = 0; n < POLL_LIMIT; n++) {
                mbar_wait_bounded(bar + BAR_M + 8 * wq, mphase);
                mphase ^= 1;
                const uint32_t c0 = lds32_volatile(ca), c1 = lds32_volatile(ca + 1024), c2 = lds32_volatile(ca + 2048), c3 = lds32_volatile(ca + 3072);
                if (!__any_sync(~0u, max(max3(c0, c1, c2), c3) == (NO_COMM ? 0x12345u : SENT))) break;
                fetch();
            }
            STAMP(0);
            named_bar_sync(0, REC_THREADS);
        } else {
            at_prefetch(0, 5);
            if (s > 0) {
                if (u_role & 1) {
                    const uint32_t ln = (fresh(l16) >> 4) & 31;
                    const uint32_t ibl = lds32_volatile(tbl + 12) + (par ^ 1) * XCHG_SLOT + ln * 8;
                    const uint32_t publ = lds32_volatile(tbl + 28) + pub_slot(s) + (ln & 16) * 256 + (ln & 8) * 16 + (ln & 7) * 4;
                    const bool odd = ln & 8;
                    const uint8_t* ib = xaddr(ibl + delay_zero<POLL_DELAY>(bar + BAR_SELF), xhi);
                    STAMP(8);
                    uint2 v[8];
                    #pragma unroll 1
                    for (uint32_t n = 0; n < POLL_LIMIT; n++) {
                        sfor<0, 8>([&](auto I) { poll_v2<I.value * 256>(v[I.value], ib); });
                        const uint32_t mx = max(max3(v[0].y, v[1].y, v[2].y), max3(max3(v[3].y, v[4].y, v[5].y), v[6].y, v[7].y));
                        if (!__any_sync(~0u, mx == (NO_COMM ? 0x12345u : SENT))) break;
                    }
                    float a0 = ((bf16_lo(v[0].x) + bf16_lo(v[1].x)) + (bf16_lo(v[2].x) + bf16_lo(v[3].x))) +
                               ((bf16_lo(v[4].x) + bf16_lo(v[5].x)) + (bf16_lo(v[6].x) + bf16_lo(v[7].x)));
                    float a1 = ((bf16_hi(v[0].x) + bf16_hi(v[1].x)) + (bf16_hi(v[2].x) + bf16_hi(v[3].x))) +
                               ((bf16_hi(v[4].x) + bf16_hi(v[5].x)) + (bf16_hi(v[6].x) + bf16_hi(v[7].x)));
                    float a2 = ((bf16_lo(v[0].y) + bf16_lo(v[1].y)) + (bf16_lo(v[2].y) + bf16_lo(v[3].y))) +
                               ((bf16_lo(v[4].y) + bf16_lo(v[5].y)) + (bf16_lo(v[6].y) + bf16_lo(v[7].y)));
                    float a3 = ((bf16_hi(v[0].y) + bf16_hi(v[1].y)) + (bf16_hi(v[2].y) + bf16_hi(v[3].y))) +
                               ((bf16_hi(v[4].y) + bf16_hi(v[5].y)) + (bf16_hi(v[6].y) + bf16_hi(v[7].y)));
                    float k0 = odd ? a2 : a0, k1 = odd ? a3 : a1;
                    k0 += __shfl_xor_sync(~0u, odd ? a0 : a2, 8);
                    k1 += __shfl_xor_sync(~0u, odd ? a1 : a3, 8);
                    k0 += __shfl_xor_sync(~0u, k0, 16);
                    k1 += __shfl_xor_sync(~0u, k1, 16);
                    st_relaxed_b32(xaddr(publ, xhi), pack_bf16(k0, k1));
                    STAMP(11);
                } else if (warp == 4) {
                    bulk_wait_read_all();
                    if (elect_one()) remote_arrive(bar + BAR_F3, 2);
                    if (!qk) {
                        mbar_wait_bounded(bar + BAR_F3, par ^ 1);
                        if (elect_one()) x_load(p, sb, s, 3);
                    }
                    if (elect_one()) {
                        bulk_wait_all();
                        signal_flag(p.flags + F_PROGRESS + s - 1);
                    }
                    __syncwarp();
                    STAMP(10);
                }
            }
            float ta[2][16];
            uint32_t w[8];
            auto unpark = [&](int i, uint32_t src) {
                mbar_wait_bounded(bar + (i ? BAR_GO : BAR_PK), par);
                #pragma unroll
                for (int j = 0; j < 4; j++) {
                    const uint4 v = lds128(l16 + src + j * 2048 + wq * 512);
                    ta[i][4 * j] = __uint_as_float(v.x); ta[i][4 * j + 1] = __uint_as_float(v.y);
                    ta[i][4 * j + 2] = __uint_as_float(v.z); ta[i][4 * j + 3] = __uint_as_float(v.w);
                }
            };
            if (warp != 4) named_bar_arrive(7, REC_THREADS - 32);
            unpark(1, SM_PARK0);
            STAMP(6);
            token_mma<1, 0, 16, 1, 2, true>(ta, wr, 1);
            unpark(0, SM_PARK1);
            token_mma<1, 16, 32, 1, 2, true>(ta, wr, 1);
            token_mma<1, 16, 32, 0, 1, true>(ta, wr, 1);
            token_mma<1, 0, 16, 0, 1, true, false>(ta, wr, 1);
            auto put_tile = [&](int m, const uint32_t (&q)[8]) {
                #pragma unroll
                for (int h = 0; h < 2; h++) {
                    if (qk) asm volatile("stmatrix.sync.aligned.m8n8.x4.trans.shared.b16 [%0], {%1,%2,%3,%4};"
                                         ::"r"(aq - (SM_WQ + 32768) + (m ? SM_K : SM_QS) + h * 2048), "r"(q[4 * h]), "r"(q[4 * h + 1]),
                                           "r"(q[4 * h + 2]), "r"(q[4 * h + 3]) : "memory");
                    else sts128(l16 + SM_V + wq * 2048 + m * 1024 + h * 512, q[4 * h], q[4 * h + 1], q[4 * h + 2], q[4 * h + 3]);
                }
            };
            auto pack_tile = [&](int i) {
                #pragma unroll
                for (int e = 0; e < 16; e++) asm volatile("" : "+f"(ta[i][e]));
                #pragma unroll
                for (int j = 0; j < 8; j++) w[j] = pack_bf16(ta[i][2 * j], ta[i][2 * j + 1]);
            };
            asm volatile("wgmma.wait_group.sync.aligned 2;" ::: "memory");
            pack_tile(1);
            at_prefetch(5, 16);
            asm volatile("wgmma.wait_group.sync.aligned 1;" ::: "memory");
            if (elect_one()) mbar_arrive(bar + BAR_OUT);
            mbar_wait_bounded(bar + BAR_OUT, par);
            if (u_free != 0 && elect_one())
                asm volatile("mbarrier.arrive.relaxed.cluster.shared::cluster.b64 _, [%0];" ::"r"(u_free) : "memory");
            put_tile(0, w);
            asm volatile("wgmma.wait_group.sync.aligned 0;" ::: "memory");
            pack_tile(0);
            put_tile(1, w);
            STAMP(0);
            named_bar_sync(0, REC_THREADS);
            if (!qk) {
                asm volatile("fence.proxy.async.shared::cta;" ::: "memory");
                mbar_wait_bounded(bar + BAR_VF, par);
                __syncwarp();
                if (elect_one()) {
                    #pragma unroll
                    for (int r = 0; r < 2; r++)
                        asm volatile("cp.async.bulk.shared::cluster.shared::cta.mbarrier::complete_tx::bytes [%0], [%1], %2, [%3];"
                                     ::"r"(mapa(sb + SM_V + wq * 2048, r)), "r"(sb + SM_V + wq * 2048), "r"(2048), "r"(mapa(bar + BAR_V, r)) : "memory");
                }
            }
            STAMP(14);
        }
        const uint32_t mb = l16 + SM_MEM + wg * 8192;
        float acc[2][2][4];
        {
            uint32_t b[2][4];
            ldsm4t(mb, b[0]);
            ldsm4t(mb + 512, b[1]);
            #pragma unroll
            for (int i = 0; i < AT_AHEAD; i++)
                if (!at_early(i)) ldsm4t(aq + (i & 1) * 16384 + (i >> 1) * 2048, at[i]);
            STAMPD(1, b[0][0]);
            #pragma unroll
            for (int i = 0; i < 4; i++) { for (int e = 0; e < 4; e++) acc[i >> 1][i & 1][e] = 0.f; }
            #pragma unroll
            for (int u = 0; u < 16; u++) {
                #pragma unroll
                for (int h = 0; h < 2; h++) {
                    const int j = 2 * u + h;
                    #pragma unroll
                    for (int m = 0; m < 2; m++) {
                        if ((j & 3) == 0) mma_a(acc[h][m], at[(j >> 2) * 2 + m], b[u & 1][2 * h], b[u & 1][2 * h + 1]);
                        else mma_a(acc[h][m], wr[reg_idx(j)][m], b[u & 1][2 * h], b[u & 1][2 * h + 1]);
                    }
                }
                if (u + 2 < 16) ldsm4t(mb + (u + 2) * 512, b[u & 1]);
                if (u + AT_AHEAD < 16 && !at_early(u + AT_AHEAD))
                    ldsm4t(aq + ((u + AT_AHEAD) & 1) * 16384 + ((u + AT_AHEAD) >> 1) * 2048, at[u + AT_AHEAD]);
            }
        }
        sts128(l16 + SM_RED + warp * 512, __float_as_uint(acc[0][1][0] + acc[1][1][0]), __float_as_uint(acc[0][1][1] + acc[1][1][1]),
               __float_as_uint(acc[0][1][2] + acc[1][1][2]), __float_as_uint(acc[0][1][3] + acc[1][1][3]));
        #pragma unroll
        for (int e = 0; e < 4; e++) acc[0][0][e] += acc[1][0][e];
        const uint32_t x16 = fresh(l16);
        const uint32_t ast = (fresh(aq) + u_st) ^ ((((x16 >> 7) ^ wq) & 1) * u_stmask);
        const uint32_t sa = fresh((x16 & 0x70) * 8 + ((((x16 >> 3) & 0x30) ^ x16) & 0x70)), sa2 = fresh(sa ^ 64);
        const uint32_t xra = __byte_perm(xa, u_bra, 0x7210), xrb = __byte_perm(xa, u_brb, 0x7210);
        STAMP(2);
        named_bar_sync(1 + wq, 64);
        uint32_t p0, p1;
        {
            const uint4 v = lds128(l16 + SM_RED + (warp ^ 4) * 512);
            p0 = pack_bf16(acc[0][0][0] + __uint_as_float(v.x), acc[0][0][1] + __uint_as_float(v.y));
            p1 = pack_bf16(acc[0][0][2] + __uint_as_float(v.z), acc[0][0][3] + __uint_as_float(v.w));
        }
        auto send = [&](uint32_t y0, uint32_t y1) {
            st_async_v2(xra, y0, y1, u_bra);
            st_async_v2(xrb, y0, y1, u_brb);
            sts64(xa, y0, y1);
            warp_arrive(u_bx);
        };
        if (qk) {
            asm volatile("stmatrix.sync.aligned.m8n8.x2.trans.shared.b16 [%0], {%1,%2};" ::"r"(ast), "r"(p0), "r"(p1) : "memory");
            named_bar_sync(5, REC_THREADS);
            if (u_key != 0) {
                uint32_t qa[2][4], kf[2][4];
                ldsm4(sa + sb + SM_QK, qa[0]);
                ldsm4(sa + u_key, kf[0]);
                ldsm4(sa2 + sb + SM_QK, qa[1]);
                ldsm4(sa2 + u_key, kf[1]);
                float se[4] = {0.f, 0.f, 0.f, 0.f}, so[4] = {0.f, 0.f, 0.f, 0.f};
                #pragma unroll
                for (int u = 0; u < 2; u++) {
                    mma_a(se, qa[u], kf[u][0], kf[u][1]);
                    mma_a(so, qa[u], kf[u][2], kf[u][3]);
                }
                send(__float_as_uint(se[0] + so[2]), __float_as_uint(se[1] + so[3]));
            }
        } else {
            send(p0, p1);
        }
        STAMP(3);
        const uint32_t lane = (fresh(l16) >> 4) & 31;
        if (u_kv != ~0u) {
            uint32_t* dst = reinterpret_cast<uint32_t*>(p.kv_mem) + (u_kv + s * (NH * 512) + lane);
            dst[0] = p0;
            dst[32] = p1;
        }
        auto tile_stores = [&]() {
            if (wg == 1) {
                asm volatile("fence.proxy.async.shared::cta;" ::: "memory");
                if (warp != 4) {
                    named_bar_arrive(14, 128);
                } else {
                    named_bar_sync(14, 128);
                    if (elect_one()) {
                        __nv_bfloat16* dst = p.qkv_tok + ((size_t)s * NH + head) * (SEG * DH);
                        constexpr size_t MAT = (size_t)NSEG * NH * SEG * DH;
                        bulk_store(dst + (qk ? rank * (SEG * 64) : 2 * MAT), sb + (qk ? SM_QS : SM_V), 4096);
                        bulk_store(dst + (qk ? MAT + rank * (SEG * 64) : 2 * MAT + SEG * 64), sb + (qk ? SM_K : SM_V + 4096), 4096);
                        bulk_commit();
                    }
                    __syncwarp();
                }
            }
        };
        if (s == NSEG - 1) { tile_stores(); break; }
        const uint32_t slot = par * XCHG_SLOT;
        if (u_role & 2) {
            if (qk) mbar_wait_bounded(bar + BAR_V, par);
            uint32_t vt[2][4][4];
            #pragma unroll
            for (int i = 0; i < 8; i++) {
                const uint4 v = lds128(l16 + SM_V + (warp & 1) * 1024 + (i & 3) * 2048 + (i >> 2) * 512);
                vt[i >> 2][i & 3][0] = v.x; vt[i >> 2][i & 3][1] = v.y; vt[i >> 2][i & 3][2] = v.z; vt[i >> 2][i & 3][3] = v.w;
            }
            const uint32_t l8 = sb + lane * 8;
            mbar_wait_bounded(bar + BAR_X, par);
            STAMP(4);
            float sv[10];
            #pragma unroll
            for (int j = 0; j < 5; j++) {
                const uint2 a = lds64(l8 + SM_SP + j * 256), b = lds64(l8 + SM_SP + 1280 + j * 256);
                sv[2 * j] = __uint_as_float(a.x) + __uint_as_float(b.x);
                sv[2 * j + 1] = __uint_as_float(a.y) + __uint_as_float(b.y);
            }
            float mx = fmaxf(fmaxf(fmaxf(sv[0], sv[1]), fmaxf(sv[2], sv[3])), fmaxf(fmaxf(sv[4], sv[5]), fmaxf(sv[6], sv[7])));
            mx = fmaxf(mx, fmaxf(sv[8], sv[9]));
            const float m1 = __shfl_xor_sync(~0u, mx, 1), m2 = __shfl_xor_sync(~0u, mx, 2), m3 = __shfl_xor_sync(~0u, mx, 3);
            const bool vm_ok = mbar_try_wait(bar + BAR_VM, par);
            mx = fmaxf(fmaxf(mx, m1), fmaxf(m2, m3));
            const float mo = mx * sl2;
            #pragma unroll
            for (int j = 0; j < 10; j++) sv[j] = ex2(fmaf(sv[j], sl2, -mo));
            const uint32_t e0 = pack_bf16(sv[0], sv[1]), e1 = pack_bf16(sv[2], sv[3]);
            const uint32_t e2 = pack_bf16(sv[4], sv[5]), e3 = pack_bf16(sv[6], sv[7]), em = pack_bf16(sv[8], sv[9]);
            float o[4][4];
            #pragma unroll
            for (int i = 0; i < 4; i++) {
                o[i][0] = o[i][1] = o[i][2] = o[i][3] = 0.f;
                mma_a(o[i], vt[0][i], e0, e1);
            }
            sts32(sb + SM_SUM + lane * 4,
                  __float_as_uint((((sv[0] + sv[1]) + (sv[2] + sv[3])) + ((sv[4] + sv[5]) + (sv[6] + sv[7]))) + (sv[8] + sv[9])));
            if (!vm_ok) mbar_wait_bounded(bar + BAR_VM, par);
            uint2 vm[4];
            #pragma unroll
            for (int i = 0; i < 4; i++) {
                vm[i] = lds64(l8 + SM_VM + (warp & 1) * 1024 + i * 256);
                mma_a(o[i], vt[1][i], e2, e3);
            }
            #pragma unroll
            for (int i = 0; i < 4; i++) mma1688(o[i], vm[i].x, vm[i].y, em);
            #pragma unroll
            for (int i = 0; i < 4; i += 2)
                stsm_x4(l16 + SM_O + (warp & 1) * 1024 + i * 256, pack_bf16(o[i][0], o[i][1]), pack_bf16(o[i][2], o[i][3]),
                        pack_bf16(o[i + 1][0], o[i + 1][1]), pack_bf16(o[i + 1][2], o[i + 1][3]));
            STAMP(5);
            uint32_t st[16][4];
            #pragma unroll
            for (int n = 0; n < WO_PF0; n++) ldsm4t(wo_addr<2>(ao, 0, n), st[n]);
            named_bar_sync(6, REC_THREADS);
            wo_phase<2, WO_PF0>(st, ao, 0, l16, tbl, sb + SM_SUM, slot, xhi, 0);
        } else {
            const uint32_t a3 = fresh(ao) + (wg == 0 ? 10 : 6) * 8192;
            uint32_t st[24][4];
            #pragma unroll
            for (int n = 0; n < WO_PFA; n++) ldsm4t(wo_addr<3>(ao, a3, n), st[n]);
            tile_stores();
            if (u_role & 1) {
                uint8_t* ib = xaddr(lds32_volatile(tbl + 12) + (par ^ 1) * XCHG_SLOT + lane * 16, xhi);
                #pragma unroll
                for (int i = 0; i < 4; i++) st_relaxed_v4(ib + i * 512, SENT);
                st_relaxed_b32(xaddr(lds32_volatile(tbl + 28) + pub_slot(s + 3) + (lane & 16) * 256 + (lane & 8) * 16 + (lane & 7) * 4, xhi), SENT);
            }
            if (warp == 1) {
                if (elect_one()) {
                    #pragma unroll
                    for (int g = 0; g < 4; g++) mbar_arrive_expect_tx(bar + BAR_XG + 8 * g, 16384);
                }
                if (s + 2 < NSEG && cta < 4 && elect_one())
                    asm volatile("cp.async.bulk.prefetch.tensor.3d.L2.global [%0, {%1, %2, %3}];"
                                 ::"l"(&p.tmX), "r"(0), "r"((s + 2) * SEG), "r"(cta * 4) : "memory");
                if (rank == 0) {
                    mbar_wait_bounded(bar + BAR_F0, par);
                    if (elect_one()) x_load(p, sb, s + 1, 0);
                }
            }
            if (WO_PFA < WO_PF1 || (u_role & 16)) mbar_wait_bounded(bar + BAR_X, par);
            if (WO_PFA < WO_PF1) {
                spin_clks(WO_PFB_DELAY);
                #pragma unroll
                for (int n = WO_PFA; n < WO_PF1; n++) ldsm4t(wo_addr<3>(ao, a3, n), st[n]);
            }
            if (u_role & 16) {
                spin_clks(XB_DELAY);
                mbar_wait_bounded(bar + BAR_VM, par);
                if (elect_one()) x_load(p, sb, s + 1, rank);
            }
            named_bar_sync(6, REC_THREADS);
            wo_phase<3, WO_PF1>(st, ao, a3, l16, tbl, sb + SM_SUM, slot, xhi, u_role & 4);
        }
        STAMP(7);
        if (wg == 0) named_bar_sync(9, REC_THREADS); else named_bar_arrive(9, REC_THREADS);
    }
    mbar_wait(bar + BAR_X, 1);
    mbar_wait(bar + BAR_VM, 1);
    if (qk) mbar_wait(bar + BAR_V, 1);
    named_bar_sync(0, REC_THREADS);
    if (warp == 4 && elect_one()) {
        bulk_wait_all();
        signal_flag(p.flags + F_PROGRESS + NSEG - 1);
    }
}

__global__ void __launch_bounds__(REC_THREADS, 1) rec_kernel(const __grid_constant__ RecParams p) {
    extern __shared__ __align__(1024) uint8_t smem_raw[];
    const uint32_t sb = smem_u32(smem_raw);
    const int tid = threadIdx.x, lane = tid & 31;
    const int warp = __shfl_sync(~0u, tid >> 5, 0);
    const int cta = blockIdx.x, head = cta / 3, rank = cta % 3;
    const int wg = warp >> 2, wq = warp & 3;
    const int t0 = (rank * 64 + 2) / 3;
    const uint32_t bar = sb + SM_BAR;
    uint8_t* const xb = p.xchg;
    const uint32_t xlo = (uint32_t)(uint64_t)xb;
    if ((sb & 0x3FFFF) != SMEM_ORIGIN) __trap();
    KENTER(1);
    auto w_box = [&](int part, int g, int i, uint32_t dst, uint32_t mb) {
        const int m = i ^ g;
        const CUtensorMap* tm = &p.tmW[rank == 2 ? 2 : m];
        const int col = head * DH + (rank == 2 ? m : rank) * 64, row = ((part + 1) & 3) * 16;
        if (mb) tma_load_3d(dst, tm, col, row, g * 8, mb);
        else asm volatile("cp.async.bulk.prefetch.tensor.3d.L2.global [%0, {%1, %2, %3}];" ::"l"(tm), "r"(col), "r"(row), "r"(g * 8) : "memory");
    };
    auto wo_box = [&](int b, uint32_t mb) {
        if (mb) tma_load_2d(sb + SM_WO + b * 8192, &p.tmWo, t0 * 16 + b * 32, head * DH, mb);
        else asm volatile("cp.async.bulk.prefetch.tensor.2d.L2.global [%0, {%1, %2}];" ::"l"(&p.tmWo), "r"(t0 * 16 + b * 32), "r"(head * DH) : "memory");
    };
    if (tid == 0) {
        mbar_init(bar + BAR_V, 1);
        for (int i = 0; i < 4; i++) { mbar_init(bar + BAR_XG + 8 * i, 1); mbar_init(bar + BAR_M + 8 * i, 1); }
        mbar_init(bar + BAR_GO, 4);
        mbar_init(bar + BAR_PK, 4);
        mbar_init(bar + BAR_OUT, 4);
        mbar_init(bar + BAR_VM, rank < 2 ? 1 : 9);
        mbar_init(bar + BAR_F0, 3);
        mbar_init(bar + BAR_F3, 3);
        mbar_init(bar + BAR_VF, 3);
        sts64(bar + BAR_MIN, ~0u, ~0u);
        mbar_init(bar + BAR_X, rank < 2 ? 6 : 1);
        for (int i = 0; i < 3; i++) mbar_init(bar + BAR_P0 + 8 * i, 1);
        mbar_init(bar + BAR_WQ, 1);
        mbar_init(bar + BAR_WO, 2);
        sts32(bar + BAR_SELF, bar + BAR_SELF);
        asm volatile("fence.mbarrier_init.release.cluster;" ::: "memory");
        for (int part = 0; part < 3; part++) {
            mbar_arrive_expect_tx(bar + BAR_P0 + 8 * part, 65536);
            for (int u = 0; u < 4; u++) w_box(part, u >> 1, u & 1, sb + part * 65536 + u * 16384, bar + BAR_P0 + 8 * part);
        }
        for (int u = 0; u < 4; u++) w_box(3, u >> 1, u & 1, 0, 0);
        if (cta < 8)
            asm volatile("cp.async.bulk.prefetch.tensor.3d.L2.global [%0, {%1, %2, %3}];"
                         ::"l"(&p.tmX), "r"(0), "r"((cta >> 2) * SEG), "r"((cta & 3) * 4) : "memory");
        for (int b = 0; b < 11; b++) wo_box(b, 0);
    }
    __syncthreads();
    if (cta == 0 && tid < F_COUNT) {
        p.flags[tid] = 0;
        __threadfence();
    }
    {
        uint8_t* pr = xb + cta * 8192;
        const uint32_t c0 = class_off(xlo + cta * 8192, 0);
        if (lane < 12) *reinterpret_cast<uint4*>(pr + (((lane >> 1) & 1) << 12) + (warp * 4 + (lane >> 2)) * 128 + (lane & 1) * 16) = make_uint4(0, 0, 0, 0);
        __syncwarp();
        if (lane == 0) {
            uint32_t x = 0;
            for (int k = 0; k < 6; k++) {
                const uint32_t t0 = clock_after(x);
                x = atomicAdd(reinterpret_cast<uint32_t*>(pr + (c0 ^ ((k & 1) << 12)) + (warp * 4 + (k >> 1)) * 128 + x), 1u);
                const uint32_t lat = clock_after(x) - t0;
                asm volatile("red.shared.min.u32 [%0], %1;" ::"r"(bar + BAR_MIN + 4 * (k & 1)), "r"(lat) : "memory");
            }
        }
    }
    __syncthreads();
    if (tid == 0) {
        pdl_launch_dependents();
        p.ctacolor[cta] = lds32_volatile(bar + BAR_MIN) > lds32_volatile(bar + BAR_MIN + 4) ? 1 : 0;
    }
    for (int pair = cta; pair < XCHG_BYTES / 8192; pair += 96) {
        uint4 v = make_uint4(SENT, SENT, SENT, SENT);
        if (pair < 4) {
            const unsigned short* m = reinterpret_cast<const unsigned short*>(p.mem0) + pair * 256 + tid;
            uint32_t w[4];
            #pragma unroll
            for (int i = 0; i < 4; i++) {
                w[i] = (uint32_t)__ldg(m + 2 * i * DM) | ((uint32_t)__ldg(m + (2 * i + 1) * DM) << 16);
                if (w[i] == SENT) w[i] = 0x7FFF7FFFu;
            }
            v = make_uint4(w[0], w[1], w[2], w[3]);
        }
        reinterpret_cast<uint4*>(xb + pair * 8192)[tid] = v;
        reinterpret_cast<uint4*>(xb + pair * 8192 + 4096)[tid] = v;
    }
    __syncthreads();
    if (tid == 224) signal_flag(p.arrivals);
    PSTAMP(4);
    uint32_t wr[NREG][2][4];
    {
        const int mi = lane >> 3, r8 = lane & 7;
        const uint32_t a0 = sb + wg * 32768 + ((mi >> 1) * 8 + r8) * 128 + (((wq * 2 + (mi & 1)) ^ r8) << 4);
        #pragma unroll
        for (int part = 0; part < 3; part++) {
            mbar_wait(bar + BAR_P0 + 8 * part, 0);
            #pragma unroll
            for (int j = 0; j < 8; j++) {
                #pragma unroll
                for (int i = 0; i < 2; i++) ldsm4t(a0 + part * 65536 + i * 16384 + j * 2048, wr[part * 8 + j][i]);
            }
            asm volatile("fence.proxy.async.shared::cta;" ::: "memory");
            __syncthreads();
            if (tid == 0) {
                if (part == 0) {
                    mbar_arrive_expect_tx(bar + BAR_WQ, 65536);
                    for (int u = 0; u < 4; u++) w_box(3, u >> 1, u & 1, sb + SM_WQ + u * 16384, bar + BAR_WQ);
                } else {
                    mbar_arrive_expect_tx(bar + BAR_WO, (part == 1 ? 8 : 3) * 8192);
                    for (int b = part == 1 ? 0 : 8; b < (part == 1 ? 8 : 11); b++) wo_box(b, bar + BAR_WO);
                }
            }
        }
    }
    PSTAMP(5);
    cluster_sync();
    if (tid == 0) {
        for (int g = 0; g < 4; g++) mbar_arrive_expect_tx(bar + BAR_XG + 8 * g, 16384);
        x_load(p, sb, 0, rank);
        if (rank == 0) x_load(p, sb, 0, 3);
    }
    PSTAMP(8);
    if (tid == 0) wait_flag(p.arrivals, 96);
    PSTAMP(9);
    __syncthreads();
    {
        uint32_t cm[3];
        #pragma unroll
        for (int i = 0; i < 3; i++) cm[i] = __ballot_sync(~0u, __ldcg(p.ctacolor + i * 32 + lane) != 0);
        auto color_of = [&](int o) { return ((o < 32 ? cm[0] : o < 64 ? cm[1] : cm[2]) >> (o & 31)) & 1u; };
        auto inbox = [&](int o, int byte) {
            uint32_t c = color_of(o);
            int ones = 0;
            #pragma unroll
            for (int i = 0; i < 3; i++) ones += __popc(o >= i * 32 + 32 ? cm[i] : (o > i * 32 ? cm[i] & ((1u << (o - i * 32)) - 1) : 0u));
            int idx = c ? ones : o - ones;
            if (idx >= INBOX_MAX) { idx = 2 * INBOX_MAX - 1 - idx; c ^= 1; }
            const uint32_t lin = idx * 6144 + byte, q = XCHG_INBOX + (lin >> 12) * 8192;
            return q + class_off(xlo + q, c) + (lin & 4095);
        };
        uint32_t off = 0;
        const int grp = (warp + 3) & 3;
        if (lane < 12) {
            const int i = lane >> 2, lt0 = rank == 0 ? 0 : (rank == 1 ? 6 : 11);
            const int o = i < 2 ? rank * 32 + warp * 4 + (lane & 3) : (lt0 + ((warp + 4) & 7)) * 4 + (lane & 3);
            off = inbox(min(o, 95), i * 2048 + head * 64);
        } else if (lane == 12) {
            off = inbox(cta, (grp % 3) * 2048);
        } else if (lane == 13) {
            int T;
            if (grp < 2) {
                T = ((cta >> 5) * 64 + 2) / 3 + 8 * grp + ((cta & 31) >> 2);
            } else {
                const int tl = (cta & 63) >> 2;
                T = tl < 6 ? 16 + tl : (tl < 11 ? 22 + 16 + (tl - 6) : 43 + 16 + (tl - 11));
            }
            off = XCHG_PUB + (T >> 4) * 8192 + (T & 15) * 256 + (cta & 3) * 32;
        } else if (lane == 14) {
            const uint32_t q = XCHG_PUB + wq * 8192;
            off = q + class_off(xlo + q, color_of(cta));
        }
        if (lane < 16) asm volatile("st.shared.b32 [%0], %1;" ::"r"(sb + SM_TBL + warp * 64 + (lane & 3) * 16 + (lane >> 2) * 4), "r"(xlo + off) : "memory");
    }
    mbar_wait(bar + BAR_WQ, 0);
    mbar_wait(bar + BAR_WO, 0);
    __syncthreads();

    rec_steps(p, wr, sb, warp, cta, head, rank);
    if (cta == 0 && tid == 0) *p.arrivals = 0;
    cluster_sync();
    if (tid == 0) KEXIT(1);
}

constexpr int ATT_A_BYTES = 3 * 8192 + 2 * 2048;
constexpr int ATT_TASKW = 4 * ATT_A_BYTES;
constexpr int ATT_SMEM = ATT_TASKW + 16;
struct AttnParams {
    const __nv_bfloat16* qkv_tok;
    const __nv_bfloat16* kv_mem;
    __nv_bfloat16* o_tok;
    const __nv_bfloat16* qkv_b;
    __nv_bfloat16* o_b;
    uint32_t* flags;
};

__device__ __forceinline__ void tok_attn_warp(uint32_t base, int hh, int mh, int lane, __nv_bfloat16* obase) {
    const uint32_t sq = base + hh * 8192, sk = sq + 32768, sv = sq + 65536, skm = base + 98304 + hh * 4096, svm = skm + 2048;
    const int g = lane >> 2, c = lane & 3, mi = lane >> 3, r8 = lane & 7;
    const int ntile = mh ? 5 : 3;
    float sc[5][4];
    #pragma unroll
    for (int j = 0; j < 5; j++) { sc[j][0] = sc[j][1] = sc[j][2] = sc[j][3] = 0.f; }
    #pragma unroll
    for (int t2 = 0; t2 < 4; t2++) {
        uint32_t a[2][4];
        #pragma unroll
        for (int h = 0; h < 2; h++) {
            const int row = mh * 16 + (mi & 1) * 8 + r8, ch16 = 4 * t2 + 2 * h + (mi >> 1);
            ldsm_x4(sq + (ch16 >> 3) * 4096 + row * 128 + (((ch16 & 7) ^ r8) << 4), a[h][0], a[h][1], a[h][2], a[h][3]);
        }
        const int ch16 = 4 * t2 + mi;
        uint32_t b[5][4];
        #pragma unroll
        for (int j = 0; j < 5; j++) {
            if (j < ntile) {
                if (j == 0) ldsm_x4_t(skm + t2 * 512 + lane * 16, b[j][0], b[j][1], b[j][2], b[j][3]);
                else ldsm_x4(sk + (ch16 >> 3) * 4096 + ((j - 1) * 8 + r8) * 128 + (((ch16 & 7) ^ r8) << 4), b[j][0], b[j][1], b[j][2], b[j][3]);
            }
        }
        #pragma unroll
        for (int h = 0; h < 2; h++) {
            #pragma unroll
            for (int j = 0; j < 5; j++)
                if (j < ntile) mma16816(sc[j], a[h][0], a[h][1], a[h][2], a[h][3], b[j][2 * h], b[j][2 * h + 1]);
        }
    }
    APROF(10);
    const float sl2 = 0.08838834764831845f * 1.4426950408889634f;
    uint32_t pf[2][5];
    float inv[2];
    #pragma unroll
    for (int q = 0; q < 2; q++) {
        const int tok = mh * 16 + q * 8 + g;
        float v[10];
        #pragma unroll
        for (int j = 0; j < 5; j++) {
            #pragma unroll
            for (int e = 0; e < 2; e++) {
                const int key = (j - 1) * 8 + 2 * c + e;
                v[2 * j + e] = (j == 0 || key <= tok) ? sc[j][2 * q + e] : -INFINITY;
            }
        }
        float mx = v[0];
        #pragma unroll
        for (int j = 1; j < 10; j++) mx = fmaxf(mx, v[j]);
        mx = fmaxf(mx, __shfl_xor_sync(~0u, mx, 1));
        mx = fmaxf(mx, __shfl_xor_sync(~0u, mx, 2));
        const float mo = mx * sl2;
        float sum = 0.f;
        #pragma unroll
        for (int j = 0; j < 10; j++) { v[j] = ex2(fmaf(v[j], sl2, -mo)); sum += v[j]; }
        sum += __shfl_xor_sync(~0u, sum, 1);
        sum += __shfl_xor_sync(~0u, sum, 2);
        inv[q] = rcp(sum);
        #pragma unroll
        for (int j = 0; j < 5; j++) pf[q][j] = pack_bf16(v[2 * j], v[2 * j + 1]);
    }
    APROF(11);
    auto load_v = [&](int n4, uint32_t (&vm)[4], uint32_t (&vt)[4][4]) {
        ldsm_x4(svm + n4 * 512 + lane * 16, vm[0], vm[1], vm[2], vm[3]);
        #pragma unroll
        for (int u = 0; u < 4; u++) {
            const int dt = 2 * n4 + (u >> 1), kh = u & 1;
            const uint4 v = lds128(sv + (dt & 3) * 2048 + (dt >> 2) * 1024 + kh * 512 + lane * 16);
            vt[u & 2][2 * kh] = v.x; vt[u & 2][2 * kh + 1] = v.z;
            vt[(u & 2) + 1][2 * kh] = v.y; vt[(u & 2) + 1][2 * kh + 1] = v.w;
        }
    };
    uint32_t vm[2][4], vt[2][4][4];
    load_v(0, vm[0], vt[0]);
    #pragma unroll
    for (int n4 = 0; n4 < 4; n4++) {
        const int cur = n4 & 1;
        if (n4 + 1 < 4) load_v(n4 + 1, vm[cur ^ 1], vt[cur ^ 1]);
        float o[4][4];
        #pragma unroll
        for (int u = 0; u < 4; u++) {
            o[u][0] = o[u][1] = o[u][2] = o[u][3] = 0.f;
            mma16816(o[u], pf[0][1], pf[1][1], pf[0][2], pf[1][2], vt[cur][u][0], vt[cur][u][1]);
        }
        if (mh) {
            #pragma unroll
            for (int u = 0; u < 4; u++) mma16816(o[u], pf[0][3], pf[1][3], pf[0][4], pf[1][4], vt[cur][u][2], vt[cur][u][3]);
        }
        #pragma unroll
        for (int u = 0; u < 4; u++) mma1688(o[u], pf[0][0], pf[1][0], vm[cur][u]);
        #pragma unroll
        for (int u = 0; u < 4; u += 2) {
            const int row = mh * 16 + (mi & 1) * 8 + r8, nt = 4 * n4 + u + (mi >> 1);
            stsm_x4(sq + (nt >> 3) * 4096 + row * 128 + (((nt & 7) ^ r8) << 4),
                    pack_bf16(o[u][0] * inv[0], o[u][1] * inv[0]), pack_bf16(o[u][2] * inv[1], o[u][3] * inv[1]),
                    pack_bf16(o[u + 1][0] * inv[0], o[u + 1][1] * inv[0]), pack_bf16(o[u + 1][2] * inv[1], o[u + 1][3] * inv[1]));
        }
    }
    __syncwarp();
    APROF(12);
    #pragma unroll
    for (int i = 0; i < 8; i++) {
        const int row = 2 * i + (lane >> 4), ch = lane & 15;
        const uint4 v = lds128(sq + (ch >> 3) * 4096 + (mh * 16 + row) * 128 + (((ch & 7) ^ (row & 7)) << 4));
        *reinterpret_cast<uint4*>(obase + (size_t)row * HD + ch * 8) = v;
    }
}

__device__ __forceinline__ void b_attn_warp(uint32_t base, int hl, int half, int tok0, int lane, __nv_bfloat16* obase) {
    const uint32_t sq = base, sk = base + 128 * 256, sv = base + (128 + 144) * 256;
    const int g = lane >> 2, c = lane & 3;
    auto addr = [&](uint32_t t, int row, int ch) { return t + row * 256 + ((ch ^ ((row >> 1) & 7)) << 4); };
    const float sl2 = 0.17677669529663687f * 1.4426950408889634f;
    #pragma unroll 2
    for (int blk = half * 4; blk < half * 4 + 4; blk++) {
        const int r0 = (blk >> 1) * 32 + (blk & 1);
        float sc[3][4];
        #pragma unroll
        for (int j = 0; j < 3; j++) { sc[j][0] = sc[j][1] = sc[j][2] = sc[j][3] = 0.f; }
        #pragma unroll
        for (int t = 0; t < 2; t++) {
            uint32_t a0, a1, a2, a3, b0, b1, b2, b3, d0, d1, d2, d3;
            const int mi = lane >> 3, r = lane & 7;
            ldsm_x4(addr(sq, r0 + 2 * ((mi & 1) * 8 + r), hl * 4 + 2 * t + (mi >> 1)), a0, a1, a2, a3);
            ldsm_x4(addr(sk, r0 + 2 + 2 * ((mi >> 1) * 8 + r), hl * 4 + 2 * t + (mi & 1)), b0, b1, b2, b3);
            ldsm_x4(addr(sk, min(r0 + 2 + 2 * (16 + r), 143), hl * 4 + 2 * t + (mi & 1)), d0, d1, d2, d3);
            mma16816(sc[0], a0, a1, a2, a3, b0, b1);
            mma16816(sc[1], a0, a1, a2, a3, b2, b3);
            mma16816(sc[2], a0, a1, a2, a3, d0, d1);
        }
        uint32_t pf[2][3];
        float inv[2];
        #pragma unroll
        for (int r = 0; r < 2; r++) {
            const int u = r * 8 + g;
            float v[6];
            #pragma unroll
            for (int j = 0; j < 3; j++) {
                #pragma unroll
                for (int e = 0; e < 2; e++) {
                    const int key = j * 8 + 2 * c + e;
                    const bool ok = key >= u && key <= u + 7 && tok0 + r0 - 14 + 2 * key >= 0;
                    v[2 * j + e] = ok ? sc[j][2 * r + e] : -INFINITY;
                }
            }
            float mx = fmaxf(fmaxf(fmaxf(v[0], v[1]), fmaxf(v[2], v[3])), fmaxf(v[4], v[5]));
            mx = fmaxf(mx, __shfl_xor_sync(~0u, mx, 1));
            mx = fmaxf(mx, __shfl_xor_sync(~0u, mx, 2));
            const float mo = mx * sl2;
            float sum = 0.f;
            #pragma unroll
            for (int j = 0; j < 6; j++) { v[j] = ex2(fmaf(v[j], sl2, -mo)); sum += v[j]; }
            sum += __shfl_xor_sync(~0u, sum, 1);
            sum += __shfl_xor_sync(~0u, sum, 2);
            inv[r] = rcp(sum);
            #pragma unroll
            for (int j = 0; j < 3; j++) pf[r][j] = pack_bf16(v[2 * j], v[2 * j + 1]);
        }
        uint32_t ow[4][2];
        {
            const int mi = lane >> 3, r = lane & 7;
            uint32_t vv[4][4];
            #pragma unroll
            for (int nt = 0; nt < 4; nt++)
                ldsm_x4_t(addr(sv, min(r0 + 2 + 2 * (min(mi, 2) * 8 + r), 143), hl * 4 + nt), vv[nt][0], vv[nt][1], vv[nt][2], vv[nt][3]);
            float o[4][4];
            #pragma unroll
            for (int nt = 0; nt < 4; nt++) {
                o[nt][0] = o[nt][1] = o[nt][2] = o[nt][3] = 0.f;
                mma16816(o[nt], pf[0][0], pf[1][0], pf[0][1], pf[1][1], vv[nt][0], vv[nt][1]);
            }
            #pragma unroll
            for (int nt = 0; nt < 4; nt++) mma1688(o[nt], pf[0][2], pf[1][2], vv[nt][2]);
            #pragma unroll
            for (int nt = 0; nt < 4; nt++) {
                ow[nt][0] = pack_bf16(o[nt][0] * inv[0], o[nt][1] * inv[0]);
                ow[nt][1] = pack_bf16(o[nt][2] * inv[1], o[nt][3] * inv[1]);
            }
        }
        #pragma unroll
        for (int u = 0; u < 4; u += 2) {
            const int mi = lane >> 3, r = lane & 7;
            stsm_x4(addr(sq, r0 + 2 * ((mi & 1) * 8 + r), hl * 4 + u + (mi >> 1)), ow[u][0], ow[u][1], ow[u + 1][0], ow[u + 1][1]);
        }
    }
    __syncwarp();
    #pragma unroll
    for (int i = 0; i < 8; i++) {
        const int row = half * 64 + i * 8 + (lane >> 2);
        const uint4 v = lds128(addr(sq, row, hl * 4 + (lane & 3)));
        *reinterpret_cast<uint4*>(obase + (size_t)row * DM + (lane & 3) * 8) = v;
    }
}

constexpr uint32_t QKVB_TARGET = 12 * 8;
constexpr uint32_t PROGRESS_TARGET = 96;
constexpr int ATT_A_TASKS = NSEG * 8;
constexpr int ATT_B_TASKS = 16 * 8;
constexpr uint32_t ATT_B_BIT = 0x10000u, ATT_DONE = 0xFFFFFFFFu;

constexpr uint32_t ATT_RETRY = 0xFFFFFFFEu;
__device__ __forceinline__ uint32_t attn_pick(uint32_t* flags) {
    const uint32_t ha = ld_relaxed_b32(flags + F_QUEUE3), hb = ld_relaxed_b32(flags + F_QUEUE4);
    const bool left_a = ha < ATT_A_TASKS, left_b = hb < ATT_B_TASKS;
    if (!left_a && !left_b) return ATT_DONE;
    uint32_t pa = left_a ? ld_relaxed_b32(flags + F_PROGRESS + (ha >> 3)) : 0u;
    const uint32_t pb = left_b ? ld_relaxed_b32(flags + F_QKVB + (hb >> 3)) : 0u;
    if (pa >= PROGRESS_TARGET || !left_b) {
        const uint32_t t = atomicAdd(flags + F_QUEUE3, 1u);
        if (t < ATT_A_TASKS) return t;
        if (!left_b) return ATT_DONE;
    }
    if (pb >= QKVB_TARGET) {
        const uint32_t t = atomicAdd(flags + F_QUEUE4, 1u);
        if (t < ATT_B_TASKS) return t | ATT_B_BIT;
    }
    return ATT_RETRY;
}

constexpr int ATT_THREADS = 288;
__global__ void __launch_bounds__(ATT_THREADS, 2) attn_kernel(const AttnParams p) {
    extern __shared__ uint8_t smem_raw[];
    const uint32_t sb = smem_u32(smem_raw), taskw = sb + ATT_TASKW;
    const int tid = threadIdx.x, warp = tid >> 5, lane = tid & 31;
    const uint32_t bar_ld = taskw + 8;
    if (tid == 0) {
        pdl_launch_dependents();
        mbar_init(bar_ld, 1);
        asm volatile("fence.mbarrier_init.release.cluster;" ::: "memory");
    }
    KENTER(3);
    __syncthreads();
    if (warp == 8) {
        auto pick = [&]() {
            uint32_t t, n = 0;
            while ((t = attn_pick(p.flags)) == ATT_RETRY) {
                __nanosleep(50);
                if (++n > SPIN_LIMIT) __trap();
            }
            return t;
        };
        uint32_t task = 0;
        if (lane == 0) task = pick();
        uint32_t* pending = nullptr;
        while (true) {
            if (lane == 0) asm volatile("st.shared.b32 [%0], %1;" ::"r"(taskw), "r"(task) : "memory");
            __syncwarp();
            named_bar_sync(1, ATT_THREADS);
            task = __shfl_sync(~0u, task, 0);
            if (lane == 0 && task != ATT_DONE && !(task & ATT_B_BIT)) {
                {
                    const uint32_t* fq = p.flags + F_PROGRESS + (task >> 3);
                    if (ld_acquire_b32(fq) < PROGRESS_TARGET) {
                        if (pending) { signal_flag(pending); pending = nullptr; }
                        wait_flag(fq, PROGRESS_TARGET);
                    }
                    asm volatile("fence.proxy.async;" ::: "memory");
                }
                asm volatile("fence.proxy.async.shared::cta;" ::: "memory");
                mbar_arrive_expect_tx(bar_ld, 3 * 32768);
                #pragma unroll
                for (int w = 0; w < 3; w++)
                    bulk_load(sb + w * 32768, p.qkv_tok + (((size_t)w * NSEG + (task >> 3)) * NH + (task & 7) * 4) * (SEG * DH), 32768, bar_ld);
            }
            if (task == ATT_DONE) {
                if (lane == 0 && pending) signal_flag(pending);
                break;
            }
            uint32_t* mine = nullptr;
            if (lane == 0) {
                const bool isb = task & ATT_B_BIT;
                const int mt = (task & 0xFFFF) >> 3;
                const uint32_t* dep = isb ? p.flags + F_QKVB + mt : p.flags + F_PROGRESS + mt;
                const uint32_t target = isb ? QKVB_TARGET : PROGRESS_TARGET;
                if (ld_acquire_b32(dep) < target) {
                    if (pending) { signal_flag(pending); pending = nullptr; }
                    wait_flag(dep, target);
                }
                if (isb && mt > 0) wait_flag(dep - 1, QKVB_TARGET);
                mine = isb ? p.flags + F_OB + mt : p.flags + F_OA + (mt >> 2);
            }
            __syncwarp();
            named_bar_sync(2, ATT_THREADS);
            if (lane == 0) {
                if (pending) signal_flag(pending);
                pending = mine;
            }
            uint32_t nxt = ATT_RETRY;
            if (lane == 0) nxt = attn_pick(p.flags);
            __syncwarp();
            named_bar_sync(3, ATT_THREADS);
            if (lane == 0) {
                if (nxt == ATT_RETRY) {
                    signal_flag(pending);
                    pending = nullptr;
                    nxt = pick();
                }
                task = nxt;
            }
        }
    } else {
        uint32_t ld_phase = 0;
        while (true) {
            named_bar_sync(1, ATT_THREADS);
            APROF(1);
            const uint32_t task = lds32_volatile(taskw);
            if (task == ATT_DONE) break;
            if (task & ATT_B_BIT) {
                const int mt = (task & 0xFFFF) >> 3, hg = task & 7, tok0 = mt * 128;
                named_bar_sync(2, ATT_THREADS);
                #pragma unroll 2
                for (int i = tid; i < 416 * 16; i += 256) {
                    const int row = i >> 4, ch = i & 15;
                    const int which = row < 128 ? 0 : (row < 272 ? 1 : 2);
                    const int r = row < 128 ? row : (row < 272 ? row - 128 : row - 272);
                    const int tok = which == 0 ? tok0 + r : max(tok0 - 16 + r, 0);
                    cp_async16(sb + row * 256 + ((ch ^ ((r >> 1) & 7)) << 4),
                               p.qkv_b + (size_t)tok * (3 * DM) + which * DM + hg * 128 + ch * 8);
                }
                cp_async_commit();
                cp_async_wait<0>();
                named_bar_sync(4, 256);
                APROF(8);
                b_attn_warp(sb, warp & 3, warp >> 2, tok0, lane, p.o_b + (size_t)tok0 * DM + hg * 128 + (warp & 3) * 32);
                APROF(9);
            } else {
                const int seg = task >> 3, hq = task & 7;
                APROF(2);
                named_bar_sync(2, ATT_THREADS);
                APROF(3);
                #pragma unroll
                for (int w = 0; w < 2; w++) {
                    const uint8_t* src = reinterpret_cast<const uint8_t*>(p.kv_mem + (((size_t)w * NSEG + seg) * NH + hq * 4) * (MROWS * DH));
                    #pragma unroll
                    for (int u = 0; u < 2; u++) {
                        const int e = u * 256 + tid;
                        cp_async16(sb + 98304 + (e >> 7) * 4096 + w * 2048 + (e & 127) * 16, src + e * 16);
                    }
                }
                cp_async_commit();
                cp_async_wait<0>();
                mbar_wait(bar_ld, ld_phase);
                ld_phase ^= 1;
                named_bar_sync(4, 256);
                APROF(4);
                const int hh = warp >> 1, mh = warp & 1;
                tok_attn_warp(sb, hh, mh, lane,
                              p.o_tok + (size_t)(seg * SEG + mh * 16) * HD + (hq * 4 + hh) * DH);
                APROF(7);
            }
            named_bar_sync(3, ATT_THREADS);
            APROF(0);
        }
    }
    if (tid == 256) KEXIT(3);
}

typedef CUresult (*EncodeFn)(CUtensorMap*, CUtensorMapDataType, cuuint32_t, void*, const cuuint64_t*, const cuuint64_t*,
                             const cuuint32_t*, const cuuint32_t*, CUtensorMapInterleave, CUtensorMapSwizzle,
                             CUtensorMapL2promotion, CUtensorMapFloatOOBfill);

void make_map_2d(EncodeFn enc, CUtensorMap* m, const void* ptr, uint64_t rows, uint64_t cols, uint32_t box_rows, uint32_t box_cols = 64) {
    cuuint64_t dims[2] = {cols, rows};
    cuuint64_t strides[1] = {cols * 2};
    cuuint32_t box[2] = {box_cols, box_rows};
    cuuint32_t es[2] = {1, 1};
    enc(m, CU_TENSOR_MAP_DATA_TYPE_BFLOAT16, 2, const_cast<void*>(ptr), dims, strides, box, es,
        CU_TENSOR_MAP_INTERLEAVE_NONE, box_cols == 64 ? CU_TENSOR_MAP_SWIZZLE_128B : CU_TENSOR_MAP_SWIZZLE_64B, CU_TENSOR_MAP_L2_PROMOTION_L2_256B,
        CU_TENSOR_MAP_FLOAT_OOB_FILL_NONE);
}
void make_map_b(EncodeFn enc, CUtensorMap* m, const void* ptr, uint64_t k, uint64_t n, uint32_t nblk, uint32_t box_rows = 64) {
    cuuint64_t dims[3] = {64, k, n / 64};
    cuuint64_t strides[2] = {n * 2, 128};
    cuuint32_t box[3] = {64, box_rows, nblk};
    cuuint32_t es[3] = {1, 1, 1};
    enc(m, CU_TENSOR_MAP_DATA_TYPE_BFLOAT16, 3, const_cast<void*>(ptr), dims, strides, box, es,
        CU_TENSOR_MAP_INTERLEAVE_NONE, CU_TENSOR_MAP_SWIZZLE_128B, CU_TENSOR_MAP_L2_PROMOTION_L2_256B,
        CU_TENSOR_MAP_FLOAT_OOB_FILL_NONE);
}

void make_map_w(EncodeFn enc, CUtensorMap* m, const void* ptr) {
    cuuint64_t dims[3] = {HD, 64, DM / 64};
    cuuint64_t strides[2] = {HD * 2, 64 * HD * 2};
    cuuint32_t box[3] = {64, 16, 8};
    cuuint32_t es[3] = {1, 1, 1};
    enc(m, CU_TENSOR_MAP_DATA_TYPE_BFLOAT16, 3, const_cast<void*>(ptr), dims, strides, box, es,
        CU_TENSOR_MAP_INTERLEAVE_NONE, CU_TENSOR_MAP_SWIZZLE_128B, CU_TENSOR_MAP_L2_PROMOTION_L2_256B,
        CU_TENSOR_MAP_FLOAT_OOB_FILL_NONE);
}

#define OUTB_SIDE_BLOCKS 8
#define SIDE_ORDER 0
#define N_POST_CTAS 0
#define N_POST_ATT 0
#define N_SIDE_CTAS 26
#define N_ATT_CTAS 20
#define TAIL_BLOCK0 12

struct HostState {
    bool ready;
    bool overlap;
    int n_side, n_att, n_sm;
    SideParams seq_a, seq_b;
    const void* key[11];
    RecParams rec;
    SideParams side, tail, outb;
    FinalParams fin;
    AttnParams attn;
    __nv_bfloat16 *qkv_tok, *kv_mem, *o_tok, *qkv_b, *o_b;
    uint8_t* xchg;
};
HostState g_host;

void setup(void* const* d_in, void* d_out) {
    HostState& h = g_host;
    void* fn = nullptr;
    cudaDriverEntryPointQueryResult qr;
    cudaGetDriverEntryPoint("cuTensorMapEncodeTiled", &fn, cudaEnableDefault, &qr);
    EncodeFn enc = reinterpret_cast<EncodeFn>(fn);
    void* ptr;
    cudaGetSymbolAddress(&ptr, g_qkv_tok); h.qkv_tok = (__nv_bfloat16*)ptr;
    cudaGetSymbolAddress(&ptr, g_kv_mem);  h.kv_mem = (__nv_bfloat16*)ptr;
    cudaGetSymbolAddress(&ptr, g_o_tok);   h.o_tok = (__nv_bfloat16*)ptr;
    cudaGetSymbolAddress(&ptr, g_qkv_b);   h.qkv_b = (__nv_bfloat16*)ptr;
    cudaGetSymbolAddress(&ptr, g_o_b);     h.o_b = (__nv_bfloat16*)ptr;
    cudaGetSymbolAddress(&ptr, g_xchg);    h.xchg = (uint8_t*)(((uint64_t)ptr + XCHG_BYTES - 1) & ~(uint64_t)(XCHG_BYTES - 1));
    cudaGetSymbolAddress(&ptr, g_ctacolor); int* ctacolor = (int*)ptr;
    cudaGetSymbolAddress(&ptr, g_flags);   uint32_t* flags = (uint32_t*)ptr;
    cudaGetSymbolAddress(&ptr, g_arrivals); uint32_t* arrivals = (uint32_t*)ptr;

    const void *xa = d_in[0], *mem0 = d_in[1], *wq = d_in[2], *wk = d_in[3], *wv = d_in[4], *wo = d_in[5];
    const void *xb = d_in[7], *wqkv = d_in[8], *wob = d_in[9];

    RecParams& r = h.rec;
    make_map_w(enc, &r.tmW[0], wq);
    make_map_w(enc, &r.tmW[1], wk);
    make_map_w(enc, &r.tmW[2], wv);
    make_map_2d(enc, &r.tmWo, wo, HD, DM, 128, 32);
    r.mem0 = (const __nv_bfloat16*)mem0;
    r.qkv_tok = h.qkv_tok; r.kv_mem = h.kv_mem; r.xchg = h.xchg; r.ctacolor = ctacolor;
    r.flags = flags; r.arrivals = arrivals; r.one[0] = r.one[1] = 1;
    make_map_b(enc, &r.tmX, xa, S_TOK, DM, 4, SEG);

    SideParams& sd = h.side;
    SideProb& p0 = sd.prob[0];
    make_map_2d(enc, &p0.tmA, xb, S_TOK, DM, BM);
    make_map_b(enc, &p0.tmB, wqkv, DM, 3 * DM, 4);
    make_map_2d(enc, &p0.tmC, h.qkv_b, S_TOK, 3 * DM, 16);
    p0.n_tiles = 3 * DM / 256; p0.k_blocks = DM / BK; p0.c_col0 = 0; p0.dep = nullptr; p0.dep_target = 0; p0.sig = flags + F_QKVB;
    SideProb& p1 = sd.prob[1];
    make_map_2d(enc, &p1.tmA, h.o_tok, S_TOK, HD, BM);
    make_map_b(enc, &p1.tmB, wo, HD, DM, 4);
    make_map_2d(enc, &p1.tmC, d_out, S_TOK, 2 * DM, 16);
    p1.n_tiles = DM / 256; p1.k_blocks = HD / BK; p1.c_col0 = 0; p1.dep = flags + F_OA; p1.dep_target = 32; p1.sig = nullptr;
    SideProb& p2 = sd.prob[2];
    make_map_2d(enc, &p2.tmA, h.o_b, S_TOK, DM, BM);
    make_map_b(enc, &p2.tmB, wob, DM, DM, 4);
    p2.tmC = p1.tmC;
    p2.n_tiles = DM / 256; p2.k_blocks = DM / BK; p2.c_col0 = DM; p2.dep = flags + F_OB; p2.dep_target = 8; p2.sig = nullptr;
    p0.tmB2 = p0.tmB; p1.tmB2 = p1.tmB; p2.tmB2 = p2.tmB;
    p0.n_split = p1.n_split = p2.n_split = 1 << 20;
    p0.blocked = p1.blocked = p2.blocked = nullptr;
    if (SIDE_ORDER == 0) { sd.seg[0] = {0, 0, 16}; sd.seg[1] = {1, 0, TAIL_BLOCK0}; }
    else { sd.seg[0] = {1, 0, TAIL_BLOCK0}; sd.seg[1] = {0, 0, 16}; }
    sd.seg[2] = {2, 0, OUTB_SIDE_BLOCKS};
    sd.nseg = 3; sd.queue = flags + F_SIDEQ;
    h.outb = sd;
    h.outb.seg[0] = {2, OUTB_SIDE_BLOCKS, 16};
    h.outb.nseg = 1; h.outb.queue = flags + F_OUTBQ;

    SideParams& tl = h.tail;
    tl.prob[0] = p1;
    make_map_b(enc, &tl.prob[0].tmB, wo, HD, DM, 2);
    tl.prob[0].n_tiles = DM / 128;
    tl.prob[0].tmB2 = tl.prob[0].tmB;
    tl.prob[1] = tl.prob[2] = tl.prob[3] = tl.prob[4] = tl.prob[0];
    tl.seg[0] = {0, TAIL_BLOCK0, 15};
    tl.nseg = 1; tl.queue = flags + F_TAILQ;

    h.fin.tmA = p1.tmA; h.fin.tmB = tl.prob[0].tmB; h.fin.out = (__nv_bfloat16*)d_out;
    h.fin.dep = flags + F_OA + 15; h.fin.dep_target = 32; h.fin.mt = 15;

    h.attn = {h.qkv_tok, h.kv_mem, h.o_tok, h.qkv_b, h.o_b, flags};

    int dev = 0, nsm = 0;
    cudaGetDevice(&dev);
    cudaDeviceGetAttribute(&nsm, cudaDevAttrMultiProcessorCount, dev);
    h.n_sm = nsm;
    h.overlap = nsm - 96 >= N_SIDE_CTAS + (N_ATT_CTAS + 1) / 2;
    h.n_side = N_SIDE_CTAS; h.n_att = N_ATT_CTAS;
    h.seq_a = sd;
    h.seq_a.seg[0] = {0, 0, 16};
    h.seq_a.seg[1] = {0, 16, 16};
    h.seq_a.nseg = 2;
    h.seq_b = sd;
    h.seq_b.seg[0] = {1, 0, 16};
    h.seq_b.seg[1] = {2, 0, 16};
    h.seq_b.nseg = 2; h.seq_b.queue = flags + F_TAILQ;

    cudaFuncSetAttribute(side_gemm_kernel<256>, cudaFuncAttributeMaxDynamicSharedMemorySize, GemmCfg<256>::SMEM);
    cudaFuncSetAttribute(side_gemm_kernel<128>, cudaFuncAttributeMaxDynamicSharedMemorySize, GemmCfg<128>::SMEM);
    cudaFuncSetAttribute(final_gemm_kernel, cudaFuncAttributeMaxDynamicSharedMemorySize, FIN_SMEM);
    cudaFuncSetAttribute(rec_kernel, cudaFuncAttributeMaxDynamicSharedMemorySize, REC_SMEM);
    cudaFuncSetAttribute(attn_kernel, cudaFuncAttributeMaxDynamicSharedMemorySize, ATT_SMEM);
    for (int i = 0; i < 10; i++) h.key[i] = d_in[i];
    h.key[10] = d_out;
    h.ready = true;
}

template <typename K, typename P>
void launch(K kernel, int grid, int block, int smem, cudaStream_t st, const P& prm, int cluster, bool pdl) {
    cudaLaunchConfig_t cfg = {};
    cfg.gridDim = dim3(grid); cfg.blockDim = dim3(block); cfg.dynamicSmemBytes = smem; cfg.stream = st;
    cudaLaunchAttribute at[2];
    int n = 0;
    if (cluster > 1) {
        at[n].id = cudaLaunchAttributeClusterDimension;
        at[n].val.clusterDim.x = cluster; at[n].val.clusterDim.y = 1; at[n].val.clusterDim.z = 1;
        n++;
    }
    if (pdl) {
        at[n].id = cudaLaunchAttributeProgrammaticStreamSerialization;
        at[n].val.programmaticStreamSerializationAllowed = 1;
        n++;
    }
    cfg.attrs = at; cfg.numAttrs = n;
    cudaLaunchKernelEx(&cfg, kernel, prm);
}

}

extern "C" void kernel_launch(void* const* d_in, const int* in_sizes, int n_in, void* d_out, int out_size) {
    HostState& h = g_host;
    bool same = h.ready;
    for (int i = 0; same && i < 10; i++) same = h.key[i] == d_in[i];
    if (!same || h.key[10] != d_out) setup(d_in, d_out);
    cudaStream_t st = cudaStreamPerThread;

    launch(rec_kernel, 96, REC_THREADS, REC_SMEM, st, h.rec, 3, false);
    {
        if (!h.overlap) {
            launch(side_gemm_kernel<256>, h.n_sm, 384, GemmCfg<256>::SMEM, st, h.seq_a, 1, false);
            launch(attn_kernel, 2 * h.n_sm, ATT_THREADS, ATT_SMEM, st, h.attn, 1, false);
            launch(side_gemm_kernel<256>, h.n_sm, 384, GemmCfg<256>::SMEM, st, h.seq_b, 1, false);
            return;
        }
    }
    launch(side_gemm_kernel<256>, h.n_side, 384, GemmCfg<256>::SMEM, st, h.side, 1, true);
    launch(attn_kernel, h.n_att, ATT_THREADS, ATT_SMEM, st, h.attn, 1, true);
    if (N_POST_ATT > 0) launch(attn_kernel, N_POST_ATT, ATT_THREADS, ATT_SMEM, st, h.attn, 1, true);
    if (N_POST_CTAS > 0) launch(side_gemm_kernel<256>, N_POST_CTAS, 384, GemmCfg<256>::SMEM, st, h.side, 1, true);
    launch(side_gemm_kernel<128>, (15 - TAIL_BLOCK0) * 8, 384, GemmCfg<128>::SMEM, st, h.tail, 1, true);
    launch(final_gemm_kernel, 8 * FIN_SPLIT, 384, FIN_SMEM, st, h.fin, FIN_SPLIT, true);
    if (OUTB_SIDE_BLOCKS < 16)
        launch(side_gemm_kernel<256>, (16 - OUTB_SIDE_BLOCKS) * 4, 384, GemmCfg<256>::SMEM, st, h.outb, 1, true);
}
```

```cpp
#include <cuda_runtime.h>
#include <cuda_bf16.h>
#include <cuda.h>
#include <stdint.h>

namespace {

constexpr int S_TOK = 2048;
constexpr int DM = 1024;
constexpr int NH = 32;
constexpr int DH = 128;
constexpr int HD = NH * DH;
constexpr int NSEG = 64;
constexpr int SEG = 32;
constexpr int MROWS = 8;
constexpr uint32_t SENT = 0xFFFFFFFFu;
constexpr uint32_t SPIN_LIMIT = 1u << 24;

__device__ __align__(1024) __nv_bfloat16 g_qkv_tok[3ull * NSEG * NH * SEG * DH];
__device__ __align__(1024) __nv_bfloat16 g_kv_mem[2ull * NSEG * NH * MROWS * DH];
__device__ __align__(1024) __nv_bfloat16 g_o_tok[(size_t)S_TOK * HD];
__device__ __align__(1024) __nv_bfloat16 g_qkv_b[(size_t)S_TOK * 3 * DM];
__device__ __align__(1024) __nv_bfloat16 g_o_b[(size_t)S_TOK * DM];
constexpr int PUB_BYTES = 32768;
constexpr int XCHG_SLOT = 1 << 20;
constexpr int XCHG_PUB = 0, XCHG_INBOX = 2 * PUB_BYTES;
constexpr int INBOX_MAX = 80;
constexpr int XCHG_BYTES = 2 * XCHG_SLOT;
__device__ __align__(8192) uint8_t g_xchg[2 * XCHG_BYTES];
enum { F_QUEUE3 = 3, F_QUEUE4 = 4, F_SIDEQ = 8, F_TAILQ = 16, F_OUTBQ = 24, F_PROGRESS = 32, F_QKVB = 96, F_OB = 112, F_OA = 128, F_COUNT = 192 };
__device__ uint32_t g_flags[F_COUNT];
__device__ __align__(16) uint32_t g_arrivals[4];

#define STAMP(k) do {} while (0)
#define STAMPD(k, x) do {} while (0)
#define PSTAMP(k) do {} while (0)
#define KENTER(k) do {} while (0)
#define APROF(k) do {} while (0)
#define KEXIT(k) do {} while (0)

__device__ __forceinline__ uint32_t class_off(uint64_t a, uint32_t c) {
    return ((__popc((uint32_t)a & 0xB3000u) ^ c) & 1u) << 12;
}
__device__ __forceinline__ uint32_t smem_u32(const void* p) { return (uint32_t)__cvta_generic_to_shared(p); }
__device__ __forceinline__ uint32_t pack_bf16(float lo, float hi) {
    uint32_t r;
    asm("cvt.rn.bf16x2.f32 %0, %1, %2;" : "=r"(r) : "f"(hi), "f"(lo));
    return r;
}
__device__ __forceinline__ float ex2(float x) {
    float y;
    asm("ex2.approx.ftz.f32 %0, %1;" : "=f"(y) : "f"(x));
    return y;
}
__device__ __forceinline__ float rcp(float x) {
    float y;
    asm("rcp.approx.ftz.f32 %0, %1;" : "=f"(y) : "f"(x));
    return y;
}
__device__ __forceinline__ uint32_t clock32() {
    uint32_t t;
    asm volatile("mov.u32 %0, %%clock;" : "=r"(t));
    return t;
}
__device__ __forceinline__ void spin_clks(uint32_t n) {
    if (n == 0) return;
    const uint32_t t0 = clock32();
    while (clock32() - t0 < n) {}
}
__device__ __forceinline__ void spin_until(uint32_t t) {
    while ((int)(clock32() - t) < 0) {}
}
__device__ __forceinline__ uint32_t clock_after(uint32_t x) {
    uint32_t t;
    asm volatile("{\n.reg .pred p;\nsetp.eq.u32 p, %1, 0x12345678;\n@p exit;\nmov.u32 %0, %%clock;\n}" : "=r"(t) : "r"(x) : "memory");
    return t;
}
__device__ __forceinline__ uint32_t opaque(uint32_t x) { return __shfl_sync(~0u, x, threadIdx.x & 31); }
__device__ __forceinline__ uint32_t uniform(uint32_t x) { return __shfl_sync(~0u, x + (threadIdx.x & 31), 0); }
__device__ __forceinline__ float bf16_lo(uint32_t w) { return __uint_as_float(w << 16); }
__device__ __forceinline__ float bf16_hi(uint32_t w) { return __uint_as_float(w & 0xFFFF0000u); }

__device__ __forceinline__ void mbar_init(uint32_t bar, uint32_t cnt) {
    asm volatile("mbarrier.init.shared::cta.b64 [%0], %1;" ::"r"(bar), "r"(cnt) : "memory");
}
__device__ __forceinline__ void mbar_arrive(uint32_t bar) {
    asm volatile("mbarrier.arrive.shared::cta.b64 _, [%0];" ::"r"(bar) : "memory");
}
__device__ __forceinline__ void mbar_arrive_expect_tx(uint32_t bar, uint32_t bytes) {
    asm volatile("mbarrier.arrive.expect_tx.shared::cta.b64 _, [%0], %1;" ::"r"(bar), "r"(bytes) : "memory");
}
__device__ __forceinline__ bool mbar_try_wait(uint32_t bar, uint32_t parity) {
    uint32_t ok;
    asm volatile(
        "{\n.reg .pred p;\n"
        "mbarrier.try_wait.parity.shared::cta.b64 p, [%1], %2;\n"
        "selp.u32 %0, 1, 0, p;\n}"
        : "=r"(ok) : "r"(bar), "r"(parity) : "memory");
    return ok != 0;
}
__device__ __forceinline__ void mbar_wait(uint32_t bar, uint32_t parity) {
    uint32_t n = 0;
    while (!mbar_try_wait(bar, parity)) {
        if (++n > SPIN_LIMIT) __trap();
    }
}
__device__ __forceinline__ void mbar_wait_sleep(uint32_t bar, uint32_t parity) {
    uint32_t n = 0;
    while (!mbar_try_wait(bar, parity)) {
        __nanosleep(20);
        if (++n > SPIN_LIMIT) __trap();
    }
}
__device__ __forceinline__ void mbar_wait_bounded(uint32_t bar, uint32_t parity) {
    for (uint32_t n = 0; n < (1u << 20) && !mbar_try_wait(bar, parity); n++) {}
}
__device__ __forceinline__ bool elect_one() {
    uint32_t ok;
    asm volatile("{\n.reg .pred p;\nelect.sync _|p, 0xFFFFFFFF;\nselp.u32 %0, 1, 0, p;\n}" : "=r"(ok));
    return ok != 0;
}
__device__ __forceinline__ void named_bar_sync(int id, int nthreads) {
    asm volatile("bar.sync %0, %1;" ::"r"(id), "r"(nthreads) : "memory");
}
__device__ __forceinline__ void named_bar_arrive(int id, int nthreads) {
    asm volatile("bar.arrive %0, %1;" ::"r"(id), "r"(nthreads) : "memory");
}
__device__ __forceinline__ void cluster_sync() {
    asm volatile("barrier.cluster.arrive.release.aligned;\nbarrier.cluster.wait.acquire.aligned;" ::: "memory");
}
__device__ __forceinline__ uint32_t mapa(uint32_t addr, uint32_t rank) {
    uint32_t r;
    asm volatile("mapa.shared::cluster.u32 %0, %1, %2;" : "=r"(r) : "r"(addr), "r"(rank));
    return r;
}

__device__ __forceinline__ void tma_load_2d(uint32_t dst, const CUtensorMap* tm, int c0, int c1, uint32_t bar) {
    asm volatile(
        "cp.async.bulk.tensor.2d.shared::cluster.global.mbarrier::complete_tx::bytes [%0], [%1, {%3, %4}], [%2];"
        ::"r"(dst), "l"(tm), "r"(bar), "r"(c0), "r"(c1) : "memory");
}
__device__ __forceinline__ void tma_load_3d(uint32_t dst, const CUtensorMap* tm, int c0, int c1, int c2, uint32_t bar) {
    asm volatile(
        "cp.async.bulk.tensor.3d.shared::cluster.global.mbarrier::complete_tx::bytes [%0], [%1, {%3, %4, %5}], [%2];"
        ::"r"(dst), "l"(tm), "r"(bar), "r"(c0), "r"(c1), "r"(c2) : "memory");
}
__device__ __forceinline__ void tma_load_3d_mc(uint32_t dst, const CUtensorMap* tm, int c0, int c1, int c2, uint32_t bar, uint16_t mask) {
    asm volatile(
        "cp.async.bulk.tensor.3d.shared::cluster.global.mbarrier::complete_tx::bytes.multicast::cluster [%0], [%1, {%3, %4, %5}], [%2], %6;"
        ::"r"(dst), "l"(tm), "r"(bar), "r"(c0), "r"(c1), "r"(c2), "h"(mask) : "memory");
}
__device__ __forceinline__ void tma_store_2d(const CUtensorMap* tm, uint32_t src, int c0, int c1) {
    asm volatile("cp.async.bulk.tensor.2d.global.shared::cta.bulk_group [%0, {%2, %3}], [%1];"
                 ::"l"(tm), "r"(src), "r"(c0), "r"(c1) : "memory");
}
__device__ __forceinline__ void bulk_store(void* dst, uint32_t src, uint32_t bytes) {
    asm volatile("cp.async.bulk.global.shared::cta.bulk_group [%0], [%1], %2;" ::"l"(dst), "r"(src), "r"(bytes) : "memory");
}
__device__ __forceinline__ void bulk_commit() { asm volatile("cp.async.bulk.commit_group;" ::: "memory"); }
__device__ __forceinline__ void bulk_wait_read_all() { asm volatile("cp.async.bulk.wait_group.read 0;" ::: "memory"); }
__device__ __forceinline__ void bulk_wait_all() { asm volatile("cp.async.bulk.wait_group 0;" ::: "memory"); }
__device__ __forceinline__ void bulk_load(uint32_t dst, const void* src, uint32_t bytes, uint32_t bar) {
    asm volatile("cp.async.bulk.shared::cluster.global.mbarrier::complete_tx::bytes [%0], [%1], %2, [%3];"
                 ::"r"(dst), "l"(src), "r"(bytes), "r"(bar) : "memory");
}
__device__ __forceinline__ void bulk_load_mc(uint32_t dst, const void* src, uint32_t bytes, uint32_t bar, uint16_t mask) {
    asm volatile(
        "cp.async.bulk.shared::cluster.global.mbarrier::complete_tx::bytes.multicast::cluster [%0], [%1], %2, [%3], %4;"
        ::"r"(dst), "l"(src), "r"(bytes), "r"(bar), "h"(mask) : "memory");
}
__device__ __forceinline__ void cp_async16(uint32_t dst, const void* src) {
    asm volatile("cp.async.cg.shared.global [%0], [%1], 16;" ::"r"(dst), "l"(src) : "memory");
}
__device__ __forceinline__ void cp_async_commit() { asm volatile("cp.async.commit_group;" ::: "memory"); }
template <int N> __device__ __forceinline__ void cp_async_wait() {
    asm volatile("cp.async.wait_group %0;" ::"n"(N) : "memory");
}

__device__ __forceinline__ void ldsm_x4(uint32_t addr, uint32_t& r0, uint32_t& r1, uint32_t& r2, uint32_t& r3) {
    asm volatile("ldmatrix.sync.aligned.m8n8.x4.shared.b16 {%0,%1,%2,%3}, [%4];"
                 : "=r"(r0), "=r"(r1), "=r"(r2), "=r"(r3) : "r"(addr) : "memory");
}
__device__ __forceinline__ void ldsm_x4_t(uint32_t addr, uint32_t& r0, uint32_t& r1, uint32_t& r2, uint32_t& r3) {
    asm volatile("ldmatrix.sync.aligned.m8n8.x4.trans.shared.b16 {%0,%1,%2,%3}, [%4];"
                 : "=r"(r0), "=r"(r1), "=r"(r2), "=r"(r3) : "r"(addr) : "memory");
}
__device__ __forceinline__ void stsm_x4(uint32_t addr, uint32_t r0, uint32_t r1, uint32_t r2, uint32_t r3) {
    asm volatile("stmatrix.sync.aligned.m8n8.x4.shared.b16 [%0], {%1,%2,%3,%4};"
                 ::"r"(addr), "r"(r0), "r"(r1), "r"(r2), "r"(r3) : "memory");
}
__device__ __forceinline__ uint32_t movmat(uint32_t a) {
    uint32_t d;
    asm volatile("movmatrix.sync.aligned.m8n8.trans.b16 %0, %1;" : "=r"(d) : "r"(a));
    return d;
}
__device__ __forceinline__ void mma16816(float* d, uint32_t a0, uint32_t a1, uint32_t a2, uint32_t a3,
                                         uint32_t b0, uint32_t b1) {
    asm volatile(
        "mma.sync.aligned.m16n8k16.row.col.f32.bf16.bf16.f32 {%0,%1,%2,%3}, {%4,%5,%6,%7}, {%8,%9}, {%0,%1,%2,%3};"
        : "+f"(d[0]), "+f"(d[1]), "+f"(d[2]), "+f"(d[3])
        : "r"(a0), "r"(a1), "r"(a2), "r"(a3), "r"(b0), "r"(b1));
}
__device__ __forceinline__ void mma1688(float* d, uint32_t a0, uint32_t a1, uint32_t b0) {
    asm volatile("mma.sync.aligned.m16n8k8.row.col.f32.bf16.bf16.f32 {%0,%1,%2,%3}, {%4,%5}, {%6}, {%0,%1,%2,%3};"
                 : "+f"(d[0]), "+f"(d[1]), "+f"(d[2]), "+f"(d[3]) : "r"(a0), "r"(a1), "r"(b0));
}
__device__ __forceinline__ uint32_t any_reg() {
    uint32_t r;
    asm volatile("" : "=r"(r));
    return r;
}
__device__ __forceinline__ uint2 lds64(uint32_t addr) {
    uint2 v;
    asm volatile("ld.volatile.shared.v2.b32 {%0,%1}, [%2];" : "=r"(v.x), "=r"(v.y) : "r"(addr) : "memory");
    return v;
}
__device__ __forceinline__ uint4 lds128(uint32_t addr) {
    uint4 v;
    asm volatile("ld.volatile.shared.v4.b32 {%0,%1,%2,%3}, [%4];" : "=r"(v.x), "=r"(v.y), "=r"(v.z), "=r"(v.w) : "r"(addr) : "memory");
    return v;
}
__device__ __forceinline__ void sts32(uint32_t addr, uint32_t x) {
    asm volatile("st.volatile.shared.b32 [%0], %1;" ::"r"(addr), "r"(x) : "memory");
}
__device__ __forceinline__ void sts64(uint32_t addr, uint32_t x, uint32_t y) {
    asm volatile("st.volatile.shared.v2.b32 [%0], {%1,%2};" ::"r"(addr), "r"(x), "r"(y) : "memory");
}
__device__ __forceinline__ void sts128(uint32_t addr, uint32_t x, uint32_t y, uint32_t z, uint32_t w) {
    asm volatile("st.volatile.shared.v4.b32 [%0], {%1,%2,%3,%4};" ::"r"(addr), "r"(x), "r"(y), "r"(z), "r"(w) : "memory");
}
__device__ __forceinline__ void st_async_v2(uint32_t addr, uint32_t x, uint32_t y, uint32_t bar) {
    asm volatile("st.async.weak.shared::cluster.mbarrier::complete_tx::bytes.v2.b32 [%0], {%1,%2}, [%3];"
                 ::"r"(addr), "r"(x), "r"(y), "r"(bar) : "memory");
}
__device__ __forceinline__ uint2 ld_relaxed_v2(const void* p) {
    uint2 v;
    asm volatile("ld.relaxed.gpu.global.v2.b32 {%0,%1}, [%2];" : "=r"(v.x), "=r"(v.y) : "l"(p) : "memory");
    return v;
}
__device__ __forceinline__ void st_relaxed_v2(void* p, uint32_t x, uint32_t y) {
    asm volatile("st.relaxed.gpu.global.v2.b32 [%0], {%1,%2};" ::"l"(p), "r"(x), "r"(y) : "memory");
}
__device__ __forceinline__ void st_relaxed_v4(void* p, uint32_t x) {
    asm volatile("st.relaxed.gpu.global.v4.b32 [%0], {%1,%1,%1,%1};" ::"l"(p), "r"(x) : "memory");
}
__device__ __forceinline__ uint32_t ld_relaxed_b32(const void* p) {
    uint32_t v;
    asm volatile("ld.relaxed.gpu.global.b32 %0, [%1];" : "=r"(v) : "l"(p) : "memory");
    return v;
}
__device__ __forceinline__ uint32_t lds32_volatile(uint32_t addr) {
    uint32_t v;
    asm volatile("ld.volatile.shared.b32 %0, [%1];" : "=r"(v) : "r"(addr) : "memory");
    return v;
}
__device__ __forceinline__ void st_relaxed_b32(void* p, uint32_t x) {
    asm volatile("st.relaxed.gpu.global.b32 [%0], %1;" ::"l"(p), "r"(x) : "memory");
}

__device__ __forceinline__ uint32_t ld_acquire_b32(const void* p) {
    uint32_t v;
    asm volatile("ld.acquire.gpu.global.b32 %0, [%1];" : "=r"(v) : "l"(p) : "memory");
    return v;
}
__device__ __forceinline__ void wait_flag(const uint32_t* p, uint32_t target) {
    uint32_t n = 0;
    while (ld_acquire_b32(p) < target) {
        __nanosleep(64);
        if (++n > SPIN_LIMIT) __trap();
    }
}
__device__ __forceinline__ void signal_flag(uint32_t* p) {
    asm volatile("red.release.gpu.global.add.u32 [%0], 1;" ::"l"(p) : "memory");
}
__device__ __forceinline__ void pdl_launch_dependents() { asm volatile("griddepcontrol.launch_dependents;" ::: "memory"); }

constexpr int BM = 128, BK = 64;
constexpr int A_STAGE = BM * BK * 2;
template <int BN> struct GemmCfg {
    static constexpr int STAGES = BN == 256 ? 3 : 6;
    static constexpr int STAGE = A_STAGE + BK * BN * 2;
    static constexpr int EPI_WARP = 16 * BN * 2;
    static constexpr int SMEM = STAGES * STAGE + 8 * EPI_WARP + 1024 + 512;
};

struct SideProb {
    CUtensorMap tmA, tmB, tmB2, tmC;
    int n_split;
    int n_tiles, k_blocks, c_col0;
    const uint32_t* dep;
    uint32_t dep_target;
    int dep_n;
    uint32_t* sig;
    __nv_bfloat16* blocked;
};
struct SideSeg { int prob, m0, m1; };
constexpr int SIDE_MAX_SEG = 6;
struct SideParams {
    SideProb prob[5];
    SideSeg seg[SIDE_MAX_SEG];
    int nseg;
    uint32_t* queue;
};
static_assert(sizeof(SideParams) <= 4096, "kernel parameter limit");

__device__ __forceinline__ uint64_t make_desc(uint32_t addr, uint32_t lbo, uint32_t sbo) {
    return (uint64_t)((addr & 0x3FFFF) >> 4) | ((uint64_t)(lbo >> 4) << 16) | ((uint64_t)(sbo >> 4) << 32) | (1ull << 62);
}

__device__ __forceinline__ void wgmma_m64n256k16(float (&d)[128], uint64_t da, uint64_t db, int scale_d) {
    asm volatile(
        "{\n.reg .pred p;\nsetp.ne.b32 p, %130, 0;\n"
        "wgmma.mma_async.sync.aligned.m64n256k16.f32.bf16.bf16 "
        "{%0,%1,%2,%3,%4,%5,%6,%7,%8,%9,%10,%11,%12,%13,%14,%15,"
        "%16,%17,%18,%19,%20,%21,%22,%23,%24,%25,%26,%27,%28,%29,%30,%31,"
        "%32,%33,%34,%35,%36,%37,%38,%39,%40,%41,%42,%43,%44,%45,%46,%47,"
        "%48,%49,%50,%51,%52,%53,%54,%55,%56,%57,%58,%59,%60,%61,%62,%63,"
        "%64,%65,%66,%67,%68,%69,%70,%71,%72,%73,%74,%75,%76,%77,%78,%79,"
        "%80,%81,%82,%83,%84,%85,%86,%87,%88,%89,%90,%91,%92,%93,%94,%95,"
        "%96,%97,%98,%99,%100,%101,%102,%103,%104,%105,%106,%107,%108,%109,%110,%111,"
        "%112,%113,%114,%115,%116,%117,%118,%119,%120,%121,%122,%123,%124,%125,%126,%127},"
        " %128, %129, p, 1, 1, 0, 1;\n}\n"
        : "+f"(d[0]), "+f"(d[1]), "+f"(d[2]), "+f"(d[3]), "+f"(d[4]), "+f"(d[5]), "+f"(d[6]), "+f"(d[7]),
          "+f"(d[8]), "+f"(d[9]), "+f"(d[10]), "+f"(d[11]), "+f"(d[12]), "+f"(d[13]), "+f"(d[14]), "+f"(d[15]),
          "+f"(d[16]), "+f"(d[17]), "+f"(d[18]), "+f"(d[19]), "+f"(d[20]), "+f"(d[21]), "+f"(d[22]), "+f"(d[23]),
          "+f"(d[24]), "+f"(d[25]), "+f"(d[26]), "+f"(d[27]), "+f"(d[28]), "+f"(d[29]), "+f"(d[30]), "+f"(d[31]),
          "+f"(d[32]), "+f"(d[33]), "+f"(d[34]), "+f"(d[35]), "+f"(d[36]), "+f"(d[37]), "+f"(d[38]), "+f"(d[39]),
          "+f"(d[40]), "+f"(d[41]), "+f"(d[42]), "+f"(d[43]), "+f"(d[44]), "+f"(d[45]), "+f"(d[46]), "+f"(d[47]),
          "+f"(d[48]), "+f"(d[49]), "+f"(d[50]), "+f"(d[51]), "+f"(d[52]), "+f"(d[53]), "+f"(d[54]), "+f"(d[55]),
          "+f"(d[56]), "+f"(d[57]), "+f"(d[58]), "+f"(d[59]), "+f"(d[60]), "+f"(d[61]), "+f"(d[62]), "+f"(d[63]),
          "+f"(d[64]), "+f"(d[65]), "+f"(d[66]), "+f"(d[67]), "+f"(d[68]), "+f"(d[69]), "+f"(d[70]), "+f"(d[71]),
          "+f"(d[72]), "+f"(d[73]), "+f"(d[74]), "+f"(d[75]), "+f"(d[76]), "+f"(d[77]), "+f"(d[78]), "+f"(d[79]),
          "+f"(d[80]), "+f"(d[81]), "+f"(d[82]), "+f"(d[83]), "+f"(d[84]), "+f"(d[85]), "+f"(d[86]), "+f"(d[87]),
          "+f"(d[88]), "+f"(d[89]), "+f"(d[90]), "+f"(d[91]), "+f"(d[92]), "+f"(d[93]), "+f"(d[94]), "+f"(d[95]),
          "+f"(d[96]), "+f"(d[97]), "+f"(d[98]), "+f"(d[99]), "+f"(d[100]), "+f"(d[101]), "+f"(d[102]), "+f"(d[103]),
          "+f"(d[104]), "+f"(d[105]), "+f"(d[106]), "+f"(d[107]), "+f"(d[108]), "+f"(d[109]), "+f"(d[110]), "+f"(d[111]),
          "+f"(d[112]), "+f"(d[113]), "+f"(d[114]), "+f"(d[115]), "+f"(d[116]), "+f"(d[117]), "+f"(d[118]), "+f"(d[119]),
          "+f"(d[120]), "+f"(d[121]), "+f"(d[122]), "+f"(d[123]), "+f"(d[124]), "+f"(d[125]), "+f"(d[126]), "+f"(d[127])
        : "l"(da), "l"(db), "r"(scale_d));
}

__device__ __forceinline__ void wgmma_m64n128k16(float (&d)[64], uint64_t da, uint64_t db, int scale_d) {
    asm volatile(
        "{\n.reg .pred p;\nsetp.ne.b32 p, %66, 0;\n"
        "wgmma.mma_async.sync.aligned.m64n128k16.f32.bf16.bf16 "
        "{%0,%1,%2,%3,%4,%5,%6,%7,%8,%9,%10,%11,%12,%13,%14,%15,"
        "%16,%17,%18,%19,%20,%21,%22,%23,%24,%25,%26,%27,%28,%29,%30,%31,"
        "%32,%33,%34,%35,%36,%37,%38,%39,%40,%41,%42,%43,%44,%45,%46,%47,"
        "%48,%49,%50,%51,%52,%53,%54,%55,%56,%57,%58,%59,%60,%61,%62,%63},"
        " %64, %65, p, 1, 1, 0, 1;\n}\n"
        : "+f"(d[0]), "+f"(d[1]), "+f"(d[2]), "+f"(d[3]), "+f"(d[4]), "+f"(d[5]), "+f"(d[6]), "+f"(d[7]),
          "+f"(d[8]), "+f"(d[9]), "+f"(d[10]), "+f"(d[11]), "+f"(d[12]), "+f"(d[13]), "+f"(d[14]), "+f"(d[15]),
          "+f"(d[16]), "+f"(d[17]), "+f"(d[18]), "+f"(d[19]), "+f"(d[20]), "+f"(d[21]), "+f"(d[22]), "+f"(d[23]),
          "+f"(d[24]), "+f"(d[25]), "+f"(d[26]), "+f"(d[27]), "+f"(d[28]), "+f"(d[29]), "+f"(d[30]), "+f"(d[31]),
          "+f"(d[32]), "+f"(d[33]), "+f"(d[34]), "+f"(d[35]), "+f"(d[36]), "+f"(d[37]), "+f"(d[38]), "+f"(d[39]),
          "+f"(d[40]), "+f"(d[41]), "+f"(d[42]), "+f"(d[43]), "+f"(d[44]), "+f"(d[45]), "+f"(d[46]), "+f"(d[47]),
          "+f"(d[48]), "+f"(d[49]), "+f"(d[50]), "+f"(d[51]), "+f"(d[52]), "+f"(d[53]), "+f"(d[54]), "+f"(d[55]),
          "+f"(d[56]), "+f"(d[57]), "+f"(d[58]), "+f"(d[59]), "+f"(d[60]), "+f"(d[61]), "+f"(d[62]), "+f"(d[63])
        : "l"(da), "l"(db), "r"(scale_d));
}
template <int BN> struct WgmmaOp;
template <> struct WgmmaOp<256> {
    static __device__ __forceinline__ void run(float (&d)[128], uint64_t a, uint64_t b, int sc) { wgmma_m64n256k16(d, a, b, sc); }
};
template <> struct WgmmaOp<128> {
    static __device__ __forceinline__ void run(float (&d)[64], uint64_t a, uint64_t b, int sc) { wgmma_m64n128k16(d, a, b, sc); }
};

struct StoreRec {
    uint64_t dst;
    uint64_t flag;
    int kind;
    int pad;
};
struct EpiCtx { uint32_t buf, rec, st_full, st_empty; uint32_t it; int lane; };
template <int N>
__device__ __forceinline__ void epi_hand_over(const float (&acc)[N], EpiCtx& e, uint64_t dst, uint64_t flag, int kind) {
    mbar_wait(e.st_empty, (e.it & 1) ^ 1);
    const int mi = e.lane >> 3, row = (mi & 1) * 8 + (e.lane & 7);
    #pragma unroll
    for (int j = 0; j < N / 4; j += 2) {
        const int chunk = (j & 7) + (mi >> 1);
        stsm_x4(e.buf + (j >> 3) * 2048 + row * 128 + ((chunk ^ (row & 7)) << 4),
                pack_bf16(acc[4 * j], acc[4 * j + 1]), pack_bf16(acc[4 * j + 2], acc[4 * j + 3]),
                pack_bf16(acc[4 * j + 4], acc[4 * j + 5]), pack_bf16(acc[4 * j + 6], acc[4 * j + 7]));
    }
    if (e.lane == 0) {
        asm volatile("st.shared.v2.b64 [%0], {%1, %2};" ::"r"(e.rec), "l"(dst), "l"(flag) : "memory");
        asm volatile("st.shared.b32 [%0], %1;" ::"r"(e.rec + 16), "r"(kind) : "memory");
    }
    asm volatile("fence.proxy.async.shared::cta;" ::: "memory");
    __syncwarp();
    if (e.lane == 0) mbar_arrive(e.st_full);
    e.it++;
}
__device__ __forceinline__ void epi_exit(EpiCtx& e) {
    mbar_wait(e.st_empty, (e.it & 1) ^ 1);
    if (e.lane == 0) {
        asm volatile("st.shared.b32 [%0], %1;" ::"r"(e.rec + 16), "r"(-1) : "memory");
        mbar_arrive(e.st_full);
    }
}
template <int BN, bool PAIR = false>
__device__ __forceinline__ void gemm_mainloop(float (&acc)[BN / 2], int k_blocks, uint32_t sbase, uint32_t bar_base, int cw,
                                              bool elected, int& stage, uint32_t& phase, uint32_t peer = 0) {
    using C = GemmCfg<BN>;
    auto release = [&](int st) {
        const uint32_t bar = bar_base + 8 * (C::STAGES + st);
        mbar_arrive(bar);
        if (PAIR) asm volatile("mbarrier.arrive.shared::cluster.b64 _, [%0];" ::"r"(mapa(bar, peer)) : "memory");
    };
    int prev_stage = -1;
    for (int kb = 0; kb < k_blocks; kb++) {
        mbar_wait(bar_base + 8 * stage, phase);
        const uint32_t sa = sbase + stage * C::STAGE + cw * (64 * 128);
        const uint32_t sb = sbase + stage * C::STAGE + A_STAGE;
        asm volatile("wgmma.fence.sync.aligned;" ::: "memory");
        #pragma unroll
        for (int kk = 0; kk < BK / 16; kk++)
            WgmmaOp<BN>::run(acc, make_desc(sa + kk * 32, 16, 1024), make_desc(sb + kk * 2048, 8192, 1024), (kb | kk) != 0);
        asm volatile("wgmma.commit_group.sync.aligned;" ::: "memory");
        asm volatile("wgmma.wait_group.sync.aligned 1;" ::: "memory");
        if (prev_stage >= 0 && elected) release(prev_stage);
        prev_stage = stage;
        if (++stage == C::STAGES) { stage = 0; phase ^= 1; }
    }
    asm volatile("wgmma.wait_group.sync.aligned 0;" ::: "memory");
    if (elected) release(prev_stage);
}
template <int BN>
__device__ __forceinline__ void store_warp(uint32_t epi_base, uint32_t rec_base, uint32_t st_full, uint32_t st_empty, int lane,
                                           const uint8_t* tmaps, int tstride) {
    for (uint32_t it = 0;; it++) {
        mbar_wait(st_full, it & 1);
        uint64_t dst = 0, flag = 0;
        int kind = -1;
        if (lane < 8) {
            const uint32_t rec = rec_base + lane * 32;
            asm volatile("ld.volatile.shared.v2.b64 {%0, %1}, [%2];" : "=l"(dst), "=l"(flag) : "r"(rec) : "memory");
            kind = (int)lds32_volatile(rec + 16);
        }
        if (__shfl_sync(~0u, kind, 0) < 0) break;
        if (lane < 8) {
            const uint32_t buf = epi_base + lane * GemmCfg<BN>::EPI_WARP;
            #pragma unroll
            for (int q = 0; q < BN / 64; q++) {
                if (kind == 0) bulk_store(reinterpret_cast<__nv_bfloat16*>(dst) + q * (SEG * 64), buf + q * 2048, 2048);
                else tma_store_2d(reinterpret_cast<const CUtensorMap*>(tmaps + (kind - 1) * tstride), buf + q * 2048,
                                  (int)(uint32_t)dst + q * 64, (int)(dst >> 32));
            }
            bulk_commit();
            bulk_wait_read_all();
            mbar_arrive(st_empty);
            if (flag) {
                bulk_wait_all();
                signal_flag(reinterpret_cast<uint32_t*>(flag));
            }
        }
        __syncwarp();
    }
    if (lane < 8) bulk_wait_all();
}

template <int BN>
__global__ void __launch_bounds__(384, 1) side_gemm_kernel(const __grid_constant__ SideParams p) {
    using C = GemmCfg<BN>;
    extern __shared__ uint8_t smem_raw[];
    const uint32_t sbase = (smem_u32(smem_raw) + 1023) & ~1023u;
    const uint32_t epi_base = sbase + C::STAGES * C::STAGE;
    const uint32_t bar_base = epi_base + 8 * C::EPI_WARP;
    const uint32_t tfull = bar_base + 16 * C::STAGES, tempty = tfull + 16, tslot = tempty + 16;
    const uint32_t st_full = bar_base + 192, st_empty = st_full + 8, rec_base = bar_base + 256;
    const int tid = threadIdx.x, wg = tid >> 7;
    if (tid == 0) {
        for (int s = 0; s < C::STAGES; s++) { mbar_init(bar_base + 8 * s, 1); mbar_init(bar_base + 8 * (C::STAGES + s), 2); }
        for (int s = 0; s < 2; s++) { mbar_init(tfull + 8 * s, 1); mbar_init(tempty + 8 * s, 2); }
        mbar_init(st_full, 8);
        mbar_init(st_empty, 8);
        asm volatile("fence.mbarrier_init.release.cluster;" ::: "memory");
        pdl_launch_dependents();
    }
    __syncthreads();
    KENTER(BN == 256 ? (p.nseg == 1 ? 6 : 2) : 4);

    if (wg == 0) {
        asm volatile("setmaxnreg.dec.sync.aligned.u32 40;");
        if (tid == 0) {
            int stage = 0; uint32_t phase = 1;
            for (uint32_t it = 0;; it++) {
                int pr = -1, mt = 0, nt = 0;
                for (uint32_t tries = 0;; tries++) {
                    uint32_t head[SIDE_MAX_SEG], ready[SIDE_MAX_SEG];
                    #pragma unroll
                    for (int g = 0; g < SIDE_MAX_SEG; g++) head[g] = g < p.nseg ? ld_relaxed_b32(p.queue + g) : 0xFFFFFFFFu;
                    bool left = false;
                    #pragma unroll
                    for (int g = 0; g < SIDE_MAX_SEG; g++) {
                        ready[g] = 0;
                        if (g < p.nseg) {
                            const SideProb& q = p.prob[p.seg[g].prob];
                            if (head[g] < (uint32_t)((p.seg[g].m1 - p.seg[g].m0) * q.n_tiles)) {
                                left = true;
                                ready[g] = q.dep ? ld_relaxed_b32(q.dep + (p.seg[g].m0 + head[g] / q.n_tiles + 1) * q.dep_n - 1) >= q.dep_target : 1u;
                            }
                        }
                    }
                    if (!left) break;
                    #pragma unroll
                    for (int g = 0; g < SIDE_MAX_SEG; g++) {
                        if (pr < 0 && ready[g]) {
                            const int nts = p.prob[p.seg[g].prob].n_tiles;
                            const uint32_t idx = atomicAdd(p.queue + g, 1u);
                            if (idx < (uint32_t)((p.seg[g].m1 - p.seg[g].m0) * nts)) {
                                pr = p.seg[g].prob; mt = p.seg[g].m0 + idx / nts; nt = idx % nts;
                            }
                        }
                    }
                    if (pr >= 0) break;
                    __nanosleep(200);
                    if (tries > SPIN_LIMIT) __trap();
                }
                mbar_wait(tempty + 8 * (it & 1), ((it >> 1) & 1) ^ 1);
                asm volatile("st.shared.b32 [%0], %1;" ::"r"(tslot + 4 * (it & 1)), "r"(pr < 0 ? -1 : (pr << 16) | (mt << 8) | nt) : "memory");
                mbar_arrive(tfull + 8 * (it & 1));
                if (pr < 0) break;
                const SideProb& q = p.prob[pr];
                if (q.dep) {
                    for (int i = q.dep_n - 1; i >= 0; i--) wait_flag(q.dep + mt * q.dep_n + i, q.dep_target);
                    asm volatile("fence.proxy.async.global;" ::: "memory");
                }
                for (int kb = 0; kb < q.k_blocks; kb++) {
                    mbar_wait(bar_base + 8 * (C::STAGES + stage), phase);
                    const uint32_t sa = sbase + stage * C::STAGE, fb = bar_base + 8 * stage;
                    mbar_arrive_expect_tx(fb, C::STAGE);
                    tma_load_2d(sa, &q.tmA, kb * BK, mt * BM, fb);
                    tma_load_3d(sa + A_STAGE, nt < q.n_split ? &q.tmB : &q.tmB2, 0, kb * BK,
                                (nt < q.n_split ? nt : nt - q.n_split) * (BN / 64), fb);
                    if (++stage == C::STAGES) { stage = 0; phase ^= 1; }
                }
            }
        } else if (tid >= 32 && tid < 64) {
            store_warp<BN>(epi_base, rec_base, st_full, st_empty, tid & 31, reinterpret_cast<const uint8_t*>(&p.prob[0].tmC),
                           (int)sizeof(SideProb));
        }
    } else {
        asm volatile("setmaxnreg.inc.sync.aligned.u32 232;");
        const int cw = wg - 1, lane = tid & 31, wi = (tid >> 5) & 3;
        const bool elected = (tid & 127) == 0;
        int stage = 0; uint32_t phase = 0;
        float acc[BN / 2];
        EpiCtx ectx = {epi_base + (cw * 4 + wi) * C::EPI_WARP, rec_base + (cw * 4 + wi) * 32, st_full, st_empty, 0, lane};
        for (uint32_t it = 0;; it++) {
            mbar_wait(tfull + 8 * (it & 1), (it >> 1) & 1);
            const int code = (int)lds32_volatile(tslot + 4 * (it & 1));
            named_bar_sync(1 + cw, 128);
            if (elected) mbar_arrive(tempty + 8 * (it & 1));
            if (code < 0) break;
            const SideProb& q = p.prob[code >> 16];
            const int mt = (code >> 8) & 255, nt = code & 255;
            gemm_mainloop<BN>(acc, q.k_blocks, sbase, bar_base, cw, elected, stage, phase);
            const int row0 = mt * BM + cw * 64 + wi * 16;
            uint64_t dst;
            if (q.blocked) {
                const int col = nt * BN;
                dst = (uint64_t)(q.blocked + (((size_t)(col / HD) * NSEG + row0 / SEG) * NH + (col % HD) / DH) * (SEG * DH) +
                                 (row0 % SEG) * 64);
            } else {
                dst = ((uint64_t)row0 << 32) | (uint32_t)(q.c_col0 + nt * BN);
            }
            epi_hand_over(acc, ectx, dst, q.sig ? (uint64_t)(q.sig + mt) : 0, q.blocked ? 0 : 1 + (code >> 16));
        }
        epi_exit(ectx);
        if (elected) KEXIT(BN == 256 ? (p.nseg == 1 ? 6 : 2) : 4);
    }
}

#define FIN_SPLIT 8
constexpr int FIN_STAGES = 5, FIN_STAGE = A_STAGE + BK * 128 * 2, FIN_RED = FIN_STAGES * FIN_STAGE;
constexpr int FIN_NACC = 64 / FIN_SPLIT;
constexpr int FIN_SLOT = 256 * FIN_NACC * 4;
constexpr int FIN_BAR = FIN_RED + (FIN_SPLIT - 1) * FIN_SLOT, FIN_SMEM = FIN_BAR + 256 + 1024;
struct FinalParams {
    CUtensorMap tmA, tmB;
    __nv_bfloat16* out;
    const uint32_t* dep;
    uint32_t dep_target;
    int mt;
};
__global__ void __launch_bounds__(384, 1) final_gemm_kernel(const __grid_constant__ FinalParams p) {
    extern __shared__ uint8_t smem_raw[];
    const uint32_t sbase = (smem_u32(smem_raw) + 1023) & ~1023u;
    const uint32_t bar_base = sbase + FIN_BAR, bar_red = bar_base + 16 * FIN_STAGES;
    const int tid = threadIdx.x, wg = tid >> 7;
    const int rank = blockIdx.x % FIN_SPLIT, nt = blockIdx.x / FIN_SPLIT;
    constexpr int KB = HD / BK / FIN_SPLIT;
    KENTER(5);
    if (tid == 0) {
        for (int s = 0; s < FIN_STAGES; s++) { mbar_init(bar_base + 8 * s, 1); mbar_init(bar_base + 8 * (FIN_STAGES + s), 2); }
        mbar_init(bar_red, 1);
        asm volatile("fence.mbarrier_init.release.cluster;" ::: "memory");
        mbar_arrive_expect_tx(bar_red, (FIN_SPLIT - 1) * FIN_SLOT);
        pdl_launch_dependents();
    }
    __syncthreads();
    cluster_sync();
    if (wg == 0) {
        if (tid == 0) {
            for (int kb = 0; kb < FIN_STAGES; kb++) {
                mbar_arrive_expect_tx(bar_base + 8 * kb, FIN_STAGE);
                tma_load_3d(sbase + kb * FIN_STAGE + A_STAGE, &p.tmB, 0, (rank * KB + kb) * BK, nt * 2, bar_base + 8 * kb);
            }
            uint32_t n = 0;
            for (int i = 0; i < 4; i++)
                while (ld_acquire_b32(p.dep + i) < p.dep_target) { if (++n > SPIN_LIMIT) __trap(); }
            asm volatile("fence.proxy.async.global;" ::: "memory");
            for (int kb = 0; kb < FIN_STAGES; kb++)
                tma_load_2d(sbase + kb * FIN_STAGE, &p.tmA, (rank * KB + kb) * BK, p.mt * BM, bar_base + 8 * kb);
            int stage = 0; uint32_t phase = 0;
            for (int kb = FIN_STAGES; kb < KB; kb++) {
                mbar_wait(bar_base + 8 * (FIN_STAGES + stage), phase);
                const uint32_t sa = sbase + stage * FIN_STAGE, fb = bar_base + 8 * stage;
                mbar_arrive_expect_tx(fb, FIN_STAGE);
                tma_load_3d(sa + A_STAGE, &p.tmB, 0, (rank * KB + kb) * BK, nt * 2, fb);
                tma_load_2d(sa, &p.tmA, (rank * KB + kb) * BK, p.mt * BM, fb);
                if (++stage == FIN_STAGES) { stage = 0; phase ^= 1; }
            }
        }
    } else {
        const int cw = wg - 1, lane = tid & 31, wi = (tid >> 5) & 3, t128 = tid & 127;
        const bool elected = t128 == 0;
        float acc[64];
        int stage = 0; uint32_t phase = 0;
        int prev_stage = -1;
        for (int kb = 0; kb < KB; kb++) {
            mbar_wait(bar_base + 8 * stage, phase);
            const uint32_t sa = sbase + stage * FIN_STAGE + cw * (64 * 128), sb = sbase + stage * FIN_STAGE + A_STAGE;
            asm volatile("wgmma.fence.sync.aligned;" ::: "memory");
            #pragma unroll
            for (int kk = 0; kk < BK / 16; kk++)
                wgmma_m64n128k16(acc, make_desc(sa + kk * 32, 16, 1024), make_desc(sb + kk * 2048, 8192, 1024), (kb | kk) != 0);
            asm volatile("wgmma.commit_group.sync.aligned;" ::: "memory");
            asm volatile("wgmma.wait_group.sync.aligned 1;" ::: "memory");
            if (prev_stage >= 0 && elected) mbar_arrive(bar_base + 8 * (FIN_STAGES + prev_stage));
            prev_stage = stage;
            if (++stage == FIN_STAGES) { stage = 0; phase ^= 1; }
        }
        asm volatile("wgmma.wait_group.sync.aligned 0;" ::: "memory");
        #pragma unroll
        for (int q = 0; q < FIN_SPLIT; q++) {
            if (q != rank) {
                const int slot = rank - (rank > q ? 1 : 0);
                const uint32_t dst = mapa(sbase + FIN_RED + slot * FIN_SLOT + cw * (FIN_SLOT / 2) + t128 * 16, q), rb = mapa(bar_red, q);
                #pragma unroll
                for (int j = 0; j < FIN_NACC / 4; j++)
                    asm volatile("st.async.weak.shared::cluster.mbarrier::complete_tx::bytes.v4.f32 [%0], {%1,%2,%3,%4}, [%5];"
                                 ::"r"(dst + j * 2048), "f"(acc[FIN_NACC * q + 4 * j]), "f"(acc[FIN_NACC * q + 4 * j + 1]),
                                   "f"(acc[FIN_NACC * q + 4 * j + 2]), "f"(acc[FIN_NACC * q + 4 * j + 3]), "r"(rb) : "memory");
            }
        }
        float o[FIN_NACC];
        #pragma unroll
        for (int q = 0; q < FIN_SPLIT; q++)
            if (q == rank) {
                #pragma unroll
                for (int e = 0; e < FIN_NACC; e++) o[e] = acc[FIN_NACC * q + e];
            }
        mbar_wait(bar_red, 0);
        #pragma unroll
        for (int sl = 0; sl < FIN_SPLIT - 1; sl++) {
            #pragma unroll
            for (int j = 0; j < FIN_NACC / 4; j++) {
                const uint4 v = lds128(sbase + FIN_RED + sl * FIN_SLOT + cw * (FIN_SLOT / 2) + j * 2048 + t128 * 16);
                o[4 * j] += __uint_as_float(v.x); o[4 * j + 1] += __uint_as_float(v.y);
                o[4 * j + 2] += __uint_as_float(v.z); o[4 * j + 3] += __uint_as_float(v.w);
            }
        }
        __nv_bfloat16* dst = p.out + (size_t)(p.mt * BM + cw * 64 + wi * 16 + (lane >> 2)) * (2 * DM) + nt * 128 +
                             rank * (128 / FIN_SPLIT) + (lane & 3) * 2;
        #pragma unroll
        for (int j = 0; j < FIN_NACC / 4; j++) {
            *reinterpret_cast<uint32_t*>(dst + j * 8) = pack_bf16(o[4 * j], o[4 * j + 1]);
            *reinterpret_cast<uint32_t*>(dst + (size_t)8 * (2 * DM) + j * 8) = pack_bf16(o[4 * j + 2], o[4 * j + 3]);
        }
    }
    __syncthreads();
    cluster_sync();
    if (tid == 0) KEXIT(5);
}

#define POLL_DELAY 4
#define FETCH_DELAY 200
#define AT_PF 6
#define AT_AHEAD 4
#define TOK_GO 12
#define PDL_POS 3
#define WO_PFA 7
#define WO_PFB_DELAY 60
#define NO_COMM 0
#define TOK_MOVED 4
#define XB_DELAY 50
#define WO_PF0 0
#define WO_PF1 11
#define WO_AHEAD 6
constexpr int REC_THREADS = 256;
constexpr uint32_t POLL_LIMIT = 1u << 16;
constexpr int NREG = 24;
__host__ __device__ constexpr int reg_idx(int j) { return ((j & 3) - 1) * 8 + (j >> 2); }
constexpr int SM_WQ = 0;
constexpr int SM_WO = 65536;
constexpr int SM_X = SM_WO + 11 * 8192;
constexpr int SM_PARK1 = SM_X;
constexpr int SM_MEM = SM_X + 4 * 4096;
constexpr int SM_RED = SM_X + 8 * 4096;
constexpr int SM_V = SM_X + 12 * 4096;
constexpr int SM_K = SM_X + 14 * 4096;
constexpr int SM_QS = SM_X + 15 * 4096;
constexpr int SM_QK = SM_X + 65536;
constexpr int SM_SP = SM_QK + 2048;
constexpr int SM_VM = SM_SP + 2560;
constexpr int SM_O = SM_VM + 2048;
constexpr int SM_PARK0 = SM_QK;
constexpr int SM_SUM = SM_O + 2048;
constexpr int SM_TBL = SM_SUM + 128;
constexpr int SM_BAR = SM_TBL + 512;
constexpr int SM_STAMP = SM_BAR + 192;
constexpr int REC_SMEM = SM_STAMP;
static_assert(REC_SMEM <= 232448, "shared memory");
enum { BAR_V = 0, BAR_X = 8, BAR_P0 = 16, BAR_WQ = 40, BAR_WO = 48, BAR_XG = 56, BAR_F0 = 88, BAR_F3 = 96, BAR_VF = 104,
       BAR_M = 112, BAR_GO = 144, BAR_PK = 152, BAR_OUT = 168, BAR_VM = 160, BAR_SELF = 176, BAR_MIN = 184 };

template <int V> struct IntC { static constexpr int value = V; };
template <int I, int N, typename F> __device__ __forceinline__ void sfor(F&& f) {
    if constexpr (I < N) { f(IntC<I>{}); sfor<I + 1, N>(f); }
}

struct RecParams {
    CUtensorMap tmW[3];
    CUtensorMap tmWo;
    CUtensorMap tmX;
    const __nv_bfloat16* mem0;
    __nv_bfloat16* qkv_tok;
    __nv_bfloat16* kv_mem;
    uint8_t* xchg;
    uint32_t* flags;
    uint32_t one[2];
    uint32_t* arrivals;
};

__device__ __forceinline__ void mma_a(float* d, const uint32_t* a, uint32_t b0, uint32_t b1) {
    mma16816(d, a[0], a[1], a[2], a[3], b0, b1);
}
__device__ __forceinline__ void ldsm4(uint32_t addr, uint32_t* r) { ldsm_x4(addr, r[0], r[1], r[2], r[3]); }
__device__ __forceinline__ void ldsm4t(uint32_t addr, uint32_t* r) { ldsm_x4_t(addr, r[0], r[1], r[2], r[3]); }
template <int OFF> __device__ __forceinline__ void poll_v2(uint2& v, const uint8_t* p) {
    asm volatile("ld.relaxed.gpu.global.v2.b32 {%0,%1}, [%2+%3];" : "=r"(v.x), "=r"(v.y) : "l"(p), "n"(OFF) : "memory");
}
__device__ __forceinline__ uint32_t max3(uint32_t a, uint32_t b, uint32_t c) { return max(max(a, b), c); }
__device__ __forceinline__ uint32_t pub_slot(int s) { return (s & 1) * XCHG_SLOT + ((s >> 1) & 1) * PUB_BYTES; }

__device__ __forceinline__ uint8_t* xaddr(uint32_t lo, uint32_t hi) {
    uint64_t a;
    asm("mov.b64 %0, {%1, %2};" : "=l"(a) : "r"(lo), "r"(hi));
    return reinterpret_cast<uint8_t*>(a);
}
template <int N> __device__ __forceinline__ uint32_t delay_zero(uint32_t a) {
    uint32_t x = a;
    #pragma unroll
    for (int i = 0; i < N; i++) x = lds32_volatile(x);
    return x - a;
}
__device__ __forceinline__ uint32_t fresh(uint32_t x) { asm volatile("" : "+r"(x)); return x; }

template <int NT> __device__ __forceinline__ uint32_t wo_addr(uint32_t ao, uint32_t a3, int n) {
    return (n % NT == 2 ? a3 : ao + (n % NT) * 32768) + (n / NT) * 1024;
}
template <int NT, int PF>
__device__ __forceinline__ void wo_phase(uint32_t (&st)[8 * NT][4], uint32_t ao, uint32_t a3, uint32_t l16, uint32_t tbl, uint32_t sums,
                                         uint32_t slot, uint32_t xhi, uint32_t third) {
    constexpr int AHEAD = PF > WO_AHEAD ? PF - NT : WO_AHEAD;
    uint32_t of[4][4], pl[3];
    float i0, i1;
    ldsm4t(l16 + SM_O, of[0]);
    #pragma unroll
    for (int n = PF; n < AHEAD; n++) ldsm4t(wo_addr<NT>(ao, a3, n), st[n]);
    float acc[NT][4];
    #pragma unroll
    for (int i = 0; i < NT; i++) { acc[i][0] = acc[i][1] = acc[i][2] = acc[i][3] = 0.f; }
    #pragma unroll
    for (int kk = 0; kk < 8; kk++) {
        if ((kk & 1) == 0 && kk + 2 < 8) ldsm4t(l16 + SM_O + ((kk >> 1) + 1) * 512, of[(kk >> 1) + 1]);
        if (kk == 4) {
            const uint32_t x = fresh(l16);
            const uint4 sa = lds128(sums + ((x << 1) & 0x60)), sc = lds128(sums + ((x << 1) & 0x60) + 16);
            i0 = rcp((__uint_as_float(sa.x) + __uint_as_float(sa.y)) + (__uint_as_float(sa.z) + __uint_as_float(sa.w)));
            i1 = rcp((__uint_as_float(sc.x) + __uint_as_float(sc.y)) + (__uint_as_float(sc.z) + __uint_as_float(sc.w)));
            const uint4 t = lds128(tbl + ((x >> 3) & 0x30));
            const uint32_t d = slot + ((x >> 1) & 0x38);
            pl[0] = t.x + d; pl[1] = t.y + d; pl[2] = t.z + d;
            __syncwarp();
        }
        #pragma unroll
        for (int i = 0; i < NT; i++) {
            const int n = kk * NT + i;
            mma_a(acc[i], st[n], of[kk >> 1][(kk & 1) * 2], of[kk >> 1][(kk & 1) * 2 + 1]);
            if (n + AHEAD >= PF && n + AHEAD < 8 * NT) ldsm4t(wo_addr<NT>(ao, a3, n + AHEAD), st[n + AHEAD]);
        }
    }
    #pragma unroll
    for (int i = 0; i < NT; i++)
        asm volatile("{\n.reg .pred p;\nsetp.ne.u32 p, %3, 0;\n@p st.relaxed.gpu.global.v2.b32 [%0], {%1,%2};\n}"
                     ::"l"(xaddr(pl[i], xhi)), "r"(pack_bf16(acc[i][0] * i0, acc[i][1] * i1)), "r"(pack_bf16(acc[i][2] * i0, acc[i][3] * i1)),
                       "r"(i < 2 ? 1u : third) : "memory");
}

constexpr uint32_t SMEM_ORIGIN = 1024;
constexpr uint64_t DESC_BASE = (1ull << 16) | (0x40000040ull << 32);
template <int OFFB, int SCALE_D>
__device__ __forceinline__ void wgmma_n32_rs(float (&d)[16], const uint32_t* a, uint32_t one) {
    asm volatile(
        "{\n.reg .b64 db;\nmad.wide.u32 db, %20, %21, %22;\n"
        "wgmma.mma_async.sync.aligned.m64n32k16.f32.bf16.bf16 {%0,%1,%2,%3,%4,%5,%6,%7,%8,%9,%10,%11,%12,%13,%14,%15}, "
        "{%16,%17,%18,%19}, db, %23, 1, 1, 0;\n}"
        : "+f"(d[0]), "+f"(d[1]), "+f"(d[2]), "+f"(d[3]), "+f"(d[4]), "+f"(d[5]), "+f"(d[6]), "+f"(d[7]),
          "+f"(d[8]), "+f"(d[9]), "+f"(d[10]), "+f"(d[11]), "+f"(d[12]), "+f"(d[13]), "+f"(d[14]), "+f"(d[15])
        : "r"(a[0]), "r"(a[1]), "r"(a[2]), "r"(a[3]), "r"(one), "n"((SMEM_ORIGIN + OFFB) >> 4), "l"(DESC_BASE), "n"(SCALE_D));
}
template <int OFFA, int OFFB, int SCALE_D>
__device__ __forceinline__ void wgmma_n32_ss(float (&d)[16], uint32_t one) {
    asm volatile(
        "{\n.reg .b64 da, db;\nmad.wide.u32 da, %16, %17, %19;\nmad.wide.u32 db, %16, %18, %19;\n"
        "wgmma.mma_async.sync.aligned.m64n32k16.f32.bf16.bf16 {%0,%1,%2,%3,%4,%5,%6,%7,%8,%9,%10,%11,%12,%13,%14,%15}, "
        "da, db, %20, 1, 1, 1, 0;\n}"
        : "+f"(d[0]), "+f"(d[1]), "+f"(d[2]), "+f"(d[3]), "+f"(d[4]), "+f"(d[5]), "+f"(d[6]), "+f"(d[7]),
          "+f"(d[8]), "+f"(d[9]), "+f"(d[10]), "+f"(d[11]), "+f"(d[12]), "+f"(d[13]), "+f"(d[14]), "+f"(d[15])
        : "r"(one), "n"((SMEM_ORIGIN + OFFA) >> 4), "n"((SMEM_ORIGIN + OFFB) >> 4), "l"(DESC_BASE), "n"(SCALE_D));
}
template <int WG, int J0, int J1, int I0, int I1, bool ACC, bool FENCE = true>
__device__ __forceinline__ void token_mma(float (&ta)[2][16], const uint32_t (&wr)[NREG][2][4], uint32_t one) {
    if (FENCE) asm volatile("wgmma.fence.sync.aligned;" ::: "memory");
    sfor<J0, J1>([&](auto J) {
        constexpr int j = J.value, offb = SM_X + WG * 32768 + (j >> 2) * 4096 + (j & 3) * 32, sc = (ACC || j != J0) ? 1 : 0;
        sfor<I0, I1>([&](auto I) {
            constexpr int i = I.value;
            if constexpr ((j & 3) != 0) wgmma_n32_rs<offb, sc>(ta[i], wr[reg_idx(j)][i], one);
            else if constexpr (WG == 0 || (j >> 2) >= TOK_MOVED) wgmma_n32_ss<SM_WQ + WG * 32768 + i * 16384 + (j >> 2) * 2048, offb, sc>(ta[i], one);
            constexpr int c = (j >> 2) - (8 - TOK_MOVED);
            if constexpr (WG == 0 && (j & 3) == 2 && c >= 0)
                wgmma_n32_ss<SM_WQ + 32768 + (1 - i) * 16384 + c * 2048, SM_X + 32768 + c * 4096, 1>(ta[i], one);
        });
    });
    asm volatile("wgmma.commit_group.sync.aligned;" ::: "memory");
}
__device__ __forceinline__ void warp_arrive(uint32_t bar) {
    __syncwarp();
    if (elect_one()) mbar_arrive(bar);
}
__device__ __forceinline__ void remote_arrive(uint32_t bar, uint32_t rank) {
    asm volatile("mbarrier.arrive.relaxed.cluster.shared::cluster.b64 _, [%0];" ::"r"(mapa(bar, rank)) : "memory");
}
__device__ __forceinline__ void x_load(const RecParams& p, uint32_t sb, int sg, int g) {
    tma_load_3d_mc(sb + SM_X + g * 16384, &p.tmX, 0, sg * SEG, g * 4, sb + SM_BAR + BAR_XG + 8 * g, (uint16_t)7);
}

__device__ __forceinline__ void rec_steps(const RecParams& p, const uint32_t (&wr)[NREG][2][4], const uint32_t sb, const int warp,
                                          const int cta, const int head, const int rank) {
    const int wq = warp & 3, wg = warp >> 2;
    const uint32_t bar = sb + SM_BAR;
    const uint32_t xhi = (uint32_t)((uint64_t)p.xchg >> 32);
    const float sl2 = 0.08838834764831845f * 1.4426950408889634f;
    const bool has_unit = warp >= 5 && (warp < 7 || cta < 64);
    const bool qk = rank < 2;
    const uint32_t pa = rank == 2 ? 0 : rank + 1, pb = rank == 0 ? 2 : rank - 1;
    const uint32_t tbl = sb + SM_TBL + warp * 64;
    const bool att = (warp & 6) == 2;
    const int stile = warp < 5 ? warp : warp - 3;

    const uint32_t u_st = uniform(SM_QK - SM_WQ - wg * (32768 - 1024)), u_stmask = uniform(wg == 0 ? 0x30 : 0);
    const uint32_t u_key = uniform(!qk || att || warp == 7 ? 0 : sb + (warp == 4 ? SM_QK + 1024 : SM_K + stile * 1024));
    const uint32_t u_bx = uniform(bar + (qk ? BAR_X : BAR_VM)), u_bra = uniform(mapa(u_bx, pa)), u_brb = uniform(mapa(u_bx, pb));
    const uint32_t u_src = uniform(lds32_volatile(tbl + 44));
    const uint32_t u_kv = uniform(qk && wg == 0 ? ~0u : (((rank >> 1) * NSEG * NH + head) * 8 + (qk ? rank * 4 + wq : warp)) * 64);
    const uint32_t u_free = uniform(warp == 5 ? mapa(bar + BAR_VF, 2) : warp == 6 ? mapa(bar + BAR_F0, 0) : 0);
    const uint32_t u_role = uniform((has_unit ? 1 : 0) | (att ? 2 : 0) | (warp != 1 || rank == 0 ? 4 : 0) | (!qk && warp == 0 ? 8 : 0) | (rank != 0 && warp == 1 ? 16 : 0));
    uint32_t l16, xa, aq, ao;
    {
        const int lane = threadIdx.x & 31, mi = lane >> 3, r8 = lane & 7, r16 = (mi >> 1) * 8 + r8;
        l16 = opaque(sb + lane * 16);
        xa = opaque(sb + lane * 8 + (qk ? SM_SP + rank * 1280 + stile * 256 : SM_VM + warp * 256));
        aq = opaque(sb + SM_WQ + wg * 32768 + r16 * 128 + (((wq * 2 + (mi & 1)) ^ r8) << 4));
        ao = opaque(sb + SM_WO + (warp >> 1) * 8192 + r16 * 64 + ((((warp & 1) * 2 + (mi & 1)) ^ ((r8 >> 1) & 3)) << 4));
    }

    uint32_t mphase = 0;
    #pragma unroll 1
    for (int s = 0; s < NSEG; s++) {
        const uint32_t par = s & 1;
        uint32_t at[16][4];
        auto at_early = [](int i) { return i < 2 || ((i & 1) == 0 && (i >> 1) <= AT_PF - 2); };
        auto at_prefetch = [&](int i0, int i1) {
            #pragma unroll
            for (int i = i0; i < i1; i++)
                if (at_early(i)) ldsm4t(aq + (i & 1) * 16384 + (i >> 1) * 2048, at[i]);
        };
        if (wg == 0) {
            float ta[2][16];
            mbar_wait_bounded(bar + BAR_XG, par);
            STAMP(6);
            auto park = [&](int i, uint32_t dst) {
                #pragma unroll
                for (int e = 0; e < 16; e++) asm volatile("" : "+f"(ta[i][e]));
                #pragma unroll
                for (int j = 0; j < 4; j++)
                    sts128(l16 + dst + j * 2048 + wq * 512, __float_as_uint(ta[i][4 * j]), __float_as_uint(ta[i][4 * j + 1]),
                           __float_as_uint(ta[i][4 * j + 2]), __float_as_uint(ta[i][4 * j + 3]));
            };
            token_mma<0, 0, 16, 0, 1, false>(ta, wr, 1);
            mbar_wait_bounded(bar + BAR_XG + 8, par);
            if (TOK_MOVED > 0) mbar_wait_bounded(bar + BAR_XG + 16, par);
            token_mma<0, 16, 32, 0, 1, true>(ta, wr, p.one[0]);
            token_mma<0, 0, TOK_GO, 1, 2, false, false>(ta, wr, p.one[1]);
            token_mma<0, TOK_GO, 32, 1, 2, true, false>(ta, wr, p.one[1]);
            if (TOK_MOVED == 0) mbar_wait_bounded(bar + BAR_XG + 16, par);
            asm volatile("wgmma.wait_group.sync.aligned 1;" ::: "memory");
            park(0, SM_PARK0);
            warp_arrive(bar + BAR_GO);
            asm volatile("wgmma.wait_group.sync.aligned 0;" ::: "memory");
            named_bar_sync(10, 128);
            park(1, SM_PARK1);
            mbar_wait_bounded(bar + BAR_XG + 24, par);
            warp_arrive(bar + BAR_PK);
            const uint8_t* src = xaddr(u_src + pub_slot(s), xhi);
            auto fetch = [&]() {
                if (elect_one()) {
                    mbar_arrive_expect_tx(bar + BAR_M + 8 * wq, 4096);
                    bulk_load(sb + SM_MEM + wq * 4096, src, 4096, bar + BAR_M + 8 * wq);
                }
            };
            named_bar_sync(7, REC_THREADS - 32);
            spin_clks(FETCH_DELAY);
            fetch();
            STAMP(12);
            if (warp == 0 && elect_one()) {
                if (qk) mbar_arrive_expect_tx(bar + BAR_V, 8192);
                mbar_arrive_expect_tx(bar + BAR_X, qk ? 1280 : 2560);
                mbar_arrive_expect_tx(bar + BAR_VM, qk ? 2048 : 0);
            }
            at_prefetch(0, 16);
            const uint32_t x = fresh(l16) - sb;
            const uint32_t ca = sb + SM_MEM + wq * 4096 + x * 2 + ((x >> 4) & 0x1C);
            #pragma unroll 1
            for (uint32_t n = 0; n < POLL_LIMIT; n++) {
                mbar_wait_bounded(bar + BAR_M + 8 * wq, mphase);
                mphase ^= 1;
                const uint32_t c0 = lds32_volatile(ca), c1 = lds32_volatile(ca + 1024), c2 = lds32_volatile(ca + 2048), c3 = lds32_volatile(ca + 3072);
                if (!__any_sync(~0u, max(max3(c0, c1, c2), c3) == (NO_COMM ? 0x12345u : SENT))) break;
                fetch();
            }
            STAMP(0);
            named_bar_sync(0, REC_THREADS);
        } else {
            at_prefetch(0, 5);
            if (s > 0) {
                if (u_role & 1) {
                    const uint32_t ln = (fresh(l16) >> 4) & 31;
                    const uint32_t ibl = lds32_volatile(tbl + 12) + (par ^ 1) * XCHG_SLOT + ln * 8;
                    const uint32_t publ = lds32_volatile(tbl + 28) + pub_slot(s) + (ln & 16) * 256 + (ln & 8) * 16 + (ln & 7) * 4;
                    const bool odd = ln & 8;
                    const uint8_t* ib = xaddr(ibl + delay_zero<POLL_DELAY>(bar + BAR_SELF), xhi);
                    STAMP(8);
                    uint2 v[8];
                    #pragma unroll 1
                    for (uint32_t n = 0; n < POLL_LIMIT; n++) {
                        sfor<0, 8>([&](auto I) { poll_v2<I.value * 256>(v[I.value], ib); });
                        const uint32_t mx = max(max3(v[0].y, v[1].y, v[2].y), max3(max3(v[3].y, v[4].y, v[5].y), v[6].y, v[7].y));
                        if (!__any_sync(~0u, mx == (NO_COMM ? 0x12345u : SENT))) break;
                    }
                    float a0 = ((bf16_lo(v[0].x) + bf16_lo(v[1].x)) + (bf16_lo(v[2].x) + bf16_lo(v[3].x))) +
                               ((bf16_lo(v[4].x) + bf16_lo(v[5].x)) + (bf16_lo(v[6].x) + bf16_lo(v[7].x)));
                    float a1 = ((bf16_hi(v[0].x) + bf16_hi(v[1].x)) + (bf16_hi(v[2].x) + bf16_hi(v[3].x))) +
                               ((bf16_hi(v[4].x) + bf16_hi(v[5].x)) + (bf16_hi(v[6].x) + bf16_hi(v[7].x)));
                    float a2 = ((bf16_lo(v[0].y) + bf16_lo(v[1].y)) + (bf16_lo(v[2].y) + bf16_lo(v[3].y))) +
                               ((bf16_lo(v[4].y) + bf16_lo(v[5].y)) + (bf16_lo(v[6].y) + bf16_lo(v[7].y)));
                    float a3 = ((bf16_hi(v[0].y) + bf16_hi(v[1].y)) + (bf16_hi(v[2].y) + bf16_hi(v[3].y))) +
                               ((bf16_hi(v[4].y) + bf16_hi(v[5].y)) + (bf16_hi(v[6].y) + bf16_hi(v[7].y)));
                    float k0 = odd ? a2 : a0, k1 = odd ? a3 : a1;
                    k0 += __shfl_xor_sync(~0u, odd ? a0 : a2, 8);
                    k1 += __shfl_xor_sync(~0u, odd ? a1 : a3, 8);
                    k0 += __shfl_xor_sync(~0u, k0, 16);
                    k1 += __shfl_xor_sync(~0u, k1, 16);
                    st_relaxed_b32(xaddr(publ, xhi), pack_bf16(k0, k1));
                    STAMP(11);
                } else if (warp == 4) {
                    bulk_wait_read_all();
                    if (elect_one()) remote_arrive(bar + BAR_F3, 2);
                    if (!qk) {
                        mbar_wait_bounded(bar + BAR_F3, par ^ 1);
                        if (elect_one()) x_load(p, sb, s, 3);
                    }
                    if (elect_one()) {
                        bulk_wait_all();
                        signal_flag(p.flags + F_PROGRESS + s - 1);
                    }
                    __syncwarp();
                    STAMP(10);
                }
            }
            float ta[2][16];
            uint32_t w[8];
            auto unpark = [&](int i, uint32_t src) {
                mbar_wait_bounded(bar + (i ? BAR_GO : BAR_PK), par);
                #pragma unroll
                for (int j = 0; j < 4; j++) {
                    const uint4 v = lds128(l16 + src + j * 2048 + wq * 512);
                    ta[i][4 * j] = __uint_as_float(v.x); ta[i][4 * j + 1] = __uint_as_float(v.y);
                    ta[i][4 * j + 2] = __uint_as_float(v.z); ta[i][4 * j + 3] = __uint_as_float(v.w);
                }
            };
            if (warp != 4) named_bar_arrive(7, REC_THREADS - 32);
            unpark(1, SM_PARK0);
            STAMP(6);
            token_mma<1, 0, 16, 1, 2, true>(ta, wr, 1);
            unpark(0, SM_PARK1);
            token_mma<1, 16, 32, 1, 2, true>(ta, wr, 1);
            token_mma<1, 16, 32, 0, 1, true>(ta, wr, 1);
            token_mma<1, 0, 16, 0, 1, true, false>(ta, wr, 1);
            auto put_tile = [&](int m, const uint32_t (&q)[8]) {
                #pragma unroll
                for (int h = 0; h < 2; h++) {
                    if (qk) asm volatile("stmatrix.sync.aligned.m8n8.x4.trans.shared.b16 [%0], {%1,%2,%3,%4};"
                                         ::"r"(aq - (SM_WQ + 32768) + (m ? SM_K : SM_QS) + h * 2048), "r"(q[4 * h]), "r"(q[4 * h + 1]),
                                           "r"(q[4 * h + 2]), "r"(q[4 * h + 3]) : "memory");
                    else sts128(l16 + SM_V + wq * 2048 + m * 1024 + h * 512, q[4 * h], q[4 * h + 1], q[4 * h + 2], q[4 * h + 3]);
                }
            };
            auto pack_tile = [&](int i) {
                #pragma unroll
                for (int e = 0; e < 16; e++) asm volatile("" : "+f"(ta[i][e]));
                #pragma unroll
                for (int j = 0; j < 8; j++) w[j] = pack_bf16(ta[i][2 * j], ta[i][2 * j + 1]);
            };
            asm volatile("wgmma.wait_group.sync.aligned 2;" ::: "memory");
            pack_tile(1);
            at_prefetch(5, 16);
            asm volatile("wgmma.wait_group.sync.aligned 1;" ::: "memory");
            if (elect_one()) mbar_arrive(bar + BAR_OUT);
            mbar_wait_bounded(bar + BAR_OUT, par);
            if (u_free != 0 && elect_one())
                asm volatile("mbarrier.arrive.relaxed.cluster.shared::cluster.b64 _, [%0];" ::"r"(u_free) : "memory");
            put_tile(0, w);
            asm volatile("wgmma.wait_group.sync.aligned 0;" ::: "memory");
            pack_tile(0);
            put_tile(1, w);
            STAMP(0);
            named_bar_sync(0, REC_THREADS);
            if (!qk) {
                asm volatile("fence.proxy.async.shared::cta;" ::: "memory");
                mbar_wait_bounded(bar + BAR_VF, par);
                __syncwarp();
                if (elect_one()) {
                    #pragma unroll
                    for (int r = 0; r < 2; r++)
                        asm volatile("cp.async.bulk.shared::cluster.shared::cta.mbarrier::complete_tx::bytes [%0], [%1], %2, [%3];"
                                     ::"r"(mapa(sb + SM_V + wq * 2048, r)), "r"(sb + SM_V + wq * 2048), "r"(2048), "r"(mapa(bar + BAR_V, r)) : "memory");
                }
            }
            STAMP(14);
        }
        const uint32_t mb = l16 + SM_MEM + wg * 8192;
        float acc[2][2][4];
        {
            uint32_t b[2][4];
            ldsm4t(mb, b[0]);
            ldsm4t(mb + 512, b[1]);
            #pragma unroll
            for (int i = 0; i < AT_AHEAD; i++)
                if (!at_early(i)) ldsm4t(aq + (i & 1) * 16384 + (i >> 1) * 2048, at[i]);
            STAMPD(1, b[0][0]);
            #pragma unroll
            for (int i = 0; i < 4; i++) { for (int e = 0; e < 4; e++) acc[i >> 1][i & 1][e] = 0.f; }
            #pragma unroll
            for (int u = 0; u < 16; u++) {
                #pragma unroll
                for (int h = 0; h < 2; h++) {
                    const int j = 2 * u + h;
                    #pragma unroll
                    for (int m = 0; m < 2; m++) {
                        if ((j & 3) == 0) mma_a(acc[h][m], at[(j >> 2) * 2 + m], b[u & 1][2 * h], b[u & 1][2 * h + 1]);
                        else mma_a(acc[h][m], wr[reg_idx(j)][m], b[u & 1][2 * h], b[u & 1][2 * h + 1]);
                    }
                }
                if (u + 2 < 16) ldsm4t(mb + (u + 2) * 512, b[u & 1]);
                if (u + AT_AHEAD < 16 && !at_early(u + AT_AHEAD))
                    ldsm4t(aq + ((u + AT_AHEAD) & 1) * 16384 + ((u + AT_AHEAD) >> 1) * 2048, at[u + AT_AHEAD]);
            }
        }
        sts128(l16 + SM_RED + warp * 512, __float_as_uint(acc[0][1][0] + acc[1][1][0]), __float_as_uint(acc[0][1][1] + acc[1][1][1]),
               __float_as_uint(acc[0][1][2] + acc[1][1][2]), __float_as_uint(acc[0][1][3] + acc[1][1][3]));
        #pragma unroll
        for (int e = 0; e < 4; e++) acc[0][0][e] += acc[1][0][e];
        const uint32_t x16 = fresh(l16);
        const uint32_t ast = (fresh(aq) + u_st) ^ ((((x16 >> 7) ^ wq) & 1) * u_stmask);
        const uint32_t sa = fresh((x16 & 0x70) * 8 + ((((x16 >> 3) & 0x30) ^ x16) & 0x70)), sa2 = fresh(sa ^ 64);
        const uint32_t xra = __byte_perm(xa, u_bra, 0x7210), xrb = __byte_perm(xa, u_brb, 0x7210);
        STAMP(2);
        named_bar_sync(1 + wq, 64);
        uint32_t p0, p1;
        {
            const uint4 v = lds128(l16 + SM_RED + (warp ^ 4) * 512);
            p0 = pack_bf16(acc[0][0][0] + __uint_as_float(v.x), acc[0][0][1] + __uint_as_float(v.y));
            p1 = pack_bf16(acc[0][0][2] + __uint_as_float(v.z), acc[0][0][3] + __uint_as_float(v.w));
        }
        auto send = [&](uint32_t y0, uint32_t y1) {
            st_async_v2(xra, y0, y1, u_bra);
            st_async_v2(xrb, y0, y1, u_brb);
            sts64(xa, y0, y1);
            warp_arrive(u_bx);
        };
        if (qk) {
            asm volatile("stmatrix.sync.aligned.m8n8.x2.trans.shared.b16 [%0], {%1,%2};" ::"r"(ast), "r"(p0), "r"(p1) : "memory");
            named_bar_sync(5, REC_THREADS);
            if (u_key != 0) {
                uint32_t qa[2][4], kf[2][4];
                ldsm4(sa + sb + SM_QK, qa[0]);
                ldsm4(sa + u_key, kf[0]);
                ldsm4(sa2 + sb + SM_QK, qa[1]);
                ldsm4(sa2 + u_key, kf[1]);
                float se[4] = {0.f, 0.f, 0.f, 0.f}, so[4] = {0.f, 0.f, 0.f, 0.f};
                #pragma unroll
                for (int u = 0; u < 2; u++) {
                    mma_a(se, qa[u], kf[u][0], kf[u][1]);
                    mma_a(so, qa[u], kf[u][2], kf[u][3]);
                }
                send(__float_as_uint(se[0] + so[2]), __float_as_uint(se[1] + so[3]));
            }
        } else {
            send(p0, p1);
        }
        STAMP(3);
        const uint32_t lane = (fresh(l16) >> 4) & 31;
        if (u_kv != ~0u) {
            uint32_t* dst = reinterpret_cast<uint32_t*>(p.kv_mem) + (u_kv + s * (NH * 512) + lane);
            dst[0] = p0;
            dst[32] = p1;
        }
        auto tile_stores = [&]() {
            if (wg == 1) {
                asm volatile("fence.proxy.async.shared::cta;" ::: "memory");
                if (warp != 4) {
                    named_bar_arrive(14, 128);
                } else {
                    named_bar_sync(14, 128);
                    if (elect_one()) {
                        __nv_bfloat16* dst = p.qkv_tok + ((size_t)s * NH + head) * (SEG * DH);
                        constexpr size_t MAT = (size_t)NSEG * NH * SEG * DH;
                        bulk_store(dst + (qk ? rank * (SEG * 64) : 2 * MAT), sb + (qk ? SM_QS : SM_V), 4096);
                        bulk_store(dst + (qk ? MAT + rank * (SEG * 64) : 2 * MAT + SEG * 64), sb + (qk ? SM_K : SM_V + 4096), 4096);
                        bulk_commit();
                    }
                    __syncwarp();
                }
            }
        };
        if (s == NSEG - 1) { tile_stores(); break; }
        if (s == 0) mbar_wait_bounded(bar + BAR_WO, 0);
        const uint32_t slot = par * XCHG_SLOT;
        if (u_role & 2) {
            if (qk) mbar_wait_bounded(bar + BAR_V, par);
            uint32_t vt[2][4][4];
            #pragma unroll
            for (int i = 0; i < 8; i++) {
                const uint4 v = lds128(l16 + SM_V + (warp & 1) * 1024 + (i & 3) * 2048 + (i >> 2) * 512);
                vt[i >> 2][i & 3][0] = v.x; vt[i >> 2][i & 3][1] = v.y; vt[i >> 2][i & 3][2] = v.z; vt[i >> 2][i & 3][3] = v.w;
            }
            const uint32_t l8 = sb + lane * 8;
            mbar_wait_bounded(bar + BAR_X, par);
            STAMP(4);
            float sv[10];
            #pragma unroll
            for (int j = 0; j < 5; j++) {
                const uint2 a = lds64(l8 + SM_SP + j * 256), b = lds64(l8 + SM_SP + 1280 + j * 256);
                sv[2 * j] = __uint_as_float(a.x) + __uint_as_float(b.x);
                sv[2 * j + 1] = __uint_as_float(a.y) + __uint_as_float(b.y);
            }
            float mx = fmaxf(fmaxf(fmaxf(sv[0], sv[1]), fmaxf(sv[2], sv[3])), fmaxf(fmaxf(sv[4], sv[5]), fmaxf(sv[6], sv[7])));
            mx = fmaxf(mx, fmaxf(sv[8], sv[9]));
            const float m1 = __shfl_xor_sync(~0u, mx, 1), m2 = __shfl_xor_sync(~0u, mx, 2), m3 = __shfl_xor_sync(~0u, mx, 3);
            const bool vm_ok = mbar_try_wait(bar + BAR_VM, par);
            mx = fmaxf(fmaxf(mx, m1), fmaxf(m2, m3));
            const float mo = mx * sl2;
            #pragma unroll
            for (int j = 0; j < 10; j++) sv[j] = ex2(fmaf(sv[j], sl2, -mo));
            const uint32_t e0 = pack_bf16(sv[0], sv[1]), e1 = pack_bf16(sv[2], sv[3]);
            const uint32_t e2 = pack_bf16(sv[4], sv[5]), e3 = pack_bf16(sv[6], sv[7]), em = pack_bf16(sv[8], sv[9]);
            float o[4][4];
            #pragma unroll
            for (int i = 0; i < 4; i++) {
                o[i][0] = o[i][1] = o[i][2] = o[i][3] = 0.f;
                mma_a(o[i], vt[0][i], e0, e1);
            }
            sts32(sb + SM_SUM + lane * 4,
                  __float_as_uint((((sv[0] + sv[1]) + (sv[2] + sv[3])) + ((sv[4] + sv[5]) + (sv[6] + sv[7]))) + (sv[8] + sv[9])));
            if (!vm_ok) mbar_wait_bounded(bar + BAR_VM, par);
            uint2 vm[4];
            #pragma unroll
            for (int i = 0; i < 4; i++) {
                vm[i] = lds64(l8 + SM_VM + (warp & 1) * 1024 + i * 256);
                mma_a(o[i], vt[1][i], e2, e3);
            }
            #pragma unroll
            for (int i = 0; i < 4; i++) mma1688(o[i], vm[i].x, vm[i].y, em);
            #pragma unroll
            for (int i = 0; i < 4; i += 2)
                stsm_x4(l16 + SM_O + (warp & 1) * 1024 + i * 256, pack_bf16(o[i][0], o[i][1]), pack_bf16(o[i][2], o[i][3]),
                        pack_bf16(o[i + 1][0], o[i + 1][1]), pack_bf16(o[i + 1][2], o[i + 1][3]));
            STAMP(5);
            uint32_t st[16][4];
            #pragma unroll
            for (int n = 0; n < WO_PF0; n++) ldsm4t(wo_addr<2>(ao, 0, n), st[n]);
            named_bar_sync(6, REC_THREADS);
            wo_phase<2, WO_PF0>(st, ao, 0, l16, tbl, sb + SM_SUM, slot, xhi, 0);
        } else {
            const uint32_t a3 = fresh(ao) + (wg == 0 ? 10 : 6) * 8192;
            uint32_t st[24][4];
            #pragma unroll
            for (int n = 0; n < WO_PFA; n++) ldsm4t(wo_addr<3>(ao, a3, n), st[n]);
            tile_stores();
            if (u_role & 1) {
                uint8_t* ib = xaddr(lds32_volatile(tbl + 12) + (par ^ 1) * XCHG_SLOT + lane * 16, xhi);
                #pragma unroll
                for (int i = 0; i < 4; i++) st_relaxed_v4(ib + i * 512, SENT);
                st_relaxed_b32(xaddr(lds32_volatile(tbl + 28) + pub_slot(s + 3) + (lane & 16) * 256 + (lane & 8) * 16 + (lane & 7) * 4, xhi), SENT);
            }
            if (warp == 1) {
                if (elect_one()) {
                    #pragma unroll
                    for (int g = 0; g < 4; g++) mbar_arrive_expect_tx(bar + BAR_XG + 8 * g, 16384);
                }
                if (s + 2 < NSEG && cta < 4 && elect_one())
                    asm volatile("cp.async.bulk.prefetch.tensor.3d.L2.global [%0, {%1, %2, %3}];"
                                 ::"l"(&p.tmX), "r"(0), "r"((s + 2) * SEG), "r"(cta * 4) : "memory");
                if (rank == 0) {
                    mbar_wait_bounded(bar + BAR_F0, par);
                    if (elect_one()) x_load(p, sb, s + 1, 0);
                }
            }
            if (WO_PFA < WO_PF1 || (u_role & 16)) mbar_wait_bounded(bar + BAR_X, par);
            if (WO_PFA < WO_PF1) {
                spin_clks(WO_PFB_DELAY);
                #pragma unroll
                for (int n = WO_PFA; n < WO_PF1; n++) ldsm4t(wo_addr<3>(ao, a3, n), st[n]);
            }
            if (u_role & 16) {
                spin_clks(XB_DELAY);
                mbar_wait_bounded(bar + BAR_VM, par);
                if (elect_one()) x_load(p, sb, s + 1, rank);
            }
            named_bar_sync(6, REC_THREADS);
            wo_phase<3, WO_PF1>(st, ao, a3, l16, tbl, sb + SM_SUM, slot, xhi, u_role & 4);
        }
        STAMP(7);
        if (wg == 0) named_bar_sync(9, REC_THREADS); else named_bar_arrive(9, REC_THREADS);
    }
    mbar_wait(bar + BAR_X, 1);
    mbar_wait(bar + BAR_VM, 1);
    if (qk) mbar_wait(bar + BAR_V, 1);
    named_bar_sync(0, REC_THREADS);
    if (warp == 4 && elect_one()) {
        bulk_wait_all();
        signal_flag(p.flags + F_PROGRESS + NSEG - 1);
    }
}

__global__ void __launch_bounds__(REC_THREADS, 1) rec_kernel(const __grid_constant__ RecParams p) {
    extern __shared__ __align__(1024) uint8_t smem_raw[];
    const uint32_t sb = smem_u32(smem_raw);
    const int tid = threadIdx.x, lane = tid & 31;
    const int warp = __shfl_sync(~0u, tid >> 5, 0);
    const int cta = blockIdx.x, head = cta / 3, rank = cta % 3;
    const int wg = warp >> 2, wq = warp & 3;
    const int t0 = (rank * 64 + 2) / 3;
    const uint32_t bar = sb + SM_BAR;
    uint8_t* const xb = p.xchg;
    const uint32_t xlo = (uint32_t)(uint64_t)xb;
    if ((sb & 0x3FFFF) != SMEM_ORIGIN) __trap();
    KENTER(1);
    auto w_box = [&](int part, int g, int i, uint32_t dst, uint32_t mb) {
        const int m = i ^ g;
        const CUtensorMap* tm = &p.tmW[rank == 2 ? 2 : m];
        const int col = head * DH + (rank == 2 ? m : rank) * 64, row = ((part + 1) & 3) * 16;
        tma_load_3d(dst, tm, col, row, g * 8, mb);
    };
    if (tid == 0) {
        mbar_init(bar + BAR_V, 1);
        for (int i = 0; i < 4; i++) { mbar_init(bar + BAR_XG + 8 * i, 1); mbar_init(bar + BAR_M + 8 * i, 1); }
        mbar_init(bar + BAR_GO, 4);
        mbar_init(bar + BAR_PK, 4);
        mbar_init(bar + BAR_OUT, 4);
        mbar_init(bar + BAR_VM, rank < 2 ? 1 : 9);
        mbar_init(bar + BAR_F0, 3);
        mbar_init(bar + BAR_F3, 3);
        mbar_init(bar + BAR_VF, 3);
        sts64(bar + BAR_MIN, ~0u, ~0u);
        mbar_init(bar + BAR_X, rank < 2 ? 6 : 1);
        for (int i = 0; i < 3; i++) mbar_init(bar + BAR_P0 + 8 * i, 1);
        mbar_init(bar + BAR_WQ, 1);
        mbar_init(bar + BAR_WO, 1);
        sts32(bar + BAR_SELF, bar + BAR_SELF);
        asm volatile("fence.mbarrier_init.release.cluster;" ::: "memory");
    }
    auto build_tables = [&]() {
        uint32_t av = 0;
        for (uint32_t n = 0; !__all_sync(~0u, (av >> 24) == 24); n++) {
            av = ld_acquire_b32(p.arrivals + (lane & 3));
            if (n > SPIN_LIMIT) __trap();
        }
        uint32_t cm[3];
        #pragma unroll
        for (int i = 0; i < 3; i++) {
            const int o = i * 32 + lane;
            cm[i] = __ballot_sync(~0u, (__shfl_sync(~0u, av, o / 24) >> (o % 24)) & 1);
        }
        auto color_of = [&](int o) { return ((o < 32 ? cm[0] : o < 64 ? cm[1] : cm[2]) >> (o & 31)) & 1u; };
        auto inbox = [&](int o, int byte) {
            uint32_t c = color_of(o);
            int ones = 0;
            #pragma unroll
            for (int i = 0; i < 3; i++) ones += __popc(o >= i * 32 + 32 ? cm[i] : (o > i * 32 ? cm[i] & ((1u << (o - i * 32)) - 1) : 0u));
            int idx = c ? ones : o - ones;
            if (idx >= INBOX_MAX) { idx = 2 * INBOX_MAX - 1 - idx; c ^= 1; }
            const uint32_t lin = idx * 6144 + byte, q = XCHG_INBOX + (lin >> 12) * 8192;
            return q + class_off(xlo + q, c) + (lin & 4095);
        };
        uint32_t off = 0;
        const int grp = (warp + 3) & 3;
        if (lane < 12) {
            const int i = lane >> 2, lt0 = rank == 0 ? 0 : (rank == 1 ? 6 : 11);
            const int o = i < 2 ? rank * 32 + warp * 4 + (lane & 3) : (lt0 + ((warp + 4) & 7)) * 4 + (lane & 3);
            off = inbox(min(o, 95), i * 2048 + head * 64);
        } else if (lane == 12) {
            off = inbox(cta, (grp % 3) * 2048);
        } else if (lane == 13) {
            int T;
            if (grp < 2) {
                T = ((cta >> 5) * 64 + 2) / 3 + 8 * grp + ((cta & 31) >> 2);
            } else {
                const int tl = (cta & 63) >> 2;
                T = tl < 6 ? 16 + tl : (tl < 11 ? 22 + 16 + (tl - 6) : 43 + 16 + (tl - 11));
            }
            off = XCHG_PUB + (T >> 4) * 8192 + (T & 15) * 256 + (cta & 3) * 32;
        } else if (lane == 14) {
            const uint32_t q = XCHG_PUB + wq * 8192;
            off = q + class_off(xlo + q, color_of(cta));
        }
        if (lane < 16) asm volatile("st.shared.b32 [%0], %1;" ::"r"(sb + SM_TBL + warp * 64 + (lane & 3) * 16 + (lane >> 2) * 4), "r"(xlo + off) : "memory");
    };
    if (cta == 0 && tid < F_COUNT) p.flags[tid] = 0;
    __syncthreads();
    asm volatile("barrier.cluster.arrive.relaxed.aligned;" ::: "memory");
    uint4 img = make_uint4(SENT, SENT, SENT, SENT);
    if (cta >= 92) {
        const unsigned short* m = reinterpret_cast<const unsigned short*>(p.mem0) + (cta - 92) * 256 + tid;
        uint32_t w[4];
        #pragma unroll
        for (int i = 0; i < 4; i++) w[i] = (uint32_t)__ldg(m + 2 * i * DM) | ((uint32_t)__ldg(m + (2 * i + 1) * DM) << 16);
        img = make_uint4(w[0], w[1], w[2], w[3]);
    }
    {
        constexpr int NPAIR = (XCHG_SLOT + PUB_BYTES) / 8192;
        uint8_t* pr = xb + (4 + cta) * 8192;
        const uint32_t c0 = class_off(xlo + (4 + cta) * 8192, 0);
        #pragma unroll
        for (int c = 0; c < 2; c++) {
            const bool timed = lane == 0 || (lane == 8 && c == (warp & 1));
            reinterpret_cast<uint4*>(pr + (c0 ^ (c << 12)))[tid] = make_uint4(timed ? 0u : SENT, SENT, SENT, SENT);
        }
        __syncwarp();
        if (lane == 0) {
            uint32_t x = 0;
            for (int k = 0; k < 3; k++) {
                const uint32_t c = (k + warp) & 1, t0 = clock_after(x);
                x = atomicExch(reinterpret_cast<uint32_t*>(pr + (c0 ^ (c << 12)) + warp * 512 + (k >> 1) * 128 + x), SENT);
                const uint32_t lat = clock_after(x) - t0;
                asm volatile("red.shared.min.u32 [%0], %1;" ::"r"(bar + BAR_MIN + 4 * c), "r"(lat) : "memory");
            }
        }
        __syncwarp();
        if (cta >= 92 || 100 + cta < NPAIR) {
            if (cta >= 92) {
                if (img.x == SENT) img.x = 0x7FFF7FFFu;
                if (img.y == SENT) img.y = 0x7FFF7FFFu;
                if (img.z == SENT) img.z = 0x7FFF7FFFu;
                if (img.w == SENT) img.w = 0x7FFF7FFFu;
            }
            uint8_t* q = xb + (cta >= 92 ? cta - 92 : 100 + cta) * 8192;
            reinterpret_cast<uint4*>(q)[tid] = img;
            reinterpret_cast<uint4*>(q + 4096)[tid] = img;
        }
    }
    __syncthreads();
    PSTAMP(4);
    auto stage = [](int part) { return ((part + 2) % 3) * 65536; };
    if (tid == 0) {
        for (int part = 0; part < 3; part++) {
            mbar_arrive_expect_tx(bar + BAR_P0 + 8 * part, 65536);
            for (int u = 0; u < 4; u++) w_box(part, u >> 1, u & 1, sb + stage(part) + u * 16384, bar + BAR_P0 + 8 * part);
        }
    }
    if (tid == 224) {
        const uint32_t c = lds32_volatile(bar + BAR_MIN) > lds32_volatile(bar + BAR_MIN + 4) ? 1 : 0;
        asm volatile("red.release.gpu.global.add.u32 [%0], %1;" ::"l"(p.arrivals + cta / 24), "r"((1u << 24) | (c << (cta % 24))) : "memory");
        if (PDL_POS == 0) pdl_launch_dependents();
    }
    uint32_t wr[NREG][2][4];
    {
        const int mi = lane >> 3, r8 = lane & 7;
        const uint32_t a0 = sb + wg * 32768 + ((mi >> 1) * 8 + r8) * 128 + (((wq * 2 + (mi & 1)) ^ r8) << 4);
        #pragma unroll
        for (int part = 0; part < 3; part++) {
            mbar_wait(bar + BAR_P0 + 8 * part, 0);
            #pragma unroll
            for (int j = 0; j < 8; j++) {
                #pragma unroll
                for (int i = 0; i < 2; i++) ldsm4t(a0 + stage(part) + i * 16384 + j * 2048, wr[part * 8 + j][i]);
            }
            asm volatile("fence.proxy.async.shared::cta;" ::: "memory");
            __syncthreads();
            PSTAMP(5 + part);
            if (tid == 224 && PDL_POS == part + 1) pdl_launch_dependents();
            if (tid == 0) {
                if (part == 0) {
                    for (int g = 0; g < 4; g++) {
                        mbar_arrive_expect_tx(bar + BAR_XG + 8 * g, 16384);
                        tma_load_3d(sb + SM_X + g * 16384, &p.tmX, 0, 0, g * 4, bar + BAR_XG + 8 * g);
                    }
                } else if (part == 1) {
                    mbar_arrive_expect_tx(bar + BAR_WQ, 65536);
                    for (int u = 0; u < 4; u++) w_box(3, u >> 1, u & 1, sb + SM_WQ + u * 16384, bar + BAR_WQ);
                } else {
                    mbar_arrive_expect_tx(bar + BAR_WO, 11 * 8192);
                    for (int b = 0; b < 11; b++) tma_load_2d(sb + SM_WO + b * 8192, &p.tmWo, t0 * 16 + b * 32, head * DH, bar + BAR_WO);
                    if (cta < 4)
                        asm volatile("cp.async.bulk.prefetch.tensor.3d.L2.global [%0, {%1, %2, %3}];"
                                     ::"l"(&p.tmX), "r"(0), "r"(SEG), "r"(cta * 4) : "memory");
                }
            }
        }
    }
    build_tables();
    __syncwarp();
    PSTAMP(9);
    mbar_wait(bar + BAR_WQ, 0);
    asm volatile("barrier.cluster.wait.aligned;" ::: "memory");

    rec_steps(p, wr, sb, warp, cta, head, rank);
    if (cta == 0 && tid < 4) p.arrivals[tid] = 0;
    cluster_sync();
    if (tid == 0) KEXIT(1);
}

constexpr int ATT_SLOT = 28672;
constexpr int ATT_PAIRS = 8;
constexpr int ATT_BAR = ATT_PAIRS * ATT_SLOT;
constexpr int ATT_CNT = ATT_BAR + ATT_PAIRS * 16;
constexpr int ATT_SMEM = ATT_CNT + 96 * 4;
constexpr int ATT_THREADS = ATT_PAIRS * 64 + 32;
static_assert(F_OA == F_OB + 16, "one range of flags");
struct AttnParams {
    CUtensorMap tmOa;
    CUtensorMap tmQb, tmKb;
    CUtensorMap tmOb;
    const __nv_bfloat16* qkv_tok;
    const __nv_bfloat16* kv_mem;
    uint32_t* flags;
};

__device__ __forceinline__ void tok_attn_warp(uint32_t base, int mh, int lane) {
    const uint32_t sq = base, sk = base + 8192, sv = base + 16384, skm = base + 24576, svm = skm + 2048;
    const int g = lane >> 2, c = lane & 3, mi = lane >> 3, r8 = lane & 7;
    const int ntile = mh ? 5 : 3;
    float sc[5][4];
    #pragma unroll
    for (int j = 0; j < 5; j++) { sc[j][0] = sc[j][1] = sc[j][2] = sc[j][3] = 0.f; }
    #pragma unroll
    for (int t2 = 0; t2 < 4; t2++) {
        uint32_t a[2][4];
        #pragma unroll
        for (int h = 0; h < 2; h++) {
            const int row = mh * 16 + (mi & 1) * 8 + r8, ch16 = 4 * t2 + 2 * h + (mi >> 1);
            ldsm_x4(sq + (ch16 >> 3) * 4096 + row * 128 + (((ch16 & 7) ^ r8) << 4), a[h][0], a[h][1], a[h][2], a[h][3]);
        }
        const int ch16 = 4 * t2 + mi;
        uint32_t b[5][4];
        #pragma unroll
        for (int j = 0; j < 5; j++) {
            if (j < ntile) {
                if (j == 0) ldsm_x4_t(skm + t2 * 512 + lane * 16, b[j][0], b[j][1], b[j][2], b[j][3]);
                else ldsm_x4(sk + (ch16 >> 3) * 4096 + ((j - 1) * 8 + r8) * 128 + (((ch16 & 7) ^ r8) << 4), b[j][0], b[j][1], b[j][2], b[j][3]);
            }
        }
        #pragma unroll
        for (int h = 0; h < 2; h++) {
            #pragma unroll
            for (int j = 0; j < 5; j++)
                if (j < ntile) mma16816(sc[j], a[h][0], a[h][1], a[h][2], a[h][3], b[j][2 * h], b[j][2 * h + 1]);
        }
    }
    const float sl2 = 0.08838834764831845f * 1.4426950408889634f;
    uint32_t pf[2][5];
    float inv[2];
    #pragma unroll
    for (int q = 0; q < 2; q++) {
        const int tok = mh * 16 + q * 8 + g;
        float v[10];
        #pragma unroll
        for (int j = 0; j < 5; j++) {
            #pragma unroll
            for (int e = 0; e < 2; e++) {
                const int key = (j - 1) * 8 + 2 * c + e;
                v[2 * j + e] = (j == 0 || key <= tok) ? sc[j][2 * q + e] : -INFINITY;
            }
        }
        float mx = v[0];
        #pragma unroll
        for (int j = 1; j < 10; j++) mx = fmaxf(mx, v[j]);
        mx = fmaxf(mx, __shfl_xor_sync(~0u, mx, 1));
        mx = fmaxf(mx, __shfl_xor_sync(~0u, mx, 2));
        const float mo = mx * sl2;
        float sum = 0.f;
        #pragma unroll
        for (int j = 0; j < 10; j++) { v[j] = ex2(fmaf(v[j], sl2, -mo)); sum += v[j]; }
        sum += __shfl_xor_sync(~0u, sum, 1);
        sum += __shfl_xor_sync(~0u, sum, 2);
        inv[q] = rcp(sum);
        #pragma unroll
        for (int j = 0; j < 5; j++) pf[q][j] = pack_bf16(v[2 * j], v[2 * j + 1]);
    }
    auto load_v = [&](int n4, uint32_t (&vm)[4], uint32_t (&vt)[4][4]) {
        ldsm_x4(svm + n4 * 512 + lane * 16, vm[0], vm[1], vm[2], vm[3]);
        #pragma unroll
        for (int u = 0; u < 4; u++) {
            const int dt = 2 * n4 + (u >> 1), kh = u & 1;
            const uint4 v = lds128(sv + (dt & 3) * 2048 + (dt >> 2) * 1024 + kh * 512 + lane * 16);
            vt[u & 2][2 * kh] = v.x; vt[u & 2][2 * kh + 1] = v.z;
            vt[(u & 2) + 1][2 * kh] = v.y; vt[(u & 2) + 1][2 * kh + 1] = v.w;
        }
    };
    uint32_t vm[2][4], vt[2][4][4];
    load_v(0, vm[0], vt[0]);
    #pragma unroll
    for (int n4 = 0; n4 < 4; n4++) {
        const int cur = n4 & 1;
        if (n4 + 1 < 4) load_v(n4 + 1, vm[cur ^ 1], vt[cur ^ 1]);
        float o[4][4];
        #pragma unroll
        for (int u = 0; u < 4; u++) {
            o[u][0] = o[u][1] = o[u][2] = o[u][3] = 0.f;
            mma16816(o[u], pf[0][1], pf[1][1], pf[0][2], pf[1][2], vt[cur][u][0], vt[cur][u][1]);
        }
        if (mh) {
            #pragma unroll
            for (int u = 0; u < 4; u++) mma16816(o[u], pf[0][3], pf[1][3], pf[0][4], pf[1][4], vt[cur][u][2], vt[cur][u][3]);
        }
        #pragma unroll
        for (int u = 0; u < 4; u++) mma1688(o[u], pf[0][0], pf[1][0], vm[cur][u]);
        #pragma unroll
        for (int u = 0; u < 4; u += 2) {
            const int row = mh * 16 + (mi & 1) * 8 + r8, nt = 4 * n4 + u + (mi >> 1);
            stsm_x4(sq + (nt >> 3) * 4096 + row * 128 + (((nt & 7) ^ r8) << 4),
                    pack_bf16(o[u][0] * inv[0], o[u][1] * inv[0]), pack_bf16(o[u][2] * inv[1], o[u][3] * inv[1]),
                    pack_bf16(o[u + 1][0] * inv[0], o[u + 1][1] * inv[0]), pack_bf16(o[u + 1][2] * inv[1], o[u + 1][3] * inv[1]));
        }
    }
}

__device__ __forceinline__ void b_attn_warp(uint32_t base, int hl, int idx0, int lane) {
    const uint32_t sq = base, sk = base + 8192, sv = base + 8192 + 9216;
    const int g = lane >> 2, c = lane & 3;
    auto addr = [&](uint32_t t, int row, int ch) { return t + row * 128 + ((ch ^ (row & 7)) << 4); };
    const float sl2 = 0.17677669529663687f * 1.4426950408889634f;
    #pragma unroll 2
    for (int blk = 0; blk < 4; blk++) {
        const int r0 = blk * 16;
        float sc[3][4];
        #pragma unroll
        for (int j = 0; j < 3; j++) { sc[j][0] = sc[j][1] = sc[j][2] = sc[j][3] = 0.f; }
        #pragma unroll
        for (int t = 0; t < 2; t++) {
            uint32_t a0, a1, a2, a3, b0, b1, b2, b3, d0, d1, d2, d3;
            const int mi = lane >> 3, r = lane & 7;
            ldsm_x4(addr(sq, r0 + (mi & 1) * 8 + r, hl * 4 + 2 * t + (mi >> 1)), a0, a1, a2, a3);
            ldsm_x4(addr(sk, r0 + (mi >> 1) * 8 + r, hl * 4 + 2 * t + (mi & 1)), b0, b1, b2, b3);
            ldsm_x4(addr(sk, r0 + 16 + r, hl * 4 + 2 * t + (mi & 1)), d0, d1, d2, d3);
            mma16816(sc[0], a0, a1, a2, a3, b0, b1);
            mma16816(sc[1], a0, a1, a2, a3, b2, b3);
            mma16816(sc[2], a0, a1, a2, a3, d0, d1);
        }
        uint32_t pf[2][3];
        float inv[2];
        #pragma unroll
        for (int r = 0; r < 2; r++) {
            const int u = r * 8 + g;
            float v[6];
            #pragma unroll
            for (int j = 0; j < 3; j++) {
                #pragma unroll
                for (int e = 0; e < 2; e++) {
                    const int key = j * 8 + 2 * c + e;
                    const bool ok = key > u && key <= u + 8 && idx0 + r0 - 8 + key >= 0;
                    v[2 * j + e] = ok ? sc[j][2 * r + e] : -INFINITY;
                }
            }
            float mx = fmaxf(fmaxf(fmaxf(v[0], v[1]), fmaxf(v[2], v[3])), fmaxf(v[4], v[5]));
            mx = fmaxf(mx, __shfl_xor_sync(~0u, mx, 1));
            mx = fmaxf(mx, __shfl_xor_sync(~0u, mx, 2));
            const float mo = mx * sl2;
            float sum = 0.f;
            #pragma unroll
            for (int j = 0; j < 6; j++) { v[j] = ex2(fmaf(v[j], sl2, -mo)); sum += v[j]; }
            sum += __shfl_xor_sync(~0u, sum, 1);
            sum += __shfl_xor_sync(~0u, sum, 2);
            inv[r] = rcp(sum);
            #pragma unroll
            for (int j = 0; j < 3; j++) pf[r][j] = pack_bf16(v[2 * j], v[2 * j + 1]);
        }
        uint32_t ow[4][2];
        {
            const int mi = lane >> 3, r = lane & 7;
            uint32_t vv[4][4];
            #pragma unroll
            for (int nt = 0; nt < 4; nt++)
                ldsm_x4_t(addr(sv, r0 + min(mi, 2) * 8 + r, hl * 4 + nt), vv[nt][0], vv[nt][1], vv[nt][2], vv[nt][3]);
            float o[4][4];
            #pragma unroll
            for (int nt = 0; nt < 4; nt++) {
                o[nt][0] = o[nt][1] = o[nt][2] = o[nt][3] = 0.f;
                mma16816(o[nt], pf[0][0], pf[1][0], pf[0][1], pf[1][1], vv[nt][0], vv[nt][1]);
            }
            #pragma unroll
            for (int nt = 0; nt < 4; nt++) mma1688(o[nt], pf[0][2], pf[1][2], vv[nt][2]);
            #pragma unroll
            for (int nt = 0; nt < 4; nt++) {
                ow[nt][0] = pack_bf16(o[nt][0] * inv[0], o[nt][1] * inv[0]);
                ow[nt][1] = pack_bf16(o[nt][2] * inv[1], o[nt][3] * inv[1]);
            }
        }
        #pragma unroll
        for (int u = 0; u < 4; u += 2) {
            const int mi = lane >> 3, r = lane & 7;
            stsm_x4(addr(sq, r0 + (mi & 1) * 8 + r, hl * 4 + u + (mi >> 1)), ow[u][0], ow[u][1], ow[u + 1][0], ow[u + 1][1]);
        }
    }
}

constexpr uint32_t QKVB_TARGET = 12 * 8;
constexpr uint32_t PROGRESS_TARGET = 96;
constexpr uint32_t OA_TARGET = 64, OB_TARGET = 32;
#define ATT_B0 6
constexpr int ATT_TASKS = (NSEG + 16) * 32;
__device__ __forceinline__ int att_group(int g, bool& isb) {
    const int q = g - ATT_B0;
    isb = q >= 0 && q < 48 && q % 3 == 0;
    return q < 0 ? g : q >= 48 ? g - 16 : isb ? q / 3 : ATT_B0 + (q / 3) * 2 + q % 3 - 1;
}

__global__ void __launch_bounds__(ATT_THREADS, 1) attn_kernel(const __grid_constant__ AttnParams p) {
    extern __shared__ __align__(1024) uint8_t smem_raw[];
    const int tid = threadIdx.x, lane = tid & 31, warp = __shfl_sync(~0u, tid >> 5, 0);
    const int pair = warp >> 1, wi = warp & 1;
    const uint32_t base = smem_u32(smem_raw) + pair * ATT_SLOT, bar = smem_u32(smem_raw) + ATT_BAR + pair * 16, taskw = bar + 8;
    const bool leader = wi == 0 && lane == 0;
    if (tid == 0) pdl_launch_dependents();
    KENTER(3);
    const uint32_t cnt = smem_u32(smem_raw) + ATT_CNT;
    if (tid < 96) sts32(cnt + tid * 4, 0);
    __syncthreads();
    if (warp == 2 * ATT_PAIRS) {
        for (uint32_t n = 0; n < SPIN_LIMIT; n++) {
            const bool last = lds32_volatile(cnt + 320) == 2 * ATT_PAIRS;
            uint32_t v[3];
            #pragma unroll
            for (int i = 0; i < 3; i++) {
                v[i] = 0;
                if (i * 32 + lane < 80 && lds32_volatile(cnt + (i * 32 + lane) * 4) != 0)
                    asm volatile("atom.acquire.cta.shared.exch.b32 %0, [%1], 0;" : "=r"(v[i]) : "r"(cnt + (i * 32 + lane) * 4) : "memory");
            }
            if (v[0] | v[1] | v[2]) {
                asm volatile("fence.acq_rel.gpu;" ::: "memory");
                #pragma unroll
                for (int i = 0; i < 3; i++)
                    if (v[i]) asm volatile("red.relaxed.gpu.global.add.u32 [%0], %1;" ::"l"(p.flags + F_OB + i * 32 + lane), "r"(v[i]) : "memory");
            }
            __syncwarp();
            if (last) break;
            __nanosleep(40);
        }
        if (lane == 0) KEXIT(3);
        return;
    }
    uint32_t next = 0, phase = 0;
    if (leader) {
        mbar_init(bar, 1);
        asm volatile("fence.mbarrier_init.release.cluster;" ::: "memory");
        next = atomicAdd(p.flags + F_QUEUE3, 1u);
    }
    uint32_t pending = 0;
    auto flush = [&]() {
        if (pending) {
            bulk_wait_all();
            asm volatile("red.release.cta.shared.add.u32 [%0], 1;" ::"r"(pending) : "memory");
            pending = 0;
        }
    };
    int ready_a = -1, ready_b = -1;
    while (true) {
        named_bar_sync(1 + pair, 64);
        if (leader) {
            const uint32_t task = next;
            sts32(taskw, task);
            if (task >= ATT_TASKS) {
                mbar_arrive(bar);
            } else {
                bool isb;
                const int grp = att_group(task >> 5, isb), i = task & 31;
                auto need = [&](const uint32_t* f, uint32_t target) {
                    if (ld_acquire_b32(f) < target) { flush(); wait_flag(f, target); }
                };
                if (isb) {
                    if (grp > ready_b) {
                        need(p.flags + F_QKVB + grp, QKVB_TARGET);
                        if (grp > 0) need(p.flags + F_QKVB + grp - 1, QKVB_TARGET);
                        asm volatile("fence.proxy.async.global;" ::: "memory");
                        ready_b = grp;
                    }
                    mbar_arrive_expect_tx(bar, 8192 + 2 * 9216);
                    tma_load_3d(base, &p.tmQb, (i >> 1) * 64, i & 1, grp * 64, bar);
                    tma_load_3d(base + 8192, &p.tmKb, DM + (i >> 1) * 64, i & 1, grp * 64 - 8, bar);
                    tma_load_3d(base + 8192 + 9216, &p.tmKb, 2 * DM + (i >> 1) * 64, i & 1, grp * 64 - 8, bar);
                } else {
                    if (grp > ready_a) {
                        need(p.flags + F_PROGRESS + grp, PROGRESS_TARGET);
                        asm volatile("fence.proxy.async.global;" ::: "memory");
                        ready_a = grp;
                    }
                    mbar_arrive_expect_tx(bar, ATT_SLOT);
                    #pragma unroll
                    for (int w = 0; w < 3; w++)
                        bulk_load(base + w * 8192, p.qkv_tok + (((size_t)w * NSEG + grp) * NH + i) * (SEG * DH), 8192, bar);
                    #pragma unroll
                    for (int w = 0; w < 2; w++)
                        bulk_load(base + 24576 + w * 2048, p.kv_mem + (((size_t)w * NSEG + grp) * NH + i) * (MROWS * DH), 2048, bar);
                }
                next = atomicAdd(p.flags + F_QUEUE3, 1u);
            }
        }
        if (lane == 0) flush();
        __syncwarp();
        mbar_wait_sleep(bar, phase);
        phase ^= 1;
        const uint32_t task = lds32_volatile(taskw);
        if (task >= ATT_TASKS) break;
        bool isb;
        const int grp = att_group(task >> 5, isb), i = task & 31;
        if (isb) {
            b_attn_warp(base, wi, grp * 64, lane);
            asm volatile("fence.proxy.async.shared::cta;" ::: "memory");
            named_bar_sync(1 + pair, 64);
            if (wi == 1 && lane == 0) {
                asm volatile("cp.async.bulk.tensor.3d.global.shared::cta.bulk_group [%0, {%2, %3, %4}], [%1];"
                             ::"l"(&p.tmOb), "r"(base), "r"((i >> 1) * 64), "r"(i & 1), "r"(grp * 64) : "memory");
                pending = cnt + grp * 4;
            }
        } else {
            tok_attn_warp(base, wi, lane);
            asm volatile("fence.proxy.async.shared::cta;" ::: "memory");
            __syncwarp();
            if (lane == 0) {
                #pragma unroll
                for (int h = 0; h < 2; h++) tma_store_2d(&p.tmOa, base + h * 4096 + wi * 2048, i * DH + h * 64, grp * SEG + wi * 16);
                pending = cnt + (16 + grp) * 4;
            }
        }
        if (lane == 0) { bulk_commit(); bulk_wait_read_all(); }
        __syncwarp();
    }
    if (lane == 0) asm volatile("red.release.cta.shared.add.u32 [%0], 1;" ::"r"(cnt + 320) : "memory");
}

typedef CUresult (*EncodeFn)(CUtensorMap*, CUtensorMapDataType, cuuint32_t, void*, const cuuint64_t*, const cuuint64_t*,
                             const cuuint32_t*, const cuuint32_t*, CUtensorMapInterleave, CUtensorMapSwizzle,
                             CUtensorMapL2promotion, CUtensorMapFloatOOBfill);

void make_map_2d(EncodeFn enc, CUtensorMap* m, const void* ptr, uint64_t rows, uint64_t cols, uint32_t box_rows, uint32_t box_cols = 64) {
    cuuint64_t dims[2] = {cols, rows};
    cuuint64_t strides[1] = {cols * 2};
    cuuint32_t box[2] = {box_cols, box_rows};
    cuuint32_t es[2] = {1, 1};
    enc(m, CU_TENSOR_MAP_DATA_TYPE_BFLOAT16, 2, const_cast<void*>(ptr), dims, strides, box, es,
        CU_TENSOR_MAP_INTERLEAVE_NONE, box_cols == 64 ? CU_TENSOR_MAP_SWIZZLE_128B : CU_TENSOR_MAP_SWIZZLE_64B, CU_TENSOR_MAP_L2_PROMOTION_L2_256B,
        CU_TENSOR_MAP_FLOAT_OOB_FILL_NONE);
}
void make_map_b(EncodeFn enc, CUtensorMap* m, const void* ptr, uint64_t k, uint64_t n, uint32_t nblk, uint32_t box_rows = 64) {
    cuuint64_t dims[3] = {64, k, n / 64};
    cuuint64_t strides[2] = {n * 2, 128};
    cuuint32_t box[3] = {64, box_rows, nblk};
    cuuint32_t es[3] = {1, 1, 1};
    enc(m, CU_TENSOR_MAP_DATA_TYPE_BFLOAT16, 3, const_cast<void*>(ptr), dims, strides, box, es,
        CU_TENSOR_MAP_INTERLEAVE_NONE, CU_TENSOR_MAP_SWIZZLE_128B, CU_TENSOR_MAP_L2_PROMOTION_L2_256B,
        CU_TENSOR_MAP_FLOAT_OOB_FILL_NONE);
}

void make_map_parity(EncodeFn enc, CUtensorMap* m, const void* ptr, uint64_t cols, uint32_t box_rows) {
    cuuint64_t dims[3] = {cols, 2, S_TOK / 2};
    cuuint64_t strides[2] = {cols * 2, cols * 4};
    cuuint32_t box[3] = {64, 1, box_rows};
    cuuint32_t es[3] = {1, 1, 1};
    enc(m, CU_TENSOR_MAP_DATA_TYPE_BFLOAT16, 3, const_cast<void*>(ptr), dims, strides, box, es,
        CU_TENSOR_MAP_INTERLEAVE_NONE, CU_TENSOR_MAP_SWIZZLE_128B, CU_TENSOR_MAP_L2_PROMOTION_L2_128B,
        CU_TENSOR_MAP_FLOAT_OOB_FILL_NONE);
}
void make_map_w(EncodeFn enc, CUtensorMap* m, const void* ptr) {
    cuuint64_t dims[3] = {HD, 64, DM / 64};
    cuuint64_t strides[2] = {HD * 2, 64 * HD * 2};
    cuuint32_t box[3] = {64, 16, 8};
    cuuint32_t es[3] = {1, 1, 1};
    enc(m, CU_TENSOR_MAP_DATA_TYPE_BFLOAT16, 3, const_cast<void*>(ptr), dims, strides, box, es,
        CU_TENSOR_MAP_INTERLEAVE_NONE, CU_TENSOR_MAP_SWIZZLE_128B, CU_TENSOR_MAP_L2_PROMOTION_L2_256B,
        CU_TENSOR_MAP_FLOAT_OOB_FILL_NONE);
}

#define OUTB_SIDE_BLOCKS 8
#define SIDE_ORDER 0
#define N_POST_CTAS 0
#define N_POST_ATT 0
#define SERIAL_ATT_CTAS h.n_sm
#define N_SIDE_CTAS 29
#define N_ATT_CTAS 7
#define TAIL_BLOCK0 12

struct HostState {
    bool ready;
    bool overlap;
    int n_side, n_att, n_sm;
    SideParams seq_a, seq_b;
    const void* key[11];
    RecParams rec;
    SideParams side, tail, outb;
    FinalParams fin;
    AttnParams attn;
    __nv_bfloat16 *qkv_tok, *kv_mem, *o_tok, *qkv_b, *o_b;
    uint8_t* xchg;
};
HostState g_host;

void setup(void* const* d_in, void* d_out) {
    HostState& h = g_host;
    void* fn = nullptr;
    cudaDriverEntryPointQueryResult qr;
    cudaGetDriverEntryPoint("cuTensorMapEncodeTiled", &fn, cudaEnableDefault, &qr);
    EncodeFn enc = reinterpret_cast<EncodeFn>(fn);
    void* ptr;
    cudaGetSymbolAddress(&ptr, g_qkv_tok); h.qkv_tok = (__nv_bfloat16*)ptr;
    cudaGetSymbolAddress(&ptr, g_kv_mem);  h.kv_mem = (__nv_bfloat16*)ptr;
    cudaGetSymbolAddress(&ptr, g_o_tok);   h.o_tok = (__nv_bfloat16*)ptr;
    cudaGetSymbolAddress(&ptr, g_qkv_b);   h.qkv_b = (__nv_bfloat16*)ptr;
    cudaGetSymbolAddress(&ptr, g_o_b);     h.o_b = (__nv_bfloat16*)ptr;
    cudaGetSymbolAddress(&ptr, g_xchg);    h.xchg = (uint8_t*)(((uint64_t)ptr + XCHG_BYTES - 1) & ~(uint64_t)(XCHG_BYTES - 1));
    cudaGetSymbolAddress(&ptr, g_flags);   uint32_t* flags = (uint32_t*)ptr;
    cudaGetSymbolAddress(&ptr, g_arrivals); uint32_t* arrivals = (uint32_t*)ptr;

    const void *xa = d_in[0], *mem0 = d_in[1], *wq = d_in[2], *wk = d_in[3], *wv = d_in[4], *wo = d_in[5];
    const void *xb = d_in[7], *wqkv = d_in[8], *wob = d_in[9];

    RecParams& r = h.rec;
    make_map_w(enc, &r.tmW[0], wq);
    make_map_w(enc, &r.tmW[1], wk);
    make_map_w(enc, &r.tmW[2], wv);
    make_map_2d(enc, &r.tmWo, wo, HD, DM, 128, 32);
    r.mem0 = (const __nv_bfloat16*)mem0;
    r.qkv_tok = h.qkv_tok; r.kv_mem = h.kv_mem; r.xchg = h.xchg;
    r.flags = flags; r.arrivals = arrivals; r.one[0] = r.one[1] = 1;
    make_map_b(enc, &r.tmX, xa, S_TOK, DM, 4, SEG);

    SideParams& sd = h.side;
    SideProb& p0 = sd.prob[0];
    make_map_2d(enc, &p0.tmA, xb, S_TOK, DM, BM);
    make_map_b(enc, &p0.tmB, wqkv, DM, 3 * DM, 4);
    make_map_2d(enc, &p0.tmC, h.qkv_b, S_TOK, 3 * DM, 16);
    p0.n_tiles = 3 * DM / 256; p0.k_blocks = DM / BK; p0.c_col0 = 0; p0.dep = nullptr; p0.dep_target = 0; p0.dep_n = 1; p0.sig = flags + F_QKVB;
    SideProb& p1 = sd.prob[1];
    make_map_2d(enc, &p1.tmA, h.o_tok, S_TOK, HD, BM);
    make_map_b(enc, &p1.tmB, wo, HD, DM, 4);
    make_map_2d(enc, &p1.tmC, d_out, S_TOK, 2 * DM, 16);
    p1.n_tiles = DM / 256; p1.k_blocks = HD / BK; p1.c_col0 = 0; p1.dep = flags + F_OA; p1.dep_target = OA_TARGET; p1.dep_n = 4; p1.sig = nullptr;
    SideProb& p2 = sd.prob[2];
    make_map_2d(enc, &p2.tmA, h.o_b, S_TOK, DM, BM);
    make_map_b(enc, &p2.tmB, wob, DM, DM, 4);
    p2.tmC = p1.tmC;
    p2.n_tiles = DM / 256; p2.k_blocks = DM / BK; p2.c_col0 = DM; p2.dep = flags + F_OB; p2.dep_target = OB_TARGET; p2.dep_n = 1; p2.sig = nullptr;
    p0.tmB2 = p0.tmB; p1.tmB2 = p1.tmB; p2.tmB2 = p2.tmB;
    p0.n_split = p1.n_split = p2.n_split = 1 << 20;
    p0.blocked = p1.blocked = p2.blocked = nullptr;
    if (SIDE_ORDER == 0) { sd.seg[0] = {0, 0, 16}; sd.seg[1] = {1, 0, TAIL_BLOCK0}; }
    else { sd.seg[0] = {1, 0, TAIL_BLOCK0}; sd.seg[1] = {0, 0, 16}; }
    sd.seg[2] = {2, 0, OUTB_SIDE_BLOCKS};
    sd.nseg = 3; sd.queue = flags + F_SIDEQ;
    h.outb = sd;
    h.outb.seg[0] = {2, OUTB_SIDE_BLOCKS, 16};
    h.outb.nseg = 1; h.outb.queue = flags + F_OUTBQ;

    SideParams& tl = h.tail;
    tl.prob[0] = p1;
    make_map_b(enc, &tl.prob[0].tmB, wo, HD, DM, 2);
    tl.prob[0].n_tiles = DM / 128;
    tl.prob[0].tmB2 = tl.prob[0].tmB;
    tl.prob[1] = tl.prob[2] = tl.prob[3] = tl.prob[4] = tl.prob[0];
    tl.seg[0] = {0, TAIL_BLOCK0, 15};
    tl.nseg = 1; tl.queue = flags + F_TAILQ;

    h.fin.tmA = p1.tmA; h.fin.tmB = tl.prob[0].tmB; h.fin.out = (__nv_bfloat16*)d_out;
    h.fin.dep = flags + F_OA + 60; h.fin.dep_target = OA_TARGET; h.fin.mt = 15;

    make_map_2d(enc, &h.attn.tmOa, h.o_tok, S_TOK, HD, 16);
    make_map_parity(enc, &h.attn.tmQb, h.qkv_b, 3 * DM, 64);
    make_map_parity(enc, &h.attn.tmKb, h.qkv_b, 3 * DM, 72);
    make_map_parity(enc, &h.attn.tmOb, h.o_b, DM, 64);
    h.attn.qkv_tok = h.qkv_tok; h.attn.kv_mem = h.kv_mem; h.attn.flags = flags;

    int dev = 0, nsm = 0;
    cudaGetDevice(&dev);
    cudaDeviceGetAttribute(&nsm, cudaDevAttrMultiProcessorCount, dev);
    h.n_sm = nsm;
    h.overlap = nsm - 96 >= N_SIDE_CTAS + N_ATT_CTAS;
    h.n_side = N_SIDE_CTAS; h.n_att = N_ATT_CTAS;
    h.seq_a = sd;
    h.seq_a.seg[0] = {0, 0, 16};
    h.seq_a.seg[1] = {0, 16, 16};
    h.seq_a.nseg = 2;
    h.seq_b = sd;
    h.seq_b.seg[0] = {1, 0, 16};
    h.seq_b.seg[1] = {2, 0, 16};
    h.seq_b.nseg = 2; h.seq_b.queue = flags + F_TAILQ;

    cudaFuncSetAttribute(side_gemm_kernel<256>, cudaFuncAttributeMaxDynamicSharedMemorySize, GemmCfg<256>::SMEM);
    cudaFuncSetAttribute(side_gemm_kernel<128>, cudaFuncAttributeMaxDynamicSharedMemorySize, GemmCfg<128>::SMEM);
    cudaFuncSetAttribute(final_gemm_kernel, cudaFuncAttributeMaxDynamicSharedMemorySize, FIN_SMEM);
    cudaFuncSetAttribute(rec_kernel, cudaFuncAttributeMaxDynamicSharedMemorySize, REC_SMEM);
    cudaFuncSetAttribute(attn_kernel, cudaFuncAttributeMaxDynamicSharedMemorySize, ATT_SMEM);
    for (int i = 0; i < 10; i++) h.key[i] = d_in[i];
    h.key[10] = d_out;
    h.ready = true;
}

template <typename K, typename P>
void launch(K kernel, int grid, int block, int smem, cudaStream_t st, const P& prm, int cluster, bool pdl) {
    cudaLaunchConfig_t cfg = {};
    cfg.gridDim = dim3(grid); cfg.blockDim = dim3(block); cfg.dynamicSmemBytes = smem; cfg.stream = st;
    cudaLaunchAttribute at[2];
    int n = 0;
    if (cluster > 1) {
        at[n].id = cudaLaunchAttributeClusterDimension;
        at[n].val.clusterDim.x = cluster; at[n].val.clusterDim.y = 1; at[n].val.clusterDim.z = 1;
        n++;
    }
    if (pdl) {
        at[n].id = cudaLaunchAttributeProgrammaticStreamSerialization;
        at[n].val.programmaticStreamSerializationAllowed = 1;
        n++;
    }
    cfg.attrs = at; cfg.numAttrs = n;
    cudaLaunchKernelEx(&cfg, kernel, prm);
}

}

extern "C" void kernel_launch(void* const* d_in, const int* in_sizes, int n_in, void* d_out, int out_size) {
    HostState& h = g_host;
    bool same = h.ready;
    for (int i = 0; same && i < 10; i++) same = h.key[i] == d_in[i];
    if (!same || h.key[10] != d_out) setup(d_in, d_out);
    cudaStream_t st = cudaStreamPerThread;

    launch(rec_kernel, 96, REC_THREADS, REC_SMEM, st, h.rec, 3, false);
    {
        if (!h.overlap) {
            launch(side_gemm_kernel<256>, h.n_sm, 384, GemmCfg<256>::SMEM, st, h.seq_a, 1, false);
            launch(attn_kernel, SERIAL_ATT_CTAS, ATT_THREADS, ATT_SMEM, st, h.attn, 1, false);
            launch(side_gemm_kernel<256>, h.n_sm, 384, GemmCfg<256>::SMEM, st, h.seq_b, 1, false);
            return;
        }
    }
    launch(side_gemm_kernel<256>, h.n_side, 384, GemmCfg<256>::SMEM, st, h.side, 1, true);
    launch(attn_kernel, h.n_att, ATT_THREADS, ATT_SMEM, st, h.attn, 1, true);
    if (N_POST_ATT > 0) launch(attn_kernel, N_POST_ATT, ATT_THREADS, ATT_SMEM, st, h.attn, 1, true);
    if (N_POST_CTAS > 0) launch(side_gemm_kernel<256>, N_POST_CTAS, 384, GemmCfg<256>::SMEM, st, h.side, 1, true);
    launch(side_gemm_kernel<128>, (15 - TAIL_BLOCK0) * 8, 384, GemmCfg<128>::SMEM, st, h.tail, 1, true);
    launch(final_gemm_kernel, 8 * FIN_SPLIT, 384, FIN_SMEM, st, h.fin, FIN_SPLIT, true);
    if (OUTB_SIDE_BLOCKS < 16)
        launch(side_gemm_kernel<256>, (16 - OUTB_SIDE_BLOCKS) * 4, 384, GemmCfg<256>::SMEM, st, h.outb, 1, true);
}
```

```cpp
#include <cuda_runtime.h>
#include <cuda_bf16.h>
#include <cuda.h>
#include <stdint.h>

namespace {

constexpr int S_TOK = 2048;
constexpr int DM = 1024;
constexpr int NH = 32;
constexpr int DH = 128;
constexpr int HD = NH * DH;
constexpr int NSEG = 64;
constexpr int SEG = 32;
constexpr int MROWS = 8;
constexpr uint32_t SENT = 0xFFFFFFFFu;
constexpr uint32_t SPIN_LIMIT = 1u << 24;

__device__ __align__(1024) __nv_bfloat16 g_qkv_tok[3ull * NSEG * NH * SEG * DH];
__device__ __align__(1024) __nv_bfloat16 g_kv_mem[2ull * NSEG * NH * MROWS * DH];
__device__ __align__(1024) __nv_bfloat16 g_o_tok[(size_t)S_TOK * HD];
__device__ __align__(1024) __nv_bfloat16 g_qkv_b[(size_t)S_TOK * 3 * DM];
__device__ __align__(1024) __nv_bfloat16 g_o_b[(size_t)S_TOK * DM];
__device__ __align__(1024) float g_part[32 * 128 * 128];
constexpr int PUB_BYTES = 32768;
constexpr int XCHG_SLOT = 1 << 20;
constexpr int XCHG_PUB = 0, XCHG_INBOX = 2 * PUB_BYTES;
constexpr int INBOX_MAX = 80;
constexpr int XCHG_BYTES = 2 * XCHG_SLOT;
__device__ __align__(8192) uint8_t g_xchg[2 * XCHG_BYTES];
enum { F_QUEUE3 = 3, F_QUEUE4 = 4, F_SIDEQ = 8, F_TAILQ = 16, F_OUTBQ = 24, F_PROGRESS = 32, F_QKVB = 96, F_OB = 112, F_OA = 128, F_PART = 192, F_COUNT = 224 };
__device__ uint32_t g_flags[F_COUNT];
__device__ __align__(16) uint32_t g_arrivals[4];

#define STAMP(k) do {} while (0)
#define STAMPD(k, x) do {} while (0)
#define PSTAMP(k) do {} while (0)
#define KENTER(k) do {} while (0)
#define APROF(k) do {} while (0)
#define KEXIT(k) do {} while (0)
#define KMARK(k) do {} while (0)

__device__ __forceinline__ uint32_t class_off(uint64_t a, uint32_t c) {
    return ((__popc((uint32_t)a & 0xB3000u) ^ c) & 1u) << 12;
}
__device__ __forceinline__ uint32_t smem_u32(const void* p) { return (uint32_t)__cvta_generic_to_shared(p); }
__device__ __forceinline__ uint32_t pack_bf16(float lo, float hi) {
    uint32_t r;
    asm("cvt.rn.bf16x2.f32 %0, %1, %2;" : "=r"(r) : "f"(hi), "f"(lo));
    return r;
}
__device__ __forceinline__ float ex2(float x) {
    float y;
    asm("ex2.approx.ftz.f32 %0, %1;" : "=f"(y) : "f"(x));
    return y;
}
__device__ __forceinline__ float rcp(float x) {
    float y;
    asm("rcp.approx.ftz.f32 %0, %1;" : "=f"(y) : "f"(x));
    return y;
}
__device__ __forceinline__ uint32_t clock32() {
    uint32_t t;
    asm volatile("mov.u32 %0, %%clock;" : "=r"(t));
    return t;
}
__device__ __forceinline__ void spin_clks(uint32_t n) {
    if (n == 0) return;
    const uint32_t t0 = clock32();
    while (clock32() - t0 < n) {}
}
__device__ __forceinline__ void spin_until(uint32_t t) {
    while ((int)(clock32() - t) < 0) {}
}
__device__ __forceinline__ uint32_t clock_after(uint32_t x) {
    uint32_t t;
    asm volatile("{\n.reg .pred p;\nsetp.eq.u32 p, %1, 0x12345678;\n@p exit;\nmov.u32 %0, %%clock;\n}" : "=r"(t) : "r"(x) : "memory");
    return t;
}
__device__ __forceinline__ uint32_t opaque(uint32_t x) { return __shfl_sync(~0u, x, threadIdx.x & 31); }
__device__ __forceinline__ uint32_t uniform(uint32_t x) { return __shfl_sync(~0u, x + (threadIdx.x & 31), 0); }
__device__ __forceinline__ float bf16_lo(uint32_t w) { return __uint_as_float(w << 16); }
__device__ __forceinline__ float bf16_hi(uint32_t w) { return __uint_as_float(w & 0xFFFF0000u); }

__device__ __forceinline__ void mbar_init(uint32_t bar, uint32_t cnt) {
    asm volatile("mbarrier.init.shared::cta.b64 [%0], %1;" ::"r"(bar), "r"(cnt) : "memory");
}
__device__ __forceinline__ void mbar_arrive(uint32_t bar) {
    asm volatile("mbarrier.arrive.shared::cta.b64 _, [%0];" ::"r"(bar) : "memory");
}
__device__ __forceinline__ void mbar_arrive_expect_tx(uint32_t bar, uint32_t bytes) {
    asm volatile("mbarrier.arrive.expect_tx.shared::cta.b64 _, [%0], %1;" ::"r"(bar), "r"(bytes) : "memory");
}
__device__ __forceinline__ bool mbar_try_wait(uint32_t bar, uint32_t parity) {
    uint32_t ok;
    asm volatile(
        "{\n.reg .pred p;\n"
        "mbarrier.try_wait.parity.shared::cta.b64 p, [%1], %2;\n"
        "selp.u32 %0, 1, 0, p;\n}"
        : "=r"(ok) : "r"(bar), "r"(parity) : "memory");
    return ok != 0;
}
__device__ __forceinline__ void mbar_wait(uint32_t bar, uint32_t parity) {
    uint32_t n = 0;
    while (!mbar_try_wait(bar, parity)) {
        if (++n > SPIN_LIMIT) __trap();
    }
}
__device__ __forceinline__ void mbar_wait_sleep(uint32_t bar, uint32_t parity) {
    uint32_t n = 0;
    while (!mbar_try_wait(bar, parity)) {
        __nanosleep(20);
        if (++n > SPIN_LIMIT) __trap();
    }
}
__device__ __forceinline__ void mbar_wait_bounded(uint32_t bar, uint32_t parity) {
    for (uint32_t n = 0; n < (1u << 20) && !mbar_try_wait(bar, parity); n++) {}
}
__device__ __forceinline__ bool elect_one() {
    uint32_t ok;
    asm volatile("{\n.reg .pred p;\nelect.sync _|p, 0xFFFFFFFF;\nselp.u32 %0, 1, 0, p;\n}" : "=r"(ok));
    return ok != 0;
}
__device__ __forceinline__ void named_bar_sync(int id, int nthreads) {
    asm volatile("bar.sync %0, %1;" ::"r"(id), "r"(nthreads) : "memory");
}
__device__ __forceinline__ void named_bar_arrive(int id, int nthreads) {
    asm volatile("bar.arrive %0, %1;" ::"r"(id), "r"(nthreads) : "memory");
}
__device__ __forceinline__ void cluster_sync() {
    asm volatile("barrier.cluster.arrive.release.aligned;\nbarrier.cluster.wait.acquire.aligned;" ::: "memory");
}
__device__ __forceinline__ uint32_t mapa(uint32_t addr, uint32_t rank) {
    uint32_t r;
    asm volatile("mapa.shared::cluster.u32 %0, %1, %2;" : "=r"(r) : "r"(addr), "r"(rank));
    return r;
}

__device__ __forceinline__ void tma_load_2d(uint32_t dst, const CUtensorMap* tm, int c0, int c1, uint32_t bar) {
    asm volatile(
        "cp.async.bulk.tensor.2d.shared::cluster.global.mbarrier::complete_tx::bytes [%0], [%1, {%3, %4}], [%2];"
        ::"r"(dst), "l"(tm), "r"(bar), "r"(c0), "r"(c1) : "memory");
}
__device__ __forceinline__ void tma_load_3d(uint32_t dst, const CUtensorMap* tm, int c0, int c1, int c2, uint32_t bar) {
    asm volatile(
        "cp.async.bulk.tensor.3d.shared::cluster.global.mbarrier::complete_tx::bytes [%0], [%1, {%3, %4, %5}], [%2];"
        ::"r"(dst), "l"(tm), "r"(bar), "r"(c0), "r"(c1), "r"(c2) : "memory");
}
__device__ __forceinline__ void tma_load_3d_mc(uint32_t dst, const CUtensorMap* tm, int c0, int c1, int c2, uint32_t bar, uint16_t mask) {
    asm volatile(
        "cp.async.bulk.tensor.3d.shared::cluster.global.mbarrier::complete_tx::bytes.multicast::cluster [%0], [%1, {%3, %4, %5}], [%2], %6;"
        ::"r"(dst), "l"(tm), "r"(bar), "r"(c0), "r"(c1), "r"(c2), "h"(mask) : "memory");
}
__device__ __forceinline__ void tma_store_2d(const CUtensorMap* tm, uint32_t src, int c0, int c1) {
    asm volatile("cp.async.bulk.tensor.2d.global.shared::cta.bulk_group [%0, {%2, %3}], [%1];"
                 ::"l"(tm), "r"(src), "r"(c0), "r"(c1) : "memory");
}
__device__ __forceinline__ void bulk_store(void* dst, uint32_t src, uint32_t bytes) {
    asm volatile("cp.async.bulk.global.shared::cta.bulk_group [%0], [%1], %2;" ::"l"(dst), "r"(src), "r"(bytes) : "memory");
}
__device__ __forceinline__ void bulk_commit() { asm volatile("cp.async.bulk.commit_group;" ::: "memory"); }
__device__ __forceinline__ void bulk_wait_read_all() { asm volatile("cp.async.bulk.wait_group.read 0;" ::: "memory"); }
__device__ __forceinline__ void bulk_wait_all() { asm volatile("cp.async.bulk.wait_group 0;" ::: "memory"); }
__device__ __forceinline__ void bulk_load(uint32_t dst, const void* src, uint32_t bytes, uint32_t bar) {
    asm volatile("cp.async.bulk.shared::cluster.global.mbarrier::complete_tx::bytes [%0], [%1], %2, [%3];"
                 ::"r"(dst), "l"(src), "r"(bytes), "r"(bar) : "memory");
}
__device__ __forceinline__ void bulk_load_mc(uint32_t dst, const void* src, uint32_t bytes, uint32_t bar, uint16_t mask) {
    asm volatile(
        "cp.async.bulk.shared::cluster.global.mbarrier::complete_tx::bytes.multicast::cluster [%0], [%1], %2, [%3], %4;"
        ::"r"(dst), "l"(src), "r"(bytes), "r"(bar), "h"(mask) : "memory");
}
__device__ __forceinline__ void cp_async16(uint32_t dst, const void* src) {
    asm volatile("cp.async.cg.shared.global [%0], [%1], 16;" ::"r"(dst), "l"(src) : "memory");
}
__device__ __forceinline__ void cp_async_commit() { asm volatile("cp.async.commit_group;" ::: "memory"); }
template <int N> __device__ __forceinline__ void cp_async_wait() {
    asm volatile("cp.async.wait_group %0;" ::"n"(N) : "memory");
}

__device__ __forceinline__ void ldsm_x4(uint32_t addr, uint32_t& r0, uint32_t& r1, uint32_t& r2, uint32_t& r3) {
    asm volatile("ldmatrix.sync.aligned.m8n8.x4.shared.b16 {%0,%1,%2,%3}, [%4];"
                 : "=r"(r0), "=r"(r1), "=r"(r2), "=r"(r3) : "r"(addr) : "memory");
}
__device__ __forceinline__ void ldsm_x4_t(uint32_t addr, uint32_t& r0, uint32_t& r1, uint32_t& r2, uint32_t& r3) {
    asm volatile("ldmatrix.sync.aligned.m8n8.x4.trans.shared.b16 {%0,%1,%2,%3}, [%4];"
                 : "=r"(r0), "=r"(r1), "=r"(r2), "=r"(r3) : "r"(addr) : "memory");
}
__device__ __forceinline__ void stsm_x4(uint32_t addr, uint32_t r0, uint32_t r1, uint32_t r2, uint32_t r3) {
    asm volatile("stmatrix.sync.aligned.m8n8.x4.shared.b16 [%0], {%1,%2,%3,%4};"
                 ::"r"(addr), "r"(r0), "r"(r1), "r"(r2), "r"(r3) : "memory");
}
__device__ __forceinline__ uint32_t movmat(uint32_t a) {
    uint32_t d;
    asm volatile("movmatrix.sync.aligned.m8n8.trans.b16 %0, %1;" : "=r"(d) : "r"(a));
    return d;
}
__device__ __forceinline__ void mma16816(float* d, uint32_t a0, uint32_t a1, uint32_t a2, uint32_t a3,
                                         uint32_t b0, uint32_t b1) {
    asm volatile(
        "mma.sync.aligned.m16n8k16.row.col.f32.bf16.bf16.f32 {%0,%1,%2,%3}, {%4,%5,%6,%7}, {%8,%9}, {%0,%1,%2,%3};"
        : "+f"(d[0]), "+f"(d[1]), "+f"(d[2]), "+f"(d[3])
        : "r"(a0), "r"(a1), "r"(a2), "r"(a3), "r"(b0), "r"(b1));
}
__device__ __forceinline__ void mma1688(float* d, uint32_t a0, uint32_t a1, uint32_t b0) {
    asm volatile("mma.sync.aligned.m16n8k8.row.col.f32.bf16.bf16.f32 {%0,%1,%2,%3}, {%4,%5}, {%6}, {%0,%1,%2,%3};"
                 : "+f"(d[0]), "+f"(d[1]), "+f"(d[2]), "+f"(d[3]) : "r"(a0), "r"(a1), "r"(b0));
}
__device__ __forceinline__ uint32_t any_reg() {
    uint32_t r;
    asm volatile("" : "=r"(r));
    return r;
}
__device__ __forceinline__ uint2 lds64(uint32_t addr) {
    uint2 v;
    asm volatile("ld.volatile.shared.v2.b32 {%0,%1}, [%2];" : "=r"(v.x), "=r"(v.y) : "r"(addr) : "memory");
    return v;
}
__device__ __forceinline__ uint4 lds128(uint32_t addr) {
    uint4 v;
    asm volatile("ld.volatile.shared.v4.b32 {%0,%1,%2,%3}, [%4];" : "=r"(v.x), "=r"(v.y), "=r"(v.z), "=r"(v.w) : "r"(addr) : "memory");
    return v;
}
__device__ __forceinline__ void sts32(uint32_t addr, uint32_t x) {
    asm volatile("st.volatile.shared.b32 [%0], %1;" ::"r"(addr), "r"(x) : "memory");
}
__device__ __forceinline__ void sts64(uint32_t addr, uint32_t x, uint32_t y) {
    asm volatile("st.volatile.shared.v2.b32 [%0], {%1,%2};" ::"r"(addr), "r"(x), "r"(y) : "memory");
}
__device__ __forceinline__ void sts128(uint32_t addr, uint32_t x, uint32_t y, uint32_t z, uint32_t w) {
    asm volatile("st.volatile.shared.v4.b32 [%0], {%1,%2,%3,%4};" ::"r"(addr), "r"(x), "r"(y), "r"(z), "r"(w) : "memory");
}
__device__ __forceinline__ void st_async_v2(uint32_t addr, uint32_t x, uint32_t y, uint32_t bar) {
    asm volatile("st.async.weak.shared::cluster.mbarrier::complete_tx::bytes.v2.b32 [%0], {%1,%2}, [%3];"
                 ::"r"(addr), "r"(x), "r"(y), "r"(bar) : "memory");
}
__device__ __forceinline__ uint2 ld_relaxed_v2(const void* p) {
    uint2 v;
    asm volatile("ld.relaxed.gpu.global.v2.b32 {%0,%1}, [%2];" : "=r"(v.x), "=r"(v.y) : "l"(p) : "memory");
    return v;
}
__device__ __forceinline__ void st_relaxed_v2(void* p, uint32_t x, uint32_t y) {
    asm volatile("st.relaxed.gpu.global.v2.b32 [%0], {%1,%2};" ::"l"(p), "r"(x), "r"(y) : "memory");
}
__device__ __forceinline__ void st_relaxed_v4(void* p, uint32_t x) {
    asm volatile("st.relaxed.gpu.global.v4.b32 [%0], {%1,%1,%1,%1};" ::"l"(p), "r"(x) : "memory");
}
__device__ __forceinline__ uint32_t ld_relaxed_b32(const void* p) {
    uint32_t v;
    asm volatile("ld.relaxed.gpu.global.b32 %0, [%1];" : "=r"(v) : "l"(p) : "memory");
    return v;
}
__device__ __forceinline__ uint32_t lds32_volatile(uint32_t addr) {
    uint32_t v;
    asm volatile("ld.volatile.shared.b32 %0, [%1];" : "=r"(v) : "r"(addr) : "memory");
    return v;
}
__device__ __forceinline__ void st_relaxed_b32(void* p, uint32_t x) {
    asm volatile("st.relaxed.gpu.global.b32 [%0], %1;" ::"l"(p), "r"(x) : "memory");
}

__device__ __forceinline__ uint32_t ld_acquire_b32(const void* p) {
    uint32_t v;
    asm volatile("ld.acquire.gpu.global.b32 %0, [%1];" : "=r"(v) : "l"(p) : "memory");
    return v;
}
__device__ __forceinline__ void wait_flag(const uint32_t* p, uint32_t target) {
    uint32_t n = 0;
    while (ld_acquire_b32(p) < target) {
        __nanosleep(64);
        if (++n > SPIN_LIMIT) __trap();
    }
}
__device__ __forceinline__ void signal_flag(uint32_t* p) {
    asm volatile("red.release.gpu.global.add.u32 [%0], 1;" ::"l"(p) : "memory");
}
__device__ __forceinline__ void pdl_launch_dependents() { asm volatile("griddepcontrol.launch_dependents;" ::: "memory"); }

constexpr int BM = 128, BK = 64;
constexpr int A_STAGE = BM * BK * 2;
template <int BN> struct GemmCfg {
    static constexpr int STAGES = BN == 256 ? 3 : 6;
    static constexpr int STAGE = A_STAGE + BK * BN * 2;
    static constexpr int EPI_WARP = 16 * BN * 2;
    static constexpr int SMEM = STAGES * STAGE + 8 * EPI_WARP + 1024 + 512;
};

struct SideProb {
    CUtensorMap tmA, tmB, tmC;
    int n_split;
    int n_tiles, k_blocks, c_col0;
    const uint32_t* dep;
    uint32_t dep_target;
    int dep_n;
    uint32_t* sig;
    float* part;
    uint32_t* part_flag;
};
struct SideSeg { int prob, m0, m1; };
constexpr int SIDE_MAX_SEG = 6;
struct SideParams {
    SideProb prob[3];
    SideSeg seg[SIDE_MAX_SEG];
    int nseg;
    uint32_t* queue;
};
static_assert(sizeof(SideParams) <= 4096, "kernel parameter limit");

__device__ __forceinline__ uint64_t make_desc(uint32_t addr, uint32_t lbo, uint32_t sbo) {
    return (uint64_t)((addr & 0x3FFFF) >> 4) | ((uint64_t)(lbo >> 4) << 16) | ((uint64_t)(sbo >> 4) << 32) | (1ull << 62);
}

__device__ __forceinline__ void wgmma_m64n256k16(float (&d)[128], uint64_t da, uint64_t db, int scale_d) {
    asm volatile(
        "{\n.reg .pred p;\nsetp.ne.b32 p, %130, 0;\n"
        "wgmma.mma_async.sync.aligned.m64n256k16.f32.bf16.bf16 "
        "{%0,%1,%2,%3,%4,%5,%6,%7,%8,%9,%10,%11,%12,%13,%14,%15,"
        "%16,%17,%18,%19,%20,%21,%22,%23,%24,%25,%26,%27,%28,%29,%30,%31,"
        "%32,%33,%34,%35,%36,%37,%38,%39,%40,%41,%42,%43,%44,%45,%46,%47,"
        "%48,%49,%50,%51,%52,%53,%54,%55,%56,%57,%58,%59,%60,%61,%62,%63,"
        "%64,%65,%66,%67,%68,%69,%70,%71,%72,%73,%74,%75,%76,%77,%78,%79,"
        "%80,%81,%82,%83,%84,%85,%86,%87,%88,%89,%90,%91,%92,%93,%94,%95,"
        "%96,%97,%98,%99,%100,%101,%102,%103,%104,%105,%106,%107,%108,%109,%110,%111,"
        "%112,%113,%114,%115,%116,%117,%118,%119,%120,%121,%122,%123,%124,%125,%126,%127},"
        " %128, %129, p, 1, 1, 0, 1;\n}\n"
        : "+f"(d[0]), "+f"(d[1]), "+f"(d[2]), "+f"(d[3]), "+f"(d[4]), "+f"(d[5]), "+f"(d[6]), "+f"(d[7]),
          "+f"(d[8]), "+f"(d[9]), "+f"(d[10]), "+f"(d[11]), "+f"(d[12]), "+f"(d[13]), "+f"(d[14]), "+f"(d[15]),
          "+f"(d[16]), "+f"(d[17]), "+f"(d[18]), "+f"(d[19]), "+f"(d[20]), "+f"(d[21]), "+f"(d[22]), "+f"(d[23]),
          "+f"(d[24]), "+f"(d[25]), "+f"(d[26]), "+f"(d[27]), "+f"(d[28]), "+f"(d[29]), "+f"(d[30]), "+f"(d[31]),
          "+f"(d[32]), "+f"(d[33]), "+f"(d[34]), "+f"(d[35]), "+f"(d[36]), "+f"(d[37]), "+f"(d[38]), "+f"(d[39]),
          "+f"(d[40]), "+f"(d[41]), "+f"(d[42]), "+f"(d[43]), "+f"(d[44]), "+f"(d[45]), "+f"(d[46]), "+f"(d[47]),
          "+f"(d[48]), "+f"(d[49]), "+f"(d[50]), "+f"(d[51]), "+f"(d[52]), "+f"(d[53]), "+f"(d[54]), "+f"(d[55]),
          "+f"(d[56]), "+f"(d[57]), "+f"(d[58]), "+f"(d[59]), "+f"(d[60]), "+f"(d[61]), "+f"(d[62]), "+f"(d[63]),
          "+f"(d[64]), "+f"(d[65]), "+f"(d[66]), "+f"(d[67]), "+f"(d[68]), "+f"(d[69]), "+f"(d[70]), "+f"(d[71]),
          "+f"(d[72]), "+f"(d[73]), "+f"(d[74]), "+f"(d[75]), "+f"(d[76]), "+f"(d[77]), "+f"(d[78]), "+f"(d[79]),
          "+f"(d[80]), "+f"(d[81]), "+f"(d[82]), "+f"(d[83]), "+f"(d[84]), "+f"(d[85]), "+f"(d[86]), "+f"(d[87]),
          "+f"(d[88]), "+f"(d[89]), "+f"(d[90]), "+f"(d[91]), "+f"(d[92]), "+f"(d[93]), "+f"(d[94]), "+f"(d[95]),
          "+f"(d[96]), "+f"(d[97]), "+f"(d[98]), "+f"(d[99]), "+f"(d[100]), "+f"(d[101]), "+f"(d[102]), "+f"(d[103]),
          "+f"(d[104]), "+f"(d[105]), "+f"(d[106]), "+f"(d[107]), "+f"(d[108]), "+f"(d[109]), "+f"(d[110]), "+f"(d[111]),
          "+f"(d[112]), "+f"(d[113]), "+f"(d[114]), "+f"(d[115]), "+f"(d[116]), "+f"(d[117]), "+f"(d[118]), "+f"(d[119]),
          "+f"(d[120]), "+f"(d[121]), "+f"(d[122]), "+f"(d[123]), "+f"(d[124]), "+f"(d[125]), "+f"(d[126]), "+f"(d[127])
        : "l"(da), "l"(db), "r"(scale_d));
}

__device__ __forceinline__ void wgmma_m64n128k16(float (&d)[64], uint64_t da, uint64_t db, int scale_d) {
    asm volatile(
        "{\n.reg .pred p;\nsetp.ne.b32 p, %66, 0;\n"
        "wgmma.mma_async.sync.aligned.m64n128k16.f32.bf16.bf16 "
        "{%0,%1,%2,%3,%4,%5,%6,%7,%8,%9,%10,%11,%12,%13,%14,%15,"
        "%16,%17,%18,%19,%20,%21,%22,%23,%24,%25,%26,%27,%28,%29,%30,%31,"
        "%32,%33,%34,%35,%36,%37,%38,%39,%40,%41,%42,%43,%44,%45,%46,%47,"
        "%48,%49,%50,%51,%52,%53,%54,%55,%56,%57,%58,%59,%60,%61,%62,%63},"
        " %64, %65, p, 1, 1, 0, 1;\n}\n"
        : "+f"(d[0]), "+f"(d[1]), "+f"(d[2]), "+f"(d[3]), "+f"(d[4]), "+f"(d[5]), "+f"(d[6]), "+f"(d[7]),
          "+f"(d[8]), "+f"(d[9]), "+f"(d[10]), "+f"(d[11]), "+f"(d[12]), "+f"(d[13]), "+f"(d[14]), "+f"(d[15]),
          "+f"(d[16]), "+f"(d[17]), "+f"(d[18]), "+f"(d[19]), "+f"(d[20]), "+f"(d[21]), "+f"(d[22]), "+f"(d[23]),
          "+f"(d[24]), "+f"(d[25]), "+f"(d[26]), "+f"(d[27]), "+f"(d[28]), "+f"(d[29]), "+f"(d[30]), "+f"(d[31]),
          "+f"(d[32]), "+f"(d[33]), "+f"(d[34]), "+f"(d[35]), "+f"(d[36]), "+f"(d[37]), "+f"(d[38]), "+f"(d[39]),
          "+f"(d[40]), "+f"(d[41]), "+f"(d[42]), "+f"(d[43]), "+f"(d[44]), "+f"(d[45]), "+f"(d[46]), "+f"(d[47]),
          "+f"(d[48]), "+f"(d[49]), "+f"(d[50]), "+f"(d[51]), "+f"(d[52]), "+f"(d[53]), "+f"(d[54]), "+f"(d[55]),
          "+f"(d[56]), "+f"(d[57]), "+f"(d[58]), "+f"(d[59]), "+f"(d[60]), "+f"(d[61]), "+f"(d[62]), "+f"(d[63])
        : "l"(da), "l"(db), "r"(scale_d));
}
template <int BN> struct WgmmaOp;
template <> struct WgmmaOp<256> {
    static __device__ __forceinline__ void run(float (&d)[128], uint64_t a, uint64_t b, int sc) { wgmma_m64n256k16(d, a, b, sc); }
};
template <> struct WgmmaOp<128> {
    static __device__ __forceinline__ void run(float (&d)[64], uint64_t a, uint64_t b, int sc) { wgmma_m64n128k16(d, a, b, sc); }
};

struct StoreRec {
    uint64_t dst;
    uint64_t flag;
    int kind;
    int pad;
};
struct EpiCtx { uint32_t buf, rec, st_full, st_empty; uint32_t it; int lane; };
template <int N>
__device__ __forceinline__ void epi_hand_over(const float (&acc)[N], EpiCtx& e, uint64_t dst, uint64_t flag, int kind) {
    mbar_wait(e.st_empty, (e.it & 1) ^ 1);
    const int mi = e.lane >> 3, row = (mi & 1) * 8 + (e.lane & 7);
    #pragma unroll
    for (int j = 0; j < N / 4; j += 2) {
        const int chunk = (j & 7) + (mi >> 1);
        stsm_x4(e.buf + (j >> 3) * 2048 + row * 128 + ((chunk ^ (row & 7)) << 4),
                pack_bf16(acc[4 * j], acc[4 * j + 1]), pack_bf16(acc[4 * j + 2], acc[4 * j + 3]),
                pack_bf16(acc[4 * j + 4], acc[4 * j + 5]), pack_bf16(acc[4 * j + 6], acc[4 * j + 7]));
    }
    if (e.lane == 0) {
        asm volatile("st.shared.v2.b64 [%0], {%1, %2};" ::"r"(e.rec), "l"(dst), "l"(flag) : "memory");
        asm volatile("st.shared.b32 [%0], %1;" ::"r"(e.rec + 16), "r"(kind) : "memory");
    }
    asm volatile("fence.proxy.async.shared::cta;" ::: "memory");
    __syncwarp();
    if (e.lane == 0) mbar_arrive(e.st_full);
    e.it++;
}
__device__ __forceinline__ void epi_exit(EpiCtx& e) {
    mbar_wait(e.st_empty, (e.it & 1) ^ 1);
    if (e.lane == 0) {
        asm volatile("st.shared.b32 [%0], %1;" ::"r"(e.rec + 16), "r"(-1) : "memory");
        mbar_arrive(e.st_full);
    }
}
template <int BN, bool PAIR = false>
__device__ __forceinline__ void gemm_mainloop(float (&acc)[BN / 2], int k_blocks, uint32_t sbase, uint32_t bar_base, int cw,
                                              bool elected, int& stage, uint32_t& phase, uint32_t peer = 0) {
    using C = GemmCfg<BN>;
    auto release = [&](int st) {
        const uint32_t bar = bar_base + 8 * (C::STAGES + st);
        mbar_arrive(bar);
        if (PAIR) asm volatile("mbarrier.arrive.shared::cluster.b64 _, [%0];" ::"r"(mapa(bar, peer)) : "memory");
    };
    int prev_stage = -1;
    for (int kb = 0; kb < k_blocks; kb++) {
        mbar_wait(bar_base + 8 * stage, phase);
        const uint32_t sa = sbase + stage * C::STAGE + cw * (64 * 128);
        const uint32_t sb = sbase + stage * C::STAGE + A_STAGE;
        asm volatile("wgmma.fence.sync.aligned;" ::: "memory");
        #pragma unroll
        for (int kk = 0; kk < BK / 16; kk++)
            WgmmaOp<BN>::run(acc, make_desc(sa + kk * 32, 16, 1024), make_desc(sb + kk * 2048, 8192, 1024), (kb | kk) != 0);
        asm volatile("wgmma.commit_group.sync.aligned;" ::: "memory");
        asm volatile("wgmma.wait_group.sync.aligned 1;" ::: "memory");
        if (prev_stage >= 0 && elected) release(prev_stage);
        prev_stage = stage;
        if (++stage == C::STAGES) { stage = 0; phase ^= 1; }
    }
    asm volatile("wgmma.wait_group.sync.aligned 0;" ::: "memory");
    if (elected) release(prev_stage);
}
template <int BN>
__device__ __forceinline__ void store_warp(uint32_t epi_base, uint32_t rec_base, uint32_t st_full, uint32_t st_empty, int lane,
                                           const uint8_t* tmaps, int tstride) {
    for (uint32_t it = 0;; it++) {
        mbar_wait(st_full, it & 1);
        uint64_t dst = 0, flag = 0;
        int kind = -1;
        if (lane < 8) {
            const uint32_t rec = rec_base + lane * 32;
            asm volatile("ld.volatile.shared.v2.b64 {%0, %1}, [%2];" : "=l"(dst), "=l"(flag) : "r"(rec) : "memory");
            kind = (int)lds32_volatile(rec + 16);
        }
        if (__shfl_sync(~0u, kind, 0) < 0) break;
        if (lane < 8) {
            const uint32_t buf = epi_base + lane * GemmCfg<BN>::EPI_WARP;
            #pragma unroll
            for (int q = 0; q < BN / 64; q++) {
                tma_store_2d(reinterpret_cast<const CUtensorMap*>(tmaps + (kind - 1) * tstride), buf + q * 2048,
                                  (int)(uint32_t)dst + q * 64, (int)(dst >> 32));
            }
            bulk_commit();
            bulk_wait_read_all();
            mbar_arrive(st_empty);
            if (flag) {
                bulk_wait_all();
                signal_flag(reinterpret_cast<uint32_t*>(flag));
            }
        }
        __syncwarp();
    }
    if (lane < 8) bulk_wait_all();
}

#define SCHED_AHEAD 4
template <int BN>
__global__ void __launch_bounds__(384, 1) side_gemm_kernel(const __grid_constant__ SideParams p) {
    using C = GemmCfg<BN>;
    extern __shared__ uint8_t smem_raw[];
    const uint32_t sbase = (smem_u32(smem_raw) + 1023) & ~1023u;
    const uint32_t epi_base = sbase + C::STAGES * C::STAGE;
    const uint32_t bar_base = epi_base + 8 * C::EPI_WARP;
    const uint32_t tfull = bar_base + 16 * C::STAGES, tempty = tfull + 16, tslot = tempty + 16, twant = tslot + 8;
    const uint32_t st_full = bar_base + 192, st_empty = st_full + 8, rec_base = bar_base + 256;
    const int tid = threadIdx.x, wg = tid >> 7;
    if (tid == 0) {
        for (int s = 0; s < C::STAGES; s++) { mbar_init(bar_base + 8 * s, 1); mbar_init(bar_base + 8 * (C::STAGES + s), 2); }
        for (int s = 0; s < 2; s++) { mbar_init(tfull + 8 * s, 1); mbar_init(tempty + 8 * s, 3); }
        mbar_init(twant, 1);
        mbar_init(st_full, 8);
        mbar_init(st_empty, 8);
        asm volatile("fence.mbarrier_init.release.cluster;" ::: "memory");
        pdl_launch_dependents();
    }
    __syncthreads();
    KENTER(BN == 256 ? (p.nseg == 1 ? 6 : 2) : 4);

    if (wg == 0) {
        asm volatile("setmaxnreg.dec.sync.aligned.u32 40;");
        if (tid == 0) {
            int stage = 0; uint32_t phase = 1;
            for (uint32_t it = 0;; it++) {
                mbar_wait(tfull + 8 * (it & 1), (it >> 1) & 1);
                const int code = (int)lds32_volatile(tslot + 4 * (it & 1));
                mbar_arrive(tempty + 8 * (it & 1));
                if (code < 0) break;
                const SideProb& q = p.prob[code >> 16];
                const int mt = (code >> 8) & 255, nt = code & 255;
                asm volatile("fence.proxy.async.global;" ::: "memory");
                for (int kb = 0; kb < q.k_blocks; kb++) {
                    if (kb == q.k_blocks - SCHED_AHEAD) mbar_arrive(twant);
                    mbar_wait(bar_base + 8 * (C::STAGES + stage), phase);
                    const uint32_t sa = sbase + stage * C::STAGE, fb = bar_base + 8 * stage;
                    mbar_arrive_expect_tx(fb, C::STAGE);
                    const int k0 = (nt < q.n_split ? kb : kb + q.k_blocks) * BK;
                    tma_load_2d(sa, &q.tmA, k0, mt * BM, fb);
                    tma_load_3d(sa + A_STAGE, &q.tmB, 0, k0, (nt < q.n_split ? nt : nt - q.n_split) * (BN / 64), fb);
                    if (++stage == C::STAGES) { stage = 0; phase ^= 1; }
                }
            }
        } else if (tid >= 64 && tid < 96) {
            const int lane = tid & 31;
            const SideSeg sg = p.seg[lane < p.nseg ? lane : 0];
            const SideProb& mq = p.prob[sg.prob];
            const uint32_t total = lane < p.nseg ? (sg.m1 - sg.m0) * mq.n_tiles : 0;
            for (uint32_t it = 0;; it++) {
                if (it > 0) mbar_wait_sleep(twant, (it - 1) & 1);
                int code = -1;
                for (uint32_t tries = 0;; tries++) {
                    const uint32_t head = total ? ld_relaxed_b32(p.queue + lane) : 0;
                    const uint32_t left = __ballot_sync(~0u, head < total);
                    if (!left) break;
                    bool ready = head < total;
                    if (ready && mq.dep && (left & (left - 1)))
                        ready = ld_relaxed_b32(mq.dep + (sg.m0 + head / mq.n_tiles + 1) * mq.dep_n - 1) >= mq.dep_target;
                    const uint32_t rm = __ballot_sync(~0u, ready);
                    if (rm) {
                        const int g = __ffs(rm) - 1;
                        if (lane == g) {
                            const uint32_t idx = atomicAdd(p.queue + g, 1u);
                            if (idx < total) code = (sg.prob << 16) | ((sg.m0 + idx / mq.n_tiles) << 8) | (idx % mq.n_tiles);
                        }
                        code = __shfl_sync(~0u, code, g);
                        if (code >= 0) break;
                    } else {
                        __nanosleep(200);
                    }
                    if (tries > SPIN_LIMIT) __trap();
                }
                if (code >= 0) {
                    const SideProb& q = p.prob[code >> 16];
                    if (q.dep && lane < q.dep_n) wait_flag(q.dep + ((code >> 8) & 255) * q.dep_n + lane, q.dep_target);
                    __syncwarp();
                }
                if (lane == 0) {
                    mbar_wait(tempty + 8 * (it & 1), ((it >> 1) & 1) ^ 1);
                    asm volatile("st.shared.b32 [%0], %1;" ::"r"(tslot + 4 * (it & 1)), "r"(code) : "memory");
                    mbar_arrive(tfull + 8 * (it & 1));
                }
                __syncwarp();
                if (code < 0) break;
            }
        } else if (tid >= 32 && tid < 64) {
            store_warp<BN>(epi_base, rec_base, st_full, st_empty, tid & 31, reinterpret_cast<const uint8_t*>(&p.prob[0].tmC),
                           (int)sizeof(SideProb));
        }
    } else {
        asm volatile("setmaxnreg.inc.sync.aligned.u32 232;");
        const int cw = wg - 1, lane = tid & 31, wi = (tid >> 5) & 3;
        const bool elected = (tid & 127) == 0;
        int stage = 0; uint32_t phase = 0;
        float acc[BN / 2];
        EpiCtx ectx = {epi_base + (cw * 4 + wi) * C::EPI_WARP, rec_base + (cw * 4 + wi) * 32, st_full, st_empty, 0, lane};
        for (uint32_t it = 0;; it++) {
            mbar_wait(tfull + 8 * (it & 1), (it >> 1) & 1);
            const int code = (int)lds32_volatile(tslot + 4 * (it & 1));
            named_bar_sync(1 + cw, 128);
            if (elected) mbar_arrive(tempty + 8 * (it & 1));
            if (code < 0) break;
            const SideProb& q = p.prob[code >> 16];
            const int mt = (code >> 8) & 255, nt = code & 255;
            gemm_mainloop<BN>(acc, q.k_blocks, sbase, bar_base, cw, elected, stage, phase);
            const int row0 = mt * BM + cw * 64 + wi * 16, ntc = nt < q.n_split ? nt : nt - q.n_split;
            if (BN == 128 && q.part) {
                const int idx = (mt & 3) * q.n_split + ntc;
                float4* part = reinterpret_cast<float4*>(q.part) + (size_t)idx * (BM * BN / 4) + (tid - 128);
                if (nt < q.n_split) {
                    #pragma unroll
                    for (int j = 0; j < BN / 8; j++) __stcg(part + j * 256, make_float4(acc[4 * j], acc[4 * j + 1], acc[4 * j + 2], acc[4 * j + 3]));
                    __syncwarp();
                    if (lane == 0) signal_flag(q.part_flag + idx);
                    continue;
                }
                if (lane == 0) wait_flag(q.part_flag + idx, 8);
                __syncwarp();
                #pragma unroll
                for (int j = 0; j < BN / 8; j++) {
                    const float4 v = __ldcg(part + j * 256);
                    acc[4 * j] += v.x; acc[4 * j + 1] += v.y; acc[4 * j + 2] += v.z; acc[4 * j + 3] += v.w;
                }
            }
            epi_hand_over(acc, ectx, ((uint64_t)row0 << 32) | (uint32_t)(q.c_col0 + ntc * BN), q.sig ? (uint64_t)(q.sig + mt) : 0, 1 + (code >> 16));
        }
        epi_exit(ectx);
        if (elected) KEXIT(BN == 256 ? (p.nseg == 1 ? 6 : 2) : 4);
    }
}

constexpr int FIN_SPLIT = 8, FIN_KB = HD / BK / FIN_SPLIT;
constexpr int FIN_A1 = FIN_KB * 16384;
constexpr int FIN_A0 = FIN_A1 + FIN_KB * 8192;
constexpr int FIN_BAR = FIN_A0 + 4 * 8192, FIN_SMEM = FIN_BAR + 256;
enum { FB_B = 0, FB_A1 = 64, FB_A0 = 128, FB_E0 = 160, FB_RDY = 192, FB_RED = 208 };
struct FinalParams {
    CUtensorMap tmA, tmB;
    __nv_bfloat16* out;
    const uint32_t* dep;
    uint32_t dep_target;
    int mt;
};
__global__ void __launch_bounds__(384, 1) final_gemm_kernel(const __grid_constant__ FinalParams p) {
    extern __shared__ __align__(1024) uint8_t smem_raw[];
    const uint32_t sbase = smem_u32(smem_raw), bar = sbase + FIN_BAR;
    const int tid = threadIdx.x, wg = tid >> 7;
    const int rank = blockIdx.x % FIN_SPLIT, nt = blockIdx.x / FIN_SPLIT;
    KENTER(5);
    if (tid == 0) {
        for (int s = 0; s < FIN_KB; s++) { mbar_init(bar + FB_B + 8 * s, 1); mbar_init(bar + FB_A1 + 8 * s, 1); }
        for (int s = 0; s < 4; s++) { mbar_init(bar + FB_A0 + 8 * s, 1); mbar_init(bar + FB_E0 + 8 * s, 1); }
        for (int h = 0; h < 2; h++) { mbar_init(bar + FB_RDY + 8 * h, FIN_SPLIT); mbar_init(bar + FB_RED + 8 * h, 1); }
        asm volatile("fence.mbarrier_init.release.cluster;" ::: "memory");
        for (int h = 0; h < 2; h++) mbar_arrive_expect_tx(bar + FB_RED + 8 * h, (FIN_SPLIT - 1) * 4096);
        pdl_launch_dependents();
    }
    __syncthreads();
    asm volatile("barrier.cluster.arrive.relaxed.aligned;" ::: "memory");
    if (wg == 0) {
        auto need = [&](int i) {
            uint32_t n = 0;
            while (ld_acquire_b32(p.dep + i) < p.dep_target) { if (++n > SPIN_LIMIT) __trap(); }
            asm volatile("fence.proxy.async.global;" ::: "memory");
        };
        auto a_load = [&](uint32_t dst, int kb, int seg, uint32_t mb) { tma_load_2d(dst, &p.tmA, (rank * FIN_KB + kb) * BK, p.mt * BM + seg * SEG, mb); };
        if (tid == 0) {
            for (int kb = 0; kb < FIN_KB; kb++) {
                mbar_arrive_expect_tx(bar + FB_B + 8 * kb, 16384);
                tma_load_3d(sbase + kb * 16384, &p.tmB, 0, (rank * FIN_KB + kb) * BK, nt * 2, bar + FB_B + 8 * kb);
            }
        } else if (tid == 32) {
            need(0);
            need(1);
            for (int kb = 0; kb < FIN_KB; kb++) {
                if (kb >= 4) mbar_wait(bar + FB_E0 + 8 * (kb & 3), 0);
                mbar_arrive_expect_tx(bar + FB_A0 + 8 * (kb & 3), 8192);
                for (int u = 0; u < 2; u++) a_load(sbase + FIN_A0 + (kb & 3) * 8192 + u * 4096, kb, u, bar + FB_A0 + 8 * (kb & 3));
            }
        } else if (tid == 64) {
            need(2);
            for (int kb = 0; kb < FIN_KB; kb++) {
                mbar_arrive_expect_tx(bar + FB_A1 + 8 * kb, 8192);
                a_load(sbase + FIN_A1 + kb * 8192, kb, 2, bar + FB_A1 + 8 * kb);
            }
            need(3);
            KMARK(15);
            for (int kb = 0; kb < FIN_KB; kb++) a_load(sbase + FIN_A1 + kb * 8192 + 4096, kb, 3, bar + FB_A1 + 8 * kb);
        }
        __syncwarp();
        asm volatile("barrier.cluster.wait.aligned;" ::: "memory");
    } else {
        const int h = wg - 1, lane = tid & 31, wi = (tid >> 5) & 3, t128 = tid & 127;
        asm volatile("barrier.cluster.wait.aligned;" ::: "memory");
        float acc[64];
        for (int kb = 0; kb < FIN_KB; kb++) {
            mbar_wait(bar + FB_B + 8 * kb, 0);
            if (h == 0) mbar_wait(bar + FB_A0 + 8 * (kb & 3), kb >> 2); else mbar_wait(bar + FB_A1 + 8 * kb, 0);
            const uint32_t sa = sbase + (h == 0 ? FIN_A0 + (kb & 3) * 8192 : FIN_A1 + kb * 8192), sb = sbase + kb * 16384;
            asm volatile("wgmma.fence.sync.aligned;" ::: "memory");
            #pragma unroll
            for (int kk = 0; kk < BK / 16; kk++)
                wgmma_m64n128k16(acc, make_desc(sa + kk * 32, 16, 1024), make_desc(sb + kk * 2048, 8192, 1024), (kb | kk) != 0);
            asm volatile("wgmma.commit_group.sync.aligned;" ::: "memory");
            asm volatile("wgmma.wait_group.sync.aligned 1;" ::: "memory");
            if (h == 0 && kb >= 1 && kb <= 4 && t128 == 0) mbar_arrive(bar + FB_E0 + 8 * (kb - 1));
        }
        asm volatile("wgmma.wait_group.sync.aligned 0;" ::: "memory");
        const uint32_t red = sbase + (h == 0 ? FIN_A0 : FIN_A1);
        named_bar_sync(1 + h, 128);
        if (tid == 256) KMARK(16);
        if (tid == 128) KMARK(19);
        if (t128 < FIN_SPLIT)
            asm volatile("mbarrier.arrive.relaxed.cluster.shared::cluster.b64 _, [%0];" ::"r"(mapa(bar + FB_RDY + 8 * h, t128)) : "memory");
        mbar_wait(bar + FB_RDY + 8 * h, 0);
        if (tid == 256) KMARK(17);
        #pragma unroll
        for (int q = 0; q < FIN_SPLIT; q++) {
            if (q != rank) {
                const uint32_t dst = mapa(red + (rank - (rank > q ? 1 : 0)) * 4096 + t128 * 16, q), rb = mapa(bar + FB_RED + 8 * h, q);
                #pragma unroll
                for (int j = 0; j < 2; j++)
                    asm volatile("st.async.weak.shared::cluster.mbarrier::complete_tx::bytes.v4.f32 [%0], {%1,%2,%3,%4}, [%5];"
                                 ::"r"(dst + j * 2048), "f"(acc[8 * q + 4 * j]), "f"(acc[8 * q + 4 * j + 1]),
                                   "f"(acc[8 * q + 4 * j + 2]), "f"(acc[8 * q + 4 * j + 3]), "r"(rb) : "memory");
            }
        }
        float o[8];
        #pragma unroll
        for (int q = 0; q < FIN_SPLIT; q++)
            if (q == rank) {
                #pragma unroll
                for (int e = 0; e < 8; e++) o[e] = acc[8 * q + e];
            }
        mbar_wait(bar + FB_RED + 8 * h, 0);
        if (tid == 256) KMARK(18);
        if (tid == 128) KMARK(20);
        #pragma unroll
        for (int sl = 0; sl < FIN_SPLIT - 1; sl++) {
            #pragma unroll
            for (int j = 0; j < 2; j++) {
                const uint4 v = lds128(red + sl * 4096 + j * 2048 + t128 * 16);
                o[4 * j] += __uint_as_float(v.x); o[4 * j + 1] += __uint_as_float(v.y);
                o[4 * j + 2] += __uint_as_float(v.z); o[4 * j + 3] += __uint_as_float(v.w);
            }
        }
        __nv_bfloat16* dst = p.out + (size_t)(p.mt * BM + h * 64 + wi * 16 + (lane >> 2)) * (2 * DM) + nt * 128 + rank * 16 + (lane & 3) * 2;
        #pragma unroll
        for (int j = 0; j < 2; j++) {
            *reinterpret_cast<uint32_t*>(dst + j * 8) = pack_bf16(o[4 * j], o[4 * j + 1]);
            *reinterpret_cast<uint32_t*>(dst + (size_t)8 * (2 * DM) + j * 8) = pack_bf16(o[4 * j + 2], o[4 * j + 3]);
        }
        if (t128 == 0) KEXIT(5);
    }
}

#define POLL_DELAY 4
#define FETCH_DELAY 200
#define AT_PF 6
#define AT_AHEAD 4
#define TOK_GO 12
#define PDL_POS 3
#define WO_PFA 7
#define WO_PFB_DELAY 60
#define NO_COMM 0
#define TOK_MOVED 4
#define XB_DELAY 50
#define WO_PF0 0
#define WO_PF1 11
#define WO_AHEAD 6
constexpr int REC_THREADS = 256;
constexpr uint32_t POLL_LIMIT = 1u << 16;
constexpr int NREG = 24;
__host__ __device__ constexpr int reg_idx(int j) { return ((j & 3) - 1) * 8 + (j >> 2); }
constexpr int SM_WQ = 0;
constexpr int SM_WO = 65536;
constexpr int SM_X = SM_WO + 11 * 8192;
constexpr int SM_PARK1 = SM_X;
constexpr int SM_MEM = SM_X + 4 * 4096;
constexpr int SM_RED = SM_X + 8 * 4096;
constexpr int SM_V = SM_X + 12 * 4096;
constexpr int SM_K = SM_X + 14 * 4096;
constexpr int SM_QS = SM_X + 15 * 4096;
constexpr int SM_QK = SM_X + 65536;
constexpr int SM_SP = SM_QK + 2048;
constexpr int SM_VM = SM_SP + 2560;
constexpr int SM_O = SM_VM + 2048;
constexpr int SM_PARK0 = SM_QK;
constexpr int SM_SUM = SM_O + 2048;
constexpr int SM_TBL = SM_SUM + 128;
constexpr int SM_BAR = SM_TBL + 512;
constexpr int SM_STAMP = SM_BAR + 192;
constexpr int REC_SMEM = SM_STAMP;
static_assert(REC_SMEM <= 232448, "shared memory");
enum { BAR_V = 0, BAR_X = 8, BAR_P0 = 16, BAR_WQ = 40, BAR_WO = 48, BAR_XG = 56, BAR_F0 = 88, BAR_F3 = 96, BAR_VF = 104,
       BAR_M = 112, BAR_GO = 144, BAR_PK = 152, BAR_OUT = 168, BAR_VM = 160, BAR_SELF = 176, BAR_MIN = 184 };

template <int V> struct IntC { static constexpr int value = V; };
template <int I, int N, typename F> __device__ __forceinline__ void sfor(F&& f) {
    if constexpr (I < N) { f(IntC<I>{}); sfor<I + 1, N>(f); }
}

struct RecParams {
    CUtensorMap tmW[3];
    CUtensorMap tmWo;
    CUtensorMap tmX;
    const __nv_bfloat16* mem0;
    __nv_bfloat16* qkv_tok;
    __nv_bfloat16* kv_mem;
    uint8_t* xchg;
    uint32_t* flags;
    uint32_t one[2];
    uint32_t* arrivals;
};

__device__ __forceinline__ void mma_a(float* d, const uint32_t* a, uint32_t b0, uint32_t b1) {
    mma16816(d, a[0], a[1], a[2], a[3], b0, b1);
}
__device__ __forceinline__ void ldsm4(uint32_t addr, uint32_t* r) { ldsm_x4(addr, r[0], r[1], r[2], r[3]); }
__device__ __forceinline__ void ldsm4t(uint32_t addr, uint32_t* r) { ldsm_x4_t(addr, r[0], r[1], r[2], r[3]); }
template <int OFF> __device__ __forceinline__ void poll_v2(uint2& v, const uint8_t* p) {
    asm volatile("ld.relaxed.gpu.global.v2.b32 {%0,%1}, [%2+%3];" : "=r"(v.x), "=r"(v.y) : "l"(p), "n"(OFF) : "memory");
}
__device__ __forceinline__ uint32_t max3(uint32_t a, uint32_t b, uint32_t c) { return max(max(a, b), c); }
__device__ __forceinline__ uint32_t pub_slot(int s) { return (s & 1) * XCHG_SLOT + ((s >> 1) & 1) * PUB_BYTES; }

__device__ __forceinline__ uint8_t* xaddr(uint32_t lo, uint32_t hi) {
    uint64_t a;
    asm("mov.b64 %0, {%1, %2};" : "=l"(a) : "r"(lo), "r"(hi));
    return reinterpret_cast<uint8_t*>(a);
}
template <int N> __device__ __forceinline__ uint32_t delay_zero(uint32_t a) {
    uint32_t x = a;
    #pragma unroll
    for (int i = 0; i < N; i++) x = lds32_volatile(x);
    return x - a;
}
__device__ __forceinline__ uint32_t fresh(uint32_t x) { asm volatile("" : "+r"(x)); return x; }

template <int NT> __device__ __forceinline__ uint32_t wo_addr(uint32_t ao, uint32_t a3, int n) {
    return (n % NT == 2 ? a3 : ao + (n % NT) * 32768) + (n / NT) * 1024;
}
template <int NT, int PF>
__device__ __forceinline__ void wo_phase(uint32_t (&st)[8 * NT][4], uint32_t ao, uint32_t a3, uint32_t l16, uint32_t tbl, uint32_t sums,
                                         uint32_t slot, uint32_t xhi, uint32_t third) {
    constexpr int AHEAD = PF > WO_AHEAD ? PF - NT : WO_AHEAD;
    uint32_t of[4][4], pl[3];
    float i0, i1;
    ldsm4t(l16 + SM_O, of[0]);
    #pragma unroll
    for (int n = PF; n < AHEAD; n++) ldsm4t(wo_addr<NT>(ao, a3, n), st[n]);
    float acc[NT][4];
    #pragma unroll
    for (int i = 0; i < NT; i++) { acc[i][0] = acc[i][1] = acc[i][2] = acc[i][3] = 0.f; }
    #pragma unroll
    for (int kk = 0; kk < 8; kk++) {
        if ((kk & 1) == 0 && kk + 2 < 8) ldsm4t(l16 + SM_O + ((kk >> 1) + 1) * 512, of[(kk >> 1) + 1]);
        if (kk == 4) {
            const uint32_t x = fresh(l16);
            const uint4 sa = lds128(sums + ((x << 1) & 0x60)), sc = lds128(sums + ((x << 1) & 0x60) + 16);
            i0 = rcp((__uint_as_float(sa.x) + __uint_as_float(sa.y)) + (__uint_as_float(sa.z) + __uint_as_float(sa.w)));
            i1 = rcp((__uint_as_float(sc.x) + __uint_as_float(sc.y)) + (__uint_as_float(sc.z) + __uint_as_float(sc.w)));
            const uint4 t = lds128(tbl + ((x >> 3) & 0x30));
            const uint32_t d = slot + ((x >> 1) & 0x38);
            pl[0] = t.x + d; pl[1] = t.y + d; pl[2] = t.z + d;
            __syncwarp();
        }
        #pragma unroll
        for (int i = 0; i < NT; i++) {
            const int n = kk * NT + i;
            mma_a(acc[i], st[n], of[kk >> 1][(kk & 1) * 2], of[kk >> 1][(kk & 1) * 2 + 1]);
            if (n + AHEAD >= PF && n + AHEAD < 8 * NT) ldsm4t(wo_addr<NT>(ao, a3, n + AHEAD), st[n + AHEAD]);
        }
    }
    #pragma unroll
    for (int i = 0; i < NT; i++)
        asm volatile("{\n.reg .pred p;\nsetp.ne.u32 p, %3, 0;\n@p st.relaxed.gpu.global.v2.b32 [%0], {%1,%2};\n}"
                     ::"l"(xaddr(pl[i], xhi)), "r"(pack_bf16(acc[i][0] * i0, acc[i][1] * i1)), "r"(pack_bf16(acc[i][2] * i0, acc[i][3] * i1)),
                       "r"(i < 2 ? 1u : third) : "memory");
}

constexpr uint32_t SMEM_ORIGIN = 1024;
constexpr uint64_t DESC_BASE = (1ull << 16) | (0x40000040ull << 32);
template <int OFFB, int SCALE_D>
__device__ __forceinline__ void wgmma_n32_rs(float (&d)[16], const uint32_t* a, uint32_t one) {
    asm volatile(
        "{\n.reg .b64 db;\nmad.wide.u32 db, %20, %21, %22;\n"
        "wgmma.mma_async.sync.aligned.m64n32k16.f32.bf16.bf16 {%0,%1,%2,%3,%4,%5,%6,%7,%8,%9,%10,%11,%12,%13,%14,%15}, "
        "{%16,%17,%18,%19}, db, %23, 1, 1, 0;\n}"
        : "+f"(d[0]), "+f"(d[1]), "+f"(d[2]), "+f"(d[3]), "+f"(d[4]), "+f"(d[5]), "+f"(d[6]), "+f"(d[7]),
          "+f"(d[8]), "+f"(d[9]), "+f"(d[10]), "+f"(d[11]), "+f"(d[12]), "+f"(d[13]), "+f"(d[14]), "+f"(d[15])
        : "r"(a[0]), "r"(a[1]), "r"(a[2]), "r"(a[3]), "r"(one), "n"((SMEM_ORIGIN + OFFB) >> 4), "l"(DESC_BASE), "n"(SCALE_D));
}
template <int OFFA, int OFFB, int SCALE_D>
__device__ __forceinline__ void wgmma_n32_ss(float (&d)[16], uint32_t one) {
    asm volatile(
        "{\n.reg .b64 da, db;\nmad.wide.u32 da, %16, %17, %19;\nmad.wide.u32 db, %16, %18, %19;\n"
        "wgmma.mma_async.sync.aligned.m64n32k16.f32.bf16.bf16 {%0,%1,%2,%3,%4,%5,%6,%7,%8,%9,%10,%11,%12,%13,%14,%15}, "
        "da, db, %20, 1, 1, 1, 0;\n}"
        : "+f"(d[0]), "+f"(d[1]), "+f"(d[2]), "+f"(d[3]), "+f"(d[4]), "+f"(d[5]), "+f"(d[6]), "+f"(d[7]),
          "+f"(d[8]), "+f"(d[9]), "+f"(d[10]), "+f"(d[11]), "+f"(d[12]), "+f"(d[13]), "+f"(d[14]), "+f"(d[15])
        : "r"(one), "n"((SMEM_ORIGIN + OFFA) >> 4), "n"((SMEM_ORIGIN + OFFB) >> 4), "l"(DESC_BASE), "n"(SCALE_D));
}
template <int WG, int J0, int J1, int I0, int I1, bool ACC, bool FENCE = true>
__device__ __forceinline__ void token_mma(float (&ta)[2][16], const uint32_t (&wr)[NREG][2][4], uint32_t one) {
    if (FENCE) asm volatile("wgmma.fence.sync.aligned;" ::: "memory");
    sfor<J0, J1>([&](auto J) {
        constexpr int j = J.value, offb = SM_X + WG * 32768 + (j >> 2) * 4096 + (j & 3) * 32, sc = (ACC || j != J0) ? 1 : 0;
        sfor<I0, I1>([&](auto I) {
            constexpr int i = I.value;
            if constexpr ((j & 3) != 0) wgmma_n32_rs<offb, sc>(ta[i], wr[reg_idx(j)][i], one);
            else if constexpr (WG == 0 || (j >> 2) >= TOK_MOVED) wgmma_n32_ss<SM_WQ + WG * 32768 + i * 16384 + (j >> 2) * 2048, offb, sc>(ta[i], one);
            constexpr int c = (j >> 2) - (8 - TOK_MOVED);
            if constexpr (WG == 0 && (j & 3) == 2 && c >= 0)
                wgmma_n32_ss<SM_WQ + 32768 + (1 - i) * 16384 + c * 2048, SM_X + 32768 + c * 4096, 1>(ta[i], one);
        });
    });
    asm volatile("wgmma.commit_group.sync.aligned;" ::: "memory");
}
__device__ __forceinline__ void warp_arrive(uint32_t bar) {
    __syncwarp();
    if (elect_one()) mbar_arrive(bar);
}
__device__ __forceinline__ void remote_arrive(uint32_t bar, uint32_t rank) {
    asm volatile("mbarrier.arrive.relaxed.cluster.shared::cluster.b64 _, [%0];" ::"r"(mapa(bar, rank)) : "memory");
}
__device__ __forceinline__ void x_load(const RecParams& p, uint32_t sb, int sg, int g) {
    tma_load_3d_mc(sb + SM_X + g * 16384, &p.tmX, 0, sg * SEG, g * 4, sb + SM_BAR + BAR_XG + 8 * g, (uint16_t)7);
}

__device__ __forceinline__ void rec_steps(const RecParams& p, const uint32_t (&wr)[NREG][2][4], const uint32_t sb, const int warp,
                                          const int cta, const int head, const int rank) {
    const int wq = warp & 3, wg = warp >> 2;
    const uint32_t bar = sb + SM_BAR;
    const uint32_t xhi = (uint32_t)((uint64_t)p.xchg >> 32);
    const float sl2 = 0.08838834764831845f * 1.4426950408889634f;
    const bool has_unit = warp >= 5 && (warp < 7 || cta < 64);
    const bool qk = rank < 2;
    const uint32_t pa = rank == 2 ? 0 : rank + 1, pb = rank == 0 ? 2 : rank - 1;
    const uint32_t tbl = sb + SM_TBL + warp * 64;
    const bool att = (warp & 6) == 2;
    const int stile = warp < 5 ? warp : warp - 3;

    const uint32_t u_st = uniform(SM_QK - SM_WQ - wg * (32768 - 1024)), u_stmask = uniform(wg == 0 ? 0x30 : 0);
    const uint32_t u_key = uniform(!qk || att || warp == 7 ? 0 : sb + (warp == 4 ? SM_QK + 1024 : SM_K + stile * 1024));
    const uint32_t u_bx = uniform(bar + (qk ? BAR_X : BAR_VM)), u_bra = uniform(mapa(u_bx, pa)), u_brb = uniform(mapa(u_bx, pb));
    const uint32_t u_src = uniform(lds32_volatile(tbl + 44));
    const uint32_t u_kv = uniform(qk && wg == 0 ? ~0u : (((rank >> 1) * NSEG * NH + head) * 8 + (qk ? rank * 4 + wq : warp)) * 64);
    const uint32_t u_free = uniform(warp == 5 ? mapa(bar + BAR_VF, 2) : warp == 6 ? mapa(bar + BAR_F0, 0) : 0);
    const uint32_t u_role = uniform((has_unit ? 1 : 0) | (att ? 2 : 0) | (warp != 1 || rank == 0 ? 4 : 0) | (!qk && warp == 0 ? 8 : 0) | (rank != 0 && warp == 1 ? 16 : 0));
    uint32_t l16, xa, aq, ao;
    {
        const int lane = threadIdx.x & 31, mi = lane >> 3, r8 = lane & 7, r16 = (mi >> 1) * 8 + r8;
        l16 = opaque(sb + lane * 16);
        xa = opaque(sb + lane * 8 + (qk ? SM_SP + rank * 1280 + stile * 256 : SM_VM + warp * 256));
        aq = opaque(sb + SM_WQ + wg * 32768 + r16 * 128 + (((wq * 2 + (mi & 1)) ^ r8) << 4));
        ao = opaque(sb + SM_WO + (warp >> 1) * 8192 + r16 * 64 + ((((warp & 1) * 2 + (mi & 1)) ^ ((r8 >> 1) & 3)) << 4));
    }

    uint32_t mphase = 0;
    #pragma unroll 1
    for (int s = 0; s < NSEG; s++) {
        const uint32_t par = s & 1;
        uint32_t at[16][4];
        auto at_early = [](int i) { return i < 2 || ((i & 1) == 0 && (i >> 1) <= AT_PF - 2); };
        auto at_prefetch = [&](int i0, int i1) {
            #pragma unroll
            for (int i = i0; i < i1; i++)
                if (at_early(i)) ldsm4t(aq + (i & 1) * 16384 + (i >> 1) * 2048, at[i]);
        };
        if (wg == 0) {
            float ta[2][16];
            mbar_wait_bounded(bar + BAR_XG, par);
            STAMP(6);
            auto park = [&](int i, uint32_t dst) {
                #pragma unroll
                for (int e = 0; e < 16; e++) asm volatile("" : "+f"(ta[i][e]));
                #pragma unroll
                for (int j = 0; j < 4; j++)
                    sts128(l16 + dst + j * 2048 + wq * 512, __float_as_uint(ta[i][4 * j]), __float_as_uint(ta[i][4 * j + 1]),
                           __float_as_uint(ta[i][4 * j + 2]), __float_as_uint(ta[i][4 * j + 3]));
            };
            token_mma<0, 0, 16, 0, 1, false>(ta, wr, 1);
            mbar_wait_bounded(bar + BAR_XG + 8, par);
            if (TOK_MOVED > 0) mbar_wait_bounded(bar + BAR_XG + 16, par);
            token_mma<0, 16, 32, 0, 1, true>(ta, wr, p.one[0]);
            token_mma<0, 0, TOK_GO, 1, 2, false, false>(ta, wr, p.one[1]);
            token_mma<0, TOK_GO, 32, 1, 2, true, false>(ta, wr, p.one[1]);
            if (TOK_MOVED == 0) mbar_wait_bounded(bar + BAR_XG + 16, par);
            asm volatile("wgmma.wait_group.sync.aligned 1;" ::: "memory");
            park(0, SM_PARK0);
            warp_arrive(bar + BAR_GO);
            asm volatile("wgmma.wait_group.sync.aligned 0;" ::: "memory");
            named_bar_sync(10, 128);
            park(1, SM_PARK1);
            mbar_wait_bounded(bar + BAR_XG + 24, par);
            warp_arrive(bar + BAR_PK);
            const uint8_t* src = xaddr(u_src + pub_slot(s), xhi);
            auto fetch = [&]() {
                if (elect_one()) {
                    mbar_arrive_expect_tx(bar + BAR_M + 8 * wq, 4096);
                    bulk_load(sb + SM_MEM + wq * 4096, src, 4096, bar + BAR_M + 8 * wq);
                }
            };
            named_bar_sync(7, REC_THREADS - 32);
            spin_clks(FETCH_DELAY);
            fetch();
            STAMP(12);
            if (warp == 0 && elect_one()) {
                if (qk) mbar_arrive_expect_tx(bar + BAR_V, 8192);
                mbar_arrive_expect_tx(bar + BAR_X, qk ? 1280 : 2560);
                mbar_arrive_expect_tx(bar + BAR_VM, qk ? 2048 : 0);
            }
            at_prefetch(0, 16);
            const uint32_t x = fresh(l16) - sb;
            const uint32_t ca = sb + SM_MEM + wq * 4096 + x * 2 + ((x >> 4) & 0x1C);
            #pragma unroll 1
            for (uint32_t n = 0; n < POLL_LIMIT; n++) {
                mbar_wait_bounded(bar + BAR_M + 8 * wq, mphase);
                mphase ^= 1;
                const uint32_t c0 = lds32_volatile(ca), c1 = lds32_volatile(ca + 1024), c2 = lds32_volatile(ca + 2048), c3 = lds32_volatile(ca + 3072);
                if (!__any_sync(~0u, max(max3(c0, c1, c2), c3) == (NO_COMM ? 0x12345u : SENT))) break;
                fetch();
            }
            STAMP(0);
            named_bar_sync(0, REC_THREADS);
        } else {
            at_prefetch(0, 5);
            if (s > 0) {
                if (u_role & 1) {
                    const uint32_t ln = (fresh(l16) >> 4) & 31;
                    const uint32_t ibl = lds32_volatile(tbl + 12) + (par ^ 1) * XCHG_SLOT + ln * 8;
                    const uint32_t publ = lds32_volatile(tbl + 28) + pub_slot(s) + (ln & 16) * 256 + (ln & 8) * 16 + (ln & 7) * 4;
                    const bool odd = ln & 8;
                    const uint8_t* ib = xaddr(ibl + delay_zero<POLL_DELAY>(bar + BAR_SELF), xhi);
                    STAMP(8);
                    uint2 v[8];
                    #pragma unroll 1
                    for (uint32_t n = 0; n < POLL_LIMIT; n++) {
                        sfor<0, 8>([&](auto I) { poll_v2<I.value * 256>(v[I.value], ib); });
                        const uint32_t mx = max(max3(v[0].y, v[1].y, v[2].y), max3(max3(v[3].y, v[4].y, v[5].y), v[6].y, v[7].y));
                        if (!__any_sync(~0u, mx == (NO_COMM ? 0x12345u : SENT))) break;
                    }
                    float a0 = ((bf16_lo(v[0].x) + bf16_lo(v[1].x)) + (bf16_lo(v[2].x) + bf16_lo(v[3].x))) +
                               ((bf16_lo(v[4].x) + bf16_lo(v[5].x)) + (bf16_lo(v[6].x) + bf16_lo(v[7].x)));
                    float a1 = ((bf16_hi(v[0].x) + bf16_hi(v[1].x)) + (bf16_hi(v[2].x) + bf16_hi(v[3].x))) +
                               ((bf16_hi(v[4].x) + bf16_hi(v[5].x)) + (bf16_hi(v[6].x) + bf16_hi(v[7].x)));
                    float a2 = ((bf16_lo(v[0].y) + bf16_lo(v[1].y)) + (bf16_lo(v[2].y) + bf16_lo(v[3].y))) +
                               ((bf16_lo(v[4].y) + bf16_lo(v[5].y)) + (bf16_lo(v[6].y) + bf16_lo(v[7].y)));
                    float a3 = ((bf16_hi(v[0].y) + bf16_hi(v[1].y)) + (bf16_hi(v[2].y) + bf16_hi(v[3].y))) +
                               ((bf16_hi(v[4].y) + bf16_hi(v[5].y)) + (bf16_hi(v[6].y) + bf16_hi(v[7].y)));
                    float k0 = odd ? a2 : a0, k1 = odd ? a3 : a1;
                    k0 += __shfl_xor_sync(~0u, odd ? a0 : a2, 8);
                    k1 += __shfl_xor_sync(~0u, odd ? a1 : a3, 8);
                    k0 += __shfl_xor_sync(~0u, k0, 16);
                    k1 += __shfl_xor_sync(~0u, k1, 16);
                    st_relaxed_b32(xaddr(publ, xhi), pack_bf16(k0, k1));
                    STAMP(11);
                } else if (warp == 4) {
                    bulk_wait_read_all();
                    if (elect_one()) remote_arrive(bar + BAR_F3, 2);
                    if (!qk) {
                        mbar_wait_bounded(bar + BAR_F3, par ^ 1);
                        if (elect_one()) x_load(p, sb, s, 3);
                    }
                    if (elect_one()) {
                        bulk_wait_all();
                        signal_flag(p.flags + F_PROGRESS + s - 1);
                    }
                    __syncwarp();
                    STAMP(10);
                }
            }
            float ta[2][16];
            uint32_t w[8];
            auto unpark = [&](int i, uint32_t src) {
                mbar_wait_bounded(bar + (i ? BAR_GO : BAR_PK), par);
                #pragma unroll
                for (int j = 0; j < 4; j++) {
                    const uint4 v = lds128(l16 + src + j * 2048 + wq * 512);
                    ta[i][4 * j] = __uint_as_float(v.x); ta[i][4 * j + 1] = __uint_as_float(v.y);
                    ta[i][4 * j + 2] = __uint_as_float(v.z); ta[i][4 * j + 3] = __uint_as_float(v.w);
                }
            };
            if (warp != 4) named_bar_arrive(7, REC_THREADS - 32);
            unpark(1, SM_PARK0);
            STAMP(6);
            token_mma<1, 0, 16, 1, 2, true>(ta, wr, 1);
            unpark(0, SM_PARK1);
            token_mma<1, 16, 32, 1, 2, true>(ta, wr, 1);
            token_mma<1, 16, 32, 0, 1, true>(ta, wr, 1);
            token_mma<1, 0, 16, 0, 1, true, false>(ta, wr, 1);
            auto put_tile = [&](int m, const uint32_t (&q)[8]) {
                #pragma unroll
                for (int h = 0; h < 2; h++) {
                    if (qk) asm volatile("stmatrix.sync.aligned.m8n8.x4.trans.shared.b16 [%0], {%1,%2,%3,%4};"
                                         ::"r"(aq - (SM_WQ + 32768) + (m ? SM_K : SM_QS) + h * 2048), "r"(q[4 * h]), "r"(q[4 * h + 1]),
                                           "r"(q[4 * h + 2]), "r"(q[4 * h + 3]) : "memory");
                    else sts128(l16 + SM_V + wq * 2048 + m * 1024 + h * 512, q[4 * h], q[4 * h + 1], q[4 * h + 2], q[4 * h + 3]);
                }
            };
            auto pack_tile = [&](int i) {
                #pragma unroll
                for (int e = 0; e < 16; e++) asm volatile("" : "+f"(ta[i][e]));
                #pragma unroll
                for (int j = 0; j < 8; j++) w[j] = pack_bf16(ta[i][2 * j], ta[i][2 * j + 1]);
            };
            asm volatile("wgmma.wait_group.sync.aligned 2;" ::: "memory");
            pack_tile(1);
            at_prefetch(5, 16);
            asm volatile("wgmma.wait_group.sync.aligned 1;" ::: "memory");
            if (elect_one()) mbar_arrive(bar + BAR_OUT);
            mbar_wait_bounded(bar + BAR_OUT, par);
            if (u_free != 0 && elect_one())
                asm volatile("mbarrier.arrive.relaxed.cluster.shared::cluster.b64 _, [%0];" ::"r"(u_free) : "memory");
            put_tile(0, w);
            asm volatile("wgmma.wait_group.sync.aligned 0;" ::: "memory");
            pack_tile(0);
            put_tile(1, w);
            STAMP(0);
            named_bar_sync(0, REC_THREADS);
            if (!qk) {
                asm volatile("fence.proxy.async.shared::cta;" ::: "memory");
                mbar_wait_bounded(bar + BAR_VF, par);
                __syncwarp();
                if (elect_one()) {
                    #pragma unroll
                    for (int r = 0; r < 2; r++)
                        asm volatile("cp.async.bulk.shared::cluster.shared::cta.mbarrier::complete_tx::bytes [%0], [%1], %2, [%3];"
                                     ::"r"(mapa(sb + SM_V + wq * 2048, r)), "r"(sb + SM_V + wq * 2048), "r"(2048), "r"(mapa(bar + BAR_V, r)) : "memory");
                }
            }
            STAMP(14);
        }
        const uint32_t mb = l16 + SM_MEM + wg * 8192;
        float acc[2][2][4];
        {
            uint32_t b[2][4];
            ldsm4t(mb, b[0]);
            ldsm4t(mb + 512, b[1]);
            #pragma unroll
            for (int i = 0; i < AT_AHEAD; i++)
                if (!at_early(i)) ldsm4t(aq + (i & 1) * 16384 + (i >> 1) * 2048, at[i]);
            STAMPD(1, b[0][0]);
            #pragma unroll
            for (int i = 0; i < 4; i++) { for (int e = 0; e < 4; e++) acc[i >> 1][i & 1][e] = 0.f; }
            #pragma unroll
            for (int u = 0; u < 16; u++) {
                #pragma unroll
                for (int h = 0; h < 2; h++) {
                    const int j = 2 * u + h;
                    #pragma unroll
                    for (int m = 0; m < 2; m++) {
                        if ((j & 3) == 0) mma_a(acc[h][m], at[(j >> 2) * 2 + m], b[u & 1][2 * h], b[u & 1][2 * h + 1]);
                        else mma_a(acc[h][m], wr[reg_idx(j)][m], b[u & 1][2 * h], b[u & 1][2 * h + 1]);
                    }
                }
                if (u + 2 < 16) ldsm4t(mb + (u + 2) * 512, b[u & 1]);
                if (u + AT_AHEAD < 16 && !at_early(u + AT_AHEAD))
                    ldsm4t(aq + ((u + AT_AHEAD) & 1) * 16384 + ((u + AT_AHEAD) >> 1) * 2048, at[u + AT_AHEAD]);
            }
        }
        sts128(l16 + SM_RED + warp * 512, __float_as_uint(acc[0][1][0] + acc[1][1][0]), __float_as_uint(acc[0][1][1] + acc[1][1][1]),
               __float_as_uint(acc[0][1][2] + acc[1][1][2]), __float_as_uint(acc[0][1][3] + acc[1][1][3]));
        #pragma unroll
        for (int e = 0; e < 4; e++) acc[0][0][e] += acc[1][0][e];
        const uint32_t x16 = fresh(l16);
        const uint32_t ast = (fresh(aq) + u_st) ^ ((((x16 >> 7) ^ wq) & 1) * u_stmask);
        const uint32_t sa = fresh((x16 & 0x70) * 8 + ((((x16 >> 3) & 0x30) ^ x16) & 0x70)), sa2 = fresh(sa ^ 64);
        const uint32_t xra = __byte_perm(xa, u_bra, 0x7210), xrb = __byte_perm(xa, u_brb, 0x7210);
        STAMP(2);
        named_bar_sync(1 + wq, 64);
        uint32_t p0, p1;
        {
            const uint4 v = lds128(l16 + SM_RED + (warp ^ 4) * 512);
            p0 = pack_bf16(acc[0][0][0] + __uint_as_float(v.x), acc[0][0][1] + __uint_as_float(v.y));
            p1 = pack_bf16(acc[0][0][2] + __uint_as_float(v.z), acc[0][0][3] + __uint_as_float(v.w));
        }
        auto send = [&](uint32_t y0, uint32_t y1) {
            st_async_v2(xra, y0, y1, u_bra);
            st_async_v2(xrb, y0, y1, u_brb);
            sts64(xa, y0, y1);
            warp_arrive(u_bx);
        };
        if (qk) {
            asm volatile("stmatrix.sync.aligned.m8n8.x2.trans.shared.b16 [%0], {%1,%2};" ::"r"(ast), "r"(p0), "r"(p1) : "memory");
            named_bar_sync(5, REC_THREADS);
            if (u_key != 0) {
                uint32_t qa[2][4], kf[2][4];
                ldsm4(sa + sb + SM_QK, qa[0]);
                ldsm4(sa + u_key, kf[0]);
                ldsm4(sa2 + sb + SM_QK, qa[1]);
                ldsm4(sa2 + u_key, kf[1]);
                float se[4] = {0.f, 0.f, 0.f, 0.f}, so[4] = {0.f, 0.f, 0.f, 0.f};
                #pragma unroll
                for (int u = 0; u < 2; u++) {
                    mma_a(se, qa[u], kf[u][0], kf[u][1]);
                    mma_a(so, qa[u], kf[u][2], kf[u][3]);
                }
                send(__float_as_uint(se[0] + so[2]), __float_as_uint(se[1] + so[3]));
            }
        } else {
            send(p0, p1);
        }
        STAMP(3);
        const uint32_t lane = (fresh(l16) >> 4) & 31;
        if (u_kv != ~0u) {
            uint32_t* dst = reinterpret_cast<uint32_t*>(p.kv_mem) + (u_kv + s * (NH * 512) + lane);
            dst[0] = p0;
            dst[32] = p1;
        }
        auto tile_stores = [&]() {
            if (wg == 1) {
                asm volatile("fence.proxy.async.shared::cta;" ::: "memory");
                if (warp != 4) {
                    named_bar_arrive(14, 128);
                } else {
                    named_bar_sync(14, 128);
                    if (elect_one()) {
                        __nv_bfloat16* dst = p.qkv_tok + ((size_t)s * NH + head) * (SEG * DH);
                        constexpr size_t MAT = (size_t)NSEG * NH * SEG * DH;
                        bulk_store(dst + (qk ? rank * (SEG * 64) : 2 * MAT), sb + (qk ? SM_QS : SM_V), 4096);
                        bulk_store(dst + (qk ? MAT + rank * (SEG * 64) : 2 * MAT + SEG * 64), sb + (qk ? SM_K : SM_V + 4096), 4096);
                        bulk_commit();
                    }
                    __syncwarp();
                }
            }
        };
        if (s == NSEG - 1) { tile_stores(); break; }
        if (s == 0) mbar_wait_bounded(bar + BAR_WO, 0);
        const uint32_t slot = par * XCHG_SLOT;
        if (u_role & 2) {
            if (qk) mbar_wait_bounded(bar + BAR_V, par);
            uint32_t vt[2][4][4];
            #pragma unroll
            for (int i = 0; i < 8; i++) {
                const uint4 v = lds128(l16 + SM_V + (warp & 1) * 1024 + (i & 3) * 2048 + (i >> 2) * 512);
                vt[i >> 2][i & 3][0] = v.x; vt[i >> 2][i & 3][1] = v.y; vt[i >> 2][i & 3][2] = v.z; vt[i >> 2][i & 3][3] = v.w;
            }
            const uint32_t l8 = sb + lane * 8;
            mbar_wait_bounded(bar + BAR_X, par);
            STAMP(4);
            float sv[10];
            #pragma unroll
            for (int j = 0; j < 5; j++) {
                const uint2 a = lds64(l8 + SM_SP + j * 256), b = lds64(l8 + SM_SP + 1280 + j * 256);
                sv[2 * j] = __uint_as_float(a.x) + __uint_as_float(b.x);
                sv[2 * j + 1] = __uint_as_float(a.y) + __uint_as_float(b.y);
            }
            float mx = fmaxf(fmaxf(fmaxf(sv[0], sv[1]), fmaxf(sv[2], sv[3])), fmaxf(fmaxf(sv[4], sv[5]), fmaxf(sv[6], sv[7])));
            mx = fmaxf(mx, fmaxf(sv[8], sv[9]));
            const float m1 = __shfl_xor_sync(~0u, mx, 1), m2 = __shfl_xor_sync(~0u, mx, 2), m3 = __shfl_xor_sync(~0u, mx, 3);
            const bool vm_ok = mbar_try_wait(bar + BAR_VM, par);
            mx = fmaxf(fmaxf(mx, m1), fmaxf(m2, m3));
            const float mo = mx * sl2;
            #pragma unroll
            for (int j = 0; j < 10; j++) sv[j] = ex2(fmaf(sv[j], sl2, -mo));
            const uint32_t e0 = pack_bf16(sv[0], sv[1]), e1 = pack_bf16(sv[2], sv[3]);
            const uint32_t e2 = pack_bf16(sv[4], sv[5]), e3 = pack_bf16(sv[6], sv[7]), em = pack_bf16(sv[8], sv[9]);
            float o[4][4];
            #pragma unroll
            for (int i = 0; i < 4; i++) {
                o[i][0] = o[i][1] = o[i][2] = o[i][3] = 0.f;
                mma_a(o[i], vt[0][i], e0, e1);
            }
            sts32(sb + SM_SUM + lane * 4,
                  __float_as_uint((((sv[0] + sv[1]) + (sv[2] + sv[3])) + ((sv[4] + sv[5]) + (sv[6] + sv[7]))) + (sv[8] + sv[9])));
            if (!vm_ok) mbar_wait_bounded(bar + BAR_VM, par);
            uint2 vm[4];
            #pragma unroll
            for (int i = 0; i < 4; i++) {
                vm[i] = lds64(l8 + SM_VM + (warp & 1) * 1024 + i * 256);
                mma_a(o[i], vt[1][i], e2, e3);
            }
            #pragma unroll
            for (int i = 0; i < 4; i++) mma1688(o[i], vm[i].x, vm[i].y, em);
            #pragma unroll
            for (int i = 0; i < 4; i += 2)
                stsm_x4(l16 + SM_O + (warp & 1) * 1024 + i * 256, pack_bf16(o[i][0], o[i][1]), pack_bf16(o[i][2], o[i][3]),
                        pack_bf16(o[i + 1][0], o[i + 1][1]), pack_bf16(o[i + 1][2], o[i + 1][3]));
            STAMP(5);
            uint32_t st[16][4];
            #pragma unroll
            for (int n = 0; n < WO_PF0; n++) ldsm4t(wo_addr<2>(ao, 0, n), st[n]);
            named_bar_sync(6, REC_THREADS);
            wo_phase<2, WO_PF0>(st, ao, 0, l16, tbl, sb + SM_SUM, slot, xhi, 0);
        } else {
            const uint32_t a3 = fresh(ao) + (wg == 0 ? 10 : 6) * 8192;
            uint32_t st[24][4];
            #pragma unroll
            for (int n = 0; n < WO_PFA; n++) ldsm4t(wo_addr<3>(ao, a3, n), st[n]);
            tile_stores();
            if (u_role & 1) {
                uint8_t* ib = xaddr(lds32_volatile(tbl + 12) + (par ^ 1) * XCHG_SLOT + lane * 16, xhi);
                #pragma unroll
                for (int i = 0; i < 4; i++) st_relaxed_v4(ib + i * 512, SENT);
                st_relaxed_b32(xaddr(lds32_volatile(tbl + 28) + pub_slot(s + 3) + (lane & 16) * 256 + (lane & 8) * 16 + (lane & 7) * 4, xhi), SENT);
            }
            if (warp == 1) {
                if (elect_one()) {
                    #pragma unroll
                    for (int g = 0; g < 4; g++) mbar_arrive_expect_tx(bar + BAR_XG + 8 * g, 16384);
                }
                if (s + 2 < NSEG && cta < 4 && elect_one())
                    asm volatile("cp.async.bulk.prefetch.tensor.3d.L2.global [%0, {%1, %2, %3}];"
                                 ::"l"(&p.tmX), "r"(0), "r"((s + 2) * SEG), "r"(cta * 4) : "memory");
                if (rank == 0) {
                    mbar_wait_bounded(bar + BAR_F0, par);
                    if (elect_one()) x_load(p, sb, s + 1, 0);
                }
            }
            if (WO_PFA < WO_PF1 || (u_role & 16)) mbar_wait_bounded(bar + BAR_X, par);
            if (WO_PFA < WO_PF1) {
                spin_clks(WO_PFB_DELAY);
                #pragma unroll
                for (int n = WO_PFA; n < WO_PF1; n++) ldsm4t(wo_addr<3>(ao, a3, n), st[n]);
            }
            if (u_role & 16) {
                spin_clks(XB_DELAY);
                mbar_wait_bounded(bar + BAR_VM, par);
                if (elect_one()) x_load(p, sb, s + 1, rank);
            }
            named_bar_sync(6, REC_THREADS);
            wo_phase<3, WO_PF1>(st, ao, a3, l16, tbl, sb + SM_SUM, slot, xhi, u_role & 4);
        }
        STAMP(7);
        if (wg == 0) named_bar_sync(9, REC_THREADS); else named_bar_arrive(9, REC_THREADS);
    }
    if (threadIdx.x == 128) KMARK(8);
    mbar_wait(bar + BAR_X, 1);
    mbar_wait(bar + BAR_VM, 1);
    if (qk) mbar_wait(bar + BAR_V, 1);
    named_bar_sync(0, REC_THREADS);
    if (warp == 4 && elect_one()) {
        bulk_wait_all();
        signal_flag(p.flags + F_PROGRESS + NSEG - 1);
        KMARK(9);
    }
}

__global__ void __launch_bounds__(REC_THREADS, 1) rec_kernel(const __grid_constant__ RecParams p) {
    extern __shared__ __align__(1024) uint8_t smem_raw[];
    const uint32_t sb = smem_u32(smem_raw);
    const int tid = threadIdx.x, lane = tid & 31;
    const int warp = __shfl_sync(~0u, tid >> 5, 0);
    const int cta = blockIdx.x, head = cta / 3, rank = cta % 3;
    const int wg = warp >> 2, wq = warp & 3;
    const int t0 = (rank * 64 + 2) / 3;
    const uint32_t bar = sb + SM_BAR;
    uint8_t* const xb = p.xchg;
    const uint32_t xlo = (uint32_t)(uint64_t)xb;
    if ((sb & 0x3FFFF) != SMEM_ORIGIN) __trap();
    KENTER(1);
    auto w_box = [&](int part, int g, int i, uint32_t dst, uint32_t mb) {
        const int m = i ^ g;
        const CUtensorMap* tm = &p.tmW[rank == 2 ? 2 : m];
        const int col = head * DH + (rank == 2 ? m : rank) * 64, row = ((part + 1) & 3) * 16;
        tma_load_3d(dst, tm, col, row, g * 8, mb);
    };
    if (tid == 0) {
        mbar_init(bar + BAR_V, 1);
        for (int i = 0; i < 4; i++) { mbar_init(bar + BAR_XG + 8 * i, 1); mbar_init(bar + BAR_M + 8 * i, 1); }
        mbar_init(bar + BAR_GO, 4);
        mbar_init(bar + BAR_PK, 4);
        mbar_init(bar + BAR_OUT, 4);
        mbar_init(bar + BAR_VM, rank < 2 ? 1 : 9);
        mbar_init(bar + BAR_F0, 3);
        mbar_init(bar + BAR_F3, 3);
        mbar_init(bar + BAR_VF, 3);
        sts64(bar + BAR_MIN, ~0u, ~0u);
        mbar_init(bar + BAR_X, rank < 2 ? 6 : 1);
        for (int i = 0; i < 3; i++) mbar_init(bar + BAR_P0 + 8 * i, 1);
        mbar_init(bar + BAR_WQ, 1);
        mbar_init(bar + BAR_WO, 1);
        sts32(bar + BAR_SELF, bar + BAR_SELF);
        asm volatile("fence.mbarrier_init.release.cluster;" ::: "memory");
    }
    auto build_tables = [&]() {
        uint32_t av = 0;
        for (uint32_t n = 0; !__all_sync(~0u, (av >> 24) == 24); n++) {
            av = ld_acquire_b32(p.arrivals + (lane & 3));
            if (n > SPIN_LIMIT) __trap();
        }
        uint32_t cm[3];
        #pragma unroll
        for (int i = 0; i < 3; i++) {
            const int o = i * 32 + lane;
            cm[i] = __ballot_sync(~0u, (__shfl_sync(~0u, av, o / 24) >> (o % 24)) & 1);
        }
        auto color_of = [&](int o) { return ((o < 32 ? cm[0] : o < 64 ? cm[1] : cm[2]) >> (o & 31)) & 1u; };
        auto inbox = [&](int o, int byte) {
            uint32_t c = color_of(o);
            int ones = 0;
            #pragma unroll
            for (int i = 0; i < 3; i++) ones += __popc(o >= i * 32 + 32 ? cm[i] : (o > i * 32 ? cm[i] & ((1u << (o - i * 32)) - 1) : 0u));
            int idx = c ? ones : o - ones;
            if (idx >= INBOX_MAX) { idx = 2 * INBOX_MAX - 1 - idx; c ^= 1; }
            const uint32_t lin = idx * 6144 + byte, q = XCHG_INBOX + (lin >> 12) * 8192;
            return q + class_off(xlo + q, c) + (lin & 4095);
        };
        uint32_t off = 0;
        const int grp = (warp + 3) & 3;
        if (lane < 12) {
            const int i = lane >> 2, lt0 = rank == 0 ? 0 : (rank == 1 ? 6 : 11);
            const int o = i < 2 ? rank * 32 + warp * 4 + (lane & 3) : (lt0 + ((warp + 4) & 7)) * 4 + (lane & 3);
            off = inbox(min(o, 95), i * 2048 + head * 64);
        } else if (lane == 12) {
            off = inbox(cta, (grp % 3) * 2048);
        } else if (lane == 13) {
            int T;
            if (grp < 2) {
                T = ((cta >> 5) * 64 + 2) / 3 + 8 * grp + ((cta & 31) >> 2);
            } else {
                const int tl = (cta & 63) >> 2;
                T = tl < 6 ? 16 + tl : (tl < 11 ? 22 + 16 + (tl - 6) : 43 + 16 + (tl - 11));
            }
            off = XCHG_PUB + (T >> 4) * 8192 + (T & 15) * 256 + (cta & 3) * 32;
        } else if (lane == 14) {
            const uint32_t q = XCHG_PUB + wq * 8192;
            off = q + class_off(xlo + q, color_of(cta));
        }
        if (lane < 16) asm volatile("st.shared.b32 [%0], %1;" ::"r"(sb + SM_TBL + warp * 64 + (lane & 3) * 16 + (lane >> 2) * 4), "r"(xlo + off) : "memory");
    };
    if (cta == 0 && tid < F_COUNT) p.flags[tid] = 0;
    __syncthreads();
    asm volatile("barrier.cluster.arrive.relaxed.aligned;" ::: "memory");
    uint4 img = make_uint4(SENT, SENT, SENT, SENT);
    if (cta >= 92) {
        const unsigned short* m = reinterpret_cast<const unsigned short*>(p.mem0) + (cta - 92) * 256 + tid;
        uint32_t w[4];
        #pragma unroll
        for (int i = 0; i < 4; i++) w[i] = (uint32_t)__ldg(m + 2 * i * DM) | ((uint32_t)__ldg(m + (2 * i + 1) * DM) << 16);
        img = make_uint4(w[0], w[1], w[2], w[3]);
    }
    {
        constexpr int NPAIR = (XCHG_SLOT + PUB_BYTES) / 8192;
        uint8_t* pr = xb + (4 + cta) * 8192;
        const uint32_t c0 = class_off(xlo + (4 + cta) * 8192, 0);
        #pragma unroll
        for (int c = 0; c < 2; c++) {
            const bool timed = lane == 0 || (lane == 8 && c == (warp & 1));
            reinterpret_cast<uint4*>(pr + (c0 ^ (c << 12)))[tid] = make_uint4(timed ? 0u : SENT, SENT, SENT, SENT);
        }
        __syncwarp();
        if (lane == 0) {
            uint32_t x = 0;
            for (int k = 0; k < 3; k++) {
                const uint32_t c = (k + warp) & 1, t0 = clock_after(x);
                x = atomicExch(reinterpret_cast<uint32_t*>(pr + (c0 ^ (c << 12)) + warp * 512 + (k >> 1) * 128 + x), SENT);
                const uint32_t lat = clock_after(x) - t0;
                asm volatile("red.shared.min.u32 [%0], %1;" ::"r"(bar + BAR_MIN + 4 * c), "r"(lat) : "memory");
            }
        }
        __syncwarp();
        if (cta >= 92 || 100 + cta < NPAIR) {
            if (cta >= 92) {
                if (img.x == SENT) img.x = 0x7FFF7FFFu;
                if (img.y == SENT) img.y = 0x7FFF7FFFu;
                if (img.z == SENT) img.z = 0x7FFF7FFFu;
                if (img.w == SENT) img.w = 0x7FFF7FFFu;
            }
            uint8_t* q = xb + (cta >= 92 ? cta - 92 : 100 + cta) * 8192;
            reinterpret_cast<uint4*>(q)[tid] = img;
            reinterpret_cast<uint4*>(q + 4096)[tid] = img;
        }
    }
    __syncthreads();
    PSTAMP(4);
    auto stage = [](int part) { return ((part + 2) % 3) * 65536; };
    if (tid == 0) {
        for (int part = 0; part < 3; part++) {
            mbar_arrive_expect_tx(bar + BAR_P0 + 8 * part, 65536);
            for (int u = 0; u < 4; u++) w_box(part, u >> 1, u & 1, sb + stage(part) + u * 16384, bar + BAR_P0 + 8 * part);
        }
    }
    if (tid == 224) {
        const uint32_t c = lds32_volatile(bar + BAR_MIN) > lds32_volatile(bar + BAR_MIN + 4) ? 1 : 0;
        asm volatile("red.release.gpu.global.add.u32 [%0], %1;" ::"l"(p.arrivals + cta / 24), "r"((1u << 24) | (c << (cta % 24))) : "memory");
        if (PDL_POS == 0) pdl_launch_dependents();
    }
    uint32_t wr[NREG][2][4];
    {
        const int mi = lane >> 3, r8 = lane & 7;
        const uint32_t a0 = sb + wg * 32768 + ((mi >> 1) * 8 + r8) * 128 + (((wq * 2 + (mi & 1)) ^ r8) << 4);
        #pragma unroll
        for (int part = 0; part < 3; part++) {
            mbar_wait(bar + BAR_P0 + 8 * part, 0);
            #pragma unroll
            for (int j = 0; j < 8; j++) {
                #pragma unroll
                for (int i = 0; i < 2; i++) ldsm4t(a0 + stage(part) + i * 16384 + j * 2048, wr[part * 8 + j][i]);
            }
            asm volatile("fence.proxy.async.shared::cta;" ::: "memory");
            __syncthreads();
            PSTAMP(5 + part);
            if (tid == 224 && PDL_POS == part + 1) pdl_launch_dependents();
            if (tid == 0) {
                if (part == 0) {
                    for (int g = 0; g < 4; g++) {
                        mbar_arrive_expect_tx(bar + BAR_XG + 8 * g, 16384);
                        tma_load_3d(sb + SM_X + g * 16384, &p.tmX, 0, 0, g * 4, bar + BAR_XG + 8 * g);
                    }
                } else if (part == 1) {
                    mbar_arrive_expect_tx(bar + BAR_WQ, 65536);
                    for (int u = 0; u < 4; u++) w_box(3, u >> 1, u & 1, sb + SM_WQ + u * 16384, bar + BAR_WQ);
                } else {
                    mbar_arrive_expect_tx(bar + BAR_WO, 11 * 8192);
                    for (int b = 0; b < 11; b++) tma_load_2d(sb + SM_WO + b * 8192, &p.tmWo, t0 * 16 + b * 32, head * DH, bar + BAR_WO);
                    if (cta < 4)
                        asm volatile("cp.async.bulk.prefetch.tensor.3d.L2.global [%0, {%1, %2, %3}];"
                                     ::"l"(&p.tmX), "r"(0), "r"(SEG), "r"(cta * 4) : "memory");
                }
            }
        }
    }
    build_tables();
    __syncwarp();
    PSTAMP(9);
    mbar_wait(bar + BAR_WQ, 0);
    asm volatile("barrier.cluster.wait.aligned;" ::: "memory");

    rec_steps(p, wr, sb, warp, cta, head, rank);
    if (cta == 0 && tid < 4) p.arrivals[tid] = 0;
    cluster_sync();
    if (tid == 0) KEXIT(1);
}

constexpr int ATT_SLOT = 28672;
constexpr int ATT_PAIRS = 8;
constexpr int ATT_BAR = ATT_PAIRS * ATT_SLOT;
constexpr int ATT_CNT = ATT_BAR + ATT_PAIRS * 16;
constexpr int ATT_SMEM = ATT_CNT + 96 * 4;
constexpr int ATT_THREADS = ATT_PAIRS * 64 + 32;
static_assert(F_OA == F_OB + 16, "one range of flags");
struct AttnParams {
    CUtensorMap tmOa;
    CUtensorMap tmQb, tmKb;
    CUtensorMap tmOb;
    const __nv_bfloat16* qkv_tok;
    const __nv_bfloat16* kv_mem;
    uint32_t* flags;
};

__device__ __forceinline__ void tok_attn_warp(uint32_t base, int mh, int lane) {
    const uint32_t sq = base, sk = base + 8192, sv = base + 16384, skm = base + 24576, svm = skm + 2048;
    const int g = lane >> 2, c = lane & 3, mi = lane >> 3, r8 = lane & 7;
    const int ntile = mh ? 5 : 3;
    float sc[5][4];
    #pragma unroll
    for (int j = 0; j < 5; j++) { sc[j][0] = sc[j][1] = sc[j][2] = sc[j][3] = 0.f; }
    #pragma unroll
    for (int t2 = 0; t2 < 4; t2++) {
        uint32_t a[2][4];
        #pragma unroll
        for (int h = 0; h < 2; h++) {
            const int row = mh * 16 + (mi & 1) * 8 + r8, ch16 = 4 * t2 + 2 * h + (mi >> 1);
            ldsm_x4(sq + (ch16 >> 3) * 4096 + row * 128 + (((ch16 & 7) ^ r8) << 4), a[h][0], a[h][1], a[h][2], a[h][3]);
        }
        const int ch16 = 4 * t2 + mi;
        uint32_t b[5][4];
        #pragma unroll
        for (int j = 0; j < 5; j++) {
            if (j < ntile) {
                if (j == 0) ldsm_x4_t(skm + t2 * 512 + lane * 16, b[j][0], b[j][1], b[j][2], b[j][3]);
                else ldsm_x4(sk + (ch16 >> 3) * 4096 + ((j - 1) * 8 + r8) * 128 + (((ch16 & 7) ^ r8) << 4), b[j][0], b[j][1], b[j][2], b[j][3]);
            }
        }
        #pragma unroll
        for (int h = 0; h < 2; h++) {
            #pragma unroll
            for (int j = 0; j < 5; j++)
                if (j < ntile) mma16816(sc[j], a[h][0], a[h][1], a[h][2], a[h][3], b[j][2 * h], b[j][2 * h + 1]);
        }
    }
    const float sl2 = 0.08838834764831845f * 1.4426950408889634f;
    uint32_t pf[2][5];
    float inv[2];
    #pragma unroll
    for (int q = 0; q < 2; q++) {
        const int tok = mh * 16 + q * 8 + g;
        float v[10];
        #pragma unroll
        for (int j = 0; j < 5; j++) {
            #pragma unroll
            for (int e = 0; e < 2; e++) {
                const int key = (j - 1) * 8 + 2 * c + e;
                v[2 * j + e] = (j == 0 || key <= tok) ? sc[j][2 * q + e] : -INFINITY;
            }
        }
        float mx = v[0];
        #pragma unroll
        for (int j = 1; j < 10; j++) mx = fmaxf(mx, v[j]);
        mx = fmaxf(mx, __shfl_xor_sync(~0u, mx, 1));
        mx = fmaxf(mx, __shfl_xor_sync(~0u, mx, 2));
        const float mo = mx * sl2;
        float sum = 0.f;
        #pragma unroll
        for (int j = 0; j < 10; j++) { v[j] = ex2(fmaf(v[j], sl2, -mo)); sum += v[j]; }
        sum += __shfl_xor_sync(~0u, sum, 1);
        sum += __shfl_xor_sync(~0u, sum, 2);
        inv[q] = rcp(sum);
        #pragma unroll
        for (int j = 0; j < 5; j++) pf[q][j] = pack_bf16(v[2 * j], v[2 * j + 1]);
    }
    auto load_v = [&](int n4, uint32_t (&vm)[4], uint32_t (&vt)[4][4]) {
        ldsm_x4(svm + n4 * 512 + lane * 16, vm[0], vm[1], vm[2], vm[3]);
        #pragma unroll
        for (int u = 0; u < 4; u++) {
            const int dt = 2 * n4 + (u >> 1), kh = u & 1;
            const uint4 v = lds128(sv + (dt & 3) * 2048 + (dt >> 2) * 1024 + kh * 512 + lane * 16);
            vt[u & 2][2 * kh] = v.x; vt[u & 2][2 * kh + 1] = v.z;
            vt[(u & 2) + 1][2 * kh] = v.y; vt[(u & 2) + 1][2 * kh + 1] = v.w;
        }
    };
    uint32_t vm[2][4], vt[2][4][4];
    load_v(0, vm[0], vt[0]);
    #pragma unroll
    for (int n4 = 0; n4 < 4; n4++) {
        const int cur = n4 & 1;
        if (n4 + 1 < 4) load_v(n4 + 1, vm[cur ^ 1], vt[cur ^ 1]);
        float o[4][4];
        #pragma unroll
        for (int u = 0; u < 4; u++) {
            o[u][0] = o[u][1] = o[u][2] = o[u][3] = 0.f;
            mma16816(o[u], pf[0][1], pf[1][1], pf[0][2], pf[1][2], vt[cur][u][0], vt[cur][u][1]);
        }
        if (mh) {
            #pragma unroll
            for (int u = 0; u < 4; u++) mma16816(o[u], pf[0][3], pf[1][3], pf[0][4], pf[1][4], vt[cur][u][2], vt[cur][u][3]);
        }
        #pragma unroll
        for (int u = 0; u < 4; u++) mma1688(o[u], pf[0][0], pf[1][0], vm[cur][u]);
        #pragma unroll
        for (int u = 0; u < 4; u += 2) {
            const int row = mh * 16 + (mi & 1) * 8 + r8, nt = 4 * n4 + u + (mi >> 1);
            stsm_x4(sq + (nt >> 3) * 4096 + row * 128 + (((nt & 7) ^ r8) << 4),
                    pack_bf16(o[u][0] * inv[0], o[u][1] * inv[0]), pack_bf16(o[u][2] * inv[1], o[u][3] * inv[1]),
                    pack_bf16(o[u + 1][0] * inv[0], o[u + 1][1] * inv[0]), pack_bf16(o[u + 1][2] * inv[1], o[u + 1][3] * inv[1]));
        }
    }
}

__device__ __forceinline__ void b_attn_warp(uint32_t base, int hl, int idx0, int lane) {
    const uint32_t sq = base, sk = base + 8192, sv = base + 8192 + 9216;
    const int g = lane >> 2, c = lane & 3;
    auto addr = [&](uint32_t t, int row, int ch) { return t + row * 128 + ((ch ^ (row & 7)) << 4); };
    const float sl2 = 0.17677669529663687f * 1.4426950408889634f;
    #pragma unroll 2
    for (int blk = 0; blk < 4; blk++) {
        const int r0 = blk * 16;
        float sc[3][4];
        #pragma unroll
        for (int j = 0; j < 3; j++) { sc[j][0] = sc[j][1] = sc[j][2] = sc[j][3] = 0.f; }
        #pragma unroll
        for (int t = 0; t < 2; t++) {
            uint32_t a0, a1, a2, a3, b0, b1, b2, b3, d0, d1, d2, d3;
            const int mi = lane >> 3, r = lane & 7;
            ldsm_x4(addr(sq, r0 + (mi & 1) * 8 + r, hl * 4 + 2 * t + (mi >> 1)), a0, a1, a2, a3);
            ldsm_x4(addr(sk, r0 + (mi >> 1) * 8 + r, hl * 4 + 2 * t + (mi & 1)), b0, b1, b2, b3);
            ldsm_x4(addr(sk, r0 + 16 + r, hl * 4 + 2 * t + (mi & 1)), d0, d1, d2, d3);
            mma16816(sc[0], a0, a1, a2, a3, b0, b1);
            mma16816(sc[1], a0, a1, a2, a3, b2, b3);
            mma16816(sc[2], a0, a1, a2, a3, d0, d1);
        }
        uint32_t pf[2][3];
        float inv[2];
        #pragma unroll
        for (int r = 0; r < 2; r++) {
            const int u = r * 8 + g;
            float v[6];
            #pragma unroll
            for (int j = 0; j < 3; j++) {
                #pragma unroll
                for (int e = 0; e < 2; e++) {
                    const int key = j * 8 + 2 * c + e;
                    const bool ok = key > u && key <= u + 8 && idx0 + r0 - 8 + key >= 0;
                    v[2 * j + e] = ok ? sc[j][2 * r + e] : -INFINITY;
                }
            }
            float mx = fmaxf(fmaxf(fmaxf(v[0], v[1]), fmaxf(v[2], v[3])), fmaxf(v[4], v[5]));
            mx = fmaxf(mx, __shfl_xor_sync(~0u, mx, 1));
            mx = fmaxf(mx, __shfl_xor_sync(~0u, mx, 2));
            const float mo = mx * sl2;
            float sum = 0.f;
            #pragma unroll
            for (int j = 0; j < 6; j++) { v[j] = ex2(fmaf(v[j], sl2, -mo)); sum += v[j]; }
            sum += __shfl_xor_sync(~0u, sum, 1);
            sum += __shfl_xor_sync(~0u, sum, 2);
            inv[r] = rcp(sum);
            #pragma unroll
            for (int j = 0; j < 3; j++) pf[r][j] = pack_bf16(v[2 * j], v[2 * j + 1]);
        }
        uint32_t ow[4][2];
        {
            const int mi = lane >> 3, r = lane & 7;
            uint32_t vv[4][4];
            #pragma unroll
            for (int nt = 0; nt < 4; nt++)
                ldsm_x4_t(addr(sv, r0 + min(mi, 2) * 8 + r, hl * 4 + nt), vv[nt][0], vv[nt][1], vv[nt][2], vv[nt][3]);
            float o[4][4];
            #pragma unroll
            for (int nt = 0; nt < 4; nt++) {
                o[nt][0] = o[nt][1] = o[nt][2] = o[nt][3] = 0.f;
                mma16816(o[nt], pf[0][0], pf[1][0], pf[0][1], pf[1][1], vv[nt][0], vv[nt][1]);
            }
            #pragma unroll
            for (int nt = 0; nt < 4; nt++) mma1688(o[nt], pf[0][2], pf[1][2], vv[nt][2]);
            #pragma unroll
            for (int nt = 0; nt < 4; nt++) {
                ow[nt][0] = pack_bf16(o[nt][0] * inv[0], o[nt][1] * inv[0]);
                ow[nt][1] = pack_bf16(o[nt][2] * inv[1], o[nt][3] * inv[1]);
            }
        }
        #pragma unroll
        for (int u = 0; u < 4; u += 2) {
            const int mi = lane >> 3, r = lane & 7;
            stsm_x4(addr(sq, r0 + (mi & 1) * 8 + r, hl * 4 + u + (mi >> 1)), ow[u][0], ow[u][1], ow[u + 1][0], ow[u + 1][1]);
        }
    }
}

constexpr uint32_t QKVB_TARGET = 12 * 8;
constexpr uint32_t PROGRESS_TARGET = 96;
constexpr uint32_t OA_TARGET = 64, OB_TARGET = 32;
#define ATT_B0 6
constexpr int ATT_TASKS = (NSEG + 16) * 32;
__device__ __forceinline__ int att_group(int g, bool& isb) {
    const int q = g - ATT_B0;
    isb = q >= 0 && q < 48 && q % 3 == 0;
    return q < 0 ? g : q >= 48 ? g - 16 : isb ? q / 3 : ATT_B0 + (q / 3) * 2 + q % 3 - 1;
}

__global__ void __launch_bounds__(ATT_THREADS, 1) attn_kernel(const __grid_constant__ AttnParams p) {
    extern __shared__ __align__(1024) uint8_t smem_raw[];
    const int tid = threadIdx.x, lane = tid & 31, warp = __shfl_sync(~0u, tid >> 5, 0);
    const int pair = warp >> 1, wi = warp & 1;
    const uint32_t base = smem_u32(smem_raw) + pair * ATT_SLOT, bar = smem_u32(smem_raw) + ATT_BAR + pair * 16, taskw = bar + 8;
    const bool leader = wi == 0 && lane == 0;
    if (tid == 0) pdl_launch_dependents();
    KENTER(3);
    const uint32_t cnt = smem_u32(smem_raw) + ATT_CNT;
    if (tid < 96) sts32(cnt + tid * 4, 0);
    __syncthreads();
    if (warp == 2 * ATT_PAIRS) {
        for (uint32_t n = 0; n < SPIN_LIMIT; n++) {
            const bool last = lds32_volatile(cnt + 320) == 2 * ATT_PAIRS;
            uint32_t v[3];
            #pragma unroll
            for (int i = 0; i < 3; i++) {
                v[i] = 0;
                if (i * 32 + lane < 80 && lds32_volatile(cnt + (i * 32 + lane) * 4) != 0)
                    asm volatile("atom.acquire.cta.shared.exch.b32 %0, [%1], 0;" : "=r"(v[i]) : "r"(cnt + (i * 32 + lane) * 4) : "memory");
            }
            if (v[0] | v[1] | v[2]) {
                asm volatile("fence.acq_rel.gpu;" ::: "memory");
                #pragma unroll
                for (int i = 0; i < 3; i++)
                    if (v[i]) asm volatile("red.relaxed.gpu.global.add.u32 [%0], %1;" ::"l"(p.flags + F_OB + i * 32 + lane), "r"(v[i]) : "memory");
                if (v[2] && lane == 15) KMARK(14);
            }
            __syncwarp();
            if (last) break;
            __nanosleep(40);
        }
        if (lane == 0) KEXIT(3);
        return;
    }
    uint32_t next = 0, phase = 0;
    if (leader) {
        mbar_init(bar, 1);
        asm volatile("fence.mbarrier_init.release.cluster;" ::: "memory");
        next = atomicAdd(p.flags + F_QUEUE3, 1u);
    }
    uint32_t pending = 0;
    auto flush = [&]() {
        if (pending) {
            bulk_wait_all();
            if (pending == cnt + 79 * 4) KMARK(13);
            asm volatile("red.release.cta.shared.add.u32 [%0], 1;" ::"r"(pending) : "memory");
            pending = 0;
        }
    };
    int ready_a = -1, ready_b = -1;
    while (true) {
        named_bar_sync(1 + pair, 64);
        if (leader) {
            const uint32_t task = next;
            sts32(taskw, task);
            if (task >= ATT_TASKS) {
                mbar_arrive(bar);
            } else {
                bool isb;
                const int grp = att_group(task >> 5, isb), i = task & 31;
                auto need = [&](const uint32_t* f, uint32_t target) {
                    if (ld_acquire_b32(f) < target) { flush(); wait_flag(f, target); }
                };
                if (isb) {
                    if (grp > ready_b) {
                        need(p.flags + F_QKVB + grp, QKVB_TARGET);
                        if (grp > 0) need(p.flags + F_QKVB + grp - 1, QKVB_TARGET);
                        asm volatile("fence.proxy.async.global;" ::: "memory");
                        ready_b = grp;
                    }
                    mbar_arrive_expect_tx(bar, 8192 + 2 * 9216);
                    tma_load_3d(base, &p.tmQb, (i >> 1) * 64, i & 1, grp * 64, bar);
                    tma_load_3d(base + 8192, &p.tmKb, DM + (i >> 1) * 64, i & 1, grp * 64 - 8, bar);
                    tma_load_3d(base + 8192 + 9216, &p.tmKb, 2 * DM + (i >> 1) * 64, i & 1, grp * 64 - 8, bar);
                } else {
                    if (grp > ready_a) {
                        need(p.flags + F_PROGRESS + grp, PROGRESS_TARGET);
                        asm volatile("fence.proxy.async.global;" ::: "memory");
                        ready_a = grp;
                    }
                    if (grp == 63) KMARK(10);
                    mbar_arrive_expect_tx(bar, ATT_SLOT);
                    #pragma unroll
                    for (int w = 0; w < 3; w++)
                        bulk_load(base + w * 8192, p.qkv_tok + (((size_t)w * NSEG + grp) * NH + i) * (SEG * DH), 8192, bar);
                    #pragma unroll
                    for (int w = 0; w < 2; w++)
                        bulk_load(base + 24576 + w * 2048, p.kv_mem + (((size_t)w * NSEG + grp) * NH + i) * (MROWS * DH), 2048, bar);
                }
                next = atomicAdd(p.flags + F_QUEUE3, 1u);
            }
        }
        if (lane == 0) flush();
        __syncwarp();
        mbar_wait_sleep(bar, phase);
        phase ^= 1;
        const uint32_t task = lds32_volatile(taskw);
        if (task >= ATT_TASKS) break;
        bool isb;
        const int grp = att_group(task >> 5, isb), i = task & 31;
        if (isb) {
            b_attn_warp(base, wi, grp * 64, lane);
            asm volatile("fence.proxy.async.shared::cta;" ::: "memory");
            named_bar_sync(1 + pair, 64);
            if (wi == 1 && lane == 0) {
                asm volatile("cp.async.bulk.tensor.3d.global.shared::cta.bulk_group [%0, {%2, %3, %4}], [%1];"
                             ::"l"(&p.tmOb), "r"(base), "r"((i >> 1) * 64), "r"(i & 1), "r"(grp * 64) : "memory");
                pending = cnt + grp * 4;
            }
        } else {
            if (grp == 63 && lane == 0) KMARK(11);
            tok_attn_warp(base, wi, lane);
            if (grp == 63 && lane == 0) KMARK(12);
            asm volatile("fence.proxy.async.shared::cta;" ::: "memory");
            __syncwarp();
            if (lane == 0) {
                #pragma unroll
                for (int h = 0; h < 2; h++) tma_store_2d(&p.tmOa, base + h * 4096 + wi * 2048, i * DH + h * 64, grp * SEG + wi * 16);
                pending = cnt + (16 + grp) * 4;
            }
        }
        if (lane == 0) { bulk_commit(); bulk_wait_read_all(); }
        __syncwarp();
    }
    if (lane == 0) asm volatile("red.release.cta.shared.add.u32 [%0], 1;" ::"r"(cnt + 320) : "memory");
}

typedef CUresult (*EncodeFn)(CUtensorMap*, CUtensorMapDataType, cuuint32_t, void*, const cuuint64_t*, const cuuint64_t*,
                             const cuuint32_t*, const cuuint32_t*, CUtensorMapInterleave, CUtensorMapSwizzle,
                             CUtensorMapL2promotion, CUtensorMapFloatOOBfill);

void make_map_2d(EncodeFn enc, CUtensorMap* m, const void* ptr, uint64_t rows, uint64_t cols, uint32_t box_rows, uint32_t box_cols = 64) {
    cuuint64_t dims[2] = {cols, rows};
    cuuint64_t strides[1] = {cols * 2};
    cuuint32_t box[2] = {box_cols, box_rows};
    cuuint32_t es[2] = {1, 1};
    enc(m, CU_TENSOR_MAP_DATA_TYPE_BFLOAT16, 2, const_cast<void*>(ptr), dims, strides, box, es,
        CU_TENSOR_MAP_INTERLEAVE_NONE, box_cols == 64 ? CU_TENSOR_MAP_SWIZZLE_128B : CU_TENSOR_MAP_SWIZZLE_64B, CU_TENSOR_MAP_L2_PROMOTION_L2_256B,
        CU_TENSOR_MAP_FLOAT_OOB_FILL_NONE);
}
void make_map_b(EncodeFn enc, CUtensorMap* m, const void* ptr, uint64_t k, uint64_t n, uint32_t nblk, uint32_t box_rows = 64) {
    cuuint64_t dims[3] = {64, k, n / 64};
    cuuint64_t strides[2] = {n * 2, 128};
    cuuint32_t box[3] = {64, box_rows, nblk};
    cuuint32_t es[3] = {1, 1, 1};
    enc(m, CU_TENSOR_MAP_DATA_TYPE_BFLOAT16, 3, const_cast<void*>(ptr), dims, strides, box, es,
        CU_TENSOR_MAP_INTERLEAVE_NONE, CU_TENSOR_MAP_SWIZZLE_128B, CU_TENSOR_MAP_L2_PROMOTION_L2_256B,
        CU_TENSOR_MAP_FLOAT_OOB_FILL_NONE);
}

void make_map_parity(EncodeFn enc, CUtensorMap* m, const void* ptr, uint64_t cols, uint32_t box_rows) {
    cuuint64_t dims[3] = {cols, 2, S_TOK / 2};
    cuuint64_t strides[2] = {cols * 2, cols * 4};
    cuuint32_t box[3] = {64, 1, box_rows};
    cuuint32_t es[3] = {1, 1, 1};
    enc(m, CU_TENSOR_MAP_DATA_TYPE_BFLOAT16, 3, const_cast<void*>(ptr), dims, strides, box, es,
        CU_TENSOR_MAP_INTERLEAVE_NONE, CU_TENSOR_MAP_SWIZZLE_128B, CU_TENSOR_MAP_L2_PROMOTION_L2_128B,
        CU_TENSOR_MAP_FLOAT_OOB_FILL_NONE);
}
void make_map_w(EncodeFn enc, CUtensorMap* m, const void* ptr) {
    cuuint64_t dims[3] = {HD, 64, DM / 64};
    cuuint64_t strides[2] = {HD * 2, 64 * HD * 2};
    cuuint32_t box[3] = {64, 16, 8};
    cuuint32_t es[3] = {1, 1, 1};
    enc(m, CU_TENSOR_MAP_DATA_TYPE_BFLOAT16, 3, const_cast<void*>(ptr), dims, strides, box, es,
        CU_TENSOR_MAP_INTERLEAVE_NONE, CU_TENSOR_MAP_SWIZZLE_128B, CU_TENSOR_MAP_L2_PROMOTION_L2_256B,
        CU_TENSOR_MAP_FLOAT_OOB_FILL_NONE);
}

#define OUTB_SIDE_BLOCKS 16
#define SIDE_ORDER 0
#define N_POST_ATT 0
#define SERIAL_ATT_CTAS h.n_sm
#define N_TAIL_CTAS 24
#define N_SIDE_CTAS 29
#define N_ATT_CTAS 7
#define TAIL_BLOCK0 12

struct HostState {
    bool ready;
    bool overlap;
    int n_side, n_att, n_sm;
    SideParams seq_a, seq_b;
    const void* key[11];
    RecParams rec;
    SideParams side, tail, outb;
    FinalParams fin;
    AttnParams attn;
    __nv_bfloat16 *qkv_tok, *kv_mem, *o_tok, *qkv_b, *o_b;
    uint8_t* xchg;
};
HostState g_host;

void setup(void* const* d_in, void* d_out) {
    HostState& h = g_host;
    void* fn = nullptr;
    cudaDriverEntryPointQueryResult qr;
    cudaGetDriverEntryPoint("cuTensorMapEncodeTiled", &fn, cudaEnableDefault, &qr);
    EncodeFn enc = reinterpret_cast<EncodeFn>(fn);
    void* ptr;
    cudaGetSymbolAddress(&ptr, g_qkv_tok); h.qkv_tok = (__nv_bfloat16*)ptr;
    cudaGetSymbolAddress(&ptr, g_kv_mem);  h.kv_mem = (__nv_bfloat16*)ptr;
    cudaGetSymbolAddress(&ptr, g_o_tok);   h.o_tok = (__nv_bfloat16*)ptr;
    cudaGetSymbolAddress(&ptr, g_qkv_b);   h.qkv_b = (__nv_bfloat16*)ptr;
    cudaGetSymbolAddress(&ptr, g_o_b);     h.o_b = (__nv_bfloat16*)ptr;
    cudaGetSymbolAddress(&ptr, g_xchg);    h.xchg = (uint8_t*)(((uint64_t)ptr + XCHG_BYTES - 1) & ~(uint64_t)(XCHG_BYTES - 1));
    cudaGetSymbolAddress(&ptr, g_flags);   uint32_t* flags = (uint32_t*)ptr;
    cudaGetSymbolAddress(&ptr, g_arrivals); uint32_t* arrivals = (uint32_t*)ptr;

    const void *xa = d_in[0], *mem0 = d_in[1], *wq = d_in[2], *wk = d_in[3], *wv = d_in[4], *wo = d_in[5];
    const void *xb = d_in[7], *wqkv = d_in[8], *wob = d_in[9];

    RecParams& r = h.rec;
    make_map_w(enc, &r.tmW[0], wq);
    make_map_w(enc, &r.tmW[1], wk);
    make_map_w(enc, &r.tmW[2], wv);
    make_map_2d(enc, &r.tmWo, wo, HD, DM, 128, 32);
    r.mem0 = (const __nv_bfloat16*)mem0;
    r.qkv_tok = h.qkv_tok; r.kv_mem = h.kv_mem; r.xchg = h.xchg;
    r.flags = flags; r.arrivals = arrivals; r.one[0] = r.one[1] = 1;
    make_map_b(enc, &r.tmX, xa, S_TOK, DM, 4, SEG);

    SideParams& sd = h.side;
    SideProb& p0 = sd.prob[0];
    make_map_2d(enc, &p0.tmA, xb, S_TOK, DM, BM);
    make_map_b(enc, &p0.tmB, wqkv, DM, 3 * DM, 4);
    make_map_2d(enc, &p0.tmC, h.qkv_b, S_TOK, 3 * DM, 16);
    p0.n_tiles = 3 * DM / 256; p0.k_blocks = DM / BK; p0.c_col0 = 0; p0.dep = nullptr; p0.dep_target = 0; p0.dep_n = 1; p0.sig = flags + F_QKVB;
    SideProb& p1 = sd.prob[1];
    make_map_2d(enc, &p1.tmA, h.o_tok, S_TOK, HD, BM);
    make_map_b(enc, &p1.tmB, wo, HD, DM, 4);
    make_map_2d(enc, &p1.tmC, d_out, S_TOK, 2 * DM, 16);
    p1.n_tiles = DM / 256; p1.k_blocks = HD / BK; p1.c_col0 = 0; p1.dep = flags + F_OA; p1.dep_target = OA_TARGET; p1.dep_n = 4; p1.sig = nullptr;
    SideProb& p2 = sd.prob[2];
    make_map_2d(enc, &p2.tmA, h.o_b, S_TOK, DM, BM);
    make_map_b(enc, &p2.tmB, wob, DM, DM, 4);
    p2.tmC = p1.tmC;
    p2.n_tiles = DM / 256; p2.k_blocks = DM / BK; p2.c_col0 = DM; p2.dep = flags + F_OB; p2.dep_target = OB_TARGET; p2.dep_n = 1; p2.sig = nullptr;
    p0.n_split = p1.n_split = p2.n_split = 1 << 20;
    p0.part = p1.part = p2.part = nullptr;
    if (SIDE_ORDER == 0) { sd.seg[0] = {0, 0, 16}; sd.seg[1] = {1, 0, TAIL_BLOCK0}; }
    else { sd.seg[0] = {1, 0, TAIL_BLOCK0}; sd.seg[1] = {0, 0, 16}; }
    sd.seg[2] = {2, 0, OUTB_SIDE_BLOCKS};
    sd.nseg = 3; sd.queue = flags + F_SIDEQ;
    h.outb = sd;
    h.outb.seg[0] = {2, OUTB_SIDE_BLOCKS, 16};
    h.outb.nseg = 1; h.outb.queue = flags + F_OUTBQ;

    SideParams& tl = h.tail;
    tl.prob[0] = p1;
    make_map_b(enc, &tl.prob[0].tmB, wo, HD, DM, 2);
    tl.prob[0].n_tiles = 2 * DM / 128; tl.prob[0].n_split = DM / 128; tl.prob[0].k_blocks = HD / BK / 2;
    cudaGetSymbolAddress(&ptr, g_part);
    tl.prob[0].part = (float*)ptr; tl.prob[0].part_flag = flags + F_PART;
    tl.prob[1] = tl.prob[2] = tl.prob[0];
    tl.seg[0] = {0, TAIL_BLOCK0, 15};
    tl.nseg = 1; tl.queue = flags + F_TAILQ;

    make_map_2d(enc, &h.fin.tmA, h.o_tok, S_TOK, HD, SEG);
    h.fin.tmB = tl.prob[0].tmB; h.fin.out = (__nv_bfloat16*)d_out;
    h.fin.dep = flags + F_OA + 60; h.fin.dep_target = OA_TARGET; h.fin.mt = 15;

    make_map_2d(enc, &h.attn.tmOa, h.o_tok, S_TOK, HD, 16);
    make_map_parity(enc, &h.attn.tmQb, h.qkv_b, 3 * DM, 64);
    make_map_parity(enc, &h.attn.tmKb, h.qkv_b, 3 * DM, 72);
    make_map_parity(enc, &h.attn.tmOb, h.o_b, DM, 64);
    h.attn.qkv_tok = h.qkv_tok; h.attn.kv_mem = h.kv_mem; h.attn.flags = flags;

    int dev = 0, nsm = 0;
    cudaGetDevice(&dev);
    cudaDeviceGetAttribute(&nsm, cudaDevAttrMultiProcessorCount, dev);
    h.n_sm = nsm;
    h.overlap = nsm - 96 >= N_SIDE_CTAS + N_ATT_CTAS;
    h.n_side = N_SIDE_CTAS; h.n_att = N_ATT_CTAS;
    h.seq_a = sd;
    h.seq_a.seg[0] = {0, 0, 16};
    h.seq_a.seg[1] = {0, 16, 16};
    h.seq_a.nseg = 2;
    h.seq_b = sd;
    h.seq_b.seg[0] = {1, 0, 16};
    h.seq_b.seg[1] = {2, 0, 16};
    h.seq_b.nseg = 2; h.seq_b.queue = flags + F_TAILQ;

    cudaFuncSetAttribute(side_gemm_kernel<256>, cudaFuncAttributeMaxDynamicSharedMemorySize, GemmCfg<256>::SMEM);
    cudaFuncSetAttribute(side_gemm_kernel<128>, cudaFuncAttributeMaxDynamicSharedMemorySize, GemmCfg<128>::SMEM);
    cudaFuncSetAttribute(final_gemm_kernel, cudaFuncAttributeMaxDynamicSharedMemorySize, FIN_SMEM);
    cudaFuncSetAttribute(rec_kernel, cudaFuncAttributeMaxDynamicSharedMemorySize, REC_SMEM);
    cudaFuncSetAttribute(attn_kernel, cudaFuncAttributeMaxDynamicSharedMemorySize, ATT_SMEM);
    for (int i = 0; i < 10; i++) h.key[i] = d_in[i];
    h.key[10] = d_out;
    h.ready = true;
}

template <typename K, typename P>
void launch(K kernel, int grid, int block, int smem, cudaStream_t st, const P& prm, int cluster, bool pdl) {
    cudaLaunchConfig_t cfg = {};
    cfg.gridDim = dim3(grid); cfg.blockDim = dim3(block); cfg.dynamicSmemBytes = smem; cfg.stream = st;
    cudaLaunchAttribute at[2];
    int n = 0;
    if (cluster > 1) {
        at[n].id = cudaLaunchAttributeClusterDimension;
        at[n].val.clusterDim.x = cluster; at[n].val.clusterDim.y = 1; at[n].val.clusterDim.z = 1;
        n++;
    }
    if (pdl) {
        at[n].id = cudaLaunchAttributeProgrammaticStreamSerialization;
        at[n].val.programmaticStreamSerializationAllowed = 1;
        n++;
    }
    cfg.attrs = at; cfg.numAttrs = n;
    cudaLaunchKernelEx(&cfg, kernel, prm);
}

}

extern "C" void kernel_launch(void* const* d_in, const int* in_sizes, int n_in, void* d_out, int out_size) {
    HostState& h = g_host;
    bool same = h.ready;
    for (int i = 0; same && i < 10; i++) same = h.key[i] == d_in[i];
    if (!same || h.key[10] != d_out) setup(d_in, d_out);
    cudaStream_t st = cudaStreamPerThread;

    launch(rec_kernel, 96, REC_THREADS, REC_SMEM, st, h.rec, 3, false);
    {
        if (!h.overlap) {
            launch(side_gemm_kernel<256>, h.n_sm, 384, GemmCfg<256>::SMEM, st, h.seq_a, 1, false);
            launch(attn_kernel, SERIAL_ATT_CTAS, ATT_THREADS, ATT_SMEM, st, h.attn, 1, false);
            launch(side_gemm_kernel<256>, h.n_sm, 384, GemmCfg<256>::SMEM, st, h.seq_b, 1, false);
            return;
        }
    }
    launch(side_gemm_kernel<256>, h.n_side, 384, GemmCfg<256>::SMEM, st, h.side, 1, true);
    launch(attn_kernel, h.n_att, ATT_THREADS, ATT_SMEM, st, h.attn, 1, true);
    launch(side_gemm_kernel<128>, N_TAIL_CTAS, 384, GemmCfg<128>::SMEM, st, h.tail, 1, true);
    if (N_POST_ATT > 0) launch(attn_kernel, N_POST_ATT, ATT_THREADS, ATT_SMEM, st, h.attn, 1, true);
    launch(final_gemm_kernel, 8 * FIN_SPLIT, 384, FIN_SMEM, st, h.fin, FIN_SPLIT, true);
    if (OUTB_SIDE_BLOCKS < 16)
        launch(side_gemm_kernel<256>, (16 - OUTB_SIDE_BLOCKS) * 4, 384, GemmCfg<256>::SMEM, st, h.outb, 1, true);
}
```

```cpp
#include <cuda_runtime.h>
#include <cuda_bf16.h>
#include <cuda.h>
#include <stdint.h>

namespace {

constexpr int S_TOK = 2048;
constexpr int DM = 1024;
constexpr int NH = 32;
constexpr int DH = 128;
constexpr int HD = NH * DH;
constexpr int NSEG = 64;
constexpr int SEG = 32;
constexpr int MROWS = 8;
constexpr uint32_t SENT = 0xFFFFFFFFu;
constexpr uint32_t SPIN_LIMIT = 1u << 24;

__device__ __align__(1024) __nv_bfloat16 g_qkv_tok[3ull * NSEG * NH * SEG * DH];
__device__ __align__(1024) __nv_bfloat16 g_kv_mem[2ull * NSEG * NH * MROWS * DH];
__device__ __align__(1024) __nv_bfloat16 g_o_tok[(size_t)S_TOK * HD];
__device__ __align__(1024) __nv_bfloat16 g_qkv_b[(size_t)S_TOK * 3 * DM];
__device__ __align__(1024) __nv_bfloat16 g_o_b[(size_t)S_TOK * DM];
__device__ __align__(1024) float g_part[32 * 128 * 128];
constexpr int PUB_BYTES = 32768;
constexpr int XCHG_SLOT = 1 << 20;
constexpr int XCHG_PUB = 0, XCHG_INBOX = 2 * PUB_BYTES;
constexpr int INBOX_MAX = 80;
constexpr int XCHG_BYTES = 2 * XCHG_SLOT;
__device__ __align__(8192) uint8_t g_xchg[2 * XCHG_BYTES];
enum { F_QUEUE3 = 3, F_QUEUE4 = 4, F_SIDEQ = 8, F_TAILQ = 16, F_OUTBQ = 24, F_PROGRESS = 32, F_QKVB = 96, F_OB = 112, F_OA = 128, F_PART = 192, F_COUNT = 224 };
__device__ uint32_t g_flags[F_COUNT];
__device__ __align__(16) uint32_t g_arrivals[4];

#define STAMP(k) do {} while (0)
#define STAMPD(k, x) do {} while (0)
#define PSTAMP(k) do {} while (0)
#define KENTER(k) do {} while (0)
#define APROF(k) do {} while (0)
#define KEXIT(k) do {} while (0)
#define KMARK(k) do {} while (0)

__device__ __forceinline__ uint32_t class_off(uint64_t a, uint32_t c) {
    return ((__popc((uint32_t)a & 0xB3000u) ^ c) & 1u) << 12;
}
__device__ __forceinline__ uint32_t smem_u32(const void* p) { return (uint32_t)__cvta_generic_to_shared(p); }
__device__ __forceinline__ uint32_t pack_bf16(float lo, float hi) {
    uint32_t r;
    asm("cvt.rn.bf16x2.f32 %0, %1, %2;" : "=r"(r) : "f"(hi), "f"(lo));
    return r;
}
__device__ __forceinline__ float ex2(float x) {
    float y;
    asm("ex2.approx.ftz.f32 %0, %1;" : "=f"(y) : "f"(x));
    return y;
}
__device__ __forceinline__ float rcp(float x) {
    float y;
    asm("rcp.approx.ftz.f32 %0, %1;" : "=f"(y) : "f"(x));
    return y;
}
__device__ __forceinline__ uint32_t clock32() {
    uint32_t t;
    asm volatile("mov.u32 %0, %%clock;" : "=r"(t));
    return t;
}
__device__ __forceinline__ void spin_clks(uint32_t n) {
    if (n == 0) return;
    const uint32_t t0 = clock32();
    while (clock32() - t0 < n) {}
}
__device__ __forceinline__ void spin_until(uint32_t t) {
    while ((int)(clock32() - t) < 0) {}
}
__device__ __forceinline__ uint32_t clock_after(uint32_t x) {
    uint32_t t;
    asm volatile("{\n.reg .pred p;\nsetp.eq.u32 p, %1, 0x12345678;\n@p exit;\nmov.u32 %0, %%clock;\n}" : "=r"(t) : "r"(x) : "memory");
    return t;
}
__device__ __forceinline__ uint32_t opaque(uint32_t x) { return __shfl_sync(~0u, x, threadIdx.x & 31); }
__device__ __forceinline__ uint32_t uniform(uint32_t x) { return __shfl_sync(~0u, x + (threadIdx.x & 31), 0); }
__device__ __forceinline__ float bf16_lo(uint32_t w) { return __uint_as_float(w << 16); }
__device__ __forceinline__ float bf16_hi(uint32_t w) { return __uint_as_float(w & 0xFFFF0000u); }

__device__ __forceinline__ void mbar_init(uint32_t bar, uint32_t cnt) {
    asm volatile("mbarrier.init.shared::cta.b64 [%0], %1;" ::"r"(bar), "r"(cnt) : "memory");
}
__device__ __forceinline__ void mbar_arrive(uint32_t bar) {
    asm volatile("mbarrier.arrive.shared::cta.b64 _, [%0];" ::"r"(bar) : "memory");
}
__device__ __forceinline__ void mbar_arrive_expect_tx(uint32_t bar, uint32_t bytes) {
    asm volatile("mbarrier.arrive.expect_tx.shared::cta.b64 _, [%0], %1;" ::"r"(bar), "r"(bytes) : "memory");
}
__device__ __forceinline__ bool mbar_try_wait(uint32_t bar, uint32_t parity) {
    uint32_t ok;
    asm volatile(
        "{\n.reg .pred p;\n"
        "mbarrier.try_wait.parity.shared::cta.b64 p, [%1], %2;\n"
        "selp.u32 %0, 1, 0, p;\n}"
        : "=r"(ok) : "r"(bar), "r"(parity) : "memory");
    return ok != 0;
}
__device__ __forceinline__ bool mbar_test_wait(uint32_t bar, uint32_t parity) {
    uint32_t ok;
    asm volatile(
        "{\n.reg .pred p;\n"
        "mbarrier.test_wait.parity.shared::cta.b64 p, [%1], %2;\n"
        "selp.u32 %0, 1, 0, p;\n}"
        : "=r"(ok) : "r"(bar), "r"(parity) : "memory");
    return ok != 0;
}
__device__ __forceinline__ void mbar_wait(uint32_t bar, uint32_t parity) {
    uint32_t n = 0;
    while (!mbar_try_wait(bar, parity)) {
        if (++n > SPIN_LIMIT) __trap();
    }
}
__device__ __forceinline__ void mbar_wait_sleep(uint32_t bar, uint32_t parity) {
    uint32_t n = 0;
    while (!mbar_try_wait(bar, parity)) {
        __nanosleep(20);
        if (++n > SPIN_LIMIT) __trap();
    }
}
__device__ __forceinline__ void mbar_wait_bounded(uint32_t bar, uint32_t parity) {
    for (uint32_t n = 0; n < (1u << 20) && !mbar_try_wait(bar, parity); n++) {}
}
__device__ __forceinline__ bool elect_one() {
    uint32_t ok;
    asm volatile("{\n.reg .pred p;\nelect.sync _|p, 0xFFFFFFFF;\nselp.u32 %0, 1, 0, p;\n}" : "=r"(ok));
    return ok != 0;
}
__device__ __forceinline__ void named_bar_sync(int id, int nthreads) {
    asm volatile("bar.sync %0, %1;" ::"r"(id), "r"(nthreads) : "memory");
}
__device__ __forceinline__ void named_bar_arrive(int id, int nthreads) {
    asm volatile("bar.arrive %0, %1;" ::"r"(id), "r"(nthreads) : "memory");
}
__device__ __forceinline__ void cluster_sync() {
    asm volatile("barrier.cluster.arrive.release.aligned;\nbarrier.cluster.wait.acquire.aligned;" ::: "memory");
}
__device__ __forceinline__ uint32_t mapa(uint32_t addr, uint32_t rank) {
    uint32_t r;
    asm volatile("mapa.shared::cluster.u32 %0, %1, %2;" : "=r"(r) : "r"(addr), "r"(rank));
    return r;
}

__device__ __forceinline__ void tma_load_2d(uint32_t dst, const CUtensorMap* tm, int c0, int c1, uint32_t bar) {
    asm volatile(
        "cp.async.bulk.tensor.2d.shared::cluster.global.mbarrier::complete_tx::bytes [%0], [%1, {%3, %4}], [%2];"
        ::"r"(dst), "l"(tm), "r"(bar), "r"(c0), "r"(c1) : "memory");
}
__device__ __forceinline__ void tma_load_3d(uint32_t dst, const CUtensorMap* tm, int c0, int c1, int c2, uint32_t bar) {
    asm volatile(
        "cp.async.bulk.tensor.3d.shared::cluster.global.mbarrier::complete_tx::bytes [%0], [%1, {%3, %4, %5}], [%2];"
        ::"r"(dst), "l"(tm), "r"(bar), "r"(c0), "r"(c1), "r"(c2) : "memory");
}
__device__ __forceinline__ void tma_load_3d_mc(uint32_t dst, const CUtensorMap* tm, int c0, int c1, int c2, uint32_t bar, uint16_t mask) {
    asm volatile(
        "cp.async.bulk.tensor.3d.shared::cluster.global.mbarrier::complete_tx::bytes.multicast::cluster [%0], [%1, {%3, %4, %5}], [%2], %6;"
        ::"r"(dst), "l"(tm), "r"(bar), "r"(c0), "r"(c1), "r"(c2), "h"(mask) : "memory");
}
__device__ __forceinline__ void tma_store_2d(const CUtensorMap* tm, uint32_t src, int c0, int c1) {
    asm volatile("cp.async.bulk.tensor.2d.global.shared::cta.bulk_group [%0, {%2, %3}], [%1];"
                 ::"l"(tm), "r"(src), "r"(c0), "r"(c1) : "memory");
}
__device__ __forceinline__ void bulk_store(void* dst, uint32_t src, uint32_t bytes) {
    asm volatile("cp.async.bulk.global.shared::cta.bulk_group [%0], [%1], %2;" ::"l"(dst), "r"(src), "r"(bytes) : "memory");
}
__device__ __forceinline__ void bulk_commit() { asm volatile("cp.async.bulk.commit_group;" ::: "memory"); }
__device__ __forceinline__ void bulk_wait_read_all() { asm volatile("cp.async.bulk.wait_group.read 0;" ::: "memory"); }
__device__ __forceinline__ void bulk_wait_all() { asm volatile("cp.async.bulk.wait_group 0;" ::: "memory"); }
__device__ __forceinline__ void bulk_load(uint32_t dst, const void* src, uint32_t bytes, uint32_t bar) {
    asm volatile("cp.async.bulk.shared::cluster.global.mbarrier::complete_tx::bytes [%0], [%1], %2, [%3];"
                 ::"r"(dst), "l"(src), "r"(bytes), "r"(bar) : "memory");
}
__device__ __forceinline__ void bulk_load_mc(uint32_t dst, const void* src, uint32_t bytes, uint32_t bar, uint16_t mask) {
    asm volatile(
        "cp.async.bulk.shared::cluster.global.mbarrier::complete_tx::bytes.multicast::cluster [%0], [%1], %2, [%3], %4;"
        ::"r"(dst), "l"(src), "r"(bytes), "r"(bar), "h"(mask) : "memory");
}
__device__ __forceinline__ void cp_async16(uint32_t dst, const void* src) {
    asm volatile("cp.async.cg.shared.global [%0], [%1], 16;" ::"r"(dst), "l"(src) : "memory");
}
__device__ __forceinline__ void cp_async_commit() { asm volatile("cp.async.commit_group;" ::: "memory"); }
template <int N> __device__ __forceinline__ void cp_async_wait() {
    asm volatile("cp.async.wait_group %0;" ::"n"(N) : "memory");
}

__device__ __forceinline__ void ldsm_x4(uint32_t addr, uint32_t& r0, uint32_t& r1, uint32_t& r2, uint32_t& r3) {
    asm volatile("ldmatrix.sync.aligned.m8n8.x4.shared.b16 {%0,%1,%2,%3}, [%4];"
                 : "=r"(r0), "=r"(r1), "=r"(r2), "=r"(r3) : "r"(addr) : "memory");
}
__device__ __forceinline__ void ldsm_x4_t(uint32_t addr, uint32_t& r0, uint32_t& r1, uint32_t& r2, uint32_t& r3) {
    asm volatile("ldmatrix.sync.aligned.m8n8.x4.trans.shared.b16 {%0,%1,%2,%3}, [%4];"
                 : "=r"(r0), "=r"(r1), "=r"(r2), "=r"(r3) : "r"(addr) : "memory");
}
__device__ __forceinline__ void stsm_x4(uint32_t addr, uint32_t r0, uint32_t r1, uint32_t r2, uint32_t r3) {
    asm volatile("stmatrix.sync.aligned.m8n8.x4.shared.b16 [%0], {%1,%2,%3,%4};"
                 ::"r"(addr), "r"(r0), "r"(r1), "r"(r2), "r"(r3) : "memory");
}
__device__ __forceinline__ uint32_t movmat(uint32_t a) {
    uint32_t d;
    asm volatile("movmatrix.sync.aligned.m8n8.trans.b16 %0, %1;" : "=r"(d) : "r"(a));
    return d;
}
__device__ __forceinline__ void mma16816(float* d, uint32_t a0, uint32_t a1, uint32_t a2, uint32_t a3,
                                         uint32_t b0, uint32_t b1) {
    asm volatile(
        "mma.sync.aligned.m16n8k16.row.col.f32.bf16.bf16.f32 {%0,%1,%2,%3}, {%4,%5,%6,%7}, {%8,%9}, {%0,%1,%2,%3};"
        : "+f"(d[0]), "+f"(d[1]), "+f"(d[2]), "+f"(d[3])
        : "r"(a0), "r"(a1), "r"(a2), "r"(a3), "r"(b0), "r"(b1));
}
__device__ __forceinline__ void mma1688(float* d, uint32_t a0, uint32_t a1, uint32_t b0) {
    asm volatile("mma.sync.aligned.m16n8k8.row.col.f32.bf16.bf16.f32 {%0,%1,%2,%3}, {%4,%5}, {%6}, {%0,%1,%2,%3};"
                 : "+f"(d[0]), "+f"(d[1]), "+f"(d[2]), "+f"(d[3]) : "r"(a0), "r"(a1), "r"(b0));
}
__device__ __forceinline__ uint32_t any_reg() {
    uint32_t r;
    asm volatile("" : "=r"(r));
    return r;
}
__device__ __forceinline__ uint2 lds64(uint32_t addr) {
    uint2 v;
    asm volatile("ld.volatile.shared.v2.b32 {%0,%1}, [%2];" : "=r"(v.x), "=r"(v.y) : "r"(addr) : "memory");
    return v;
}
__device__ __forceinline__ uint4 lds128(uint32_t addr) {
    uint4 v;
    asm volatile("ld.volatile.shared.v4.b32 {%0,%1,%2,%3}, [%4];" : "=r"(v.x), "=r"(v.y), "=r"(v.z), "=r"(v.w) : "r"(addr) : "memory");
    return v;
}
__device__ __forceinline__ void sts32(uint32_t addr, uint32_t x) {
    asm volatile("st.volatile.shared.b32 [%0], %1;" ::"r"(addr), "r"(x) : "memory");
}
__device__ __forceinline__ void sts64(uint32_t addr, uint32_t x, uint32_t y) {
    asm volatile("st.volatile.shared.v2.b32 [%0], {%1,%2};" ::"r"(addr), "r"(x), "r"(y) : "memory");
}
__device__ __forceinline__ void sts128(uint32_t addr, uint32_t x, uint32_t y, uint32_t z, uint32_t w) {
    asm volatile("st.volatile.shared.v4.b32 [%0], {%1,%2,%3,%4};" ::"r"(addr), "r"(x), "r"(y), "r"(z), "r"(w) : "memory");
}
__device__ __forceinline__ void st_async_v2(uint32_t addr, uint32_t x, uint32_t y, uint32_t bar) {
    asm volatile("st.async.weak.shared::cluster.mbarrier::complete_tx::bytes.v2.b32 [%0], {%1,%2}, [%3];"
                 ::"r"(addr), "r"(x), "r"(y), "r"(bar) : "memory");
}
__device__ __forceinline__ uint2 ld_relaxed_v2(const void* p) {
    uint2 v;
    asm volatile("ld.relaxed.gpu.global.v2.b32 {%0,%1}, [%2];" : "=r"(v.x), "=r"(v.y) : "l"(p) : "memory");
    return v;
}
__device__ __forceinline__ void st_relaxed_v2(void* p, uint32_t x, uint32_t y) {
    asm volatile("st.relaxed.gpu.global.v2.b32 [%0], {%1,%2};" ::"l"(p), "r"(x), "r"(y) : "memory");
}
__device__ __forceinline__ void st_relaxed_v4(void* p, uint32_t x) {
    asm volatile("st.relaxed.gpu.global.v4.b32 [%0], {%1,%1,%1,%1};" ::"l"(p), "r"(x) : "memory");
}
__device__ __forceinline__ uint32_t ld_relaxed_b32(const void* p) {
    uint32_t v;
    asm volatile("ld.relaxed.gpu.global.b32 %0, [%1];" : "=r"(v) : "l"(p) : "memory");
    return v;
}
__device__ __forceinline__ uint32_t lds32_volatile(uint32_t addr) {
    uint32_t v;
    asm volatile("ld.volatile.shared.b32 %0, [%1];" : "=r"(v) : "r"(addr) : "memory");
    return v;
}
__device__ __forceinline__ void st_relaxed_b32(void* p, uint32_t x) {
    asm volatile("st.relaxed.gpu.global.b32 [%0], %1;" ::"l"(p), "r"(x) : "memory");
}

__device__ __forceinline__ uint32_t ld_acquire_b32(const void* p) {
    uint32_t v;
    asm volatile("ld.acquire.gpu.global.b32 %0, [%1];" : "=r"(v) : "l"(p) : "memory");
    return v;
}
__device__ __forceinline__ void wait_flag(const uint32_t* p, uint32_t target) {
    uint32_t n = 0;
    while (ld_acquire_b32(p) < target) {
        __nanosleep(64);
        if (++n > SPIN_LIMIT) __trap();
    }
}
__device__ __forceinline__ void signal_flag(uint32_t* p) {
    asm volatile("red.release.gpu.global.add.u32 [%0], 1;" ::"l"(p) : "memory");
}
__device__ __forceinline__ void pdl_launch_dependents() { asm volatile("griddepcontrol.launch_dependents;" ::: "memory"); }

constexpr int BM = 128, BK = 64;
constexpr int A_STAGE = BM * BK * 2;
template <int BN> struct GemmCfg {
    static constexpr int STAGES = BN == 256 ? 3 : 6;
    static constexpr int STAGE = A_STAGE + BK * BN * 2;
    static constexpr int EPI_WARP = 16 * BN * 2;
    static constexpr int SMEM = STAGES * STAGE + 8 * EPI_WARP + 1024 + 512;
};

struct SideProb {
    CUtensorMap tmA, tmB, tmC;
    int n_split;
    int n_tiles, k_blocks, c_col0;
    const uint32_t* dep;
    uint32_t dep_target;
    int dep_n;
    uint32_t* sig;
    float* part;
    uint32_t* part_flag;
};
struct SideSeg { int prob, m0, m1; };
constexpr int SIDE_MAX_SEG = 6;
struct SideParams {
    SideProb prob[3];
    SideSeg seg[SIDE_MAX_SEG];
    int nseg;
    uint32_t* queue;
};
static_assert(sizeof(SideParams) <= 4096, "kernel parameter limit");

__device__ __forceinline__ uint64_t make_desc(uint32_t addr, uint32_t lbo, uint32_t sbo) {
    return (uint64_t)((addr & 0x3FFFF) >> 4) | ((uint64_t)(lbo >> 4) << 16) | ((uint64_t)(sbo >> 4) << 32) | (1ull << 62);
}

__device__ __forceinline__ void wgmma_m64n256k16(float (&d)[128], uint64_t da, uint64_t db, int scale_d) {
    asm volatile(
        "{\n.reg .pred p;\nsetp.ne.b32 p, %130, 0;\n"
        "wgmma.mma_async.sync.aligned.m64n256k16.f32.bf16.bf16 "
        "{%0,%1,%2,%3,%4,%5,%6,%7,%8,%9,%10,%11,%12,%13,%14,%15,"
        "%16,%17,%18,%19,%20,%21,%22,%23,%24,%25,%26,%27,%28,%29,%30,%31,"
        "%32,%33,%34,%35,%36,%37,%38,%39,%40,%41,%42,%43,%44,%45,%46,%47,"
        "%48,%49,%50,%51,%52,%53,%54,%55,%56,%57,%58,%59,%60,%61,%62,%63,"
        "%64,%65,%66,%67,%68,%69,%70,%71,%72,%73,%74,%75,%76,%77,%78,%79,"
        "%80,%81,%82,%83,%84,%85,%86,%87,%88,%89,%90,%91,%92,%93,%94,%95,"
        "%96,%97,%98,%99,%100,%101,%102,%103,%104,%105,%106,%107,%108,%109,%110,%111,"
        "%112,%113,%114,%115,%116,%117,%118,%119,%120,%121,%122,%123,%124,%125,%126,%127},"
        " %128, %129, p, 1, 1, 0, 1;\n}\n"
        : "+f"(d[0]), "+f"(d[1]), "+f"(d[2]), "+f"(d[3]), "+f"(d[4]), "+f"(d[5]), "+f"(d[6]), "+f"(d[7]),
          "+f"(d[8]), "+f"(d[9]), "+f"(d[10]), "+f"(d[11]), "+f"(d[12]), "+f"(d[13]), "+f"(d[14]), "+f"(d[15]),
          "+f"(d[16]), "+f"(d[17]), "+f"(d[18]), "+f"(d[19]), "+f"(d[20]), "+f"(d[21]), "+f"(d[22]), "+f"(d[23]),
          "+f"(d[24]), "+f"(d[25]), "+f"(d[26]), "+f"(d[27]), "+f"(d[28]), "+f"(d[29]), "+f"(d[30]), "+f"(d[31]),
          "+f"(d[32]), "+f"(d[33]), "+f"(d[34]), "+f"(d[35]), "+f"(d[36]), "+f"(d[37]), "+f"(d[38]), "+f"(d[39]),
          "+f"(d[40]), "+f"(d[41]), "+f"(d[42]), "+f"(d[43]), "+f"(d[44]), "+f"(d[45]), "+f"(d[46]), "+f"(d[47]),
          "+f"(d[48]), "+f"(d[49]), "+f"(d[50]), "+f"(d[51]), "+f"(d[52]), "+f"(d[53]), "+f"(d[54]), "+f"(d[55]),
          "+f"(d[56]), "+f"(d[57]), "+f"(d[58]), "+f"(d[59]), "+f"(d[60]), "+f"(d[61]), "+f"(d[62]), "+f"(d[63]),
          "+f"(d[64]), "+f"(d[65]), "+f"(d[66]), "+f"(d[67]), "+f"(d[68]), "+f"(d[69]), "+f"(d[70]), "+f"(d[71]),
          "+f"(d[72]), "+f"(d[73]), "+f"(d[74]), "+f"(d[75]), "+f"(d[76]), "+f"(d[77]), "+f"(d[78]), "+f"(d[79]),
          "+f"(d[80]), "+f"(d[81]), "+f"(d[82]), "+f"(d[83]), "+f"(d[84]), "+f"(d[85]), "+f"(d[86]), "+f"(d[87]),
          "+f"(d[88]), "+f"(d[89]), "+f"(d[90]), "+f"(d[91]), "+f"(d[92]), "+f"(d[93]), "+f"(d[94]), "+f"(d[95]),
          "+f"(d[96]), "+f"(d[97]), "+f"(d[98]), "+f"(d[99]), "+f"(d[100]), "+f"(d[101]), "+f"(d[102]), "+f"(d[103]),
          "+f"(d[104]), "+f"(d[105]), "+f"(d[106]), "+f"(d[107]), "+f"(d[108]), "+f"(d[109]), "+f"(d[110]), "+f"(d[111]),
          "+f"(d[112]), "+f"(d[113]), "+f"(d[114]), "+f"(d[115]), "+f"(d[116]), "+f"(d[117]), "+f"(d[118]), "+f"(d[119]),
          "+f"(d[120]), "+f"(d[121]), "+f"(d[122]), "+f"(d[123]), "+f"(d[124]), "+f"(d[125]), "+f"(d[126]), "+f"(d[127])
        : "l"(da), "l"(db), "r"(scale_d));
}

__device__ __forceinline__ void wgmma_m64n128k16(float (&d)[64], uint64_t da, uint64_t db, int scale_d) {
    asm volatile(
        "{\n.reg .pred p;\nsetp.ne.b32 p, %66, 0;\n"
        "wgmma.mma_async.sync.aligned.m64n128k16.f32.bf16.bf16 "
        "{%0,%1,%2,%3,%4,%5,%6,%7,%8,%9,%10,%11,%12,%13,%14,%15,"
        "%16,%17,%18,%19,%20,%21,%22,%23,%24,%25,%26,%27,%28,%29,%30,%31,"
        "%32,%33,%34,%35,%36,%37,%38,%39,%40,%41,%42,%43,%44,%45,%46,%47,"
        "%48,%49,%50,%51,%52,%53,%54,%55,%56,%57,%58,%59,%60,%61,%62,%63},"
        " %64, %65, p, 1, 1, 0, 1;\n}\n"
        : "+f"(d[0]), "+f"(d[1]), "+f"(d[2]), "+f"(d[3]), "+f"(d[4]), "+f"(d[5]), "+f"(d[6]), "+f"(d[7]),
          "+f"(d[8]), "+f"(d[9]), "+f"(d[10]), "+f"(d[11]), "+f"(d[12]), "+f"(d[13]), "+f"(d[14]), "+f"(d[15]),
          "+f"(d[16]), "+f"(d[17]), "+f"(d[18]), "+f"(d[19]), "+f"(d[20]), "+f"(d[21]), "+f"(d[22]), "+f"(d[23]),
          "+f"(d[24]), "+f"(d[25]), "+f"(d[26]), "+f"(d[27]), "+f"(d[28]), "+f"(d[29]), "+f"(d[30]), "+f"(d[31]),
          "+f"(d[32]), "+f"(d[33]), "+f"(d[34]), "+f"(d[35]), "+f"(d[36]), "+f"(d[37]), "+f"(d[38]), "+f"(d[39]),
          "+f"(d[40]), "+f"(d[41]), "+f"(d[42]), "+f"(d[43]), "+f"(d[44]), "+f"(d[45]), "+f"(d[46]), "+f"(d[47]),
          "+f"(d[48]), "+f"(d[49]), "+f"(d[50]), "+f"(d[51]), "+f"(d[52]), "+f"(d[53]), "+f"(d[54]), "+f"(d[55]),
          "+f"(d[56]), "+f"(d[57]), "+f"(d[58]), "+f"(d[59]), "+f"(d[60]), "+f"(d[61]), "+f"(d[62]), "+f"(d[63])
        : "l"(da), "l"(db), "r"(scale_d));
}
template <int BN> struct WgmmaOp;
template <> struct WgmmaOp<256> {
    static __device__ __forceinline__ void run(float (&d)[128], uint64_t a, uint64_t b, int sc) { wgmma_m64n256k16(d, a, b, sc); }
};
template <> struct WgmmaOp<128> {
    static __device__ __forceinline__ void run(float (&d)[64], uint64_t a, uint64_t b, int sc) { wgmma_m64n128k16(d, a, b, sc); }
};

struct StoreRec {
    uint64_t dst;
    uint64_t flag;
    int kind;
    int pad;
};
struct EpiCtx { uint32_t buf, rec, st_full, st_empty; uint32_t it; int lane; };
template <int N>
__device__ __forceinline__ void epi_hand_over(const float (&acc)[N], EpiCtx& e, uint64_t dst, uint64_t flag, int kind) {
    mbar_wait(e.st_empty, (e.it & 1) ^ 1);
    const int mi = e.lane >> 3, row = (mi & 1) * 8 + (e.lane & 7);
    #pragma unroll
    for (int j = 0; j < N / 4; j += 2) {
        const int chunk = (j & 7) + (mi >> 1);
        stsm_x4(e.buf + (j >> 3) * 2048 + row * 128 + ((chunk ^ (row & 7)) << 4),
                pack_bf16(acc[4 * j], acc[4 * j + 1]), pack_bf16(acc[4 * j + 2], acc[4 * j + 3]),
                pack_bf16(acc[4 * j + 4], acc[4 * j + 5]), pack_bf16(acc[4 * j + 6], acc[4 * j + 7]));
    }
    if (e.lane == 0) {
        asm volatile("st.shared.v2.b64 [%0], {%1, %2};" ::"r"(e.rec), "l"(dst), "l"(flag) : "memory");
        asm volatile("st.shared.b32 [%0], %1;" ::"r"(e.rec + 16), "r"(kind) : "memory");
    }
    asm volatile("fence.proxy.async.shared::cta;" ::: "memory");
    __syncwarp();
    if (e.lane == 0) mbar_arrive(e.st_full);
    e.it++;
}
__device__ __forceinline__ void epi_exit(EpiCtx& e) {
    mbar_wait(e.st_empty, (e.it & 1) ^ 1);
    if (e.lane == 0) {
        asm volatile("st.shared.b32 [%0], %1;" ::"r"(e.rec + 16), "r"(-1) : "memory");
        mbar_arrive(e.st_full);
    }
}
template <int BN, bool PAIR = false>
__device__ __forceinline__ void gemm_mainloop(float (&acc)[BN / 2], int k_blocks, uint32_t sbase, uint32_t bar_base, int cw,
                                              bool elected, int& stage, uint32_t& phase, uint32_t peer = 0) {
    using C = GemmCfg<BN>;
    auto release = [&](int st) {
        const uint32_t bar = bar_base + 8 * (C::STAGES + st);
        mbar_arrive(bar);
        if (PAIR) asm volatile("mbarrier.arrive.shared::cluster.b64 _, [%0];" ::"r"(mapa(bar, peer)) : "memory");
    };
    int prev_stage = -1;
    for (int kb = 0; kb < k_blocks; kb++) {
        mbar_wait(bar_base + 8 * stage, phase);
        const uint32_t sa = sbase + stage * C::STAGE + cw * (64 * 128);
        const uint32_t sb = sbase + stage * C::STAGE + A_STAGE;
        asm volatile("wgmma.fence.sync.aligned;" ::: "memory");
        #pragma unroll
        for (int kk = 0; kk < BK / 16; kk++)
            WgmmaOp<BN>::run(acc, make_desc(sa + kk * 32, 16, 1024), make_desc(sb + kk * 2048, 8192, 1024), (kb | kk) != 0);
        asm volatile("wgmma.commit_group.sync.aligned;" ::: "memory");
        asm volatile("wgmma.wait_group.sync.aligned 1;" ::: "memory");
        if (prev_stage >= 0 && elected) release(prev_stage);
        prev_stage = stage;
        if (++stage == C::STAGES) { stage = 0; phase ^= 1; }
    }
    asm volatile("wgmma.wait_group.sync.aligned 0;" ::: "memory");
    if (elected) release(prev_stage);
}
template <int BN>
__device__ __forceinline__ void store_warp(uint32_t epi_base, uint32_t rec_base, uint32_t st_full, uint32_t st_empty, int lane,
                                           const uint8_t* tmaps, int tstride) {
    for (uint32_t it = 0;; it++) {
        mbar_wait(st_full, it & 1);
        uint64_t dst = 0, flag = 0;
        int kind = -1;
        if (lane < 8) {
            const uint32_t rec = rec_base + lane * 32;
            asm volatile("ld.volatile.shared.v2.b64 {%0, %1}, [%2];" : "=l"(dst), "=l"(flag) : "r"(rec) : "memory");
            kind = (int)lds32_volatile(rec + 16);
        }
        if (__shfl_sync(~0u, kind, 0) < 0) break;
        if (lane < 8) {
            const uint32_t buf = epi_base + lane * GemmCfg<BN>::EPI_WARP;
            #pragma unroll
            for (int q = 0; q < BN / 64; q++) {
                tma_store_2d(reinterpret_cast<const CUtensorMap*>(tmaps + (kind - 1) * tstride), buf + q * 2048,
                                  (int)(uint32_t)dst + q * 64, (int)(dst >> 32));
            }
            bulk_commit();
            bulk_wait_read_all();
            mbar_arrive(st_empty);
            if (flag) {
                bulk_wait_all();
                signal_flag(reinterpret_cast<uint32_t*>(flag));
            }
        }
        __syncwarp();
    }
    if (lane < 8) bulk_wait_all();
}

#define SCHED_AHEAD 4
template <int BN>
__global__ void __launch_bounds__(384, 1) side_gemm_kernel(const __grid_constant__ SideParams p) {
    using C = GemmCfg<BN>;
    extern __shared__ uint8_t smem_raw[];
    const uint32_t sbase = (smem_u32(smem_raw) + 1023) & ~1023u;
    const uint32_t epi_base = sbase + C::STAGES * C::STAGE;
    const uint32_t bar_base = epi_base + 8 * C::EPI_WARP;
    const uint32_t tfull = bar_base + 16 * C::STAGES, tempty = tfull + 16, tslot = tempty + 16, twant = tslot + 8;
    const uint32_t st_full = bar_base + 192, st_empty = st_full + 8, rec_base = bar_base + 256;
    const int tid = threadIdx.x, wg = tid >> 7;
    if (tid == 0) {
        for (int s = 0; s < C::STAGES; s++) { mbar_init(bar_base + 8 * s, 1); mbar_init(bar_base + 8 * (C::STAGES + s), 2); }
        for (int s = 0; s < 2; s++) { mbar_init(tfull + 8 * s, 1); mbar_init(tempty + 8 * s, 3); }
        mbar_init(twant, 1);
        mbar_init(st_full, 8);
        mbar_init(st_empty, 8);
        asm volatile("fence.mbarrier_init.release.cluster;" ::: "memory");
        pdl_launch_dependents();
    }
    __syncthreads();
    KENTER(BN == 256 ? (p.nseg == 1 ? 6 : 2) : 4);

    if (wg == 0) {
        asm volatile("setmaxnreg.dec.sync.aligned.u32 40;");
        if (tid == 0) {
            int stage = 0; uint32_t phase = 1;
            for (uint32_t it = 0;; it++) {
                mbar_wait(tfull + 8 * (it & 1), (it >> 1) & 1);
                const int code = (int)lds32_volatile(tslot + 4 * (it & 1));
                mbar_arrive(tempty + 8 * (it & 1));
                if (code < 0) break;
                const SideProb& q = p.prob[code >> 16];
                const int mt = (code >> 8) & 255, nt = code & 255;
                asm volatile("fence.proxy.async.global;" ::: "memory");
                for (int kb = 0; kb < q.k_blocks; kb++) {
                    if (kb == q.k_blocks - SCHED_AHEAD) mbar_arrive(twant);
                    mbar_wait(bar_base + 8 * (C::STAGES + stage), phase);
                    const uint32_t sa = sbase + stage * C::STAGE, fb = bar_base + 8 * stage;
                    mbar_arrive_expect_tx(fb, C::STAGE);
                    const int k0 = (nt < q.n_split ? kb : kb + q.k_blocks) * BK;
                    tma_load_2d(sa, &q.tmA, k0, mt * BM, fb);
                    tma_load_3d(sa + A_STAGE, &q.tmB, 0, k0, (nt < q.n_split ? nt : nt - q.n_split) * (BN / 64), fb);
                    if (++stage == C::STAGES) { stage = 0; phase ^= 1; }
                }
            }
        } else if (tid >= 64 && tid < 96) {
            const int lane = tid & 31;
            const SideSeg sg = p.seg[lane < p.nseg ? lane : 0];
            const SideProb& mq = p.prob[sg.prob];
            const uint32_t total = lane < p.nseg ? (sg.m1 - sg.m0) * mq.n_tiles : 0;
            for (uint32_t it = 0;; it++) {
                if (it > 0) mbar_wait_sleep(twant, (it - 1) & 1);
                int code = -1;
                for (uint32_t tries = 0;; tries++) {
                    const uint32_t head = total ? ld_relaxed_b32(p.queue + lane) : 0;
                    const uint32_t left = __ballot_sync(~0u, head < total);
                    if (!left) break;
                    bool ready = head < total;
                    if (ready && mq.dep && (left & (left - 1)))
                        ready = ld_relaxed_b32(mq.dep + (sg.m0 + head / mq.n_tiles + 1) * mq.dep_n - 1) >= mq.dep_target;
                    const uint32_t rm = __ballot_sync(~0u, ready);
                    if (rm) {
                        const int g = __ffs(rm) - 1;
                        if (lane == g) {
                            const uint32_t idx = atomicAdd(p.queue + g, 1u);
                            if (idx < total) code = (sg.prob << 16) | ((sg.m0 + idx / mq.n_tiles) << 8) | (idx % mq.n_tiles);
                        }
                        code = __shfl_sync(~0u, code, g);
                        if (code >= 0) break;
                    } else {
                        __nanosleep(200);
                    }
                    if (tries > SPIN_LIMIT) __trap();
                }
                if (code >= 0) {
                    const SideProb& q = p.prob[code >> 16];
                    if (q.dep && lane < q.dep_n) wait_flag(q.dep + ((code >> 8) & 255) * q.dep_n + lane, q.dep_target);
                    __syncwarp();
                }
                if (lane == 0) {
                    mbar_wait(tempty + 8 * (it & 1), ((it >> 1) & 1) ^ 1);
                    asm volatile("st.shared.b32 [%0], %1;" ::"r"(tslot + 4 * (it & 1)), "r"(code) : "memory");
                    mbar_arrive(tfull + 8 * (it & 1));
                }
                __syncwarp();
                if (code < 0) break;
            }
        } else if (tid >= 32 && tid < 64) {
            store_warp<BN>(epi_base, rec_base, st_full, st_empty, tid & 31, reinterpret_cast<const uint8_t*>(&p.prob[0].tmC),
                           (int)sizeof(SideProb));
        }
    } else {
        asm volatile("setmaxnreg.inc.sync.aligned.u32 232;");
        const int cw = wg - 1, lane = tid & 31, wi = (tid >> 5) & 3;
        const bool elected = (tid & 127) == 0;
        int stage = 0; uint32_t phase = 0;
        float acc[BN / 2];
        EpiCtx ectx = {epi_base + (cw * 4 + wi) * C::EPI_WARP, rec_base + (cw * 4 + wi) * 32, st_full, st_empty, 0, lane};
        for (uint32_t it = 0;; it++) {
            mbar_wait(tfull + 8 * (it & 1), (it >> 1) & 1);
            const int code = (int)lds32_volatile(tslot + 4 * (it & 1));
            named_bar_sync(1 + cw, 128);
            if (elected) mbar_arrive(tempty + 8 * (it & 1));
            if (code < 0) break;
            const SideProb& q = p.prob[code >> 16];
            const int mt = (code >> 8) & 255, nt = code & 255;
            gemm_mainloop<BN>(acc, q.k_blocks, sbase, bar_base, cw, elected, stage, phase);
            const int row0 = mt * BM + cw * 64 + wi * 16, ntc = nt < q.n_split ? nt : nt - q.n_split;
            if (BN == 128 && q.part) {
                const int idx = (mt & 3) * q.n_split + ntc;
                float4* part = reinterpret_cast<float4*>(q.part) + (size_t)idx * (BM * BN / 4) + (tid - 128);
                if (nt < q.n_split) {
                    #pragma unroll
                    for (int j = 0; j < BN / 8; j++) __stcg(part + j * 256, make_float4(acc[4 * j], acc[4 * j + 1], acc[4 * j + 2], acc[4 * j + 3]));
                    __syncwarp();
                    if (lane == 0) signal_flag(q.part_flag + idx);
                    continue;
                }
                if (lane == 0) wait_flag(q.part_flag + idx, 8);
                __syncwarp();
                #pragma unroll
                for (int j = 0; j < BN / 8; j++) {
                    const float4 v = __ldcg(part + j * 256);
                    acc[4 * j] += v.x; acc[4 * j + 1] += v.y; acc[4 * j + 2] += v.z; acc[4 * j + 3] += v.w;
                }
            }
            epi_hand_over(acc, ectx, ((uint64_t)row0 << 32) | (uint32_t)(q.c_col0 + ntc * BN), q.sig ? (uint64_t)(q.sig + mt) : 0, 1 + (code >> 16));
        }
        epi_exit(ectx);
        if (elected) KEXIT(BN == 256 ? (p.nseg == 1 ? 6 : 2) : 4);
    }
}

constexpr int FIN_SPLIT = 8, FIN_KB = HD / BK / FIN_SPLIT;
constexpr int FIN_A1 = FIN_KB * 16384;
constexpr int FIN_A0 = FIN_A1 + FIN_KB * 8192;
constexpr int FIN_BAR = FIN_A0 + 4 * 8192, FIN_SMEM = FIN_BAR + 256;
enum { FB_B = 0, FB_A1 = 64, FB_A0 = 128, FB_E0 = 160, FB_RDY = 192, FB_RED = 208 };
struct FinalParams {
    CUtensorMap tmA, tmB;
    __nv_bfloat16* out;
    const uint32_t* dep;
    uint32_t dep_target;
    int mt;
};
__global__ void __launch_bounds__(384, 1) final_gemm_kernel(const __grid_constant__ FinalParams p) {
    extern __shared__ __align__(1024) uint8_t smem_raw[];
    const uint32_t sbase = smem_u32(smem_raw), bar = sbase + FIN_BAR;
    const int tid = threadIdx.x, wg = tid >> 7;
    const int rank = blockIdx.x % FIN_SPLIT, nt = blockIdx.x / FIN_SPLIT;
    KENTER(5);
    if (tid == 0) {
        for (int s = 0; s < FIN_KB; s++) { mbar_init(bar + FB_B + 8 * s, 1); mbar_init(bar + FB_A1 + 8 * s, 1); }
        for (int s = 0; s < 4; s++) { mbar_init(bar + FB_A0 + 8 * s, 1); mbar_init(bar + FB_E0 + 8 * s, 1); }
        for (int h = 0; h < 2; h++) { mbar_init(bar + FB_RDY + 8 * h, FIN_SPLIT); mbar_init(bar + FB_RED + 8 * h, 1); }
        asm volatile("fence.mbarrier_init.release.cluster;" ::: "memory");
        for (int h = 0; h < 2; h++) mbar_arrive_expect_tx(bar + FB_RED + 8 * h, (FIN_SPLIT - 1) * 4096);
        pdl_launch_dependents();
    }
    __syncthreads();
    asm volatile("barrier.cluster.arrive.relaxed.aligned;" ::: "memory");
    if (wg == 0) {
        auto need = [&](int i) {
            uint32_t n = 0;
            while (ld_acquire_b32(p.dep + i) < p.dep_target) { if (++n > SPIN_LIMIT) __trap(); }
            asm volatile("fence.proxy.async.global;" ::: "memory");
        };
        auto a_load = [&](uint32_t dst, int kb, int seg, uint32_t mb) { tma_load_2d(dst, &p.tmA, (rank * FIN_KB + kb) * BK, p.mt * BM + seg * SEG, mb); };
        if (tid == 0) {
            for (int kb = 0; kb < FIN_KB; kb++) {
                mbar_arrive_expect_tx(bar + FB_B + 8 * kb, 16384);
                tma_load_3d(sbase + kb * 16384, &p.tmB, 0, (rank * FIN_KB + kb) * BK, nt * 2, bar + FB_B + 8 * kb);
            }
        } else if (tid == 32) {
            need(0);
            need(1);
            for (int kb = 0; kb < FIN_KB; kb++) {
                if (kb >= 4) mbar_wait(bar + FB_E0 + 8 * (kb & 3), 0);
                mbar_arrive_expect_tx(bar + FB_A0 + 8 * (kb & 3), 8192);
                for (int u = 0; u < 2; u++) a_load(sbase + FIN_A0 + (kb & 3) * 8192 + u * 4096, kb, u, bar + FB_A0 + 8 * (kb & 3));
            }
        } else if (tid == 64) {
            need(2);
            for (int kb = 0; kb < FIN_KB; kb++) {
                mbar_arrive_expect_tx(bar + FB_A1 + 8 * kb, 8192);
                a_load(sbase + FIN_A1 + kb * 8192, kb, 2, bar + FB_A1 + 8 * kb);
            }
            need(3);
            KMARK(15);
            for (int kb = 0; kb < FIN_KB; kb++) a_load(sbase + FIN_A1 + kb * 8192 + 4096, kb, 3, bar + FB_A1 + 8 * kb);
        }
        __syncwarp();
        asm volatile("barrier.cluster.wait.aligned;" ::: "memory");
    } else {
        const int h = wg - 1, lane = tid & 31, wi = (tid >> 5) & 3, t128 = tid & 127;
        asm volatile("barrier.cluster.wait.aligned;" ::: "memory");
        float acc[64];
        for (int kb = 0; kb < FIN_KB; kb++) {
            mbar_wait(bar + FB_B + 8 * kb, 0);
            if (h == 0) mbar_wait(bar + FB_A0 + 8 * (kb & 3), kb >> 2); else mbar_wait(bar + FB_A1 + 8 * kb, 0);
            const uint32_t sa = sbase + (h == 0 ? FIN_A0 + (kb & 3) * 8192 : FIN_A1 + kb * 8192), sb = sbase + kb * 16384;
            asm volatile("wgmma.fence.sync.aligned;" ::: "memory");
            #pragma unroll
            for (int kk = 0; kk < BK / 16; kk++)
                wgmma_m64n128k16(acc, make_desc(sa + kk * 32, 16, 1024), make_desc(sb + kk * 2048, 8192, 1024), (kb | kk) != 0);
            asm volatile("wgmma.commit_group.sync.aligned;" ::: "memory");
            asm volatile("wgmma.wait_group.sync.aligned 1;" ::: "memory");
            if (h == 0 && kb >= 1 && kb <= 4 && t128 == 0) mbar_arrive(bar + FB_E0 + 8 * (kb - 1));
        }
        asm volatile("wgmma.wait_group.sync.aligned 0;" ::: "memory");
        const uint32_t red = sbase + (h == 0 ? FIN_A0 : FIN_A1);
        named_bar_sync(1 + h, 128);
        if (tid == 256) KMARK(16);
        if (tid == 128) KMARK(19);
        if (t128 < FIN_SPLIT)
            asm volatile("mbarrier.arrive.relaxed.cluster.shared::cluster.b64 _, [%0];" ::"r"(mapa(bar + FB_RDY + 8 * h, t128)) : "memory");
        mbar_wait(bar + FB_RDY + 8 * h, 0);
        if (tid == 256) KMARK(17);
        #pragma unroll
        for (int q = 0; q < FIN_SPLIT; q++) {
            if (q != rank) {
                const uint32_t dst = mapa(red + (rank - (rank > q ? 1 : 0)) * 4096 + t128 * 16, q), rb = mapa(bar + FB_RED + 8 * h, q);
                #pragma unroll
                for (int j = 0; j < 2; j++)
                    asm volatile("st.async.weak.shared::cluster.mbarrier::complete_tx::bytes.v4.f32 [%0], {%1,%2,%3,%4}, [%5];"
                                 ::"r"(dst + j * 2048), "f"(acc[8 * q + 4 * j]), "f"(acc[8 * q + 4 * j + 1]),
                                   "f"(acc[8 * q + 4 * j + 2]), "f"(acc[8 * q + 4 * j + 3]), "r"(rb) : "memory");
            }
        }
        float o[8];
        #pragma unroll
        for (int q = 0; q < FIN_SPLIT; q++)
            if (q == rank) {
                #pragma unroll
                for (int e = 0; e < 8; e++) o[e] = acc[8 * q + e];
            }
        mbar_wait(bar + FB_RED + 8 * h, 0);
        if (tid == 256) KMARK(18);
        if (tid == 128) KMARK(20);
        #pragma unroll
        for (int sl = 0; sl < FIN_SPLIT - 1; sl++) {
            #pragma unroll
            for (int j = 0; j < 2; j++) {
                const uint4 v = lds128(red + sl * 4096 + j * 2048 + t128 * 16);
                o[4 * j] += __uint_as_float(v.x); o[4 * j + 1] += __uint_as_float(v.y);
                o[4 * j + 2] += __uint_as_float(v.z); o[4 * j + 3] += __uint_as_float(v.w);
            }
        }
        __nv_bfloat16* dst = p.out + (size_t)(p.mt * BM + h * 64 + wi * 16 + (lane >> 2)) * (2 * DM) + nt * 128 + rank * 16 + (lane & 3) * 2;
        #pragma unroll
        for (int j = 0; j < 2; j++) {
            *reinterpret_cast<uint32_t*>(dst + j * 8) = pack_bf16(o[4 * j], o[4 * j + 1]);
            *reinterpret_cast<uint32_t*>(dst + (size_t)8 * (2 * DM) + j * 8) = pack_bf16(o[4 * j + 2], o[4 * j + 3]);
        }
        if (t128 == 0) KEXIT(5);
    }
}

#define POLL_DELAY 7
#define FETCH_DELAY 300
#define AT_PF 7
#define TOK_MOVED1 4
#define AT_POS0 0
#define SPEC_SUM 0
#define AT_FIRST 4
#define AT_AHEAD 4
#define PDL_POS 3
#define WO_FENCE 0
#define WO_PFA 5
#define WO_PFB_DELAY 60
#define EXP 0
#define NO_COMM 0
#define TOK_MOVED 8
#define XB_DELAY 50
#define WO_PF0 0
#define WO_PF1 11
#define WO_AHEAD 10
constexpr int REC_THREADS = 256;
constexpr uint32_t POLL_LIMIT = 1u << 16;
constexpr int NREG = 24;
__host__ __device__ constexpr int reg_idx(int j) { return ((j & 3) - 1) * 8 + (j >> 2); }
constexpr int SM_WQ = 0;
constexpr int SM_WO = 65536;
constexpr int SM_X = SM_WO + 11 * 8192;
constexpr int SM_PARK0 = SM_X, SM_PARK1 = SM_X + 8192;
constexpr int SM_MEM = SM_X + 4 * 4096;
constexpr int SM_RED = SM_X + 8 * 4096;
constexpr int SM_V = SM_X + 12 * 4096;
constexpr int SM_K = SM_X + 14 * 4096;
constexpr int SM_QS = SM_X + 15 * 4096;
constexpr int SM_QK = SM_X + 65536;
constexpr int SM_SP = SM_QK + 2048;
constexpr int SM_VM = SM_SP + 2560;
constexpr int SM_O = SM_VM + 2048;
constexpr int SM_SUM = SM_O + 2048;
constexpr int SM_TBL = SM_SUM + 128;
constexpr int SM_BAR = SM_TBL + 512;
constexpr int SM_STAMP = SM_BAR + 192;
constexpr int REC_SMEM = SM_STAMP;
static_assert(REC_SMEM <= 232448, "shared memory");
enum { BAR_V = 0, BAR_X = 8, BAR_P0 = 16, BAR_WQ = 40, BAR_WO = 48, BAR_XG = 56, BAR_F0 = 88, BAR_F3 = 96, BAR_VF = 104,
       BAR_M = 112, BAR_GO = 144, BAR_PK = 152, BAR_VM = 160, BAR_SELF = 176, BAR_MIN = 184 };

template <int V> struct IntC { static constexpr int value = V; };
template <int I, int N, typename F> __device__ __forceinline__ void sfor(F&& f) {
    if constexpr (I < N) { f(IntC<I>{}); sfor<I + 1, N>(f); }
}

struct RecParams {
    CUtensorMap tmW[3];
    CUtensorMap tmWo;
    CUtensorMap tmX;
    const __nv_bfloat16* mem0;
    __nv_bfloat16* qkv_tok;
    __nv_bfloat16* kv_mem;
    uint8_t* xchg;
    uint32_t* flags;
    uint32_t one[2];
    uint32_t* arrivals;
};

__device__ __forceinline__ void mma_a(float* d, const uint32_t* a, uint32_t b0, uint32_t b1) {
    mma16816(d, a[0], a[1], a[2], a[3], b0, b1);
}
__device__ __forceinline__ void ldsm4(uint32_t addr, uint32_t* r) { ldsm_x4(addr, r[0], r[1], r[2], r[3]); }
__device__ __forceinline__ void ldsm4t(uint32_t addr, uint32_t* r) { ldsm_x4_t(addr, r[0], r[1], r[2], r[3]); }
template <int OFF> __device__ __forceinline__ void poll_v2(uint2& v, const uint8_t* p) {
    asm volatile("ld.relaxed.gpu.global.v2.b32 {%0,%1}, [%2+%3];" : "=r"(v.x), "=r"(v.y) : "l"(p), "n"(OFF) : "memory");
}
__device__ __forceinline__ uint32_t max3(uint32_t a, uint32_t b, uint32_t c) { return max(max(a, b), c); }
__device__ __forceinline__ uint32_t pub_slot(int s) { return (s & 1) * XCHG_SLOT + ((s >> 1) & 1) * PUB_BYTES; }

__device__ __forceinline__ uint8_t* xaddr(uint32_t lo, uint32_t hi) {
    uint64_t a;
    asm("mov.b64 %0, {%1, %2};" : "=l"(a) : "r"(lo), "r"(hi));
    return reinterpret_cast<uint8_t*>(a);
}
template <int N> __device__ __forceinline__ uint32_t delay_zero(uint32_t a) {
    uint32_t x = a;
    #pragma unroll
    for (int i = 0; i < N; i++) x = lds32_volatile(x);
    return x - a;
}
__device__ __forceinline__ uint32_t fresh(uint32_t x) { asm volatile("" : "+r"(x)); return x; }

template <int NT> __device__ __forceinline__ uint32_t wo_addr(uint32_t ao, uint32_t a3, int n) {
    return (n % NT == 2 ? a3 : ao + (n % NT) * 32768) + (n / NT) * 1024;
}
__device__ __forceinline__ void sched_fence(uint32_t& x, uint32_t zero) { x ^= clock32() & zero; }
template <int NT, int PF>
__device__ __forceinline__ void wo_phase(uint32_t (&st)[8 * NT][4], uint32_t ao, uint32_t a3, uint32_t l16, uint32_t tbl, uint32_t sums,
                                         uint32_t slot, uint32_t xhi, uint32_t third, uint32_t zero, uint32_t& tok, uint32_t xbar, uint32_t xpar, bool& x_ok) {
    constexpr int AHEAD = PF > WO_AHEAD ? PF - NT : WO_AHEAD;
    uint32_t of[4][4];
    uint2 sm;
    uint4 t;
    ldsm4t(l16 + SM_O, of[0]);
    #pragma unroll
    for (int n = PF; n < AHEAD; n++) {
        ldsm4t(wo_addr<NT>(ao, a3, n), st[n]);
        if (n == 2 * NT - 1) ldsm4t(l16 + SM_O + 512, of[1]);
    }
    if (PF >= 2 * NT) ldsm4t(l16 + SM_O + 512, of[1]);
    float acc[NT][4];
    #pragma unroll
    for (int i = 0; i < NT; i++) { acc[i][0] = acc[i][1] = acc[i][2] = acc[i][3] = 0.f; }
    #pragma unroll
    for (int kk = 0; kk < 8; kk++) {
        if (WO_FENCE && kk < 7) sched_fence(tok, zero);
        #pragma unroll
        for (int i = 0; i < NT; i++) {
            const int n = kk * NT + i;
            mma_a(acc[i], st[n], of[kk >> 1][(kk & 1) * 2], of[kk >> 1][(kk & 1) * 2 + 1]);
            if (n + AHEAD >= PF && n + AHEAD < 8 * NT) ldsm4t(wo_addr<NT>(ao, a3, n + AHEAD), st[n + AHEAD]);
        }
        if (kk == 1 || kk == 3) ldsm4t(l16 + SM_O + ((kk >> 1) + 2) * 512, of[(kk >> 1) + 2]);
        if (kk == (NT == 3 ? 5 : 4)) {
            const uint32_t x = fresh(l16);
            sm = lds64(sums + ((x >> 1) & 0x18));
            t = lds128(tbl + ((x >> 3) & 0x30));
            x_ok = mbar_test_wait(xbar, xpar);
        }
    }
    const float i0 = rcp(__uint_as_float(sm.x)), i1 = rcp(__uint_as_float(sm.y));
    const uint32_t d = slot + ((fresh(l16) >> 1) & 0x38);
    const uint32_t pl[3] = {t.x + d, t.y + d, t.z + d};
    #pragma unroll
    for (int i = 0; i < NT; i++)
        asm volatile("{\n.reg .pred p;\nsetp.ne.u32 p, %3, 0;\n@p st.relaxed.gpu.global.v2.b32 [%0], {%1,%2};\n}"
                     ::"l"(xaddr(pl[i], xhi)), "r"(pack_bf16(acc[i][0] * i0, acc[i][1] * i1)), "r"(pack_bf16(acc[i][2] * i0, acc[i][3] * i1)),
                       "r"(i < 2 ? 1u : third) : "memory");
}

constexpr uint32_t SMEM_ORIGIN = 1024;
constexpr uint64_t DESC_BASE = (1ull << 16) | (0x40000040ull << 32);
template <int OFFB, int SCALE_D>
__device__ __forceinline__ void wgmma_n32_rs(float (&d)[16], const uint32_t* a, uint32_t one) {
    asm volatile(
        "{\n.reg .b64 db;\nmad.wide.u32 db, %20, %21, %22;\n"
        "wgmma.mma_async.sync.aligned.m64n32k16.f32.bf16.bf16 {%0,%1,%2,%3,%4,%5,%6,%7,%8,%9,%10,%11,%12,%13,%14,%15}, "
        "{%16,%17,%18,%19}, db, %23, 1, 1, 0;\n}"
        : "+f"(d[0]), "+f"(d[1]), "+f"(d[2]), "+f"(d[3]), "+f"(d[4]), "+f"(d[5]), "+f"(d[6]), "+f"(d[7]),
          "+f"(d[8]), "+f"(d[9]), "+f"(d[10]), "+f"(d[11]), "+f"(d[12]), "+f"(d[13]), "+f"(d[14]), "+f"(d[15])
        : "r"(a[0]), "r"(a[1]), "r"(a[2]), "r"(a[3]), "r"(one), "n"((SMEM_ORIGIN + OFFB) >> 4), "l"(DESC_BASE), "n"(SCALE_D));
}
template <int OFFA, int OFFB, int SCALE_D>
__device__ __forceinline__ void wgmma_n32_ss(float (&d)[16], uint32_t one) {
    asm volatile(
        "{\n.reg .b64 da, db;\nmad.wide.u32 da, %16, %17, %19;\nmad.wide.u32 db, %16, %18, %19;\n"
        "wgmma.mma_async.sync.aligned.m64n32k16.f32.bf16.bf16 {%0,%1,%2,%3,%4,%5,%6,%7,%8,%9,%10,%11,%12,%13,%14,%15}, "
        "da, db, %20, 1, 1, 1, 0;\n}"
        : "+f"(d[0]), "+f"(d[1]), "+f"(d[2]), "+f"(d[3]), "+f"(d[4]), "+f"(d[5]), "+f"(d[6]), "+f"(d[7]),
          "+f"(d[8]), "+f"(d[9]), "+f"(d[10]), "+f"(d[11]), "+f"(d[12]), "+f"(d[13]), "+f"(d[14]), "+f"(d[15])
        : "r"(one), "n"((SMEM_ORIGIN + OFFA) >> 4), "n"((SMEM_ORIGIN + OFFB) >> 4), "l"(DESC_BASE), "n"(SCALE_D));
}
template <int WG, int J0, int J1, int I, bool ACC, bool FENCE = true>
__device__ __forceinline__ void token_mma(float (&ta)[2][16], const uint32_t (&wr)[NREG][2][4], uint32_t one) {
    if (FENCE) asm volatile("wgmma.fence.sync.aligned;" ::: "memory");
    sfor<J0, J1>([&](auto J) {
        constexpr int j = J.value, c = j >> 2, offb = SM_X + WG * 32768 + c * 4096 + (j & 3) * 32, sc = (ACC || j != J0) ? 1 : 0;
        if constexpr ((j & 3) != 0) wgmma_n32_rs<offb, sc>(ta[I], wr[reg_idx(j)][I], one);
        else if constexpr (WG == 0 || c >= (I ? TOK_MOVED1 : TOK_MOVED)) wgmma_n32_ss<SM_WQ + WG * 32768 + I * 16384 + c * 2048, offb, sc>(ta[I], one);
        constexpr int m = I ? c : c - 4;
        if constexpr (WG == 0 && (j & 3) == 1 && m >= 0 && m < (I ? TOK_MOVED : TOK_MOVED1))
            wgmma_n32_ss<SM_WQ + 32768 + (1 - I) * 16384 + m * 2048, SM_X + 32768 + m * 4096, 1>(ta[I], one);
    });
    asm volatile("wgmma.commit_group.sync.aligned;" ::: "memory");
}
__device__ __forceinline__ void warp_arrive(uint32_t bar) {
    __syncwarp();
    if (elect_one()) mbar_arrive(bar);
}
__device__ __forceinline__ void remote_arrive(uint32_t bar, uint32_t rank) {
    asm volatile("mbarrier.arrive.relaxed.cluster.shared::cluster.b64 _, [%0];" ::"r"(mapa(bar, rank)) : "memory");
}
__device__ __forceinline__ void x_load(const RecParams& p, uint32_t sb, int sg, int g) {
    if ((EXP >> g) & 1) return;
    tma_load_3d_mc(sb + SM_X + g * 16384, &p.tmX, 0, sg * SEG, g * 4, sb + SM_BAR + BAR_XG + 8 * g, (uint16_t)7);
}

__device__ __forceinline__ void rec_steps(const RecParams& p, const uint32_t (&wr)[NREG][2][4], const uint32_t sb, const int warp,
                                          const int cta, const int head, const int rank) {
    const int wq = warp & 3, wg = warp >> 2;
    const uint32_t bar = sb + SM_BAR;
    const uint32_t xhi = (uint32_t)((uint64_t)p.xchg >> 32);
    const float sl2 = 0.08838834764831845f * 1.4426950408889634f;
    const bool has_unit = warp >= 5 && (warp < 7 || cta < 64);
    const bool qk = rank < 2;
    const uint32_t pa = rank == 2 ? 0 : rank + 1, pb = rank == 0 ? 2 : rank - 1;
    const uint32_t tbl = sb + SM_TBL + warp * 64;
    const bool att = (warp & 6) == 2;
    const int stile = warp < 5 ? warp : warp - 3;

    const uint32_t u_st = uniform(SM_QK - SM_WQ - wg * (32768 - 1024));
    const uint32_t u_xa = uniform(sb + (qk ? SM_SP + rank * 1280 + stile * 256 : SM_VM + warp * 256));
    const uint32_t u_key = uniform(!qk || att || warp == 7 ? 0 : sb + (warp == 4 ? SM_QK + 1024 : SM_K + stile * 1024));
    const uint32_t u_bx = uniform(bar + (qk ? BAR_X : BAR_VM)), u_bra = uniform(mapa(u_bx, pa)), u_brb = uniform(mapa(u_bx, pb));
    const uint32_t u_src = uniform(lds32_volatile(tbl + 44));
    const uint32_t u_kv = uniform(qk && wg == 0 ? ~0u : (((rank >> 1) * NSEG * NH + head) * 8 + (qk ? rank * 4 + wq : warp)) * 64);
    const uint32_t u_free = uniform(mapa(bar + (warp == 5 ? BAR_VF : BAR_F0), warp == 5 ? 2 : 0));
    const uint32_t u_role = uniform((has_unit ? 1 : 0) | (att ? 2 : 0) | (warp != 1 || rank == 0 ? 4 : 0) | (!qk && warp == 0 ? 8 : 0) | (rank != 0 && warp == 1 ? 16 : 0) |
                                    (warp == 5 || warp == 6 ? 32 : 0));
    uint32_t l16, aq, ao;
    {
        const int lane = threadIdx.x & 31, mi = lane >> 3, r8 = lane & 7, r16 = (mi >> 1) * 8 + r8;
        l16 = opaque(sb + lane * 16);
        aq = opaque(sb + SM_WQ + wg * 32768 + r16 * 128 + (((wq * 2 + (mi & 1)) ^ r8) << 4));
        ao = opaque(sb + SM_WO + (warp >> 1) * 8192 + r16 * 64 + ((((warp & 1) * 2 + (mi & 1)) ^ ((r8 >> 1) & 3)) << 4));
    }

    uint32_t mphase = 0;
    bool x0_ok = false;
    #pragma unroll 1
    for (int s = 0;; s++) {
        const uint32_t par = s & 1;
        uint32_t at[16][4];
        auto at_early = [](int i) { return i < 2 || ((i & 1) == 1 && (i >> 1) <= AT_PF - 2); };
        auto at_prefetch = [&](bool first) {
            #pragma unroll
            for (int i = 0; i < 16; i++)
                if (at_early(i) && first == ((i & 1) == 1 && (i >> 1) < AT_FIRST)) ldsm4t(aq + (i & 1) * 16384 + (i >> 1) * 2048, at[i]);
        };
        if (wg == 0) {
            float ta[2][16];
            if (!x0_ok) mbar_wait_bounded(bar + BAR_XG, par);
            STAMP(6);
            auto park = [&](int i, uint32_t dst) {
                #pragma unroll
                for (int e = 0; e < 16; e++) asm volatile("" : "+f"(ta[i][e]));
                #pragma unroll
                for (int j = 0; j < 4; j++)
                    sts128(l16 + dst + j * 2048 + wq * 512, __float_as_uint(ta[i][4 * j]), __float_as_uint(ta[i][4 * j + 1]),
                           __float_as_uint(ta[i][4 * j + 2]), __float_as_uint(ta[i][4 * j + 3]));
            };
            token_mma<0, 0, 16, 0, false>(ta, wr, 1);
            mbar_wait_bounded(bar + BAR_XG + 8, par);
            if (TOK_MOVED1 > 0) mbar_wait_bounded(bar + BAR_XG + 16, par);
            if (AT_POS0 == 0) at_prefetch(true);
            token_mma<0, 16, 32, 0, true>(ta, wr, p.one[1]);
            if (TOK_MOVED1 == 0) mbar_wait_bounded(bar + BAR_XG + 16, par);
            token_mma<0, 0, 16, 1, false, TOK_MOVED1 == 0>(ta, wr, p.one[0]);
            if (TOK_MOVED > 4) mbar_wait_bounded(bar + BAR_XG + 24, par);
            token_mma<0, 16, 32, 1, true, (TOK_MOVED > 4)>(ta, wr, 1);
            asm volatile("wgmma.wait_group.sync.aligned 1;" ::: "memory");
            park(0, SM_PARK0);
            warp_arrive(bar + BAR_GO);
            asm volatile("wgmma.wait_group.sync.aligned 0;" ::: "memory");
            park(1, SM_PARK1);
            if (TOK_MOVED <= 4) mbar_wait_bounded(bar + BAR_XG + 24, par);
            warp_arrive(bar + BAR_PK);
            const uint8_t* src = xaddr(u_src + pub_slot(s), xhi);
            auto fetch = [&]() {
                if (elect_one()) {
                    mbar_arrive_expect_tx(bar + BAR_M + 8 * wq, 4096);
                    bulk_load(sb + SM_MEM + wq * 4096, src, 4096, bar + BAR_M + 8 * wq);
                }
            };
            named_bar_sync(7, REC_THREADS - 32);
            spin_clks(FETCH_DELAY);
            fetch();
            STAMP(12);
            if (warp == 0 && elect_one()) {
                if (qk) mbar_arrive_expect_tx(bar + BAR_V, (EXP & 16) ? 32 : 8192);
                mbar_arrive_expect_tx(bar + BAR_X, qk ? 1280 : 2560);
                mbar_arrive_expect_tx(bar + BAR_VM, qk ? 2048 : 0);
            }
            if (AT_POS0 == 1) at_prefetch(true);
            at_prefetch(false);
            const uint32_t x = fresh(l16) - sb;
            const uint32_t ca = sb + SM_MEM + wq * 4096 + x * 2 + ((x >> 4) & 0x1C);
            #pragma unroll 1
            for (uint32_t n = 0; n < POLL_LIMIT; n++) {
                mbar_wait_bounded(bar + BAR_M + 8 * wq, mphase);
                mphase ^= 1;
                const uint32_t c0 = lds32_volatile(ca), c1 = lds32_volatile(ca + 1024), c2 = lds32_volatile(ca + 2048), c3 = lds32_volatile(ca + 3072);
                if (!__any_sync(~0u, max(max3(c0, c1, c2), c3) == (NO_COMM ? 0x12345u : SENT))) break;
                fetch();
            }
            STAMP(0);
            named_bar_sync(0, REC_THREADS);
            if (u_role & 8) {
                asm volatile("fence.proxy.async.shared::cta;" ::: "memory");
                mbar_wait_bounded(bar + BAR_VF, par);
                if (elect_one()) {
                    #pragma unroll
                    for (int r = 0; r < 2; r++)
                        asm volatile("cp.async.bulk.shared::cluster.shared::cta.mbarrier::complete_tx::bytes [%0], [%1], %2, [%3];"
                                     ::"r"(mapa(sb + SM_V, r)), "r"(sb + SM_V), "r"((EXP & 16) ? 32 : 8192), "r"(mapa(bar + BAR_V, r)) : "memory");
                }
            }
        } else {
            at_prefetch(true);
            if (s > 0) {
                if (u_role & 1) {
                    const uint32_t ln = (fresh(l16) >> 4) & 31;
                    const uint32_t ibl = lds32_volatile(tbl + 12) + (par ^ 1) * XCHG_SLOT + ln * 8;
                    const uint32_t publ = lds32_volatile(tbl + 28) + pub_slot(s) + (ln & 16) * 256 + (ln & 8) * 16 + (ln & 7) * 4;
                    const bool odd = ln & 8;
                    const uint8_t* ib = xaddr(ibl + delay_zero<POLL_DELAY>(bar + BAR_SELF), xhi);
                    STAMP(8);
                    uint2 v[8];
                    float a0, a1, a2, a3;
                    auto sum8 = [&]() {
                        a0 = ((bf16_lo(v[0].x) + bf16_lo(v[1].x)) + (bf16_lo(v[2].x) + bf16_lo(v[3].x))) +
                             ((bf16_lo(v[4].x) + bf16_lo(v[5].x)) + (bf16_lo(v[6].x) + bf16_lo(v[7].x)));
                        a1 = ((bf16_hi(v[0].x) + bf16_hi(v[1].x)) + (bf16_hi(v[2].x) + bf16_hi(v[3].x))) +
                             ((bf16_hi(v[4].x) + bf16_hi(v[5].x)) + (bf16_hi(v[6].x) + bf16_hi(v[7].x)));
                        a2 = ((bf16_lo(v[0].y) + bf16_lo(v[1].y)) + (bf16_lo(v[2].y) + bf16_lo(v[3].y))) +
                             ((bf16_lo(v[4].y) + bf16_lo(v[5].y)) + (bf16_lo(v[6].y) + bf16_lo(v[7].y)));
                        a3 = ((bf16_hi(v[0].y) + bf16_hi(v[1].y)) + (bf16_hi(v[2].y) + bf16_hi(v[3].y))) +
                             ((bf16_hi(v[4].y) + bf16_hi(v[5].y)) + (bf16_hi(v[6].y) + bf16_hi(v[7].y)));
                    };
                    #pragma unroll 1
                    for (uint32_t n = 0; n < POLL_LIMIT; n++) {
                        sfor<0, 8>([&](auto I) { poll_v2<I.value * 256>(v[I.value], ib); });
                        const uint32_t mx = max(max3(v[0].y, v[1].y, v[2].y), max3(max3(v[3].y, v[4].y, v[5].y), v[6].y, v[7].y));
                        if (SPEC_SUM) { sum8(); asm volatile("" : "+f"(a0), "+f"(a1), "+f"(a2), "+f"(a3)); }
                        if (!__any_sync(~0u, mx == (NO_COMM ? 0x12345u : SENT))) break;
                    }
                    if (!SPEC_SUM) sum8();
                    float k0 = odd ? a2 : a0, k1 = odd ? a3 : a1;
                    k0 += __shfl_xor_sync(~0u, odd ? a0 : a2, 8);
                    k1 += __shfl_xor_sync(~0u, odd ? a1 : a3, 8);
                    k0 += __shfl_xor_sync(~0u, k0, 16);
                    k1 += __shfl_xor_sync(~0u, k1, 16);
                    st_relaxed_b32(xaddr(publ, xhi), pack_bf16(k0, k1));
                    STAMP(11);
                } else if (warp == 4) {
                    bulk_wait_read_all();
                    if (elect_one()) remote_arrive(bar + BAR_F3, 2);
                    if (!qk) {
                        mbar_wait_bounded(bar + BAR_F3, par ^ 1);
                        if (elect_one()) x_load(p, sb, s, 3);
                    }
                    if (elect_one()) {
                        bulk_wait_all();
                        signal_flag(p.flags + F_PROGRESS + s - 1);
                    }
                    __syncwarp();
                    STAMP(10);
                }
            }
            float ta[2][16];
            uint32_t w[8];
            auto unpark = [&](int i, uint32_t src) {
                mbar_wait_bounded(bar + (i ? BAR_GO : BAR_PK), par);
                #pragma unroll
                for (int j = 0; j < 4; j++) {
                    const uint4 v = lds128(l16 + src + j * 2048 + wq * 512);
                    ta[i][4 * j] = __uint_as_float(v.x); ta[i][4 * j + 1] = __uint_as_float(v.y);
                    ta[i][4 * j + 2] = __uint_as_float(v.z); ta[i][4 * j + 3] = __uint_as_float(v.w);
                }
            };
            if (warp != 4) named_bar_arrive(7, REC_THREADS - 32);
            unpark(1, SM_PARK0);
            STAMP(6);
            token_mma<1, 0, 16, 1, true>(ta, wr, 1);
            unpark(0, SM_PARK1);
            token_mma<1, 16, 32, 1, true>(ta, wr, 1);
            token_mma<1, 16, 32, 0, true>(ta, wr, 1);
            token_mma<1, 0, 16, 0, true, false>(ta, wr, 1);
            auto put_tile = [&](int m, const uint32_t (&q)[8]) {
                #pragma unroll
                for (int h = 0; h < 2; h++) {
                    if (qk) asm volatile("stmatrix.sync.aligned.m8n8.x4.trans.shared.b16 [%0], {%1,%2,%3,%4};"
                                         ::"r"(aq - (SM_WQ + 32768) + (m ? SM_K : SM_QS) + h * 2048), "r"(q[4 * h]), "r"(q[4 * h + 1]),
                                           "r"(q[4 * h + 2]), "r"(q[4 * h + 3]) : "memory");
                    else sts128(l16 + SM_V + wq * 2048 + m * 1024 + h * 512, q[4 * h], q[4 * h + 1], q[4 * h + 2], q[4 * h + 3]);
                }
            };
            auto pack_tile = [&](int i) {
                #pragma unroll
                for (int e = 0; e < 16; e++) asm volatile("" : "+f"(ta[i][e]));
                #pragma unroll
                for (int j = 0; j < 8; j++) w[j] = pack_bf16(ta[i][2 * j], ta[i][2 * j + 1]);
            };
            asm volatile("wgmma.wait_group.sync.aligned 2;" ::: "memory");
            pack_tile(1);
            at_prefetch(false);
            asm volatile("wgmma.wait_group.sync.aligned 1;" ::: "memory");
            if ((u_role & 32) && elect_one())
                asm volatile("mbarrier.arrive.relaxed.cluster.shared::cluster.b64 _, [%0];" ::"r"(u_free) : "memory");
            put_tile(0, w);
            asm volatile("wgmma.wait_group.sync.aligned 0;" ::: "memory");
            pack_tile(0);
            put_tile(1, w);
            STAMP(0);
            named_bar_sync(0, REC_THREADS);
            STAMP(14);
        }
        const uint32_t mb = l16 + SM_MEM + wg * 8192;
        float acc[2][2][4];
        {
            uint32_t b[2][4];
            ldsm4t(mb, b[0]);
            ldsm4t(mb + 512, b[1]);
            #pragma unroll
            for (int i = 0; i < AT_AHEAD; i++)
                if (!at_early(i)) ldsm4t(aq + (i & 1) * 16384 + (i >> 1) * 2048, at[i]);
            STAMPD(1, b[0][0]);
            #pragma unroll
            for (int i = 0; i < 4; i++) { for (int e = 0; e < 4; e++) acc[i >> 1][i & 1][e] = 0.f; }
            #pragma unroll
            for (int u = 0; u < 16; u++) {
                #pragma unroll
                for (int h = 0; h < 2; h++) {
                    const int j = 2 * u + h;
                    #pragma unroll
                    for (int m = 0; m < 2; m++) {
                        if ((j & 3) == 0) mma_a(acc[h][m], at[(j >> 2) * 2 + m], b[u & 1][2 * h], b[u & 1][2 * h + 1]);
                        else mma_a(acc[h][m], wr[reg_idx(j)][m], b[u & 1][2 * h], b[u & 1][2 * h + 1]);
                    }
                }
                if (u + 2 < 16) ldsm4t(mb + (u + 2) * 512, b[u & 1]);
                if (u + AT_AHEAD < 16 && !at_early(u + AT_AHEAD))
                    ldsm4t(aq + ((u + AT_AHEAD) & 1) * 16384 + ((u + AT_AHEAD) >> 1) * 2048, at[u + AT_AHEAD]);
            }
        }
        sts128(l16 + SM_RED + warp * 512, __float_as_uint(acc[0][1][0] + acc[1][1][0]), __float_as_uint(acc[0][1][1] + acc[1][1][1]),
               __float_as_uint(acc[0][1][2] + acc[1][1][2]), __float_as_uint(acc[0][1][3] + acc[1][1][3]));
        #pragma unroll
        for (int e = 0; e < 4; e++) acc[0][0][e] += acc[1][0][e];
        const uint32_t x16 = fresh(l16);
        const uint32_t sa = fresh((x16 & 0x70) * 8 + ((((x16 >> 3) & 0x30) ^ x16) & 0x70));
        const uint32_t sq = fresh(sa ^ ((((x16 >> 7) ^ (x16 >> 8)) & 1) * 0x30));
        const uint32_t x8 = (x16 & 0x1F0) >> 1;
        const uint32_t xra = fresh(x8 + __byte_perm(u_xa, u_bra, 0x7210)), xrb = fresh(x8 + __byte_perm(u_xa, u_brb, 0x7210));
        STAMP(2);
        named_bar_sync(1 + wq, 64);
        uint32_t p0, p1;
        {
            const uint4 v = lds128(l16 + SM_RED + (warp ^ 4) * 512);
            p0 = pack_bf16(acc[0][0][0] + __uint_as_float(v.x), acc[0][0][1] + __uint_as_float(v.y));
            p1 = pack_bf16(acc[0][0][2] + __uint_as_float(v.z), acc[0][0][3] + __uint_as_float(v.w));
        }
        auto send = [&](uint32_t y0, uint32_t y1) {
            st_async_v2(xra, y0, y1, u_bra);
            st_async_v2(xrb, y0, y1, u_brb);
            sts64(x8 + u_xa, y0, y1);
            warp_arrive(u_bx);
        };
        if (qk) {
            asm volatile("stmatrix.sync.aligned.m8n8.x2.trans.shared.b16 [%0], {%1,%2};" ::"r"(aq + u_st), "r"(p0), "r"(p1) : "memory");
            named_bar_sync(5, REC_THREADS);
            if (u_key != 0) {
                uint32_t qa[2][4], kf[2][4];
                ldsm4(sq + sb + SM_QK, qa[0]);
                ldsm4(sa + u_key, kf[0]);
                ldsm4((sq ^ 64) + sb + SM_QK, qa[1]);
                ldsm4((sa ^ 64) + u_key, kf[1]);
                float se[4] = {0.f, 0.f, 0.f, 0.f}, so[4] = {0.f, 0.f, 0.f, 0.f};
                #pragma unroll
                for (int u = 0; u < 2; u++) {
                    mma_a(se, qa[u], kf[u][0], kf[u][1]);
                    mma_a(so, qa[u], kf[u][2], kf[u][3]);
                }
                send(__float_as_uint(se[0] + so[2]), __float_as_uint(se[1] + so[3]));
            }
        } else {
            send(p0, p1);
        }
        STAMP(3);
        const uint32_t lane = (fresh(l16) >> 4) & 31;
        auto kv_stores = [&]() {
            if (u_kv != ~0u) {
                uint32_t* dst = reinterpret_cast<uint32_t*>(p.kv_mem) + (u_kv + s * (NH * 512) + lane);
                dst[0] = p0;
                dst[32] = p1;
            }
        };
        auto tile_stores = [&]() {
            if (warp == 4) {
                asm volatile("fence.proxy.async.shared::cta;" ::: "memory");
                if (elect_one()) {
                    __nv_bfloat16* dst = p.qkv_tok + ((size_t)s * NH + head) * (SEG * DH);
                    constexpr size_t MAT = (size_t)NSEG * NH * SEG * DH;
                    bulk_store(dst + (qk ? rank * (SEG * 64) : 2 * MAT), sb + (qk ? SM_QS : SM_V), (EXP & 32) ? 32 : 4096);
                    bulk_store(dst + (qk ? MAT + rank * (SEG * 64) : 2 * MAT + SEG * 64), sb + (qk ? SM_K : SM_V + 4096), (EXP & 32) ? 32 : 4096);
                    bulk_commit();
                }
            }
        };
        if (((s + 1) & 62) == 0) {
            if (s == NSEG - 1) { kv_stores(); tile_stores(); break; }
            mbar_wait_bounded(bar + BAR_WO, 0);
        }
        const uint32_t slot = par * XCHG_SLOT;
        if (u_role & 2) {
            if (qk) mbar_wait_bounded(bar + BAR_V, par);
            uint32_t vt[2][4][4];
            #pragma unroll
            for (int i = 0; i < 8; i++) {
                const uint4 v = lds128(l16 + SM_V + (warp & 1) * 1024 + (i & 3) * 2048 + (i >> 2) * 512);
                vt[i >> 2][i & 3][0] = v.x; vt[i >> 2][i & 3][1] = v.y; vt[i >> 2][i & 3][2] = v.z; vt[i >> 2][i & 3][3] = v.w;
            }
            kv_stores();
            const uint32_t l8 = sb + lane * 8;
            mbar_wait_bounded(bar + BAR_X, par);
            STAMP(4);
            float sv[10];
            #pragma unroll
            for (int j = 0; j < 5; j++) {
                const uint2 a = lds64(l8 + SM_SP + j * 256), b = lds64(l8 + SM_SP + 1280 + j * 256);
                sv[2 * j] = __uint_as_float(a.x) + __uint_as_float(b.x);
                sv[2 * j + 1] = __uint_as_float(a.y) + __uint_as_float(b.y);
            }
            float mx = fmaxf(fmaxf(fmaxf(sv[0], sv[1]), fmaxf(sv[2], sv[3])), fmaxf(fmaxf(sv[4], sv[5]), fmaxf(sv[6], sv[7])));
            mx = fmaxf(mx, fmaxf(sv[8], sv[9]));
            const float m1 = __shfl_xor_sync(~0u, mx, 1), m2 = __shfl_xor_sync(~0u, mx, 2), m3 = __shfl_xor_sync(~0u, mx, 3);
            const bool vm_ok = mbar_try_wait(bar + BAR_VM, par);
            mx = fmaxf(fmaxf(mx, m1), fmaxf(m2, m3));
            const float mo = mx * sl2;
            #pragma unroll
            for (int j = 0; j < 10; j++) sv[j] = ex2(fmaf(sv[j], sl2, -mo));
            const uint32_t e0 = pack_bf16(sv[0], sv[1]), e1 = pack_bf16(sv[2], sv[3]);
            const uint32_t e2 = pack_bf16(sv[4], sv[5]), e3 = pack_bf16(sv[6], sv[7]), em = pack_bf16(sv[8], sv[9]);
            float o[4][4];
            #pragma unroll
            for (int i = 0; i < 4; i++) {
                o[i][0] = o[i][1] = o[i][2] = o[i][3] = 0.f;
                mma_a(o[i], vt[0][i], e0, e1);
            }
            const float sum = (((sv[0] + sv[1]) + (sv[2] + sv[3])) + ((sv[4] + sv[5]) + (sv[6] + sv[7]))) + (sv[8] + sv[9]);
            if (!vm_ok) mbar_wait_bounded(bar + BAR_VM, par);
            uint2 vm[4];
            #pragma unroll
            for (int i = 0; i < 4; i++) {
                vm[i] = lds64(l8 + SM_VM + (warp & 1) * 1024 + i * 256);
                mma_a(o[i], vt[1][i], e2, e3);
            }
            #pragma unroll
            for (int i = 0; i < 4; i++) mma1688(o[i], vm[i].x, vm[i].y, em);
            {
                const float s1 = __shfl_xor_sync(~0u, sum, 1), s2 = __shfl_xor_sync(~0u, sum, 2), s3 = __shfl_xor_sync(~0u, sum, 3);
                sts32(sb + SM_SUM + (lane & 28), __float_as_uint((sum + s1) + (s2 + s3)));
            }
            #pragma unroll
            for (int i = 0; i < 4; i += 2)
                stsm_x4(l16 + SM_O + (warp & 1) * 1024 + i * 256, pack_bf16(o[i][0], o[i][1]), pack_bf16(o[i][2], o[i][3]),
                        pack_bf16(o[i + 1][0], o[i + 1][1]), pack_bf16(o[i + 1][2], o[i + 1][3]));
            STAMP(5);
            uint32_t st[16][4];
            #pragma unroll
            for (int n = 0; n < WO_PF0; n++) ldsm4t(wo_addr<2>(ao, 0, n), st[n]);
            named_bar_sync(6, REC_THREADS);
            wo_phase<2, WO_PF0>(st, ao, 0, l16, tbl, sb + SM_SUM, slot, xhi, 0, p.one[0] - 1, aq, bar + BAR_XG, par ^ 1, x0_ok);
        } else {
            const uint32_t a3 = fresh(ao) + (wg == 0 ? 10 : 6) * 8192;
            uint32_t st[24][4];
            #pragma unroll
            for (int n = 0; n < WO_PFA; n++) ldsm4t(wo_addr<3>(ao, a3, n), st[n]);
            kv_stores();
            tile_stores();
            if (u_role & 1) {
                uint8_t* ib = xaddr(lds32_volatile(tbl + 12) + (par ^ 1) * XCHG_SLOT + lane * 16, xhi);
                #pragma unroll
                for (int i = 0; i < 4; i++) st_relaxed_v4(ib + i * 512, SENT);
                st_relaxed_b32(xaddr(lds32_volatile(tbl + 28) + pub_slot(s + 3) + (lane & 16) * 256 + (lane & 8) * 16 + (lane & 7) * 4, xhi), SENT);
            }
            if (warp == 1) {
                if (elect_one()) {
                    #pragma unroll
                    for (int g = 0; g < 4; g++) mbar_arrive_expect_tx(bar + BAR_XG + 8 * g, ((EXP >> g) & 1) ? 0 : 16384);
                }
                if (s + 2 < NSEG && cta < 4 && elect_one())
                    asm volatile("cp.async.bulk.prefetch.tensor.3d.L2.global [%0, {%1, %2, %3}];"
                                 ::"l"(&p.tmX), "r"(0), "r"((s + 2) * SEG), "r"(cta * 4) : "memory");
                if (rank == 0) {
                    mbar_wait_bounded(bar + BAR_F0, par);
                    if (elect_one()) x_load(p, sb, s + 1, 0);
                }
            }
            if (WO_PFA < WO_PF1 || (u_role & 16)) mbar_wait_bounded(bar + BAR_X, par);
            if (WO_PFA < WO_PF1) {
                spin_clks(WO_PFB_DELAY);
                #pragma unroll
                for (int n = WO_PFA; n < WO_PF1; n++) ldsm4t(wo_addr<3>(ao, a3, n), st[n]);
            }
            if (u_role & 16) {
                spin_clks(XB_DELAY);
                mbar_wait_bounded(bar + BAR_VM, par);
                if (elect_one()) x_load(p, sb, s + 1, rank);
            }
            named_bar_sync(6, REC_THREADS);
            wo_phase<3, WO_PF1>(st, ao, a3, l16, tbl, sb + SM_SUM, slot, xhi, u_role & 4, p.one[0] - 1, aq, bar + BAR_XG, par ^ 1, x0_ok);
        }
        STAMP(7);
        if (wg == 0) named_bar_sync(9, REC_THREADS); else named_bar_arrive(9, REC_THREADS);
    }
    if (threadIdx.x == 128) KMARK(8);
    mbar_wait(bar + BAR_X, 1);
    mbar_wait(bar + BAR_VM, 1);
    if (qk) mbar_wait(bar + BAR_V, 1);
    named_bar_sync(0, REC_THREADS);
    if (warp == 4 && elect_one()) {
        bulk_wait_all();
        signal_flag(p.flags + F_PROGRESS + NSEG - 1);
        KMARK(9);
    }
}

__global__ void __launch_bounds__(REC_THREADS, 1) rec_kernel(const __grid_constant__ RecParams p) {
    extern __shared__ __align__(1024) uint8_t smem_raw[];
    const uint32_t sb = smem_u32(smem_raw);
    const int tid = threadIdx.x, lane = tid & 31;
    const int warp = __shfl_sync(~0u, tid >> 5, 0);
    const int cta = blockIdx.x, head = cta / 3, rank = cta % 3;
    const int wg = warp >> 2, wq = warp & 3;
    const int t0 = (rank * 64 + 2) / 3;
    const uint32_t bar = sb + SM_BAR;
    uint8_t* const xb = p.xchg;
    const uint32_t xlo = (uint32_t)(uint64_t)xb;
    if ((sb & 0x3FFFF) != SMEM_ORIGIN) __trap();
    KENTER(1);
    auto w_box = [&](int part, int g, int i, uint32_t dst, uint32_t mb) {
        const int m = i ^ g;
        const CUtensorMap* tm = &p.tmW[rank == 2 ? 2 : m];
        const int col = head * DH + (rank == 2 ? m : rank) * 64, row = ((part + 1) & 3) * 16;
        tma_load_3d(dst, tm, col, row, g * 8, mb);
    };
    if (tid == 0) {
        mbar_init(bar + BAR_V, 1);
        for (int i = 0; i < 4; i++) { mbar_init(bar + BAR_XG + 8 * i, 1); mbar_init(bar + BAR_M + 8 * i, 1); }
        mbar_init(bar + BAR_GO, 4);
        mbar_init(bar + BAR_PK, 4);
        mbar_init(bar + BAR_VM, rank < 2 ? 1 : 9);
        mbar_init(bar + BAR_F0, 3);
        mbar_init(bar + BAR_F3, 3);
        mbar_init(bar + BAR_VF, 3);
        sts64(bar + BAR_MIN, ~0u, ~0u);
        mbar_init(bar + BAR_X, rank < 2 ? 6 : 1);
        for (int i = 0; i < 3; i++) mbar_init(bar + BAR_P0 + 8 * i, 1);
        mbar_init(bar + BAR_WQ, 1);
        mbar_init(bar + BAR_WO, 1);
        sts32(bar + BAR_SELF, bar + BAR_SELF);
        asm volatile("fence.mbarrier_init.release.cluster;" ::: "memory");
    }
    auto build_tables = [&]() {
        uint32_t av = 0;
        for (uint32_t n = 0; !__all_sync(~0u, (av >> 24) == 24); n++) {
            av = ld_acquire_b32(p.arrivals + (lane & 3));
            if (n > SPIN_LIMIT) __trap();
        }
        uint32_t cm[3];
        #pragma unroll
        for (int i = 0; i < 3; i++) {
            const int o = i * 32 + lane;
            cm[i] = __ballot_sync(~0u, (__shfl_sync(~0u, av, o / 24) >> (o % 24)) & 1);
        }
        auto color_of = [&](int o) { return ((o < 32 ? cm[0] : o < 64 ? cm[1] : cm[2]) >> (o & 31)) & 1u; };
        auto inbox = [&](int o, int byte) {
            uint32_t c = color_of(o);
            int ones = 0;
            #pragma unroll
            for (int i = 0; i < 3; i++) ones += __popc(o >= i * 32 + 32 ? cm[i] : (o > i * 32 ? cm[i] & ((1u << (o - i * 32)) - 1) : 0u));
            int idx = c ? ones : o - ones;
            if (idx >= INBOX_MAX) { idx = 2 * INBOX_MAX - 1 - idx; c ^= 1; }
            const uint32_t lin = idx * 6144 + byte, q = XCHG_INBOX + (lin >> 12) * 8192;
            return q + class_off(xlo + q, c) + (lin & 4095);
        };
        uint32_t off = 0;
        const int grp = (warp + 3) & 3;
        if (lane < 12) {
            const int i = lane >> 2, lt0 = rank == 0 ? 0 : (rank == 1 ? 6 : 11);
            const int o = i < 2 ? rank * 32 + warp * 4 + (lane & 3) : (lt0 + ((warp + 4) & 7)) * 4 + (lane & 3);
            off = inbox(min(o, 95), i * 2048 + head * 64);
        } else if (lane == 12) {
            off = inbox(cta, (grp % 3) * 2048);
        } else if (lane == 13) {
            int T;
            if (grp < 2) {
                T = ((cta >> 5) * 64 + 2) / 3 + 8 * grp + ((cta & 31) >> 2);
            } else {
                const int tl = (cta & 63) >> 2;
                T = tl < 6 ? 16 + tl : (tl < 11 ? 22 + 16 + (tl - 6) : 43 + 16 + (tl - 11));
            }
            off = XCHG_PUB + (T >> 4) * 8192 + (T & 15) * 256 + (cta & 3) * 32;
        } else if (lane == 14) {
            const uint32_t q = XCHG_PUB + wq * 8192;
            off = q + class_off(xlo + q, color_of(cta));
        }
        if (lane < 16) asm volatile("st.shared.b32 [%0], %1;" ::"r"(sb + SM_TBL + warp * 64 + (lane & 3) * 16 + (lane >> 2) * 4), "r"(xlo + off) : "memory");
    };
    if (cta == 0 && tid < F_COUNT) p.flags[tid] = 0;
    __syncthreads();
    asm volatile("barrier.cluster.arrive.relaxed.aligned;" ::: "memory");
    uint4 img = make_uint4(SENT, SENT, SENT, SENT);
    if (cta >= 92) {
        const unsigned short* m = reinterpret_cast<const unsigned short*>(p.mem0) + (cta - 92) * 256 + tid;
        uint32_t w[4];
        #pragma unroll
        for (int i = 0; i < 4; i++) w[i] = (uint32_t)__ldg(m + 2 * i * DM) | ((uint32_t)__ldg(m + (2 * i + 1) * DM) << 16);
        img = make_uint4(w[0], w[1], w[2], w[3]);
    }
    {
        constexpr int NPAIR = (XCHG_SLOT + PUB_BYTES) / 8192;
        uint8_t* pr = xb + (4 + cta) * 8192;
        const uint32_t c0 = class_off(xlo + (4 + cta) * 8192, 0);
        #pragma unroll
        for (int c = 0; c < 2; c++) {
            const bool timed = lane == 0 || (lane == 8 && c == (warp & 1));
            reinterpret_cast<uint4*>(pr + (c0 ^ (c << 12)))[tid] = make_uint4(timed ? 0u : SENT, SENT, SENT, SENT);
        }
        __syncwarp();
        if (lane == 0) {
            uint32_t x = 0;
            for (int k = 0; k < 3; k++) {
                const uint32_t c = (k + warp) & 1, t0 = clock_after(x);
                x = atomicExch(reinterpret_cast<uint32_t*>(pr + (c0 ^ (c << 12)) + warp * 512 + (k >> 1) * 128 + x), SENT);
                const uint32_t lat = clock_after(x) - t0;
                asm volatile("red.shared.min.u32 [%0], %1;" ::"r"(bar + BAR_MIN + 4 * c), "r"(lat) : "memory");
            }
        }
        __syncwarp();
        if (cta >= 92 || 100 + cta < NPAIR) {
            if (cta >= 92) {
                if (img.x == SENT) img.x = 0x7FFF7FFFu;
                if (img.y == SENT) img.y = 0x7FFF7FFFu;
                if (img.z == SENT) img.z = 0x7FFF7FFFu;
                if (img.w == SENT) img.w = 0x7FFF7FFFu;
            }
            uint8_t* q = xb + (cta >= 92 ? cta - 92 : 100 + cta) * 8192;
            reinterpret_cast<uint4*>(q)[tid] = img;
            reinterpret_cast<uint4*>(q + 4096)[tid] = img;
        }
    }
    __syncthreads();
    PSTAMP(4);
    auto stage = [](int part) { return ((part + 2) % 3) * 65536; };
    if (tid == 0) {
        for (int part = 0; part < 3; part++) {
            mbar_arrive_expect_tx(bar + BAR_P0 + 8 * part, 65536);
            for (int u = 0; u < 4; u++) w_box(part, u >> 1, u & 1, sb + stage(part) + u * 16384, bar + BAR_P0 + 8 * part);
        }
    }
    if (tid == 224) {
        const uint32_t c = lds32_volatile(bar + BAR_MIN) > lds32_volatile(bar + BAR_MIN + 4) ? 1 : 0;
        asm volatile("red.release.gpu.global.add.u32 [%0], %1;" ::"l"(p.arrivals + cta / 24), "r"((1u << 24) | (c << (cta % 24))) : "memory");
        if (PDL_POS == 0) pdl_launch_dependents();
    }
    uint32_t wr[NREG][2][4];
    {
        const int mi = lane >> 3, r8 = lane & 7;
        const uint32_t a0 = sb + wg * 32768 + ((mi >> 1) * 8 + r8) * 128 + (((wq * 2 + (mi & 1)) ^ r8) << 4);
        #pragma unroll
        for (int part = 0; part < 3; part++) {
            mbar_wait(bar + BAR_P0 + 8 * part, 0);
            #pragma unroll
            for (int j = 0; j < 8; j++) {
                #pragma unroll
                for (int i = 0; i < 2; i++) ldsm4t(a0 + stage(part) + i * 16384 + j * 2048, wr[part * 8 + j][i]);
            }
            asm volatile("fence.proxy.async.shared::cta;" ::: "memory");
            __syncthreads();
            PSTAMP(5 + part);
            if (tid == 224 && PDL_POS == part + 1) pdl_launch_dependents();
            if (tid == 0) {
                if (part == 0) {
                    for (int g = 0; g < 4; g++) {
                        mbar_arrive_expect_tx(bar + BAR_XG + 8 * g, 16384);
                        tma_load_3d(sb + SM_X + g * 16384, &p.tmX, 0, 0, g * 4, bar + BAR_XG + 8 * g);
                    }
                } else if (part == 1) {
                    mbar_arrive_expect_tx(bar + BAR_WQ, 65536);
                    for (int u = 0; u < 4; u++) w_box(3, u >> 1, u & 1, sb + SM_WQ + u * 16384, bar + BAR_WQ);
                } else {
                    mbar_arrive_expect_tx(bar + BAR_WO, 11 * 8192);
                    for (int b = 0; b < 11; b++) tma_load_2d(sb + SM_WO + b * 8192, &p.tmWo, t0 * 16 + b * 32, head * DH, bar + BAR_WO);
                    if (cta < 4)
                        asm volatile("cp.async.bulk.prefetch.tensor.3d.L2.global [%0, {%1, %2, %3}];"
                                     ::"l"(&p.tmX), "r"(0), "r"(SEG), "r"(cta * 4) : "memory");
                }
            }
        }
    }
    build_tables();
    __syncwarp();
    PSTAMP(9);
    mbar_wait(bar + BAR_WQ, 0);
    asm volatile("barrier.cluster.wait.aligned;" ::: "memory");

    rec_steps(p, wr, sb, warp, cta, head, rank);
    if (cta == 0 && tid < 4) p.arrivals[tid] = 0;
    cluster_sync();
    if (tid == 0) KEXIT(1);
}

constexpr int ATT_SLOT = 28672;
constexpr int ATT_PAIRS = 8;
constexpr int ATT_BAR = ATT_PAIRS * ATT_SLOT;
constexpr int ATT_CNT = ATT_BAR + ATT_PAIRS * 16;
constexpr int ATT_SMEM = ATT_CNT + 96 * 4;
constexpr int ATT_THREADS = ATT_PAIRS * 64 + 32;
static_assert(F_OA == F_OB + 16, "one range of flags");
struct AttnParams {
    CUtensorMap tmOa;
    CUtensorMap tmQb, tmKb;
    CUtensorMap tmOb;
    const __nv_bfloat16* qkv_tok;
    const __nv_bfloat16* kv_mem;
    uint32_t* flags;
};

__device__ __forceinline__ void tok_attn_warp(uint32_t base, int mh, int lane) {
    const uint32_t sq = base, sk = base + 8192, sv = base + 16384, skm = base + 24576, svm = skm + 2048;
    const int g = lane >> 2, c = lane & 3, mi = lane >> 3, r8 = lane & 7;
    const int ntile = mh ? 5 : 3;
    float sc[5][4];
    #pragma unroll
    for (int j = 0; j < 5; j++) { sc[j][0] = sc[j][1] = sc[j][2] = sc[j][3] = 0.f; }
    #pragma unroll
    for (int t2 = 0; t2 < 4; t2++) {
        uint32_t a[2][4];
        #pragma unroll
        for (int h = 0; h < 2; h++) {
            const int row = mh * 16 + (mi & 1) * 8 + r8, ch16 = 4 * t2 + 2 * h + (mi >> 1);
            ldsm_x4(sq + (ch16 >> 3) * 4096 + row * 128 + (((ch16 & 7) ^ r8) << 4), a[h][0], a[h][1], a[h][2], a[h][3]);
        }
        const int ch16 = 4 * t2 + mi;
        uint32_t b[5][4];
        #pragma unroll
        for (int j = 0; j < 5; j++) {
            if (j < ntile) {
                if (j == 0) ldsm_x4_t(skm + t2 * 512 + lane * 16, b[j][0], b[j][1], b[j][2], b[j][3]);
                else ldsm_x4(sk + (ch16 >> 3) * 4096 + ((j - 1) * 8 + r8) * 128 + (((ch16 & 7) ^ r8) << 4), b[j][0], b[j][1], b[j][2], b[j][3]);
            }
        }
        #pragma unroll
        for (int h = 0; h < 2; h++) {
            #pragma unroll
            for (int j = 0; j < 5; j++)
                if (j < ntile) mma16816(sc[j], a[h][0], a[h][1], a[h][2], a[h][3], b[j][2 * h], b[j][2 * h + 1]);
        }
    }
    const float sl2 = 0.08838834764831845f * 1.4426950408889634f;
    uint32_t pf[2][5];
    float inv[2];
    #pragma unroll
    for (int q = 0; q < 2; q++) {
        const int tok = mh * 16 + q * 8 + g;
        float v[10];
        #pragma unroll
        for (int j = 0; j < 5; j++) {
            #pragma unroll
            for (int e = 0; e < 2; e++) {
                const int key = (j - 1) * 8 + 2 * c + e;
                v[2 * j + e] = (j == 0 || key <= tok) ? sc[j][2 * q + e] : -INFINITY;
            }
        }
        float mx = v[0];
        #pragma unroll
        for (int j = 1; j < 10; j++) mx = fmaxf(mx, v[j]);
        mx = fmaxf(mx, __shfl_xor_sync(~0u, mx, 1));
        mx = fmaxf(mx, __shfl_xor_sync(~0u, mx, 2));
        const float mo = mx * sl2;
        float sum = 0.f;
        #pragma unroll
        for (int j = 0; j < 10; j++) { v[j] = ex2(fmaf(v[j], sl2, -mo)); sum += v[j]; }
        sum += __shfl_xor_sync(~0u, sum, 1);
        sum += __shfl_xor_sync(~0u, sum, 2);
        inv[q] = rcp(sum);
        #pragma unroll
        for (int j = 0; j < 5; j++) pf[q][j] = pack_bf16(v[2 * j], v[2 * j + 1]);
    }
    auto load_v = [&](int n4, uint32_t (&vm)[4], uint32_t (&vt)[4][4]) {
        ldsm_x4(svm + n4 * 512 + lane * 16, vm[0], vm[1], vm[2], vm[3]);
        #pragma unroll
        for (int u = 0; u < 4; u++) {
            const int dt = 2 * n4 + (u >> 1), kh = u & 1;
            const uint4 v = lds128(sv + (dt & 3) * 2048 + (dt >> 2) * 1024 + kh * 512 + lane * 16);
            vt[u & 2][2 * kh] = v.x; vt[u & 2][2 * kh + 1] = v.z;
            vt[(u & 2) + 1][2 * kh] = v.y; vt[(u & 2) + 1][2 * kh + 1] = v.w;
        }
    };
    uint32_t vm[2][4], vt[2][4][4];
    load_v(0, vm[0], vt[0]);
    #pragma unroll
    for (int n4 = 0; n4 < 4; n4++) {
        const int cur = n4 & 1;
        if (n4 + 1 < 4) load_v(n4 + 1, vm[cur ^ 1], vt[cur ^ 1]);
        float o[4][4];
        #pragma unroll
        for (int u = 0; u < 4; u++) {
            o[u][0] = o[u][1] = o[u][2] = o[u][3] = 0.f;
            mma16816(o[u], pf[0][1], pf[1][1], pf[0][2], pf[1][2], vt[cur][u][0], vt[cur][u][1]);
        }
        if (mh) {
            #pragma unroll
            for (int u = 0; u < 4; u++) mma16816(o[u], pf[0][3], pf[1][3], pf[0][4], pf[1][4], vt[cur][u][2], vt[cur][u][3]);
        }
        #pragma unroll
        for (int u = 0; u < 4; u++) mma1688(o[u], pf[0][0], pf[1][0], vm[cur][u]);
        #pragma unroll
        for (int u = 0; u < 4; u += 2) {
            const int row = mh * 16 + (mi & 1) * 8 + r8, nt = 4 * n4 + u + (mi >> 1);
            stsm_x4(sq + (nt >> 3) * 4096 + row * 128 + (((nt & 7) ^ r8) << 4),
                    pack_bf16(o[u][0] * inv[0], o[u][1] * inv[0]), pack_bf16(o[u][2] * inv[1], o[u][3] * inv[1]),
                    pack_bf16(o[u + 1][0] * inv[0], o[u + 1][1] * inv[0]), pack_bf16(o[u + 1][2] * inv[1], o[u + 1][3] * inv[1]));
        }
    }
}

__device__ __forceinline__ void b_attn_warp(uint32_t base, int hl, int idx0, int lane) {
    const uint32_t sq = base, sk = base + 8192, sv = base + 8192 + 9216;
    const int g = lane >> 2, c = lane & 3;
    auto addr = [&](uint32_t t, int row, int ch) { return t + row * 128 + ((ch ^ (row & 7)) << 4); };
    const float sl2 = 0.17677669529663687f * 1.4426950408889634f;
    #pragma unroll 2
    for (int blk = 0; blk < 4; blk++) {
        const int r0 = blk * 16;
        float sc[3][4];
        #pragma unroll
        for (int j = 0; j < 3; j++) { sc[j][0] = sc[j][1] = sc[j][2] = sc[j][3] = 0.f; }
        #pragma unroll
        for (int t = 0; t < 2; t++) {
            uint32_t a0, a1, a2, a3, b0, b1, b2, b3, d0, d1, d2, d3;
            const int mi = lane >> 3, r = lane & 7;
            ldsm_x4(addr(sq, r0 + (mi & 1) * 8 + r, hl * 4 + 2 * t + (mi >> 1)), a0, a1, a2, a3);
            ldsm_x4(addr(sk, r0 + (mi >> 1) * 8 + r, hl * 4 + 2 * t + (mi & 1)), b0, b1, b2, b3);
            ldsm_x4(addr(sk, r0 + 16 + r, hl * 4 + 2 * t + (mi & 1)), d0, d1, d2, d3);
            mma16816(sc[0], a0, a1, a2, a3, b0, b1);
            mma16816(sc[1], a0, a1, a2, a3, b2, b3);
            mma16816(sc[2], a0, a1, a2, a3, d0, d1);
        }
        uint32_t pf[2][3];
        float inv[2];
        #pragma unroll
        for (int r = 0; r < 2; r++) {
            const int u = r * 8 + g;
            float v[6];
            #pragma unroll
            for (int j = 0; j < 3; j++) {
                #pragma unroll
                for (int e = 0; e < 2; e++) {
                    const int key = j * 8 + 2 * c + e;
                    const bool ok = key > u && key <= u + 8 && idx0 + r0 - 8 + key >= 0;
                    v[2 * j + e] = ok ? sc[j][2 * r + e] : -INFINITY;
                }
            }
            float mx = fmaxf(fmaxf(fmaxf(v[0], v[1]), fmaxf(v[2], v[3])), fmaxf(v[4], v[5]));
            mx = fmaxf(mx, __shfl_xor_sync(~0u, mx, 1));
            mx = fmaxf(mx, __shfl_xor_sync(~0u, mx, 2));
            const float mo = mx * sl2;
            float sum = 0.f;
            #pragma unroll
            for (int j = 0; j < 6; j++) { v[j] = ex2(fmaf(v[j], sl2, -mo)); sum += v[j]; }
            sum += __shfl_xor_sync(~0u, sum, 1);
            sum += __shfl_xor_sync(~0u, sum, 2);
            inv[r] = rcp(sum);
            #pragma unroll
            for (int j = 0; j < 3; j++) pf[r][j] = pack_bf16(v[2 * j], v[2 * j + 1]);
        }
        uint32_t ow[4][2];
        {
            const int mi = lane >> 3, r = lane & 7;
            uint32_t vv[4][4];
            #pragma unroll
            for (int nt = 0; nt < 4; nt++)
                ldsm_x4_t(addr(sv, r0 + min(mi, 2) * 8 + r, hl * 4 + nt), vv[nt][0], vv[nt][1], vv[nt][2], vv[nt][3]);
            float o[4][4];
            #pragma unroll
            for (int nt = 0; nt < 4; nt++) {
                o[nt][0] = o[nt][1] = o[nt][2] = o[nt][3] = 0.f;
                mma16816(o[nt], pf[0][0], pf[1][0], pf[0][1], pf[1][1], vv[nt][0], vv[nt][1]);
            }
            #pragma unroll
            for (int nt = 0; nt < 4; nt++) mma1688(o[nt], pf[0][2], pf[1][2], vv[nt][2]);
            #pragma unroll
            for (int nt = 0; nt < 4; nt++) {
                ow[nt][0] = pack_bf16(o[nt][0] * inv[0], o[nt][1] * inv[0]);
                ow[nt][1] = pack_bf16(o[nt][2] * inv[1], o[nt][3] * inv[1]);
            }
        }
        #pragma unroll
        for (int u = 0; u < 4; u += 2) {
            const int mi = lane >> 3, r = lane & 7;
            stsm_x4(addr(sq, r0 + (mi & 1) * 8 + r, hl * 4 + u + (mi >> 1)), ow[u][0], ow[u][1], ow[u + 1][0], ow[u + 1][1]);
        }
    }
}

constexpr uint32_t QKVB_TARGET = 12 * 8;
constexpr uint32_t PROGRESS_TARGET = 96;
constexpr uint32_t OA_TARGET = 64, OB_TARGET = 32;
#define ATT_B0 6
constexpr int ATT_TASKS = (NSEG + 16) * 32;
__device__ __forceinline__ int att_group(int g, bool& isb) {
    const int q = g - ATT_B0;
    isb = q >= 0 && q < 48 && q % 3 == 0;
    return q < 0 ? g : q >= 48 ? g - 16 : isb ? q / 3 : ATT_B0 + (q / 3) * 2 + q % 3 - 1;
}

__global__ void __launch_bounds__(ATT_THREADS, 1) attn_kernel(const __grid_constant__ AttnParams p) {
    extern __shared__ __align__(1024) uint8_t smem_raw[];
    const int tid = threadIdx.x, lane = tid & 31, warp = __shfl_sync(~0u, tid >> 5, 0);
    const int pair = warp >> 1, wi = warp & 1;
    const uint32_t base = smem_u32(smem_raw) + pair * ATT_SLOT, bar = smem_u32(smem_raw) + ATT_BAR + pair * 16, taskw = bar + 8;
    const bool leader = wi == 0 && lane == 0;
    if (tid == 0) pdl_launch_dependents();
    KENTER(3);
    const uint32_t cnt = smem_u32(smem_raw) + ATT_CNT;
    if (tid < 96) sts32(cnt + tid * 4, 0);
    __syncthreads();
    if (warp == 2 * ATT_PAIRS) {
        for (uint32_t n = 0; n < SPIN_LIMIT; n++) {
            const bool last = lds32_volatile(cnt + 320) == 2 * ATT_PAIRS;
            uint32_t v[3];
            #pragma unroll
            for (int i = 0; i < 3; i++) {
                v[i] = 0;
                if (i * 32 + lane < 80 && lds32_volatile(cnt + (i * 32 + lane) * 4) != 0)
                    asm volatile("atom.acquire.cta.shared.exch.b32 %0, [%1], 0;" : "=r"(v[i]) : "r"(cnt + (i * 32 + lane) * 4) : "memory");
            }
            if (v[0] | v[1] | v[2]) {
                asm volatile("fence.acq_rel.gpu;" ::: "memory");
                #pragma unroll
                for (int i = 0; i < 3; i++)
                    if (v[i]) asm volatile("red.relaxed.gpu.global.add.u32 [%0], %1;" ::"l"(p.flags + F_OB + i * 32 + lane), "r"(v[i]) : "memory");
                if (v[2] && lane == 15) KMARK(14);
            }
            __syncwarp();
            if (last) break;
            __nanosleep(40);
        }
        if (lane == 0) KEXIT(3);
        return;
    }
    uint32_t next = 0, phase = 0;
    if (leader) {
        mbar_init(bar, 1);
        asm volatile("fence.mbarrier_init.release.cluster;" ::: "memory");
        next = atomicAdd(p.flags + F_QUEUE3, 1u);
    }
    uint32_t pending = 0;
    auto flush = [&]() {
        if (pending) {
            bulk_wait_all();
            if (pending == cnt + 79 * 4) KMARK(13);
            asm volatile("red.release.cta.shared.add.u32 [%0], 1;" ::"r"(pending) : "memory");
            pending = 0;
        }
    };
    int ready_a = -1, ready_b = -1;
    while (true) {
        named_bar_sync(1 + pair, 64);
        if (leader) {
            const uint32_t task = next;
            sts32(taskw, task);
            if (task >= ATT_TASKS) {
                mbar_arrive(bar);
            } else {
                bool isb;
                const int grp = att_group(task >> 5, isb), i = task & 31;
                auto need = [&](const uint32_t* f, uint32_t target) {
                    if (ld_acquire_b32(f) < target) { flush(); wait_flag(f, target); }
                };
                if (isb) {
                    if (grp > ready_b) {
                        need(p.flags + F_QKVB + grp, QKVB_TARGET);
                        if (grp > 0) need(p.flags + F_QKVB + grp - 1, QKVB_TARGET);
                        asm volatile("fence.proxy.async.global;" ::: "memory");
                        ready_b = grp;
                    }
                    mbar_arrive_expect_tx(bar, 8192 + 2 * 9216);
                    tma_load_3d(base, &p.tmQb, (i >> 1) * 64, i & 1, grp * 64, bar);
                    tma_load_3d(base + 8192, &p.tmKb, DM + (i >> 1) * 64, i & 1, grp * 64 - 8, bar);
                    tma_load_3d(base + 8192 + 9216, &p.tmKb, 2 * DM + (i >> 1) * 64, i & 1, grp * 64 - 8, bar);
                } else {
                    if (grp > ready_a) {
                        need(p.flags + F_PROGRESS + grp, PROGRESS_TARGET);
                        asm volatile("fence.proxy.async.global;" ::: "memory");
                        ready_a = grp;
                    }
                    if (grp == 63) KMARK(10);
                    mbar_arrive_expect_tx(bar, ATT_SLOT);
                    #pragma unroll
                    for (int w = 0; w < 3; w++)
                        bulk_load(base + w * 8192, p.qkv_tok + (((size_t)w * NSEG + grp) * NH + i) * (SEG * DH), 8192, bar);
                    #pragma unroll
                    for (int w = 0; w < 2; w++)
                        bulk_load(base + 24576 + w * 2048, p.kv_mem + (((size_t)w * NSEG + grp) * NH + i) * (MROWS * DH), 2048, bar);
                }
                next = atomicAdd(p.flags + F_QUEUE3, 1u);
            }
        }
        if (lane == 0) flush();
        __syncwarp();
        mbar_wait_sleep(bar, phase);
        phase ^= 1;
        const uint32_t task = lds32_volatile(taskw);
        if (task >= ATT_TASKS) break;
        bool isb;
        const int grp = att_group(task >> 5, isb), i = task & 31;
        if (isb) {
            b_attn_warp(base, wi, grp * 64, lane);
            asm volatile("fence.proxy.async.shared::cta;" ::: "memory");
            named_bar_sync(1 + pair, 64);
            if (wi == 1 && lane == 0) {
                asm volatile("cp.async.bulk.tensor.3d.global.shared::cta.bulk_group [%0, {%2, %3, %4}], [%1];"
                             ::"l"(&p.tmOb), "r"(base), "r"((i >> 1) * 64), "r"(i & 1), "r"(grp * 64) : "memory");
                pending = cnt + grp * 4;
            }
        } else {
            if (grp == 63 && lane == 0) KMARK(11);
            tok_attn_warp(base, wi, lane);
            if (grp == 63 && lane == 0) KMARK(12);
            asm volatile("fence.proxy.async.shared::cta;" ::: "memory");
            __syncwarp();
            if (lane == 0) {
                #pragma unroll
                for (int h = 0; h < 2; h++) tma_store_2d(&p.tmOa, base + h * 4096 + wi * 2048, i * DH + h * 64, grp * SEG + wi * 16);
                pending = cnt + (16 + grp) * 4;
            }
        }
        if (lane == 0) { bulk_commit(); bulk_wait_read_all(); }
        __syncwarp();
    }
    if (lane == 0) asm volatile("red.release.cta.shared.add.u32 [%0], 1;" ::"r"(cnt + 320) : "memory");
}

typedef CUresult (*EncodeFn)(CUtensorMap*, CUtensorMapDataType, cuuint32_t, void*, const cuuint64_t*, const cuuint64_t*,
                             const cuuint32_t*, const cuuint32_t*, CUtensorMapInterleave, CUtensorMapSwizzle,
                             CUtensorMapL2promotion, CUtensorMapFloatOOBfill);

void make_map_2d(EncodeFn enc, CUtensorMap* m, const void* ptr, uint64_t rows, uint64_t cols, uint32_t box_rows, uint32_t box_cols = 64) {
    cuuint64_t dims[2] = {cols, rows};
    cuuint64_t strides[1] = {cols * 2};
    cuuint32_t box[2] = {box_cols, box_rows};
    cuuint32_t es[2] = {1, 1};
    enc(m, CU_TENSOR_MAP_DATA_TYPE_BFLOAT16, 2, const_cast<void*>(ptr), dims, strides, box, es,
        CU_TENSOR_MAP_INTERLEAVE_NONE, box_cols == 64 ? CU_TENSOR_MAP_SWIZZLE_128B : CU_TENSOR_MAP_SWIZZLE_64B, CU_TENSOR_MAP_L2_PROMOTION_L2_256B,
        CU_TENSOR_MAP_FLOAT_OOB_FILL_NONE);
}
void make_map_b(EncodeFn enc, CUtensorMap* m, const void* ptr, uint64_t k, uint64_t n, uint32_t nblk, uint32_t box_rows = 64) {
    cuuint64_t dims[3] = {64, k, n / 64};
    cuuint64_t strides[2] = {n * 2, 128};
    cuuint32_t box[3] = {64, box_rows, nblk};
    cuuint32_t es[3] = {1, 1, 1};
    enc(m, CU_TENSOR_MAP_DATA_TYPE_BFLOAT16, 3, const_cast<void*>(ptr), dims, strides, box, es,
        CU_TENSOR_MAP_INTERLEAVE_NONE, CU_TENSOR_MAP_SWIZZLE_128B, CU_TENSOR_MAP_L2_PROMOTION_L2_256B,
        CU_TENSOR_MAP_FLOAT_OOB_FILL_NONE);
}

void make_map_parity(EncodeFn enc, CUtensorMap* m, const void* ptr, uint64_t cols, uint32_t box_rows) {
    cuuint64_t dims[3] = {cols, 2, S_TOK / 2};
    cuuint64_t strides[2] = {cols * 2, cols * 4};
    cuuint32_t box[3] = {64, 1, box_rows};
    cuuint32_t es[3] = {1, 1, 1};
    enc(m, CU_TENSOR_MAP_DATA_TYPE_BFLOAT16, 3, const_cast<void*>(ptr), dims, strides, box, es,
        CU_TENSOR_MAP_INTERLEAVE_NONE, CU_TENSOR_MAP_SWIZZLE_128B, CU_TENSOR_MAP_L2_PROMOTION_L2_128B,
        CU_TENSOR_MAP_FLOAT_OOB_FILL_NONE);
}
void make_map_w(EncodeFn enc, CUtensorMap* m, const void* ptr) {
    cuuint64_t dims[3] = {HD, 64, DM / 64};
    cuuint64_t strides[2] = {HD * 2, 64 * HD * 2};
    cuuint32_t box[3] = {64, 16, 8};
    cuuint32_t es[3] = {1, 1, 1};
    enc(m, CU_TENSOR_MAP_DATA_TYPE_BFLOAT16, 3, const_cast<void*>(ptr), dims, strides, box, es,
        CU_TENSOR_MAP_INTERLEAVE_NONE, CU_TENSOR_MAP_SWIZZLE_128B, CU_TENSOR_MAP_L2_PROMOTION_L2_256B,
        CU_TENSOR_MAP_FLOAT_OOB_FILL_NONE);
}

#define OUTB_SIDE_BLOCKS 16
#define SIDE_ORDER 0
#define N_POST_ATT 0
#define SERIAL_ATT_CTAS h.n_sm
#define N_TAIL_CTAS 24
#define N_SIDE_CTAS 29
#define N_ATT_CTAS 7
#define TAIL_BLOCK0 12

struct HostState {
    bool ready;
    bool overlap;
    int n_side, n_att, n_sm;
    SideParams seq_a, seq_b;
    const void* key[11];
    RecParams rec;
    SideParams side, tail, outb;
    FinalParams fin;
    AttnParams attn;
    __nv_bfloat16 *qkv_tok, *kv_mem, *o_tok, *qkv_b, *o_b;
    uint8_t* xchg;
};
HostState g_host;

void setup(void* const* d_in, void* d_out) {
    HostState& h = g_host;
    void* fn = nullptr;
    cudaDriverEntryPointQueryResult qr;
    cudaGetDriverEntryPoint("cuTensorMapEncodeTiled", &fn, cudaEnableDefault, &qr);
    EncodeFn enc = reinterpret_cast<EncodeFn>(fn);
    void* ptr;
    cudaGetSymbolAddress(&ptr, g_qkv_tok); h.qkv_tok = (__nv_bfloat16*)ptr;
    cudaGetSymbolAddress(&ptr, g_kv_mem);  h.kv_mem = (__nv_bfloat16*)ptr;
    cudaGetSymbolAddress(&ptr, g_o_tok);   h.o_tok = (__nv_bfloat16*)ptr;
    cudaGetSymbolAddress(&ptr, g_qkv_b);   h.qkv_b = (__nv_bfloat16*)ptr;
    cudaGetSymbolAddress(&ptr, g_o_b);     h.o_b = (__nv_bfloat16*)ptr;
    cudaGetSymbolAddress(&ptr, g_xchg);    h.xchg = (uint8_t*)(((uint64_t)ptr + XCHG_BYTES - 1) & ~(uint64_t)(XCHG_BYTES - 1));
    cudaGetSymbolAddress(&ptr, g_flags);   uint32_t* flags = (uint32_t*)ptr;
    cudaGetSymbolAddress(&ptr, g_arrivals); uint32_t* arrivals = (uint32_t*)ptr;

    const void *xa = d_in[0], *mem0 = d_in[1], *wq = d_in[2], *wk = d_in[3], *wv = d_in[4], *wo = d_in[5];
    const void *xb = d_in[7], *wqkv = d_in[8], *wob = d_in[9];

    RecParams& r = h.rec;
    make_map_w(enc, &r.tmW[0], wq);
    make_map_w(enc, &r.tmW[1], wk);
    make_map_w(enc, &r.tmW[2], wv);
    make_map_2d(enc, &r.tmWo, wo, HD, DM, 128, 32);
    r.mem0 = (const __nv_bfloat16*)mem0;
    r.qkv_tok = h.qkv_tok; r.kv_mem = h.kv_mem; r.xchg = h.xchg;
    r.flags = flags; r.arrivals = arrivals; r.one[0] = r.one[1] = 1;
    make_map_b(enc, &r.tmX, xa, S_TOK, DM, 4, SEG);

    SideParams& sd = h.side;
    SideProb& p0 = sd.prob[0];
    make_map_2d(enc, &p0.tmA, xb, S_TOK, DM, BM);
    make_map_b(enc, &p0.tmB, wqkv, DM, 3 * DM, 4);
    make_map_2d(enc, &p0.tmC, h.qkv_b, S_TOK, 3 * DM, 16);
    p0.n_tiles = 3 * DM / 256; p0.k_blocks = DM / BK; p0.c_col0 = 0; p0.dep = nullptr; p0.dep_target = 0; p0.dep_n = 1; p0.sig = flags + F_QKVB;
    SideProb& p1 = sd.prob[1];
    make_map_2d(enc, &p1.tmA, h.o_tok, S_TOK, HD, BM);
    make_map_b(enc, &p1.tmB, wo, HD, DM, 4);
    make_map_2d(enc, &p1.tmC, d_out, S_TOK, 2 * DM, 16);
    p1.n_tiles = DM / 256; p1.k_blocks = HD / BK; p1.c_col0 = 0; p1.dep = flags + F_OA; p1.dep_target = OA_TARGET; p1.dep_n = 4; p1.sig = nullptr;
    SideProb& p2 = sd.prob[2];
    make_map_2d(enc, &p2.tmA, h.o_b, S_TOK, DM, BM);
    make_map_b(enc, &p2.tmB, wob, DM, DM, 4);
    p2.tmC = p1.tmC;
    p2.n_tiles = DM / 256; p2.k_blocks = DM / BK; p2.c_col0 = DM; p2.dep = flags + F_OB; p2.dep_target = OB_TARGET; p2.dep_n = 1; p2.sig = nullptr;
    p0.n_split = p1.n_split = p2.n_split = 1 << 20;
    p0.part = p1.part = p2.part = nullptr;
    if (SIDE_ORDER == 0) { sd.seg[0] = {0, 0, 16}; sd.seg[1] = {1, 0, TAIL_BLOCK0}; }
    else { sd.seg[0] = {1, 0, TAIL_BLOCK0}; sd.seg[1] = {0, 0, 16}; }
    sd.seg[2] = {2, 0, OUTB_SIDE_BLOCKS};
    sd.nseg = 3; sd.queue = flags + F_SIDEQ;
    h.outb = sd;
    h.outb.seg[0] = {2, OUTB_SIDE_BLOCKS, 16};
    h.outb.nseg = 1; h.outb.queue = flags + F_OUTBQ;

    SideParams& tl = h.tail;
    tl.prob[0] = p1;
    make_map_b(enc, &tl.prob[0].tmB, wo, HD, DM, 2);
    tl.prob[0].n_tiles = 2 * DM / 128; tl.prob[0].n_split = DM / 128; tl.prob[0].k_blocks = HD / BK / 2;
    cudaGetSymbolAddress(&ptr, g_part);
    tl.prob[0].part = (float*)ptr; tl.prob[0].part_flag = flags + F_PART;
    tl.prob[1] = tl.prob[2] = tl.prob[0];
    tl.seg[0] = {0, TAIL_BLOCK0, 15};
    tl.nseg = 1; tl.queue = flags + F_TAILQ;

    make_map_2d(enc, &h.fin.tmA, h.o_tok, S_TOK, HD, SEG);
    h.fin.tmB = tl.prob[0].tmB; h.fin.out = (__nv_bfloat16*)d_out;
    h.fin.dep = flags + F_OA + 60; h.fin.dep_target = OA_TARGET; h.fin.mt = 15;

    make_map_2d(enc, &h.attn.tmOa, h.o_tok, S_TOK, HD, 16);
    make_map_parity(enc, &h.attn.tmQb, h.qkv_b, 3 * DM, 64);
    make_map_parity(enc, &h.attn.tmKb, h.qkv_b, 3 * DM, 72);
    make_map_parity(enc, &h.attn.tmOb, h.o_b, DM, 64);
    h.attn.qkv_tok = h.qkv_tok; h.attn.kv_mem = h.kv_mem; h.attn.flags = flags;

    int dev = 0, nsm = 0;
    cudaGetDevice(&dev);
    cudaDeviceGetAttribute(&nsm, cudaDevAttrMultiProcessorCount, dev);
    h.n_sm = nsm;
    h.overlap = nsm - 96 >= N_SIDE_CTAS + N_ATT_CTAS;
    h.n_side = N_SIDE_CTAS; h.n_att = N_ATT_CTAS;
    h.seq_a = sd;
    h.seq_a.seg[0] = {0, 0, 16};
    h.seq_a.seg[1] = {0, 16, 16};
    h.seq_a.nseg = 2;
    h.seq_b = sd;
    h.seq_b.seg[0] = {1, 0, 16};
    h.seq_b.seg[1] = {2, 0, 16};
    h.seq_b.nseg = 2; h.seq_b.queue = flags + F_TAILQ;

    cudaFuncSetAttribute(side_gemm_kernel<256>, cudaFuncAttributeMaxDynamicSharedMemorySize, GemmCfg<256>::SMEM);
    cudaFuncSetAttribute(side_gemm_kernel<128>, cudaFuncAttributeMaxDynamicSharedMemorySize, GemmCfg<128>::SMEM);
    cudaFuncSetAttribute(final_gemm_kernel, cudaFuncAttributeMaxDynamicSharedMemorySize, FIN_SMEM);
    cudaFuncSetAttribute(rec_kernel, cudaFuncAttributeMaxDynamicSharedMemorySize, REC_SMEM);
    cudaFuncSetAttribute(attn_kernel, cudaFuncAttributeMaxDynamicSharedMemorySize, ATT_SMEM);
    for (int i = 0; i < 10; i++) h.key[i] = d_in[i];
    h.key[10] = d_out;
    h.ready = true;
}

template <typename K, typename P>
void launch(K kernel, int grid, int block, int smem, cudaStream_t st, const P& prm, int cluster, bool pdl) {
    cudaLaunchConfig_t cfg = {};
    cfg.gridDim = dim3(grid); cfg.blockDim = dim3(block); cfg.dynamicSmemBytes = smem; cfg.stream = st;
    cudaLaunchAttribute at[2];
    int n = 0;
    if (cluster > 1) {
        at[n].id = cudaLaunchAttributeClusterDimension;
        at[n].val.clusterDim.x = cluster; at[n].val.clusterDim.y = 1; at[n].val.clusterDim.z = 1;
        n++;
    }
    if (pdl) {
        at[n].id = cudaLaunchAttributeProgrammaticStreamSerialization;
        at[n].val.programmaticStreamSerializationAllowed = 1;
        n++;
    }
    cfg.attrs = at; cfg.numAttrs = n;
    cudaLaunchKernelEx(&cfg, kernel, prm);
}

}

extern "C" void kernel_launch(void* const* d_in, const int* in_sizes, int n_in, void* d_out, int out_size) {
    HostState& h = g_host;
    bool same = h.ready;
    for (int i = 0; same && i < 10; i++) same = h.key[i] == d_in[i];
    if (!same || h.key[10] != d_out) setup(d_in, d_out);
    cudaStream_t st = cudaStreamPerThread;

    launch(rec_kernel, 96, REC_THREADS, REC_SMEM, st, h.rec, 3, false);
    {
        if (!h.overlap) {
            launch(side_gemm_kernel<256>, h.n_sm, 384, GemmCfg<256>::SMEM, st, h.seq_a, 1, false);
            launch(attn_kernel, SERIAL_ATT_CTAS, ATT_THREADS, ATT_SMEM, st, h.attn, 1, false);
            launch(side_gemm_kernel<256>, h.n_sm, 384, GemmCfg<256>::SMEM, st, h.seq_b, 1, false);
            return;
        }
    }
    launch(side_gemm_kernel<256>, h.n_side, 384, GemmCfg<256>::SMEM, st, h.side, 1, true);
    launch(attn_kernel, h.n_att, ATT_THREADS, ATT_SMEM, st, h.attn, 1, true);
    launch(side_gemm_kernel<128>, N_TAIL_CTAS, 384, GemmCfg<128>::SMEM, st, h.tail, 1, true);
    if (N_POST_ATT > 0) launch(attn_kernel, N_POST_ATT, ATT_THREADS, ATT_SMEM, st, h.attn, 1, true);
    launch(final_gemm_kernel, 8 * FIN_SPLIT, 384, FIN_SMEM, st, h.fin, FIN_SPLIT, true);
    if (OUTB_SIDE_BLOCKS < 16)
        launch(side_gemm_kernel<256>, (16 - OUTB_SIDE_BLOCKS) * 4, 384, GemmCfg<256>::SMEM, st, h.outb, 1, true);
}
```

```cpp
#include <cuda_runtime.h>
#include <cuda_bf16.h>
#include <cuda.h>
#include <stdint.h>

namespace {

constexpr int S_TOK = 2048;
constexpr int DM = 1024;
constexpr int NH = 32;
constexpr int DH = 128;
constexpr int HD = NH * DH;
constexpr int NSEG = 64;
constexpr int SEG = 32;
constexpr int MROWS = 8;
constexpr uint32_t SENT = 0xFFFFFFFFu;
constexpr uint32_t SPIN_LIMIT = 1u << 24;

__device__ __align__(1024) __nv_bfloat16 g_qkv_tok[3ull * NSEG * NH * SEG * DH];
__device__ __align__(1024) __nv_bfloat16 g_kv_mem[2ull * NSEG * NH * MROWS * DH];
__device__ __align__(1024) __nv_bfloat16 g_o_tok[(size_t)S_TOK * HD];
__device__ __align__(1024) __nv_bfloat16 g_qkv_b[(size_t)S_TOK * 3 * DM];
__device__ __align__(1024) __nv_bfloat16 g_o_b[(size_t)S_TOK * DM];
__device__ __align__(1024) float g_part[32 * 128 * 128];
constexpr int PUB_BYTES = 32768;
constexpr int XCHG_SLOT = 1 << 20;
constexpr int XCHG_PUB = 0, XCHG_INBOX = 2 * PUB_BYTES;
constexpr int INBOX_MAX = 80;
constexpr int XCHG_BYTES = 2 * XCHG_SLOT;
__device__ __align__(8192) uint8_t g_xchg[2 * XCHG_BYTES];
enum { F_QUEUE3 = 3, F_QUEUE4 = 4, F_SIDEQ = 8, F_TAILQ = 16, F_OUTBQ = 24, F_PROGRESS = 32, F_QKVB = 96, F_OB = 112, F_OA = 128, F_PART = 192, F_COUNT = 224 };
__device__ uint32_t g_flags[F_COUNT];
__device__ __align__(16) uint32_t g_arrivals[4];

#define STAMP(k) do {} while (0)
#define STAMPD(k, x) do {} while (0)
#define PSTAMP(k) do {} while (0)
#define KENTER(k) do {} while (0)
#define APROF(k) do {} while (0)
#define KEXIT(k) do {} while (0)
#define KMARK(k) do {} while (0)

__device__ __forceinline__ uint32_t class_off(uint64_t a, uint32_t c) {
    return ((__popc((uint32_t)a & 0xB3000u) ^ c) & 1u) << 12;
}
__device__ __forceinline__ uint32_t smem_u32(const void* p) { return (uint32_t)__cvta_generic_to_shared(p); }
__device__ __forceinline__ uint32_t pack_bf16(float lo, float hi) {
    uint32_t r;
    asm("cvt.rn.bf16x2.f32 %0, %1, %2;" : "=r"(r) : "f"(hi), "f"(lo));
    return r;
}
__device__ __forceinline__ float ex2(float x) {
    float y;
    asm("ex2.approx.ftz.f32 %0, %1;" : "=f"(y) : "f"(x));
    return y;
}
__device__ __forceinline__ float rcp(float x) {
    float y;
    asm("rcp.approx.ftz.f32 %0, %1;" : "=f"(y) : "f"(x));
    return y;
}
__device__ __forceinline__ uint32_t clock32() {
    uint32_t t;
    asm volatile("mov.u32 %0, %%clock;" : "=r"(t));
    return t;
}
__device__ __forceinline__ void spin_clks(uint32_t n) {
    if (n == 0) return;
    const uint32_t t0 = clock32();
    while (clock32() - t0 < n) {}
}
__device__ __forceinline__ void spin_until(uint32_t t) {
    while ((int)(clock32() - t) < 0) {}
}
__device__ __forceinline__ uint32_t clock_after(uint32_t x) {
    uint32_t t;
    asm volatile("{\n.reg .pred p;\nsetp.eq.u32 p, %1, 0x12345678;\n@p exit;\nmov.u32 %0, %%clock;\n}" : "=r"(t) : "r"(x) : "memory");
    return t;
}
__device__ __forceinline__ uint32_t opaque(uint32_t x) { return __shfl_sync(~0u, x, threadIdx.x & 31); }
__device__ __forceinline__ uint32_t uniform(uint32_t x) { return __shfl_sync(~0u, x + (threadIdx.x & 31), 0); }
__device__ __forceinline__ float bf16_lo(uint32_t w) { return __uint_as_float(w << 16); }
__device__ __forceinline__ float bf16_hi(uint32_t w) { return __uint_as_float(w & 0xFFFF0000u); }

__device__ __forceinline__ void mbar_init(uint32_t bar, uint32_t cnt) {
    asm volatile("mbarrier.init.shared::cta.b64 [%0], %1;" ::"r"(bar), "r"(cnt) : "memory");
}
__device__ __forceinline__ void mbar_arrive(uint32_t bar) {
    asm volatile("mbarrier.arrive.shared::cta.b64 _, [%0];" ::"r"(bar) : "memory");
}
__device__ __forceinline__ void mbar_arrive_expect_tx(uint32_t bar, uint32_t bytes) {
    asm volatile("mbarrier.arrive.expect_tx.shared::cta.b64 _, [%0], %1;" ::"r"(bar), "r"(bytes) : "memory");
}
__device__ __forceinline__ bool mbar_try_wait(uint32_t bar, uint32_t parity) {
    uint32_t ok;
    asm volatile(
        "{\n.reg .pred p;\n"
        "mbarrier.try_wait.parity.shared::cta.b64 p, [%1], %2;\n"
        "selp.u32 %0, 1, 0, p;\n}"
        : "=r"(ok) : "r"(bar), "r"(parity) : "memory");
    return ok != 0;
}
__device__ __forceinline__ bool mbar_test_wait(uint32_t bar, uint32_t parity) {
    uint32_t ok;
    asm volatile(
        "{\n.reg .pred p;\n"
        "mbarrier.test_wait.parity.shared::cta.b64 p, [%1], %2;\n"
        "selp.u32 %0, 1, 0, p;\n}"
        : "=r"(ok) : "r"(bar), "r"(parity) : "memory");
    return ok != 0;
}
__device__ __forceinline__ void mbar_wait(uint32_t bar, uint32_t parity) {
    uint32_t n = 0;
    while (!mbar_try_wait(bar, parity)) {
        if (++n > SPIN_LIMIT) __trap();
    }
}
__device__ __forceinline__ void mbar_wait_sleep(uint32_t bar, uint32_t parity) {
    uint32_t n = 0;
    while (!mbar_try_wait(bar, parity)) {
        __nanosleep(20);
        if (++n > SPIN_LIMIT) __trap();
    }
}
__device__ __forceinline__ void mbar_wait_bounded(uint32_t bar, uint32_t parity) {
    for (uint32_t n = 0; n < (1u << 20) && !mbar_try_wait(bar, parity); n++) {}
}
__device__ __forceinline__ bool elect_one() {
    uint32_t ok;
    asm volatile("{\n.reg .pred p;\nelect.sync _|p, 0xFFFFFFFF;\nselp.u32 %0, 1, 0, p;\n}" : "=r"(ok));
    return ok != 0;
}
__device__ __forceinline__ void named_bar_sync(int id, int nthreads) {
    asm volatile("bar.sync %0, %1;" ::"r"(id), "r"(nthreads) : "memory");
}
__device__ __forceinline__ void named_bar_arrive(int id, int nthreads) {
    asm volatile("bar.arrive %0, %1;" ::"r"(id), "r"(nthreads) : "memory");
}
__device__ __forceinline__ void cluster_sync() {
    asm volatile("barrier.cluster.arrive.release.aligned;\nbarrier.cluster.wait.acquire.aligned;" ::: "memory");
}
__device__ __forceinline__ uint32_t mapa(uint32_t addr, uint32_t rank) {
    uint32_t r;
    asm volatile("mapa.shared::cluster.u32 %0, %1, %2;" : "=r"(r) : "r"(addr), "r"(rank));
    return r;
}

__device__ __forceinline__ void tma_load_2d(uint32_t dst, const CUtensorMap* tm, int c0, int c1, uint32_t bar) {
    asm volatile(
        "cp.async.bulk.tensor.2d.shared::cluster.global.mbarrier::complete_tx::bytes [%0], [%1, {%3, %4}], [%2];"
        ::"r"(dst), "l"(tm), "r"(bar), "r"(c0), "r"(c1) : "memory");
}
__device__ __forceinline__ void tma_load_3d(uint32_t dst, const CUtensorMap* tm, int c0, int c1, int c2, uint32_t bar) {
    asm volatile(
        "cp.async.bulk.tensor.3d.shared::cluster.global.mbarrier::complete_tx::bytes [%0], [%1, {%3, %4, %5}], [%2];"
        ::"r"(dst), "l"(tm), "r"(bar), "r"(c0), "r"(c1), "r"(c2) : "memory");
}
__device__ __forceinline__ void tma_load_3d_mc(uint32_t dst, const CUtensorMap* tm, int c0, int c1, int c2, uint32_t bar, uint16_t mask) {
    asm volatile(
        "cp.async.bulk.tensor.3d.shared::cluster.global.mbarrier::complete_tx::bytes.multicast::cluster [%0], [%1, {%3, %4, %5}], [%2], %6;"
        ::"r"(dst), "l"(tm), "r"(bar), "r"(c0), "r"(c1), "r"(c2), "h"(mask) : "memory");
}
__device__ __forceinline__ void tma_store_2d(const CUtensorMap* tm, uint32_t src, int c0, int c1) {
    asm volatile("cp.async.bulk.tensor.2d.global.shared::cta.bulk_group [%0, {%2, %3}], [%1];"
                 ::"l"(tm), "r"(src), "r"(c0), "r"(c1) : "memory");
}
__device__ __forceinline__ void bulk_store(void* dst, uint32_t src, uint32_t bytes) {
    asm volatile("cp.async.bulk.global.shared::cta.bulk_group [%0], [%1], %2;" ::"l"(dst), "r"(src), "r"(bytes) : "memory");
}
__device__ __forceinline__ void bulk_commit() { asm volatile("cp.async.bulk.commit_group;" ::: "memory"); }
__device__ __forceinline__ void bulk_wait_read_all() { asm volatile("cp.async.bulk.wait_group.read 0;" ::: "memory"); }
__device__ __forceinline__ void bulk_wait_all() { asm volatile("cp.async.bulk.wait_group 0;" ::: "memory"); }
__device__ __forceinline__ void bulk_load(uint32_t dst, const void* src, uint32_t bytes, uint32_t bar) {
    asm volatile("cp.async.bulk.shared::cluster.global.mbarrier::complete_tx::bytes [%0], [%1], %2, [%3];"
                 ::"r"(dst), "l"(src), "r"(bytes), "r"(bar) : "memory");
}
__device__ __forceinline__ void bulk_load_mc(uint32_t dst, const void* src, uint32_t bytes, uint32_t bar, uint16_t mask) {
    asm volatile(
        "cp.async.bulk.shared::cluster.global.mbarrier::complete_tx::bytes.multicast::cluster [%0], [%1], %2, [%3], %4;"
        ::"r"(dst), "l"(src), "r"(bytes), "r"(bar), "h"(mask) : "memory");
}
__device__ __forceinline__ void cp_async16(uint32_t dst, const void* src) {
    asm volatile("cp.async.cg.shared.global [%0], [%1], 16;" ::"r"(dst), "l"(src) : "memory");
}
__device__ __forceinline__ void cp_async_commit() { asm volatile("cp.async.commit_group;" ::: "memory"); }
template <int N> __device__ __forceinline__ void cp_async_wait() {
    asm volatile("cp.async.wait_group %0;" ::"n"(N) : "memory");
}

__device__ __forceinline__ void ldsm_x4(uint32_t addr, uint32_t& r0, uint32_t& r1, uint32_t& r2, uint32_t& r3) {
    asm volatile("ldmatrix.sync.aligned.m8n8.x4.shared.b16 {%0,%1,%2,%3}, [%4];"
                 : "=r"(r0), "=r"(r1), "=r"(r2), "=r"(r3) : "r"(addr) : "memory");
}
__device__ __forceinline__ void ldsm_x4_t(uint32_t addr, uint32_t& r0, uint32_t& r1, uint32_t& r2, uint32_t& r3) {
    asm volatile("ldmatrix.sync.aligned.m8n8.x4.trans.shared.b16 {%0,%1,%2,%3}, [%4];"
                 : "=r"(r0), "=r"(r1), "=r"(r2), "=r"(r3) : "r"(addr) : "memory");
}
__device__ __forceinline__ void stsm_x4(uint32_t addr, uint32_t r0, uint32_t r1, uint32_t r2, uint32_t r3) {
    asm volatile("stmatrix.sync.aligned.m8n8.x4.shared.b16 [%0], {%1,%2,%3,%4};"
                 ::"r"(addr), "r"(r0), "r"(r1), "r"(r2), "r"(r3) : "memory");
}
__device__ __forceinline__ uint32_t movmat(uint32_t a) {
    uint32_t d;
    asm volatile("movmatrix.sync.aligned.m8n8.trans.b16 %0, %1;" : "=r"(d) : "r"(a));
    return d;
}
__device__ __forceinline__ void mma16816(float* d, uint32_t a0, uint32_t a1, uint32_t a2, uint32_t a3,
                                         uint32_t b0, uint32_t b1) {
    asm volatile(
        "mma.sync.aligned.m16n8k16.row.col.f32.bf16.bf16.f32 {%0,%1,%2,%3}, {%4,%5,%6,%7}, {%8,%9}, {%0,%1,%2,%3};"
        : "+f"(d[0]), "+f"(d[1]), "+f"(d[2]), "+f"(d[3])
        : "r"(a0), "r"(a1), "r"(a2), "r"(a3), "r"(b0), "r"(b1));
}
__device__ __forceinline__ void mma1688(float* d, uint32_t a0, uint32_t a1, uint32_t b0) {
    asm volatile("mma.sync.aligned.m16n8k8.row.col.f32.bf16.bf16.f32 {%0,%1,%2,%3}, {%4,%5}, {%6}, {%0,%1,%2,%3};"
                 : "+f"(d[0]), "+f"(d[1]), "+f"(d[2]), "+f"(d[3]) : "r"(a0), "r"(a1), "r"(b0));
}
__device__ __forceinline__ uint32_t any_reg() {
    uint32_t r;
    asm volatile("" : "=r"(r));
    return r;
}
__device__ __forceinline__ uint2 lds64(uint32_t addr) {
    uint2 v;
    asm volatile("ld.volatile.shared.v2.b32 {%0,%1}, [%2];" : "=r"(v.x), "=r"(v.y) : "r"(addr) : "memory");
    return v;
}
__device__ __forceinline__ uint4 lds128(uint32_t addr) {
    uint4 v;
    asm volatile("ld.volatile.shared.v4.b32 {%0,%1,%2,%3}, [%4];" : "=r"(v.x), "=r"(v.y), "=r"(v.z), "=r"(v.w) : "r"(addr) : "memory");
    return v;
}
__device__ __forceinline__ void sts32(uint32_t addr, uint32_t x) {
    asm volatile("st.volatile.shared.b32 [%0], %1;" ::"r"(addr), "r"(x) : "memory");
}
__device__ __forceinline__ void sts64(uint32_t addr, uint32_t x, uint32_t y) {
    asm volatile("st.volatile.shared.v2.b32 [%0], {%1,%2};" ::"r"(addr), "r"(x), "r"(y) : "memory");
}
__device__ __forceinline__ void sts128(uint32_t addr, uint32_t x, uint32_t y, uint32_t z, uint32_t w) {
    asm volatile("st.volatile.shared.v4.b32 [%0], {%1,%2,%3,%4};" ::"r"(addr), "r"(x), "r"(y), "r"(z), "r"(w) : "memory");
}
__device__ __forceinline__ void st_async_v2(uint32_t addr, uint32_t x, uint32_t y, uint32_t bar) {
    asm volatile("st.async.weak.shared::cluster.mbarrier::complete_tx::bytes.v2.b32 [%0], {%1,%2}, [%3];"
                 ::"r"(addr), "r"(x), "r"(y), "r"(bar) : "memory");
}
__device__ __forceinline__ uint2 ld_relaxed_v2(const void* p) {
    uint2 v;
    asm volatile("ld.relaxed.gpu.global.v2.b32 {%0,%1}, [%2];" : "=r"(v.x), "=r"(v.y) : "l"(p) : "memory");
    return v;
}
__device__ __forceinline__ void st_relaxed_v2(void* p, uint32_t x, uint32_t y) {
    asm volatile("st.relaxed.gpu.global.v2.b32 [%0], {%1,%2};" ::"l"(p), "r"(x), "r"(y) : "memory");
}
__device__ __forceinline__ void st_relaxed_v4(void* p, uint32_t x) {
    asm volatile("st.relaxed.gpu.global.v4.b32 [%0], {%1,%1,%1,%1};" ::"l"(p), "r"(x) : "memory");
}
__device__ __forceinline__ uint32_t ld_relaxed_b32(const void* p) {
    uint32_t v;
    asm volatile("ld.relaxed.gpu.global.b32 %0, [%1];" : "=r"(v) : "l"(p) : "memory");
    return v;
}
__device__ __forceinline__ uint32_t lds32_volatile(uint32_t addr) {
    uint32_t v;
    asm volatile("ld.volatile.shared.b32 %0, [%1];" : "=r"(v) : "r"(addr) : "memory");
    return v;
}
__device__ __forceinline__ void st_relaxed_b32(void* p, uint32_t x) {
    asm volatile("st.relaxed.gpu.global.b32 [%0], %1;" ::"l"(p), "r"(x) : "memory");
}

__device__ __forceinline__ uint32_t ld_acquire_b32(const void* p) {
    uint32_t v;
    asm volatile("ld.acquire.gpu.global.b32 %0, [%1];" : "=r"(v) : "l"(p) : "memory");
    return v;
}
__device__ __forceinline__ void wait_flag(const uint32_t* p, uint32_t target) {
    uint32_t n = 0;
    while (ld_acquire_b32(p) < target) {
        __nanosleep(64);
        if (++n > SPIN_LIMIT) __trap();
    }
}
__device__ __forceinline__ void signal_flag(uint32_t* p) {
    asm volatile("red.release.gpu.global.add.u32 [%0], 1;" ::"l"(p) : "memory");
}
__device__ __forceinline__ void pdl_launch_dependents() { asm volatile("griddepcontrol.launch_dependents;" ::: "memory"); }

constexpr int BM = 128, BK = 64;
constexpr int A_STAGE = BM * BK * 2;
template <int BN> struct GemmCfg {
    static constexpr int STAGES = BN == 256 ? 3 : 6;
    static constexpr int STAGE = A_STAGE + BK * BN * 2;
    static constexpr int EPI_WARP = 16 * BN * 2;
    static constexpr int SMEM = STAGES * STAGE + 8 * EPI_WARP + 1024 + 512;
};

struct SideProb {
    CUtensorMap tmA, tmB, tmC;
    int n_split;
    int n_tiles, k_blocks, c_col0;
    const uint32_t* dep;
    uint32_t dep_target;
    int dep_n;
    uint32_t* sig;
    float* part;
    uint32_t* part_flag;
};
struct SideSeg { int prob, m0, m1; };
constexpr int SIDE_MAX_SEG = 6;
struct SideParams {
    SideProb prob[3];
    SideSeg seg[SIDE_MAX_SEG];
    int nseg;
    uint32_t* queue;
};
static_assert(sizeof(SideParams) <= 4096, "kernel parameter limit");

__device__ __forceinline__ uint64_t make_desc(uint32_t addr, uint32_t lbo, uint32_t sbo) {
    return (uint64_t)((addr & 0x3FFFF) >> 4) | ((uint64_t)(lbo >> 4) << 16) | ((uint64_t)(sbo >> 4) << 32) | (1ull << 62);
}

__device__ __forceinline__ void wgmma_m64n256k16(float (&d)[128], uint64_t da, uint64_t db, int scale_d) {
    asm volatile(
        "{\n.reg .pred p;\nsetp.ne.b32 p, %130, 0;\n"
        "wgmma.mma_async.sync.aligned.m64n256k16.f32.bf16.bf16 "
        "{%0,%1,%2,%3,%4,%5,%6,%7,%8,%9,%10,%11,%12,%13,%14,%15,"
        "%16,%17,%18,%19,%20,%21,%22,%23,%24,%25,%26,%27,%28,%29,%30,%31,"
        "%32,%33,%34,%35,%36,%37,%38,%39,%40,%41,%42,%43,%44,%45,%46,%47,"
        "%48,%49,%50,%51,%52,%53,%54,%55,%56,%57,%58,%59,%60,%61,%62,%63,"
        "%64,%65,%66,%67,%68,%69,%70,%71,%72,%73,%74,%75,%76,%77,%78,%79,"
        "%80,%81,%82,%83,%84,%85,%86,%87,%88,%89,%90,%91,%92,%93,%94,%95,"
        "%96,%97,%98,%99,%100,%101,%102,%103,%104,%105,%106,%107,%108,%109,%110,%111,"
        "%112,%113,%114,%115,%116,%117,%118,%119,%120,%121,%122,%123,%124,%125,%126,%127},"
        " %128, %129, p, 1, 1, 0, 1;\n}\n"
        : "+f"(d[0]), "+f"(d[1]), "+f"(d[2]), "+f"(d[3]), "+f"(d[4]), "+f"(d[5]), "+f"(d[6]), "+f"(d[7]),
          "+f"(d[8]), "+f"(d[9]), "+f"(d[10]), "+f"(d[11]), "+f"(d[12]), "+f"(d[13]), "+f"(d[14]), "+f"(d[15]),
          "+f"(d[16]), "+f"(d[17]), "+f"(d[18]), "+f"(d[19]), "+f"(d[20]), "+f"(d[21]), "+f"(d[22]), "+f"(d[23]),
          "+f"(d[24]), "+f"(d[25]), "+f"(d[26]), "+f"(d[27]), "+f"(d[28]), "+f"(d[29]), "+f"(d[30]), "+f"(d[31]),
          "+f"(d[32]), "+f"(d[33]), "+f"(d[34]), "+f"(d[35]), "+f"(d[36]), "+f"(d[37]), "+f"(d[38]), "+f"(d[39]),
          "+f"(d[40]), "+f"(d[41]), "+f"(d[42]), "+f"(d[43]), "+f"(d[44]), "+f"(d[45]), "+f"(d[46]), "+f"(d[47]),
          "+f"(d[48]), "+f"(d[49]), "+f"(d[50]), "+f"(d[51]), "+f"(d[52]), "+f"(d[53]), "+f"(d[54]), "+f"(d[55]),
          "+f"(d[56]), "+f"(d[57]), "+f"(d[58]), "+f"(d[59]), "+f"(d[60]), "+f"(d[61]), "+f"(d[62]), "+f"(d[63]),
          "+f"(d[64]), "+f"(d[65]), "+f"(d[66]), "+f"(d[67]), "+f"(d[68]), "+f"(d[69]), "+f"(d[70]), "+f"(d[71]),
          "+f"(d[72]), "+f"(d[73]), "+f"(d[74]), "+f"(d[75]), "+f"(d[76]), "+f"(d[77]), "+f"(d[78]), "+f"(d[79]),
          "+f"(d[80]), "+f"(d[81]), "+f"(d[82]), "+f"(d[83]), "+f"(d[84]), "+f"(d[85]), "+f"(d[86]), "+f"(d[87]),
          "+f"(d[88]), "+f"(d[89]), "+f"(d[90]), "+f"(d[91]), "+f"(d[92]), "+f"(d[93]), "+f"(d[94]), "+f"(d[95]),
          "+f"(d[96]), "+f"(d[97]), "+f"(d[98]), "+f"(d[99]), "+f"(d[100]), "+f"(d[101]), "+f"(d[102]), "+f"(d[103]),
          "+f"(d[104]), "+f"(d[105]), "+f"(d[106]), "+f"(d[107]), "+f"(d[108]), "+f"(d[109]), "+f"(d[110]), "+f"(d[111]),
          "+f"(d[112]), "+f"(d[113]), "+f"(d[114]), "+f"(d[115]), "+f"(d[116]), "+f"(d[117]), "+f"(d[118]), "+f"(d[119]),
          "+f"(d[120]), "+f"(d[121]), "+f"(d[122]), "+f"(d[123]), "+f"(d[124]), "+f"(d[125]), "+f"(d[126]), "+f"(d[127])
        : "l"(da), "l"(db), "r"(scale_d));
}

__device__ __forceinline__ void wgmma_m64n128k16(float (&d)[64], uint64_t da, uint64_t db, int scale_d) {
    asm volatile(
        "{\n.reg .pred p;\nsetp.ne.b32 p, %66, 0;\n"
        "wgmma.mma_async.sync.aligned.m64n128k16.f32.bf16.bf16 "
        "{%0,%1,%2,%3,%4,%5,%6,%7,%8,%9,%10,%11,%12,%13,%14,%15,"
        "%16,%17,%18,%19,%20,%21,%22,%23,%24,%25,%26,%27,%28,%29,%30,%31,"
        "%32,%33,%34,%35,%36,%37,%38,%39,%40,%41,%42,%43,%44,%45,%46,%47,"
        "%48,%49,%50,%51,%52,%53,%54,%55,%56,%57,%58,%59,%60,%61,%62,%63},"
        " %64, %65, p, 1, 1, 0, 1;\n}\n"
        : "+f"(d[0]), "+f"(d[1]), "+f"(d[2]), "+f"(d[3]), "+f"(d[4]), "+f"(d[5]), "+f"(d[6]), "+f"(d[7]),
          "+f"(d[8]), "+f"(d[9]), "+f"(d[10]), "+f"(d[11]), "+f"(d[12]), "+f"(d[13]), "+f"(d[14]), "+f"(d[15]),
          "+f"(d[16]), "+f"(d[17]), "+f"(d[18]), "+f"(d[19]), "+f"(d[20]), "+f"(d[21]), "+f"(d[22]), "+f"(d[23]),
          "+f"(d[24]), "+f"(d[25]), "+f"(d[26]), "+f"(d[27]), "+f"(d[28]), "+f"(d[29]), "+f"(d[30]), "+f"(d[31]),
          "+f"(d[32]), "+f"(d[33]), "+f"(d[34]), "+f"(d[35]), "+f"(d[36]), "+f"(d[37]), "+f"(d[38]), "+f"(d[39]),
          "+f"(d[40]), "+f"(d[41]), "+f"(d[42]), "+f"(d[43]), "+f"(d[44]), "+f"(d[45]), "+f"(d[46]), "+f"(d[47]),
          "+f"(d[48]), "+f"(d[49]), "+f"(d[50]), "+f"(d[51]), "+f"(d[52]), "+f"(d[53]), "+f"(d[54]), "+f"(d[55]),
          "+f"(d[56]), "+f"(d[57]), "+f"(d[58]), "+f"(d[59]), "+f"(d[60]), "+f"(d[61]), "+f"(d[62]), "+f"(d[63])
        : "l"(da), "l"(db), "r"(scale_d));
}
template <int BN> struct WgmmaOp;
template <> struct WgmmaOp<256> {
    static __device__ __forceinline__ void run(float (&d)[128], uint64_t a, uint64_t b, int sc) { wgmma_m64n256k16(d, a, b, sc); }
};
template <> struct WgmmaOp<128> {
    static __device__ __forceinline__ void run(float (&d)[64], uint64_t a, uint64_t b, int sc) { wgmma_m64n128k16(d, a, b, sc); }
};

struct StoreRec {
    uint64_t dst;
    uint64_t flag;
    int kind;
    int pad;
};
struct EpiCtx { uint32_t buf, rec, st_full, st_empty; uint32_t it; int lane; };
template <int N>
__device__ __forceinline__ void epi_hand_over(const float (&acc)[N], EpiCtx& e, uint64_t dst, uint64_t flag, int kind) {
    mbar_wait(e.st_empty, (e.it & 1) ^ 1);
    const int mi = e.lane >> 3, row = (mi & 1) * 8 + (e.lane & 7);
    #pragma unroll
    for (int j = 0; j < N / 4; j += 2) {
        const int chunk = (j & 7) + (mi >> 1);
        stsm_x4(e.buf + (j >> 3) * 2048 + row * 128 + ((chunk ^ (row & 7)) << 4),
                pack_bf16(acc[4 * j], acc[4 * j + 1]), pack_bf16(acc[4 * j + 2], acc[4 * j + 3]),
                pack_bf16(acc[4 * j + 4], acc[4 * j + 5]), pack_bf16(acc[4 * j + 6], acc[4 * j + 7]));
    }
    if (e.lane == 0) {
        asm volatile("st.shared.v2.b64 [%0], {%1, %2};" ::"r"(e.rec), "l"(dst), "l"(flag) : "memory");
        asm volatile("st.shared.b32 [%0], %1;" ::"r"(e.rec + 16), "r"(kind) : "memory");
    }
    asm volatile("fence.proxy.async.shared::cta;" ::: "memory");
    __syncwarp();
    if (e.lane == 0) mbar_arrive(e.st_full);
    e.it++;
}
__device__ __forceinline__ void epi_exit(EpiCtx& e) {
    mbar_wait(e.st_empty, (e.it & 1) ^ 1);
    if (e.lane == 0) {
        asm volatile("st.shared.b32 [%0], %1;" ::"r"(e.rec + 16), "r"(-1) : "memory");
        mbar_arrive(e.st_full);
    }
}
template <int BN, bool PAIR = false>
__device__ __forceinline__ void gemm_mainloop(float (&acc)[BN / 2], int k_blocks, uint32_t sbase, uint32_t bar_base, int cw,
                                              bool elected, int& stage, uint32_t& phase, uint32_t peer = 0) {
    using C = GemmCfg<BN>;
    auto release = [&](int st) {
        const uint32_t bar = bar_base + 8 * (C::STAGES + st);
        mbar_arrive(bar);
        if (PAIR) asm volatile("mbarrier.arrive.shared::cluster.b64 _, [%0];" ::"r"(mapa(bar, peer)) : "memory");
    };
    int prev_stage = -1;
    for (int kb = 0; kb < k_blocks; kb++) {
        mbar_wait(bar_base + 8 * stage, phase);
        const uint32_t sa = sbase + stage * C::STAGE + cw * (64 * 128);
        const uint32_t sb = sbase + stage * C::STAGE + A_STAGE;
        asm volatile("wgmma.fence.sync.aligned;" ::: "memory");
        #pragma unroll
        for (int kk = 0; kk < BK / 16; kk++)
            WgmmaOp<BN>::run(acc, make_desc(sa + kk * 32, 16, 1024), make_desc(sb + kk * 2048, 8192, 1024), (kb | kk) != 0);
        asm volatile("wgmma.commit_group.sync.aligned;" ::: "memory");
        asm volatile("wgmma.wait_group.sync.aligned 1;" ::: "memory");
        if (prev_stage >= 0 && elected) release(prev_stage);
        prev_stage = stage;
        if (++stage == C::STAGES) { stage = 0; phase ^= 1; }
    }
    asm volatile("wgmma.wait_group.sync.aligned 0;" ::: "memory");
    if (elected) release(prev_stage);
}
template <int BN>
__device__ __forceinline__ void store_warp(uint32_t epi_base, uint32_t rec_base, uint32_t st_full, uint32_t st_empty, int lane,
                                           const uint8_t* tmaps, int tstride) {
    for (uint32_t it = 0;; it++) {
        mbar_wait(st_full, it & 1);
        uint64_t dst = 0, flag = 0;
        int kind = -1;
        if (lane < 8) {
            const uint32_t rec = rec_base + lane * 32;
            asm volatile("ld.volatile.shared.v2.b64 {%0, %1}, [%2];" : "=l"(dst), "=l"(flag) : "r"(rec) : "memory");
            kind = (int)lds32_volatile(rec + 16);
        }
        if (__shfl_sync(~0u, kind, 0) < 0) break;
        if (lane < 8) {
            const uint32_t buf = epi_base + lane * GemmCfg<BN>::EPI_WARP;
            #pragma unroll
            for (int q = 0; q < BN / 64; q++) {
                tma_store_2d(reinterpret_cast<const CUtensorMap*>(tmaps + (kind - 1) * tstride), buf + q * 2048,
                                  (int)(uint32_t)dst + q * 64, (int)(dst >> 32));
            }
            bulk_commit();
            bulk_wait_read_all();
            mbar_arrive(st_empty);
            if (flag) {
                bulk_wait_all();
                signal_flag(reinterpret_cast<uint32_t*>(flag));
            }
        }
        __syncwarp();
    }
    if (lane < 8) bulk_wait_all();
}

#define SCHED_AHEAD 4
template <int BN>
__global__ void __launch_bounds__(384, 1) side_gemm_kernel(const __grid_constant__ SideParams p) {
    using C = GemmCfg<BN>;
    extern __shared__ uint8_t smem_raw[];
    const uint32_t sbase = (smem_u32(smem_raw) + 1023) & ~1023u;
    const uint32_t epi_base = sbase + C::STAGES * C::STAGE;
    const uint32_t bar_base = epi_base + 8 * C::EPI_WARP;
    const uint32_t tfull = bar_base + 16 * C::STAGES, tempty = tfull + 16, tslot = tempty + 16, twant = tslot + 8;
    const uint32_t st_full = bar_base + 192, st_empty = st_full + 8, rec_base = bar_base + 256;
    const int tid = threadIdx.x, wg = tid >> 7;
    if (tid == 0) {
        for (int s = 0; s < C::STAGES; s++) { mbar_init(bar_base + 8 * s, 1); mbar_init(bar_base + 8 * (C::STAGES + s), 2); }
        for (int s = 0; s < 2; s++) { mbar_init(tfull + 8 * s, 1); mbar_init(tempty + 8 * s, 3); }
        mbar_init(twant, 1);
        mbar_init(st_full, 8);
        mbar_init(st_empty, 8);
        asm volatile("fence.mbarrier_init.release.cluster;" ::: "memory");
        pdl_launch_dependents();
    }
    __syncthreads();
    KENTER(BN == 256 ? (p.nseg == 1 ? 6 : 2) : 4);

    if (wg == 0) {
        asm volatile("setmaxnreg.dec.sync.aligned.u32 40;");
        if (tid == 0) {
            int stage = 0; uint32_t phase = 1;
            for (uint32_t it = 0;; it++) {
                mbar_wait(tfull + 8 * (it & 1), (it >> 1) & 1);
                const int code = (int)lds32_volatile(tslot + 4 * (it & 1));
                mbar_arrive(tempty + 8 * (it & 1));
                if (code < 0) break;
                const SideProb& q = p.prob[code >> 16];
                const int mt = (code >> 8) & 255, nt = code & 255;
                asm volatile("fence.proxy.async.global;" ::: "memory");
                for (int kb = 0; kb < q.k_blocks; kb++) {
                    if (kb == q.k_blocks - SCHED_AHEAD) mbar_arrive(twant);
                    mbar_wait(bar_base + 8 * (C::STAGES + stage), phase);
                    const uint32_t sa = sbase + stage * C::STAGE, fb = bar_base + 8 * stage;
                    mbar_arrive_expect_tx(fb, C::STAGE);
                    const int k0 = (nt < q.n_split ? kb : kb + q.k_blocks) * BK;
                    tma_load_2d(sa, &q.tmA, k0, mt * BM, fb);
                    tma_load_3d(sa + A_STAGE, &q.tmB, 0, k0, (nt < q.n_split ? nt : nt - q.n_split) * (BN / 64), fb);
                    if (++stage == C::STAGES) { stage = 0; phase ^= 1; }
                }
            }
        } else if (tid >= 64 && tid < 96) {
            const int lane = tid & 31;
            const SideSeg sg = p.seg[lane < p.nseg ? lane : 0];
            const SideProb& mq = p.prob[sg.prob];
            const uint32_t total = lane < p.nseg ? (sg.m1 - sg.m0) * mq.n_tiles : 0;
            for (uint32_t it = 0;; it++) {
                if (it > 0) mbar_wait_sleep(twant, (it - 1) & 1);
                int code = -1;
                for (uint32_t tries = 0;; tries++) {
                    const uint32_t head = total ? ld_relaxed_b32(p.queue + lane) : 0;
                    const uint32_t left = __ballot_sync(~0u, head < total);
                    if (!left) break;
                    bool ready = head < total;
                    if (ready && mq.dep && (left & (left - 1)))
                        ready = ld_relaxed_b32(mq.dep + (sg.m0 + head / mq.n_tiles + 1) * mq.dep_n - 1) >= mq.dep_target;
                    const uint32_t rm = __ballot_sync(~0u, ready);
                    if (rm) {
                        const int g = __ffs(rm) - 1;
                        if (lane == g) {
                            const uint32_t idx = atomicAdd(p.queue + g, 1u);
                            if (idx < total) code = (sg.prob << 16) | ((sg.m0 + idx / mq.n_tiles) << 8) | (idx % mq.n_tiles);
                        }
                        code = __shfl_sync(~0u, code, g);
                        if (code >= 0) break;
                    } else {
                        __nanosleep(200);
                    }
                    if (tries > SPIN_LIMIT) __trap();
                }
                if (code >= 0) {
                    const SideProb& q = p.prob[code >> 16];
                    if (q.dep && lane < q.dep_n) wait_flag(q.dep + ((code >> 8) & 255) * q.dep_n + lane, q.dep_target);
                    __syncwarp();
                }
                if (lane == 0) {
                    mbar_wait(tempty + 8 * (it & 1), ((it >> 1) & 1) ^ 1);
                    asm volatile("st.shared.b32 [%0], %1;" ::"r"(tslot + 4 * (it & 1)), "r"(code) : "memory");
                    mbar_arrive(tfull + 8 * (it & 1));
                }
                __syncwarp();
                if (code < 0) break;
            }
        } else if (tid >= 32 && tid < 64) {
            store_warp<BN>(epi_base, rec_base, st_full, st_empty, tid & 31, reinterpret_cast<const uint8_t*>(&p.prob[0].tmC),
                           (int)sizeof(SideProb));
        }
    } else {
        asm volatile("setmaxnreg.inc.sync.aligned.u32 232;");
        const int cw = wg - 1, lane = tid & 31, wi = (tid >> 5) & 3;
        const bool elected = (tid & 127) == 0;
        int stage = 0; uint32_t phase = 0;
        float acc[BN / 2];
        EpiCtx ectx = {epi_base + (cw * 4 + wi) * C::EPI_WARP, rec_base + (cw * 4 + wi) * 32, st_full, st_empty, 0, lane};
        for (uint32_t it = 0;; it++) {
            mbar_wait(tfull + 8 * (it & 1), (it >> 1) & 1);
            const int code = (int)lds32_volatile(tslot + 4 * (it & 1));
            named_bar_sync(1 + cw, 128);
            if (elected) mbar_arrive(tempty + 8 * (it & 1));
            if (code < 0) break;
            const SideProb& q = p.prob[code >> 16];
            const int mt = (code >> 8) & 255, nt = code & 255;
            gemm_mainloop<BN>(acc, q.k_blocks, sbase, bar_base, cw, elected, stage, phase);
            const int row0 = mt * BM + cw * 64 + wi * 16, ntc = nt < q.n_split ? nt : nt - q.n_split;
            if (BN == 128 && q.part) {
                const int idx = (mt & 3) * q.n_split + ntc;
                float4* part = reinterpret_cast<float4*>(q.part) + (size_t)idx * (BM * BN / 4) + (tid - 128);
                if (nt < q.n_split) {
                    #pragma unroll
                    for (int j = 0; j < BN / 8; j++) __stcg(part + j * 256, make_float4(acc[4 * j], acc[4 * j + 1], acc[4 * j + 2], acc[4 * j + 3]));
                    __syncwarp();
                    if (lane == 0) signal_flag(q.part_flag + idx);
                    continue;
                }
                if (lane == 0) wait_flag(q.part_flag + idx, 8);
                __syncwarp();
                #pragma unroll
                for (int j = 0; j < BN / 8; j++) {
                    const float4 v = __ldcg(part + j * 256);
                    acc[4 * j] += v.x; acc[4 * j + 1] += v.y; acc[4 * j + 2] += v.z; acc[4 * j + 3] += v.w;
                }
            }
            epi_hand_over(acc, ectx, ((uint64_t)row0 << 32) | (uint32_t)(q.c_col0 + ntc * BN), q.sig ? (uint64_t)(q.sig + mt) : 0, 1 + (code >> 16));
        }
        epi_exit(ectx);
        if (elected) KEXIT(BN == 256 ? (p.nseg == 1 ? 6 : 2) : 4);
    }
}

constexpr int FIN_SPLIT = 8, FIN_KB = HD / BK / FIN_SPLIT;
constexpr int FIN_A1 = FIN_KB * 16384;
constexpr int FIN_A0 = FIN_A1 + FIN_KB * 8192;
constexpr int FIN_BAR = FIN_A0 + 4 * 8192, FIN_SMEM = FIN_BAR + 256;
enum { FB_B = 0, FB_A1 = 64, FB_A0 = 128, FB_E0 = 160, FB_RDY = 192, FB_RED = 208 };
struct FinalParams {
    CUtensorMap tmA, tmB;
    __nv_bfloat16* out;
    const uint32_t* dep;
    uint32_t dep_target;
    int mt;
};
__global__ void __launch_bounds__(384, 1) final_gemm_kernel(const __grid_constant__ FinalParams p) {
    extern __shared__ __align__(1024) uint8_t smem_raw[];
    const uint32_t sbase = smem_u32(smem_raw), bar = sbase + FIN_BAR;
    const int tid = threadIdx.x, wg = tid >> 7;
    const int rank = blockIdx.x % FIN_SPLIT, nt = blockIdx.x / FIN_SPLIT;
    KENTER(5);
    if (tid == 0) {
        for (int s = 0; s < FIN_KB; s++) { mbar_init(bar + FB_B + 8 * s, 1); mbar_init(bar + FB_A1 + 8 * s, 1); }
        for (int s = 0; s < 4; s++) { mbar_init(bar + FB_A0 + 8 * s, 1); mbar_init(bar + FB_E0 + 8 * s, 1); }
        for (int h = 0; h < 2; h++) { mbar_init(bar + FB_RDY + 8 * h, FIN_SPLIT); mbar_init(bar + FB_RED + 8 * h, 1); }
        asm volatile("fence.mbarrier_init.release.cluster;" ::: "memory");
        for (int h = 0; h < 2; h++) mbar_arrive_expect_tx(bar + FB_RED + 8 * h, (FIN_SPLIT - 1) * 4096);
        pdl_launch_dependents();
    }
    __syncthreads();
    asm volatile("barrier.cluster.arrive.relaxed.aligned;" ::: "memory");
    if (wg == 0) {
        auto need = [&](int i) {
            uint32_t n = 0;
            while (ld_acquire_b32(p.dep + i) < p.dep_target) { if (++n > SPIN_LIMIT) __trap(); }
            asm volatile("fence.proxy.async.global;" ::: "memory");
        };
        auto a_load = [&](uint32_t dst, int kb, int seg, uint32_t mb) { tma_load_2d(dst, &p.tmA, (rank * FIN_KB + kb) * BK, p.mt * BM + seg * SEG, mb); };
        if (tid == 0) {
            for (int kb = 0; kb < FIN_KB; kb++) {
                mbar_arrive_expect_tx(bar + FB_B + 8 * kb, 16384);
                tma_load_3d(sbase + kb * 16384, &p.tmB, 0, (rank * FIN_KB + kb) * BK, nt * 2, bar + FB_B + 8 * kb);
            }
        } else if (tid == 32) {
            need(0);
            need(1);
            for (int kb = 0; kb < FIN_KB; kb++) {
                if (kb >= 4) mbar_wait(bar + FB_E0 + 8 * (kb & 3), 0);
                mbar_arrive_expect_tx(bar + FB_A0 + 8 * (kb & 3), 8192);
                for (int u = 0; u < 2; u++) a_load(sbase + FIN_A0 + (kb & 3) * 8192 + u * 4096, kb, u, bar + FB_A0 + 8 * (kb & 3));
            }
        } else if (tid == 64) {
            need(2);
            for (int kb = 0; kb < FIN_KB; kb++) {
                mbar_arrive_expect_tx(bar + FB_A1 + 8 * kb, 8192);
                a_load(sbase + FIN_A1 + kb * 8192, kb, 2, bar + FB_A1 + 8 * kb);
            }
            need(3);
            KMARK(15);
            for (int kb = 0; kb < FIN_KB; kb++) a_load(sbase + FIN_A1 + kb * 8192 + 4096, kb, 3, bar + FB_A1 + 8 * kb);
        }
        __syncwarp();
        asm volatile("barrier.cluster.wait.aligned;" ::: "memory");
    } else {
        const int h = wg - 1, lane = tid & 31, wi = (tid >> 5) & 3, t128 = tid & 127;
        asm volatile("barrier.cluster.wait.aligned;" ::: "memory");
        float acc[64];
        for (int kb = 0; kb < FIN_KB; kb++) {
            mbar_wait(bar + FB_B + 8 * kb, 0);
            if (h == 0) mbar_wait(bar + FB_A0 + 8 * (kb & 3), kb >> 2); else mbar_wait(bar + FB_A1 + 8 * kb, 0);
            const uint32_t sa = sbase + (h == 0 ? FIN_A0 + (kb & 3) * 8192 : FIN_A1 + kb * 8192), sb = sbase + kb * 16384;
            asm volatile("wgmma.fence.sync.aligned;" ::: "memory");
            #pragma unroll
            for (int kk = 0; kk < BK / 16; kk++)
                wgmma_m64n128k16(acc, make_desc(sa + kk * 32, 16, 1024), make_desc(sb + kk * 2048, 8192, 1024), (kb | kk) != 0);
            asm volatile("wgmma.commit_group.sync.aligned;" ::: "memory");
            asm volatile("wgmma.wait_group.sync.aligned 1;" ::: "memory");
            if (h == 0 && kb >= 1 && kb <= 4 && t128 == 0) mbar_arrive(bar + FB_E0 + 8 * (kb - 1));
        }
        asm volatile("wgmma.wait_group.sync.aligned 0;" ::: "memory");
        const uint32_t red = sbase + (h == 0 ? FIN_A0 : FIN_A1);
        named_bar_sync(1 + h, 128);
        if (tid == 256) KMARK(16);
        if (tid == 128) KMARK(19);
        if (t128 < FIN_SPLIT)
            asm volatile("mbarrier.arrive.relaxed.cluster.shared::cluster.b64 _, [%0];" ::"r"(mapa(bar + FB_RDY + 8 * h, t128)) : "memory");
        mbar_wait(bar + FB_RDY + 8 * h, 0);
        if (tid == 256) KMARK(17);
        #pragma unroll
        for (int q = 0; q < FIN_SPLIT; q++) {
            if (q != rank) {
                const uint32_t dst = mapa(red + (rank - (rank > q ? 1 : 0)) * 4096 + t128 * 16, q), rb = mapa(bar + FB_RED + 8 * h, q);
                #pragma unroll
                for (int j = 0; j < 2; j++)
                    asm volatile("st.async.weak.shared::cluster.mbarrier::complete_tx::bytes.v4.f32 [%0], {%1,%2,%3,%4}, [%5];"
                                 ::"r"(dst + j * 2048), "f"(acc[8 * q + 4 * j]), "f"(acc[8 * q + 4 * j + 1]),
                                   "f"(acc[8 * q + 4 * j + 2]), "f"(acc[8 * q + 4 * j + 3]), "r"(rb) : "memory");
            }
        }
        float o[8];
        #pragma unroll
        for (int q = 0; q < FIN_SPLIT; q++)
            if (q == rank) {
                #pragma unroll
                for (int e = 0; e < 8; e++) o[e] = acc[8 * q + e];
            }
        mbar_wait(bar + FB_RED + 8 * h, 0);
        if (tid == 256) KMARK(18);
        if (tid == 128) KMARK(20);
        #pragma unroll
        for (int sl = 0; sl < FIN_SPLIT - 1; sl++) {
            #pragma unroll
            for (int j = 0; j < 2; j++) {
                const uint4 v = lds128(red + sl * 4096 + j * 2048 + t128 * 16);
                o[4 * j] += __uint_as_float(v.x); o[4 * j + 1] += __uint_as_float(v.y);
                o[4 * j + 2] += __uint_as_float(v.z); o[4 * j + 3] += __uint_as_float(v.w);
            }
        }
        __nv_bfloat16* dst = p.out + (size_t)(p.mt * BM + h * 64 + wi * 16 + (lane >> 2)) * (2 * DM) + nt * 128 + rank * 16 + (lane & 3) * 2;
        #pragma unroll
        for (int j = 0; j < 2; j++) {
            *reinterpret_cast<uint32_t*>(dst + j * 8) = pack_bf16(o[4 * j], o[4 * j + 1]);
            *reinterpret_cast<uint32_t*>(dst + (size_t)8 * (2 * DM) + j * 8) = pack_bf16(o[4 * j + 2], o[4 * j + 3]);
        }
        if (t128 == 0) KEXIT(5);
    }
}

#define POLL_DELAY 2
#define FETCH_DELAY 400
#define AT_PF 7
#define TOK_MOVED1 4
#define AT_POS0 0
#define FETCH_REL 1
#define REPOLL 1
#define V_EARLY 6
#define XB_POS 0
#define SPEC_SUM 0
#define AT_FIRST 4
#define AT_AHEAD 4
#define PRO_EARLY 0
#define PDL_POS 5
#define WO_FENCE 0
#define WO_PFA 5
#define WO_PFB_DELAY 60
#define EXP 0
#define NO_COMM 0
#define TOK_MOVED 8
#define XB_DELAY 50
#define WO_PF0 0
#define WO_PF1 11
#define WO_AHEAD 10
constexpr int REC_THREADS = 256;
constexpr uint32_t POLL_LIMIT = 1u << 16;
constexpr int NREG = 24;
__host__ __device__ constexpr int reg_idx(int j) { return ((j & 3) - 1) * 8 + (j >> 2); }
constexpr int SM_WQ = 0;
constexpr int SM_WO = 65536;
constexpr int SM_X = SM_WO + 11 * 8192;
constexpr int SM_PARK0 = SM_X, SM_PARK1 = SM_X + 8192;
constexpr int SM_MEM = SM_X + 4 * 4096;
constexpr int SM_RED = SM_X + 8 * 4096;
constexpr int SM_V = SM_X + 12 * 4096;
constexpr int SM_K = SM_X + 14 * 4096;
constexpr int SM_QS = SM_X + 15 * 4096;
constexpr int SM_QK = SM_X + 65536;
constexpr int SM_SP = SM_QK + 2048;
constexpr int SM_VM = SM_SP + 2560;
constexpr int SM_O = SM_VM + 2048;
constexpr int SM_SUM = SM_O + 2048;
constexpr int SM_TBL = SM_SUM + 128;
constexpr int SM_BAR = SM_TBL + 512;
constexpr int SM_STAMP = SM_BAR + 192;
constexpr int REC_SMEM = SM_STAMP;
static_assert(REC_SMEM <= 232448, "shared memory");
enum { BAR_V = 0, BAR_X = 8, BAR_P0 = 16, BAR_WQ = 40, BAR_WO = 48, BAR_XG = 56, BAR_F0 = 88, BAR_F3 = 96, BAR_VF = 104,
       BAR_M = 112, BAR_GO = 144, BAR_PK = 152, BAR_VM = 160, BAR_SELF = 168, BAR_TPUB = 176, BAR_MIN = 176 };

template <int V> struct IntC { static constexpr int value = V; };
template <int I, int N, typename F> __device__ __forceinline__ void sfor(F&& f) {
    if constexpr (I < N) { f(IntC<I>{}); sfor<I + 1, N>(f); }
}

struct RecParams {
    CUtensorMap tmW[3];
    CUtensorMap tmWo;
    CUtensorMap tmX;
    const __nv_bfloat16* mem0;
    __nv_bfloat16* qkv_tok;
    __nv_bfloat16* kv_mem;
    uint8_t* xchg;
    uint32_t* flags;
    uint32_t one[2];
    uint32_t* arrivals;
};

__device__ __forceinline__ void mma_a(float* d, const uint32_t* a, uint32_t b0, uint32_t b1) {
    mma16816(d, a[0], a[1], a[2], a[3], b0, b1);
}
__device__ __forceinline__ void ldsm4(uint32_t addr, uint32_t* r) { ldsm_x4(addr, r[0], r[1], r[2], r[3]); }
__device__ __forceinline__ void ldsm4t(uint32_t addr, uint32_t* r) { ldsm_x4_t(addr, r[0], r[1], r[2], r[3]); }
template <int OFF> __device__ __forceinline__ void poll_v2(uint2& v, const uint8_t* p) {
    asm volatile("ld.relaxed.gpu.global.v2.b32 {%0,%1}, [%2+%3];" : "=r"(v.x), "=r"(v.y) : "l"(p), "n"(OFF) : "memory");
}
template <int OFF> __device__ __forceinline__ void repoll_v2(uint2& v, const uint8_t* p) {
    asm volatile("{\n.reg .pred q;\nsetp.eq.u32 q, %1, 0xFFFFFFFF;\n@q ld.relaxed.gpu.global.v2.b32 {%0,%1}, [%2+%3];\n}"
                 : "+r"(v.x), "+r"(v.y) : "l"(p), "n"(OFF) : "memory");
}
__device__ __forceinline__ uint32_t max3(uint32_t a, uint32_t b, uint32_t c) { return max(max(a, b), c); }
__device__ __forceinline__ uint32_t pub_slot(int s) { return (s & 1) * XCHG_SLOT + ((s >> 1) & 1) * PUB_BYTES; }

__device__ __forceinline__ uint8_t* xaddr(uint32_t lo, uint32_t hi) {
    uint64_t a;
    asm("mov.b64 %0, {%1, %2};" : "=l"(a) : "r"(lo), "r"(hi));
    return reinterpret_cast<uint8_t*>(a);
}
template <int N> __device__ __forceinline__ uint32_t delay_zero(uint32_t a) {
    uint32_t x = a;
    #pragma unroll
    for (int i = 0; i < N; i++) x = lds32_volatile(x);
    return x - a;
}
__device__ __forceinline__ uint32_t fresh(uint32_t x) { asm volatile("" : "+r"(x)); return x; }

template <int NT> __device__ __forceinline__ uint32_t wo_addr(uint32_t ao, uint32_t a3, int n) {
    return (n % NT == 2 ? a3 : ao + (n % NT) * 32768) + (n / NT) * 1024;
}
__device__ __forceinline__ void sched_fence(uint32_t& x, uint32_t zero) { x ^= clock32() & zero; }
template <int NT, int PF, typename F>
__device__ __forceinline__ void wo_phase(F&& hook, uint32_t (&st)[8 * NT][4], uint32_t ao, uint32_t a3, uint32_t l16, uint32_t tbl, uint32_t sums,
                                         uint32_t slot, uint32_t xhi, uint32_t third, uint32_t zero, uint32_t& tok, uint32_t xbar, uint32_t xpar, bool& x_ok) {
    constexpr int AHEAD = PF > WO_AHEAD ? PF - NT : WO_AHEAD;
    uint32_t of[4][4];
    uint2 sm;
    uint4 t;
    ldsm4t(l16 + SM_O, of[0]);
    #pragma unroll
    for (int n = PF; n < AHEAD; n++) {
        ldsm4t(wo_addr<NT>(ao, a3, n), st[n]);
        if (n == 2 * NT - 1) ldsm4t(l16 + SM_O + 512, of[1]);
    }
    if (PF >= 2 * NT) ldsm4t(l16 + SM_O + 512, of[1]);
    float acc[NT][4];
    #pragma unroll
    for (int i = 0; i < NT; i++) { acc[i][0] = acc[i][1] = acc[i][2] = acc[i][3] = 0.f; }
    #pragma unroll
    for (int kk = 0; kk < 8; kk++) {
        if (WO_FENCE && kk < 7) sched_fence(tok, zero);
        #pragma unroll
        for (int i = 0; i < NT; i++) {
            const int n = kk * NT + i;
            mma_a(acc[i], st[n], of[kk >> 1][(kk & 1) * 2], of[kk >> 1][(kk & 1) * 2 + 1]);
            if (n + AHEAD >= PF && n + AHEAD < 8 * NT) ldsm4t(wo_addr<NT>(ao, a3, n + AHEAD), st[n + AHEAD]);
        }
        if (kk == XB_POS - 1) hook();
        if (kk == 1 || kk == 3) ldsm4t(l16 + SM_O + ((kk >> 1) + 2) * 512, of[(kk >> 1) + 2]);
        if (kk == (NT == 3 ? 5 : 4)) {
            const uint32_t x = fresh(l16);
            sm = lds64(sums + ((x >> 1) & 0x18));
            t = lds128(tbl + ((x >> 3) & 0x30));
            x_ok = mbar_test_wait(xbar, xpar);
        }
    }
    const float i0 = rcp(__uint_as_float(sm.x)), i1 = rcp(__uint_as_float(sm.y));
    const uint32_t d = slot + ((fresh(l16) >> 1) & 0x38);
    const uint32_t pl[3] = {t.x + d, t.y + d, t.z + d};
    #pragma unroll
    for (int i = 0; i < NT; i++)
        asm volatile("{\n.reg .pred p;\nsetp.ne.u32 p, %3, 0;\n@p st.relaxed.gpu.global.v2.b32 [%0], {%1,%2};\n}"
                     ::"l"(xaddr(pl[i], xhi)), "r"(pack_bf16(acc[i][0] * i0, acc[i][1] * i1)), "r"(pack_bf16(acc[i][2] * i0, acc[i][3] * i1)),
                       "r"(i < 2 ? 1u : third) : "memory");
}

constexpr uint32_t SMEM_ORIGIN = 1024;
constexpr uint64_t DESC_BASE = (1ull << 16) | (0x40000040ull << 32);
template <int OFFB, int SCALE_D>
__device__ __forceinline__ void wgmma_n32_rs(float (&d)[16], const uint32_t* a, uint32_t one) {
    asm volatile(
        "{\n.reg .b64 db;\nmad.wide.u32 db, %20, %21, %22;\n"
        "wgmma.mma_async.sync.aligned.m64n32k16.f32.bf16.bf16 {%0,%1,%2,%3,%4,%5,%6,%7,%8,%9,%10,%11,%12,%13,%14,%15}, "
        "{%16,%17,%18,%19}, db, %23, 1, 1, 0;\n}"
        : "+f"(d[0]), "+f"(d[1]), "+f"(d[2]), "+f"(d[3]), "+f"(d[4]), "+f"(d[5]), "+f"(d[6]), "+f"(d[7]),
          "+f"(d[8]), "+f"(d[9]), "+f"(d[10]), "+f"(d[11]), "+f"(d[12]), "+f"(d[13]), "+f"(d[14]), "+f"(d[15])
        : "r"(a[0]), "r"(a[1]), "r"(a[2]), "r"(a[3]), "r"(one), "n"((SMEM_ORIGIN + OFFB) >> 4), "l"(DESC_BASE), "n"(SCALE_D));
}
template <int OFFA, int OFFB, int SCALE_D>
__device__ __forceinline__ void wgmma_n32_ss(float (&d)[16], uint32_t one) {
    asm volatile(
        "{\n.reg .b64 da, db;\nmad.wide.u32 da, %16, %17, %19;\nmad.wide.u32 db, %16, %18, %19;\n"
        "wgmma.mma_async.sync.aligned.m64n32k16.f32.bf16.bf16 {%0,%1,%2,%3,%4,%5,%6,%7,%8,%9,%10,%11,%12,%13,%14,%15}, "
        "da, db, %20, 1, 1, 1, 0;\n}"
        : "+f"(d[0]), "+f"(d[1]), "+f"(d[2]), "+f"(d[3]), "+f"(d[4]), "+f"(d[5]), "+f"(d[6]), "+f"(d[7]),
          "+f"(d[8]), "+f"(d[9]), "+f"(d[10]), "+f"(d[11]), "+f"(d[12]), "+f"(d[13]), "+f"(d[14]), "+f"(d[15])
        : "r"(one), "n"((SMEM_ORIGIN + OFFA) >> 4), "n"((SMEM_ORIGIN + OFFB) >> 4), "l"(DESC_BASE), "n"(SCALE_D));
}
template <int WG, int J0, int J1, int I, bool ACC, bool FENCE = true>
__device__ __forceinline__ void token_mma(float (&ta)[2][16], const uint32_t (&wr)[NREG][2][4], uint32_t one) {
    if (FENCE) asm volatile("wgmma.fence.sync.aligned;" ::: "memory");
    sfor<J0, J1>([&](auto J) {
        constexpr int j = J.value, c = j >> 2, offb = SM_X + WG * 32768 + c * 4096 + (j & 3) * 32, sc = (ACC || j != J0) ? 1 : 0;
        if constexpr ((j & 3) != 0) wgmma_n32_rs<offb, sc>(ta[I], wr[reg_idx(j)][I], one);
        else if constexpr (WG == 0 || c >= (I ? TOK_MOVED1 : TOK_MOVED)) wgmma_n32_ss<SM_WQ + WG * 32768 + I * 16384 + c * 2048, offb, sc>(ta[I], one);
        constexpr int m = I ? c : c - 4;
        if constexpr (WG == 0 && (j & 3) == 1 && m >= 0 && m < (I ? TOK_MOVED : TOK_MOVED1))
            wgmma_n32_ss<SM_WQ + 32768 + (1 - I) * 16384 + m * 2048, SM_X + 32768 + m * 4096, 1>(ta[I], one);
    });
    asm volatile("wgmma.commit_group.sync.aligned;" ::: "memory");
}
__device__ __forceinline__ void warp_arrive(uint32_t bar) {
    __syncwarp();
    if (elect_one()) mbar_arrive(bar);
}
__device__ __forceinline__ void remote_arrive(uint32_t bar, uint32_t rank) {
    asm volatile("mbarrier.arrive.relaxed.cluster.shared::cluster.b64 _, [%0];" ::"r"(mapa(bar, rank)) : "memory");
}
__device__ __forceinline__ void x_load(const RecParams& p, uint32_t sb, int sg, int g) {
    if ((EXP >> g) & 1) return;
    tma_load_3d_mc(sb + SM_X + g * 16384, &p.tmX, 0, sg * SEG, g * 4, sb + SM_BAR + BAR_XG + 8 * g, (uint16_t)7);
}

__device__ __forceinline__ void rec_steps(const RecParams& p, const uint32_t (&wr)[NREG][2][4], const uint32_t sb, const int warp,
                                          const int cta, const int head, const int rank) {
    const int wq = warp & 3, wg = warp >> 2;
    const uint32_t bar = sb + SM_BAR;
    const uint32_t xhi = (uint32_t)((uint64_t)p.xchg >> 32);
    const float sl2 = 0.08838834764831845f * 1.4426950408889634f;
    const bool has_unit = warp >= 5 && (warp < 7 || cta < 64);
    const bool qk = rank < 2;
    const uint32_t pa = rank == 2 ? 0 : rank + 1, pb = rank == 0 ? 2 : rank - 1;
    const uint32_t tbl = sb + SM_TBL + warp * 64;
    const bool att = (warp & 6) == 2;
    const int stile = warp < 5 ? warp : warp - 3;

    const uint32_t u_st = uniform(SM_QK - SM_WQ - wg * (32768 - 1024));
    const uint32_t u_xa = uniform(sb + (qk ? SM_SP + rank * 1280 + stile * 256 : SM_VM + warp * 256));
    const uint32_t u_key = uniform(!qk || att || warp == 7 ? 0 : sb + (warp == 4 ? SM_QK + 1024 : SM_K + stile * 1024));
    const uint32_t u_bx = uniform(bar + (qk ? BAR_X : BAR_VM)), u_bra = uniform(mapa(u_bx, pa)), u_brb = uniform(mapa(u_bx, pb));
    const uint32_t u_src = uniform(lds32_volatile(tbl + 44));
    const uint32_t u_kv = uniform(qk && wg == 0 ? ~0u : (((rank >> 1) * NSEG * NH + head) * 8 + (qk ? rank * 4 + wq : warp)) * 64);
    const uint32_t u_free = uniform(mapa(bar + (warp == 5 ? BAR_VF : BAR_F0), warp == 5 ? 2 : 0));
    const uint32_t u_role = uniform((has_unit ? 1 : 0) | (att ? 2 : 0) | (wg == 1 || qk ? 4 : 0) | (!qk && warp == 0 ? 8 : 0) | (rank != 0 && warp == (XB_POS ? 2 : 1) ? 16 : 0) |
                                    (warp == 5 || warp == 6 ? 32 : 0));
    uint32_t l16, aq, ao;
    {
        const int lane = threadIdx.x & 31, mi = lane >> 3, r8 = lane & 7, r16 = (mi >> 1) * 8 + r8;
        l16 = opaque(sb + lane * 16);
        aq = opaque(sb + SM_WQ + wg * 32768 + r16 * 128 + (((wq * 2 + (mi & 1)) ^ r8) << 4));
        ao = opaque(sb + SM_WO + (warp >> 1) * 8192 + r16 * 64 + ((((warp & 1) * 2 + (mi & 1)) ^ ((r8 >> 1) & 3)) << 4));
    }

    uint32_t mphase = 0;
    bool x0_ok = false;
    #pragma unroll 1
    for (int s = 0;; s++) {
        const uint32_t par = s & 1;
        uint32_t at[16][4];
        auto at_early = [](int i) { return i < 2 || ((i & 1) == 1 && (i >> 1) <= AT_PF - 2); };
        auto at_prefetch = [&](bool first) {
            #pragma unroll
            for (int i = 0; i < 16; i++)
                if (at_early(i) && first == ((i & 1) == 1 && (i >> 1) < AT_FIRST)) ldsm4t(aq + (i & 1) * 16384 + (i >> 1) * 2048, at[i]);
        };
        if (wg == 0) {
            float ta[2][16];
            if (!x0_ok) mbar_wait_bounded(bar + BAR_XG, par);
            STAMP(6);
            auto park = [&](int i, uint32_t dst) {
                #pragma unroll
                for (int e = 0; e < 16; e++) asm volatile("" : "+f"(ta[i][e]));
                #pragma unroll
                for (int j = 0; j < 4; j++)
                    sts128(l16 + dst + j * 2048 + wq * 512, __float_as_uint(ta[i][4 * j]), __float_as_uint(ta[i][4 * j + 1]),
                           __float_as_uint(ta[i][4 * j + 2]), __float_as_uint(ta[i][4 * j + 3]));
            };
            if (EXP & 64) spin_clks(1200);
            token_mma<0, 0, 16, 0, false>(ta, wr, 1);
            mbar_wait_bounded(bar + BAR_XG + 8, par);
            if (TOK_MOVED1 > 0) mbar_wait_bounded(bar + BAR_XG + 16, par);
            if (AT_POS0 == 0) at_prefetch(true);
            token_mma<0, 16, 32, 0, true>(ta, wr, p.one[1]);
            if (TOK_MOVED1 == 0) mbar_wait_bounded(bar + BAR_XG + 16, par);
            token_mma<0, 0, 16, 1, false, TOK_MOVED1 == 0>(ta, wr, p.one[0]);
            if (TOK_MOVED > 4) mbar_wait_bounded(bar + BAR_XG + 24, par);
            token_mma<0, 16, 32, 1, true, (TOK_MOVED > 4)>(ta, wr, 1);
            asm volatile("wgmma.wait_group.sync.aligned 1;" ::: "memory");
            park(0, SM_PARK0);
            warp_arrive(bar + BAR_GO);
            asm volatile("wgmma.wait_group.sync.aligned 0;" ::: "memory");
            park(1, SM_PARK1);
            if (TOK_MOVED <= 4) mbar_wait_bounded(bar + BAR_XG + 24, par);
            warp_arrive(bar + BAR_PK);
            const uint8_t* src = xaddr(u_src + pub_slot(s), xhi);
            auto fetch = [&]() {
                if (elect_one()) {
                    mbar_arrive_expect_tx(bar + BAR_M + 8 * wq, 4096);
                    bulk_load(sb + SM_MEM + wq * 4096, src, 4096, bar + BAR_M + 8 * wq);
                }
            };
            named_bar_sync(7, REC_THREADS - 32);
            if (FETCH_REL) {
                const uint4 t = lds128(bar + BAR_TPUB);
                const uint32_t now = clock32();
                spin_until(now + FETCH_DELAY - min(min(min(now - t.y, now - t.z), now - t.w), (uint32_t)FETCH_DELAY));
            } else {
                spin_clks(FETCH_DELAY);
            }
            fetch();
            STAMP(12);
            if (warp == 0 && elect_one()) {
                if (qk) mbar_arrive_expect_tx(bar + BAR_V, (EXP & 16) ? 32 : 8192);
                mbar_arrive_expect_tx(bar + BAR_X, qk ? 1280 : 2560);
                mbar_arrive_expect_tx(bar + BAR_VM, qk ? 2048 : 0);
            }
            if (AT_POS0 == 1) at_prefetch(true);
            at_prefetch(false);
            const uint32_t x = fresh(l16) - sb;
            const uint32_t ca = sb + SM_MEM + wq * 4096 + x * 2 + ((x >> 4) & 0x1C);
            #pragma unroll 1
            for (uint32_t n = 0; n < POLL_LIMIT; n++) {
                mbar_wait_bounded(bar + BAR_M + 8 * wq, mphase);
                mphase ^= 1;
                const uint32_t c0 = lds32_volatile(ca), c1 = lds32_volatile(ca + 1024), c2 = lds32_volatile(ca + 2048), c3 = lds32_volatile(ca + 3072);
                if (!__any_sync(~0u, max(max3(c0, c1, c2), c3) == (NO_COMM ? 0x12345u : SENT))) break;
                fetch();
            }
            STAMP(0);
            named_bar_sync(0, REC_THREADS);
            if (u_role & 8) {
                asm volatile("fence.proxy.async.shared::cta;" ::: "memory");
                mbar_wait_bounded(bar + BAR_VF, par);
                if (elect_one()) {
                    #pragma unroll
                    for (int r = 0; r < 2; r++)
                        asm volatile("cp.async.bulk.shared::cluster.shared::cta.mbarrier::complete_tx::bytes [%0], [%1], %2, [%3];"
                                     ::"r"(mapa(sb + SM_V, r)), "r"(sb + SM_V), "r"((EXP & 16) ? 32 : 8192), "r"(mapa(bar + BAR_V, r)) : "memory");
                }
            }
        } else {
            at_prefetch(true);
            if (s > 0) {
                if (u_role & 1) {
                    const uint32_t ln = (fresh(l16) >> 4) & 31;
                    const uint32_t ibl = lds32_volatile(tbl + 12) + (par ^ 1) * XCHG_SLOT + ln * 8;
                    const uint32_t publ = lds32_volatile(tbl + 28) + pub_slot(s) + (ln & 16) * 256 + (ln & 8) * 16 + (ln & 7) * 4;
                    const bool odd = ln & 8;
                    const uint8_t* ib = xaddr(ibl + delay_zero<POLL_DELAY>(bar + BAR_SELF), xhi);
                    STAMP(8);
                    uint2 v[8];
                    float a0, a1, a2, a3;
                    auto sum8 = [&]() {
                        a0 = ((bf16_lo(v[0].x) + bf16_lo(v[1].x)) + (bf16_lo(v[2].x) + bf16_lo(v[3].x))) +
                             ((bf16_lo(v[4].x) + bf16_lo(v[5].x)) + (bf16_lo(v[6].x) + bf16_lo(v[7].x)));
                        a1 = ((bf16_hi(v[0].x) + bf16_hi(v[1].x)) + (bf16_hi(v[2].x) + bf16_hi(v[3].x))) +
                             ((bf16_hi(v[4].x) + bf16_hi(v[5].x)) + (bf16_hi(v[6].x) + bf16_hi(v[7].x)));
                        a2 = ((bf16_lo(v[0].y) + bf16_lo(v[1].y)) + (bf16_lo(v[2].y) + bf16_lo(v[3].y))) +
                             ((bf16_lo(v[4].y) + bf16_lo(v[5].y)) + (bf16_lo(v[6].y) + bf16_lo(v[7].y)));
                        a3 = ((bf16_hi(v[0].y) + bf16_hi(v[1].y)) + (bf16_hi(v[2].y) + bf16_hi(v[3].y))) +
                             ((bf16_hi(v[4].y) + bf16_hi(v[5].y)) + (bf16_hi(v[6].y) + bf16_hi(v[7].y)));
                    };
                    if (REPOLL) {
                        #pragma unroll
                        for (int i = 0; i < 8; i++) v[i] = make_uint2(SENT, SENT);
                    }
                    #pragma unroll 1
                    for (uint32_t n = 0; n < POLL_LIMIT; n++) {
                        if (REPOLL) sfor<0, 8>([&](auto I) { repoll_v2<I.value * 256>(v[I.value], ib); });
                        else sfor<0, 8>([&](auto I) { poll_v2<I.value * 256>(v[I.value], ib); });
                        const uint32_t mx = max(max3(v[0].y, v[1].y, v[2].y), max3(max3(v[3].y, v[4].y, v[5].y), v[6].y, v[7].y));
                        if (SPEC_SUM) { sum8(); asm volatile("" : "+f"(a0), "+f"(a1), "+f"(a2), "+f"(a3)); }
                        if (!__any_sync(~0u, mx == (NO_COMM ? 0x12345u : SENT))) break;
                    }
                    STAMP(9);
                    if (!SPEC_SUM) sum8();
                    float k0 = odd ? a2 : a0, k1 = odd ? a3 : a1;
                    k0 += __shfl_xor_sync(~0u, odd ? a0 : a2, 8);
                    k1 += __shfl_xor_sync(~0u, odd ? a1 : a3, 8);
                    k0 += __shfl_xor_sync(~0u, k0, 16);
                    k1 += __shfl_xor_sync(~0u, k1, 16);
                    st_relaxed_b32(xaddr(publ, xhi), pack_bf16(k0, k1));
                    STAMP(11);
                } else if (warp == 4) {
                    bulk_wait_read_all();
                    if (elect_one()) remote_arrive(bar + BAR_F3, 2);
                    if (!qk) {
                        mbar_wait_bounded(bar + BAR_F3, par ^ 1);
                        if (elect_one()) x_load(p, sb, s, 3);
                    }
                    if (elect_one()) {
                        bulk_wait_all();
                        signal_flag(p.flags + F_PROGRESS + s - 1);
                    }
                    __syncwarp();
                    STAMP(10);
                }
            }
            float ta[2][16];
            uint32_t w[8];
            auto unpark = [&](int i, uint32_t src) {
                mbar_wait_bounded(bar + (i ? BAR_GO : BAR_PK), par);
                #pragma unroll
                for (int j = 0; j < 4; j++) {
                    const uint4 v = lds128(l16 + src + j * 2048 + wq * 512);
                    ta[i][4 * j] = __uint_as_float(v.x); ta[i][4 * j + 1] = __uint_as_float(v.y);
                    ta[i][4 * j + 2] = __uint_as_float(v.z); ta[i][4 * j + 3] = __uint_as_float(v.w);
                }
            };
            if (FETCH_REL) sts32(bar + BAR_TPUB + 4 * wq, clock32());
            if (warp != 4) named_bar_arrive(7, REC_THREADS - 32);
            unpark(1, SM_PARK0);
            STAMP(6);
            token_mma<1, 0, 16, 1, true>(ta, wr, 1);
            unpark(0, SM_PARK1);
            token_mma<1, 16, 32, 1, true>(ta, wr, 1);
            token_mma<1, 16, 32, 0, true>(ta, wr, 1);
            token_mma<1, 0, 16, 0, true, false>(ta, wr, 1);
            auto put_tile = [&](int m, const uint32_t (&q)[8]) {
                #pragma unroll
                for (int h = 0; h < 2; h++) {
                    if (qk) asm volatile("stmatrix.sync.aligned.m8n8.x4.trans.shared.b16 [%0], {%1,%2,%3,%4};"
                                         ::"r"(aq - (SM_WQ + 32768) + (m ? SM_K : SM_QS) + h * 2048), "r"(q[4 * h]), "r"(q[4 * h + 1]),
                                           "r"(q[4 * h + 2]), "r"(q[4 * h + 3]) : "memory");
                    else sts128(l16 + SM_V + wq * 2048 + m * 1024 + h * 512, q[4 * h], q[4 * h + 1], q[4 * h + 2], q[4 * h + 3]);
                }
            };
            auto pack_tile = [&](int i) {
                #pragma unroll
                for (int e = 0; e < 16; e++) asm volatile("" : "+f"(ta[i][e]));
                #pragma unroll
                for (int j = 0; j < 8; j++) w[j] = pack_bf16(ta[i][2 * j], ta[i][2 * j + 1]);
            };
            asm volatile("wgmma.wait_group.sync.aligned 2;" ::: "memory");
            pack_tile(1);
            at_prefetch(false);
            asm volatile("wgmma.wait_group.sync.aligned 1;" ::: "memory");
            if ((u_role & 32) && elect_one())
                asm volatile("mbarrier.arrive.relaxed.cluster.shared::cluster.b64 _, [%0];" ::"r"(u_free) : "memory");
            put_tile(0, w);
            asm volatile("wgmma.wait_group.sync.aligned 0;" ::: "memory");
            pack_tile(0);
            put_tile(1, w);
            STAMP(0);
            named_bar_sync(0, REC_THREADS);
            STAMP(14);
        }
        const uint32_t mb = l16 + SM_MEM + wg * 8192;
        float acc[2][2][4];
        {
            uint32_t b[2][4];
            ldsm4t(mb, b[0]);
            ldsm4t(mb + 512, b[1]);
            #pragma unroll
            for (int i = 0; i < AT_AHEAD; i++)
                if (!at_early(i)) ldsm4t(aq + (i & 1) * 16384 + (i >> 1) * 2048, at[i]);
            STAMPD(1, b[0][0]);
            #pragma unroll
            for (int i = 0; i < 4; i++) { for (int e = 0; e < 4; e++) acc[i >> 1][i & 1][e] = 0.f; }
            #pragma unroll
            for (int u = 0; u < 16; u++) {
                #pragma unroll
                for (int h = 0; h < 2; h++) {
                    const int j = 2 * u + h;
                    #pragma unroll
                    for (int m = 0; m < 2; m++) {
                        if ((j & 3) == 0) mma_a(acc[h][m], at[(j >> 2) * 2 + m], b[u & 1][2 * h], b[u & 1][2 * h + 1]);
                        else mma_a(acc[h][m], wr[reg_idx(j)][m], b[u & 1][2 * h], b[u & 1][2 * h + 1]);
                    }
                }
                if (u + 2 < 16) ldsm4t(mb + (u + 2) * 512, b[u & 1]);
                if (u + AT_AHEAD < 16 && !at_early(u + AT_AHEAD))
                    ldsm4t(aq + ((u + AT_AHEAD) & 1) * 16384 + ((u + AT_AHEAD) >> 1) * 2048, at[u + AT_AHEAD]);
            }
        }
        sts128(l16 + SM_RED + warp * 512, __float_as_uint(acc[0][1][0] + acc[1][1][0]), __float_as_uint(acc[0][1][1] + acc[1][1][1]),
               __float_as_uint(acc[0][1][2] + acc[1][1][2]), __float_as_uint(acc[0][1][3] + acc[1][1][3]));
        #pragma unroll
        for (int e = 0; e < 4; e++) acc[0][0][e] += acc[1][0][e];
        const uint32_t x16 = fresh(l16);
        const uint32_t sa = fresh((x16 & 0x70) * 8 + ((((x16 >> 3) & 0x30) ^ x16) & 0x70));
        const uint32_t sq = fresh(sa ^ ((((x16 >> 7) ^ (x16 >> 8)) & 1) * 0x30));
        const uint32_t x8 = (x16 & 0x1F0) >> 1;
        const uint32_t xra = fresh(x8 + __byte_perm(u_xa, u_bra, 0x7210)), xrb = fresh(x8 + __byte_perm(u_xa, u_brb, 0x7210));
        STAMP(2);
        named_bar_sync(1 + wq, 64);
        uint32_t p0, p1;
        {
            const uint4 v = lds128(l16 + SM_RED + (warp ^ 4) * 512);
            p0 = pack_bf16(acc[0][0][0] + __uint_as_float(v.x), acc[0][0][1] + __uint_as_float(v.y));
            p1 = pack_bf16(acc[0][0][2] + __uint_as_float(v.z), acc[0][0][3] + __uint_as_float(v.w));
        }
        auto send = [&](uint32_t y0, uint32_t y1) {
            st_async_v2(xra, y0, y1, u_bra);
            st_async_v2(xrb, y0, y1, u_brb);
            sts64(x8 + u_xa, y0, y1);
            warp_arrive(u_bx);
        };
        if (qk) {
            asm volatile("stmatrix.sync.aligned.m8n8.x2.trans.shared.b16 [%0], {%1,%2};" ::"r"(aq + u_st), "r"(p0), "r"(p1) : "memory");
            named_bar_sync(5, REC_THREADS);
            if (u_key != 0) {
                uint32_t qa[2][4], kf[2][4];
                ldsm4(sq + sb + SM_QK, qa[0]);
                ldsm4(sa + u_key, kf[0]);
                ldsm4((sq ^ 64) + sb + SM_QK, qa[1]);
                ldsm4((sa ^ 64) + u_key, kf[1]);
                float se[4] = {0.f, 0.f, 0.f, 0.f}, so[4] = {0.f, 0.f, 0.f, 0.f};
                #pragma unroll
                for (int u = 0; u < 2; u++) {
                    mma_a(se, qa[u], kf[u][0], kf[u][1]);
                    mma_a(so, qa[u], kf[u][2], kf[u][3]);
                }
                send(__float_as_uint(se[0] + so[2]), __float_as_uint(se[1] + so[3]));
            }
        } else {
            send(p0, p1);
        }
        STAMP(3);
        const uint32_t lane = (fresh(l16) >> 4) & 31;
        auto kv_stores = [&]() {
            if (u_kv != ~0u) {
                uint32_t* dst = reinterpret_cast<uint32_t*>(p.kv_mem) + (u_kv + s * (NH * 512) + lane);
                dst[0] = p0;
                dst[32] = p1;
            }
        };
        auto tile_stores = [&]() {
            if (warp == 4) {
                asm volatile("fence.proxy.async.shared::cta;" ::: "memory");
                if (elect_one()) {
                    __nv_bfloat16* dst = p.qkv_tok + ((size_t)s * NH + head) * (SEG * DH);
                    constexpr size_t MAT = (size_t)NSEG * NH * SEG * DH;
                    bulk_store(dst + (qk ? rank * (SEG * 64) : 2 * MAT), sb + (qk ? SM_QS : SM_V), (EXP & 32) ? 32 : 4096);
                    bulk_store(dst + (qk ? MAT + rank * (SEG * 64) : 2 * MAT + SEG * 64), sb + (qk ? SM_K : SM_V + 4096), (EXP & 32) ? 32 : 4096);
                    bulk_commit();
                }
            }
        };
        if (((s + 1) & 62) == 0) {
            if (s == NSEG - 1) { kv_stores(); tile_stores(); break; }
            mbar_wait_bounded(bar + BAR_WO, 0);
            if (PDL_POS == 5) pdl_launch_dependents();
            PSTAMP(8);
        }
        const uint32_t slot = par * XCHG_SLOT;
        if (u_role & 2) {
            if (qk) mbar_wait_bounded(bar + BAR_V, par);
            uint32_t vt[2][4][4];
            auto v_load = [&](int i0, int i1) {
                #pragma unroll
                for (int i = i0; i < i1; i++) {
                    const uint4 v = lds128(l16 + SM_V + (warp & 1) * 1024 + (i & 3) * 2048 + (i >> 2) * 512);
                    vt[i >> 2][i & 3][0] = v.x; vt[i >> 2][i & 3][1] = v.y; vt[i >> 2][i & 3][2] = v.z; vt[i >> 2][i & 3][3] = v.w;
                }
            };
            v_load(0, V_EARLY);
            kv_stores();
            const uint32_t l8 = fresh(sb + lane * 8);
            mbar_wait_bounded(bar + BAR_X, par);
            STAMP(4);
            float sv[10];
            #pragma unroll
            for (int j = 0; j < 5; j++) {
                const uint2 a = lds64(l8 + SM_SP + j * 256), b = lds64(l8 + SM_SP + 1280 + j * 256);
                sv[2 * j] = __uint_as_float(a.x) + __uint_as_float(b.x);
                sv[2 * j + 1] = __uint_as_float(a.y) + __uint_as_float(b.y);
            }
            float mx = fmaxf(fmaxf(fmaxf(sv[0], sv[1]), fmaxf(sv[2], sv[3])), fmaxf(fmaxf(sv[4], sv[5]), fmaxf(sv[6], sv[7])));
            mx = fmaxf(mx, fmaxf(sv[8], sv[9]));
            const float m1 = __shfl_xor_sync(~0u, mx, 1), m2 = __shfl_xor_sync(~0u, mx, 2), m3 = __shfl_xor_sync(~0u, mx, 3);
            __syncwarp();
            v_load(V_EARLY, 8);
            const bool vm_ok = mbar_test_wait(bar + BAR_VM, par);
            mx = fmaxf(fmaxf(mx, m1), fmaxf(m2, m3));
            const float mo = mx * sl2;
            #pragma unroll
            for (int j = 0; j < 10; j++) sv[j] = ex2(fmaf(sv[j], sl2, -mo));
            const uint32_t e0 = pack_bf16(sv[0], sv[1]), e1 = pack_bf16(sv[2], sv[3]);
            const uint32_t e2 = pack_bf16(sv[4], sv[5]), e3 = pack_bf16(sv[6], sv[7]), em = pack_bf16(sv[8], sv[9]);
            float o[4][4];
            #pragma unroll
            for (int i = 0; i < 4; i++) {
                o[i][0] = o[i][1] = o[i][2] = o[i][3] = 0.f;
                mma_a(o[i], vt[0][i], e0, e1);
            }
            const float sum = (((sv[0] + sv[1]) + (sv[2] + sv[3])) + ((sv[4] + sv[5]) + (sv[6] + sv[7]))) + (sv[8] + sv[9]);
            if (!vm_ok) mbar_wait_bounded(bar + BAR_VM, par);
            uint2 vm[4];
            #pragma unroll
            for (int i = 0; i < 4; i++) {
                vm[i] = lds64(l8 + SM_VM + (warp & 1) * 1024 + i * 256);
                mma_a(o[i], vt[1][i], e2, e3);
            }
            #pragma unroll
            for (int i = 0; i < 4; i++) mma1688(o[i], vm[i].x, vm[i].y, em);
            {
                const float s1 = __shfl_xor_sync(~0u, sum, 1), s2 = __shfl_xor_sync(~0u, sum, 2), s3 = __shfl_xor_sync(~0u, sum, 3);
                sts32(sb + SM_SUM + (lane & 28), __float_as_uint((sum + s1) + (s2 + s3)));
            }
            #pragma unroll
            for (int i = 0; i < 4; i += 2)
                stsm_x4(l16 + SM_O + (warp & 1) * 1024 + i * 256, pack_bf16(o[i][0], o[i][1]), pack_bf16(o[i][2], o[i][3]),
                        pack_bf16(o[i + 1][0], o[i + 1][1]), pack_bf16(o[i + 1][2], o[i + 1][3]));
            STAMP(5);
            uint32_t st[16][4];
            #pragma unroll
            for (int n = 0; n < WO_PF0; n++) ldsm4t(wo_addr<2>(ao, 0, n), st[n]);
            named_bar_sync(6, REC_THREADS);
            wo_phase<2, WO_PF0>([&]() { if ((u_role & 16) && elect_one()) x_load(p, sb, s + 1, rank); }, st, ao, 0, l16, tbl, sb + SM_SUM, slot, xhi, 0, p.one[0] - 1, aq, bar + BAR_XG, par ^ 1, x0_ok);
        } else {
            const uint32_t a3 = fresh(ao) + (wg == 0 ? 10 : 6) * 8192;
            uint32_t st[24][4];
            #pragma unroll
            for (int n = 0; n < WO_PFA; n++) ldsm4t(wo_addr<3>(ao, a3, n), st[n]);
            kv_stores();
            tile_stores();
            if (u_role & 1) {
                uint8_t* ib = xaddr(lds32_volatile(tbl + 12) + (par ^ 1) * XCHG_SLOT + lane * 16, xhi);
                #pragma unroll
                for (int i = 0; i < 4; i++) st_relaxed_v4(ib + i * 512, SENT);
                st_relaxed_b32(xaddr(lds32_volatile(tbl + 28) + pub_slot(s + 3) + (lane & 16) * 256 + (lane & 8) * 16 + (lane & 7) * 4, xhi), SENT);
            }
            if (warp == 1) {
                if (elect_one()) {
                    #pragma unroll
                    for (int g = 0; g < 4; g++) mbar_arrive_expect_tx(bar + BAR_XG + 8 * g, ((EXP >> g) & 1) ? 0 : 16384);
                }
                if (s + 2 < NSEG && cta < 4 && elect_one())
                    asm volatile("cp.async.bulk.prefetch.tensor.3d.L2.global [%0, {%1, %2, %3}];"
                                 ::"l"(&p.tmX), "r"(0), "r"((s + 2) * SEG), "r"(cta * 4) : "memory");
                if (rank == 0) {
                    mbar_wait_bounded(bar + BAR_F0, par);
                    if (elect_one()) x_load(p, sb, s + 1, 0);
                }
            }
            if (WO_PFA < WO_PF1 || (u_role & 16)) mbar_wait_bounded(bar + BAR_X, par);
            if (WO_PFA < WO_PF1) {
                spin_clks(WO_PFB_DELAY);
                #pragma unroll
                for (int n = WO_PFA; n < WO_PF1; n++) ldsm4t(wo_addr<3>(ao, a3, n), st[n]);
            }
            if (XB_POS == 0 && (u_role & 16)) {
                spin_clks(XB_DELAY);
                mbar_wait_bounded(bar + BAR_VM, par);
                if (elect_one()) x_load(p, sb, s + 1, rank);
            }
            named_bar_sync(6, REC_THREADS);
            wo_phase<3, WO_PF1>([]() {}, st, ao, a3, l16, tbl, sb + SM_SUM, slot, xhi, u_role & 4, p.one[0] - 1, aq, bar + BAR_XG, par ^ 1, x0_ok);
        }
        STAMP(7);
        if (wg == 0) named_bar_sync(9, REC_THREADS); else named_bar_arrive(9, REC_THREADS);
    }
    if (threadIdx.x == 128) KMARK(8);
    mbar_wait(bar + BAR_X, 1);
    mbar_wait(bar + BAR_VM, 1);
    if (qk) mbar_wait(bar + BAR_V, 1);
    named_bar_sync(0, REC_THREADS);
    if (warp == 4 && elect_one()) {
        bulk_wait_all();
        signal_flag(p.flags + F_PROGRESS + NSEG - 1);
        KMARK(9);
    }
}

__global__ void __launch_bounds__(REC_THREADS, 1) rec_kernel(const __grid_constant__ RecParams p) {
    extern __shared__ __align__(1024) uint8_t smem_raw[];
    const uint32_t sb = smem_u32(smem_raw);
    const int tid = threadIdx.x, lane = tid & 31;
    const int warp = __shfl_sync(~0u, tid >> 5, 0);
    const int cta = blockIdx.x, head = cta / 3, rank = cta % 3;
    const int wg = warp >> 2, wq = warp & 3;
    const uint32_t bar = sb + SM_BAR;
    uint8_t* const xb = p.xchg;
    const uint32_t xlo = (uint32_t)(uint64_t)xb;
    if ((sb & 0x3FFFF) != SMEM_ORIGIN) __trap();
    KENTER(1);
    auto w_box = [&](int part, int g, int i, uint32_t dst, uint32_t mb) {
        const int m = i ^ g;
        const CUtensorMap* tm = &p.tmW[rank == 2 ? 2 : m];
        const int col = head * DH + (rank == 2 ? m : rank) * 64, row = ((part + 1) & 3) * 16;
        tma_load_3d(dst, tm, col, row, g * 8, mb);
    };
    if (tid == 0) {
        mbar_init(bar + BAR_V, 1);
        for (int i = 0; i < 4; i++) { mbar_init(bar + BAR_XG + 8 * i, 1); mbar_init(bar + BAR_M + 8 * i, 1); }
        mbar_init(bar + BAR_GO, 4);
        mbar_init(bar + BAR_PK, 4);
        mbar_init(bar + BAR_VM, rank < 2 ? 1 : 9);
        mbar_init(bar + BAR_F0, 3);
        mbar_init(bar + BAR_F3, 3);
        mbar_init(bar + BAR_VF, 3);
        sts64(bar + BAR_MIN, ~0u, ~0u);
        mbar_init(bar + BAR_X, rank < 2 ? 6 : 1);
        for (int i = 0; i < 3; i++) mbar_init(bar + BAR_P0 + 8 * i, 1);
        mbar_init(bar + BAR_WQ, 1);
        mbar_init(bar + BAR_WO, 1);
        sts32(bar + BAR_SELF, bar + BAR_SELF);
        asm volatile("fence.mbarrier_init.release.cluster;" ::: "memory");
    }
    auto build_tables = [&](uint32_t av) {
        for (uint32_t n = 0; !__all_sync(~0u, (av >> 24) == 24); n++) {
            av = ld_acquire_b32(p.arrivals + (lane & 3));
            if (n > SPIN_LIMIT) __trap();
        }
        uint32_t cm[3];
        #pragma unroll
        for (int i = 0; i < 3; i++) {
            const int o = i * 32 + lane;
            cm[i] = __ballot_sync(~0u, __popc((__shfl_sync(~0u, av, o / 24) >> (o % 24 / 3 * 3)) & 7) >= 2);
        }
        auto color_of = [&](int o) { return ((o < 32 ? cm[0] : o < 64 ? cm[1] : cm[2]) >> (o & 31)) & 1u; };
        auto inbox = [&](int o, int byte) {
            uint32_t c = color_of(o);
            int ones = 0;
            #pragma unroll
            for (int i = 0; i < 3; i++) ones += __popc(o >= i * 32 + 32 ? cm[i] : (o > i * 32 ? cm[i] & ((1u << (o - i * 32)) - 1) : 0u));
            int idx = c ? ones : o - ones;
            if (idx >= INBOX_MAX) { idx = 2 * INBOX_MAX - 1 - idx; c ^= 1; }
            const uint32_t lin = idx * 6144 + byte, q = XCHG_INBOX + (lin >> 12) * 8192;
            return q + class_off(xlo + q, c) + (lin & 4095);
        };
        uint32_t off = 0;
        const int grp = (warp + 3) & 3;
        if (lane < 12) {
            const int i = lane >> 2, lt0 = rank * 6;
            const int o = i < 2 ? rank * 32 + warp * 4 + (lane & 3) : (lt0 + ((warp + 4) & 7)) * 4 + (lane & 3);
            off = inbox(min(o, 95), i * 2048 + head * 64);
        } else if (lane == 12) {
            off = inbox(cta, (grp % 3) * 2048);
        } else if (lane == 13) {
            int T;
            if (grp < 2) {
                T = (cta >> 5) * 22 + 8 * grp + ((cta & 31) >> 2);
            } else {
                const int tl = (cta & 63) >> 2;
                T = (tl / 6) * 22 + 16 + tl % 6;
            }
            off = XCHG_PUB + (T >> 4) * 8192 + (T & 15) * 256 + (cta & 3) * 32;
        } else if (lane == 14) {
            const uint32_t q = XCHG_PUB + wq * 8192;
            off = q + class_off(xlo + q, color_of(cta));
        }
        if (lane < 16) asm volatile("st.shared.b32 [%0], %1;" ::"r"(sb + SM_TBL + warp * 64 + (lane & 3) * 16 + (lane >> 2) * 4), "r"(xlo + off) : "memory");
    };
    if (tid >= 32 && tid < 37) asm volatile("prefetch.tensormap [%0];" ::"l"(&p.tmW[0] + (tid - 32)) : "memory");
    if (cta == 0 && tid < F_COUNT) p.flags[tid] = 0;
    __syncthreads();
    auto stage = [](int part) { return ((part + 2) % 3) * 65536; };
    auto load_part = [&](int part) {
        mbar_arrive_expect_tx(bar + BAR_P0 + 8 * part, 65536);
        for (int u = 0; u < 4; u++) w_box(part, u >> 1, u & 1, sb + stage(part) + u * 16384, bar + BAR_P0 + 8 * part);
    };
    asm volatile("barrier.cluster.arrive.relaxed.aligned;" ::: "memory");
    uint4 img = make_uint4(SENT, SENT, SENT, SENT);
    if (cta >= 92) {
        const unsigned short* m = reinterpret_cast<const unsigned short*>(p.mem0) + (cta - 92) * 256 + tid;
        uint32_t w[4];
        #pragma unroll
        for (int i = 0; i < 4; i++) w[i] = (uint32_t)__ldg(m + 2 * i * DM) | ((uint32_t)__ldg(m + (2 * i + 1) * DM) << 16);
        img = make_uint4(w[0], w[1], w[2], w[3]);
    }
    {
        constexpr int NPAIR = (XCHG_SLOT + PUB_BYTES) / 8192;
        uint8_t* pr = xb + (4 + cta) * 8192;
        const uint32_t c0 = class_off(xlo + (4 + cta) * 8192, 0);
        #pragma unroll
        for (int c = 0; c < 2; c++) {
            const bool timed = lane == 0 || (lane == 8 && c == (warp & 1));
            reinterpret_cast<uint4*>(pr + (c0 ^ (c << 12)))[tid] = make_uint4(timed ? 0u : SENT, SENT, SENT, SENT);
        }
        __syncwarp();
        if (lane == 0) {
            uint32_t x = 0;
            for (int k = 0; k < 3; k++) {
                if (k == PRO_EARLY && warp == 0) load_part(0);
                const uint32_t c = (k + warp) & 1, t0 = clock_after(x);
                x = atomicExch(reinterpret_cast<uint32_t*>(pr + (c0 ^ (c << 12)) + warp * 512 + (k >> 1) * 128 + x), SENT);
                const uint32_t lat = clock_after(x) - t0;
                asm volatile("red.shared.min.u32 [%0], %1;" ::"r"(bar + BAR_MIN + 4 * c), "r"(lat) : "memory");
            }
        }
        __syncwarp();
        if (cta >= 92 || 100 + cta < NPAIR) {
            if (cta >= 92) {
                if (img.x == SENT) img.x = 0x7FFF7FFFu;
                if (img.y == SENT) img.y = 0x7FFF7FFFu;
                if (img.z == SENT) img.z = 0x7FFF7FFFu;
                if (img.w == SENT) img.w = 0x7FFF7FFFu;
            }
            uint8_t* q = xb + (cta >= 92 ? cta - 92 : 100 + cta) * 8192;
            reinterpret_cast<uint4*>(q)[tid] = img;
            reinterpret_cast<uint4*>(q + 4096)[tid] = img;
        }
    }
    __syncthreads();
    PSTAMP(4);
    if (tid == 0) {
        for (int part = PRO_EARLY < 3 ? 1 : 0; part < 3; part++) load_part(part);
    }
    if (tid == 224) {
        const uint32_t c = lds32_volatile(bar + BAR_MIN) > lds32_volatile(bar + BAR_MIN + 4) ? 1 : 0;
        asm volatile("red.release.gpu.global.add.u32 [%0], %1;" ::"l"(p.arrivals + cta / 24), "r"((1u << 24) | (c << (cta % 24))) : "memory");
        if (PDL_POS == 0) pdl_launch_dependents();
    }
    uint32_t wr[NREG][2][4];
    uint32_t arrived = 0;
    {
        const int mi = lane >> 3, r8 = lane & 7;
        const uint32_t a0 = sb + wg * 32768 + ((mi >> 1) * 8 + r8) * 128 + (((wq * 2 + (mi & 1)) ^ r8) << 4);
        #pragma unroll
        for (int part = 0; part < 3; part++) {
            mbar_wait_bounded(bar + BAR_P0 + 8 * part, 0);
            if (part == 0) arrived = ld_relaxed_b32(p.arrivals + (lane & 3));
            #pragma unroll
            for (int j = 0; j < 8; j++) {
                #pragma unroll
                for (int i = 0; i < 2; i++) ldsm4t(a0 + stage(part) + i * 16384 + j * 2048, wr[part * 8 + j][i]);
            }
            asm volatile("fence.proxy.async.shared::cta;" ::: "memory");
            __syncthreads();
            PSTAMP(5 + part);
            if (tid == 224 && PDL_POS == part + 1) pdl_launch_dependents();
            if (tid == 0) {
                if (part == 0) {
                    for (int g = 0; g < 4; g++) {
                        mbar_arrive_expect_tx(bar + BAR_XG + 8 * g, 16384);
                        tma_load_3d(sb + SM_X + g * 16384, &p.tmX, 0, 0, g * 4, bar + BAR_XG + 8 * g);
                    }
                } else if (part == 1) {
                    mbar_arrive_expect_tx(bar + BAR_WQ, 65536);
                    for (int u = 0; u < 4; u++) w_box(3, u >> 1, u & 1, sb + SM_WQ + u * 16384, bar + BAR_WQ);
                } else {
                    mbar_arrive_expect_tx(bar + BAR_WO, 11 * 8192);
                    tma_load_3d(sb + SM_WO, &p.tmWo, 0, head * DH, rank * 11, bar + BAR_WO);
                    if (cta < 4)
                        asm volatile("cp.async.bulk.prefetch.tensor.3d.L2.global [%0, {%1, %2, %3}];"
                                     ::"l"(&p.tmX), "r"(0), "r"(SEG), "r"(cta * 4) : "memory");
                }
            }
        }
    }
    build_tables(arrived);
    __syncwarp();
    PSTAMP(9);
    mbar_wait(bar + BAR_WQ, 0);
    if (PDL_POS == 4) pdl_launch_dependents();
    asm volatile("barrier.cluster.wait.aligned;" ::: "memory");

    rec_steps(p, wr, sb, warp, cta, head, rank);
    if (cta == 0 && tid < 4) p.arrivals[tid] = 0;
    cluster_sync();
    if (tid == 0) KEXIT(1);
}

constexpr int ATT_SLOT = 28672;
constexpr int ATT_PAIRS = 8;
constexpr int ATT_BAR = ATT_PAIRS * ATT_SLOT;
constexpr int ATT_CNT = ATT_BAR + ATT_PAIRS * 16;
constexpr int ATT_SMEM = ATT_CNT + 96 * 4;
constexpr int ATT_THREADS = ATT_PAIRS * 64 + 32;
static_assert(F_OA == F_OB + 16, "one range of flags");
struct AttnParams {
    CUtensorMap tmOa;
    CUtensorMap tmQb, tmKb;
    CUtensorMap tmOb;
    const __nv_bfloat16* qkv_tok;
    const __nv_bfloat16* kv_mem;
    uint32_t* flags;
};

__device__ __forceinline__ void tok_attn_warp(uint32_t base, int mh, int lane) {
    const uint32_t sq = base, sk = base + 8192, sv = base + 16384, skm = base + 24576, svm = skm + 2048;
    const int g = lane >> 2, c = lane & 3, mi = lane >> 3, r8 = lane & 7;
    const int ntile = mh ? 5 : 3;
    float sc[5][4];
    #pragma unroll
    for (int j = 0; j < 5; j++) { sc[j][0] = sc[j][1] = sc[j][2] = sc[j][3] = 0.f; }
    #pragma unroll
    for (int t2 = 0; t2 < 4; t2++) {
        uint32_t a[2][4];
        #pragma unroll
        for (int h = 0; h < 2; h++) {
            const int row = mh * 16 + (mi & 1) * 8 + r8, ch16 = 4 * t2 + 2 * h + (mi >> 1);
            ldsm_x4(sq + (ch16 >> 3) * 4096 + row * 128 + (((ch16 & 7) ^ r8) << 4), a[h][0], a[h][1], a[h][2], a[h][3]);
        }
        const int ch16 = 4 * t2 + mi;
        uint32_t b[5][4];
        #pragma unroll
        for (int j = 0; j < 5; j++) {
            if (j < ntile) {
                if (j == 0) ldsm_x4_t(skm + t2 * 512 + lane * 16, b[j][0], b[j][1], b[j][2], b[j][3]);
                else ldsm_x4(sk + (ch16 >> 3) * 4096 + ((j - 1) * 8 + r8) * 128 + (((ch16 & 7) ^ r8) << 4), b[j][0], b[j][1], b[j][2], b[j][3]);
            }
        }
        #pragma unroll
        for (int h = 0; h < 2; h++) {
            #pragma unroll
            for (int j = 0; j < 5; j++)
                if (j < ntile) mma16816(sc[j], a[h][0], a[h][1], a[h][2], a[h][3], b[j][2 * h], b[j][2 * h + 1]);
        }
    }
    const float sl2 = 0.08838834764831845f * 1.4426950408889634f;
    uint32_t pf[2][5];
    float inv[2];
    #pragma unroll
    for (int q = 0; q < 2; q++) {
        const int tok = mh * 16 + q * 8 + g;
        float v[10];
        #pragma unroll
        for (int j = 0; j < 5; j++) {
            #pragma unroll
            for (int e = 0; e < 2; e++) {
                const int key = (j - 1) * 8 + 2 * c + e;
                v[2 * j + e] = (j == 0 || key <= tok) ? sc[j][2 * q + e] : -INFINITY;
            }
        }
        float mx = v[0];
        #pragma unroll
        for (int j = 1; j < 10; j++) mx = fmaxf(mx, v[j]);
        mx = fmaxf(mx, __shfl_xor_sync(~0u, mx, 1));
        mx = fmaxf(mx, __shfl_xor_sync(~0u, mx, 2));
        const float mo = mx * sl2;
        float sum = 0.f;
        #pragma unroll
        for (int j = 0; j < 10; j++) { v[j] = ex2(fmaf(v[j], sl2, -mo)); sum += v[j]; }
        sum += __shfl_xor_sync(~0u, sum, 1);
        sum += __shfl_xor_sync(~0u, sum, 2);
        inv[q] = rcp(sum);
        #pragma unroll
        for (int j = 0; j < 5; j++) pf[q][j] = pack_bf16(v[2 * j], v[2 * j + 1]);
    }
    auto load_v = [&](int n4, uint32_t (&vm)[4], uint32_t (&vt)[4][4]) {
        ldsm_x4(svm + n4 * 512 + lane * 16, vm[0], vm[1], vm[2], vm[3]);
        #pragma unroll
        for (int u = 0; u < 4; u++) {
            const int dt = 2 * n4 + (u >> 1), kh = u & 1;
            const uint4 v = lds128(sv + (dt & 3) * 2048 + (dt >> 2) * 1024 + kh * 512 + lane * 16);
            vt[u & 2][2 * kh] = v.x; vt[u & 2][2 * kh + 1] = v.z;
            vt[(u & 2) + 1][2 * kh] = v.y; vt[(u & 2) + 1][2 * kh + 1] = v.w;
        }
    };
    uint32_t vm[2][4], vt[2][4][4];
    load_v(0, vm[0], vt[0]);
    #pragma unroll
    for (int n4 = 0; n4 < 4; n4++) {
        const int cur = n4 & 1;
        if (n4 + 1 < 4) load_v(n4 + 1, vm[cur ^ 1], vt[cur ^ 1]);
        float o[4][4];
        #pragma unroll
        for (int u = 0; u < 4; u++) {
            o[u][0] = o[u][1] = o[u][2] = o[u][3] = 0.f;
            mma16816(o[u], pf[0][1], pf[1][1], pf[0][2], pf[1][2], vt[cur][u][0], vt[cur][u][1]);
        }
        if (mh) {
            #pragma unroll
            for (int u = 0; u < 4; u++) mma16816(o[u], pf[0][3], pf[1][3], pf[0][4], pf[1][4], vt[cur][u][2], vt[cur][u][3]);
        }
        #pragma unroll
        for (int u = 0; u < 4; u++) mma1688(o[u], pf[0][0], pf[1][0], vm[cur][u]);
        #pragma unroll
        for (int u = 0; u < 4; u += 2) {
            const int row = mh * 16 + (mi & 1) * 8 + r8, nt = 4 * n4 + u + (mi >> 1);
            stsm_x4(sq + (nt >> 3) * 4096 + row * 128 + (((nt & 7) ^ r8) << 4),
                    pack_bf16(o[u][0] * inv[0], o[u][1] * inv[0]), pack_bf16(o[u][2] * inv[1], o[u][3] * inv[1]),
                    pack_bf16(o[u + 1][0] * inv[0], o[u + 1][1] * inv[0]), pack_bf16(o[u + 1][2] * inv[1], o[u + 1][3] * inv[1]));
        }
    }
}

__device__ __forceinline__ void b_attn_warp(uint32_t base, int hl, int idx0, int lane) {
    const uint32_t sq = base, sk = base + 8192, sv = base + 8192 + 9216;
    const int g = lane >> 2, c = lane & 3;
    auto addr = [&](uint32_t t, int row, int ch) { return t + row * 128 + ((ch ^ (row & 7)) << 4); };
    const float sl2 = 0.17677669529663687f * 1.4426950408889634f;
    #pragma unroll 2
    for (int blk = 0; blk < 4; blk++) {
        const int r0 = blk * 16;
        float sc[3][4];
        #pragma unroll
        for (int j = 0; j < 3; j++) { sc[j][0] = sc[j][1] = sc[j][2] = sc[j][3] = 0.f; }
        #pragma unroll
        for (int t = 0; t < 2; t++) {
            uint32_t a0, a1, a2, a3, b0, b1, b2, b3, d0, d1, d2, d3;
            const int mi = lane >> 3, r = lane & 7;
            ldsm_x4(addr(sq, r0 + (mi & 1) * 8 + r, hl * 4 + 2 * t + (mi >> 1)), a0, a1, a2, a3);
            ldsm_x4(addr(sk, r0 + (mi >> 1) * 8 + r, hl * 4 + 2 * t + (mi & 1)), b0, b1, b2, b3);
            ldsm_x4(addr(sk, r0 + 16 + r, hl * 4 + 2 * t + (mi & 1)), d0, d1, d2, d3);
            mma16816(sc[0], a0, a1, a2, a3, b0, b1);
            mma16816(sc[1], a0, a1, a2, a3, b2, b3);
            mma16816(sc[2], a0, a1, a2, a3, d0, d1);
        }
        uint32_t pf[2][3];
        float inv[2];
        #pragma unroll
        for (int r = 0; r < 2; r++) {
            const int u = r * 8 + g;
            float v[6];
            #pragma unroll
            for (int j = 0; j < 3; j++) {
                #pragma unroll
                for (int e = 0; e < 2; e++) {
                    const int key = j * 8 + 2 * c + e;
                    const bool ok = key > u && key <= u + 8 && idx0 + r0 - 8 + key >= 0;
                    v[2 * j + e] = ok ? sc[j][2 * r + e] : -INFINITY;
                }
            }
            float mx = fmaxf(fmaxf(fmaxf(v[0], v[1]), fmaxf(v[2], v[3])), fmaxf(v[4], v[5]));
            mx = fmaxf(mx, __shfl_xor_sync(~0u, mx, 1));
            mx = fmaxf(mx, __shfl_xor_sync(~0u, mx, 2));
            const float mo = mx * sl2;
            float sum = 0.f;
            #pragma unroll
            for (int j = 0; j < 6; j++) { v[j] = ex2(fmaf(v[j], sl2, -mo)); sum += v[j]; }
            sum += __shfl_xor_sync(~0u, sum, 1);
            sum += __shfl_xor_sync(~0u, sum, 2);
            inv[r] = rcp(sum);
            #pragma unroll
            for (int j = 0; j < 3; j++) pf[r][j] = pack_bf16(v[2 * j], v[2 * j + 1]);
        }
        uint32_t ow[4][2];
        {
            const int mi = lane >> 3, r = lane & 7;
            uint32_t vv[4][4];
            #pragma unroll
            for (int nt = 0; nt < 4; nt++)
                ldsm_x4_t(addr(sv, r0 + min(mi, 2) * 8 + r, hl * 4 + nt), vv[nt][0], vv[nt][1], vv[nt][2], vv[nt][3]);
            float o[4][4];
            #pragma unroll
            for (int nt = 0; nt < 4; nt++) {
                o[nt][0] = o[nt][1] = o[nt][2] = o[nt][3] = 0.f;
                mma16816(o[nt], pf[0][0], pf[1][0], pf[0][1], pf[1][1], vv[nt][0], vv[nt][1]);
            }
            #pragma unroll
            for (int nt = 0; nt < 4; nt++) mma1688(o[nt], pf[0][2], pf[1][2], vv[nt][2]);
            #pragma unroll
            for (int nt = 0; nt < 4; nt++) {
                ow[nt][0] = pack_bf16(o[nt][0] * inv[0], o[nt][1] * inv[0]);
                ow[nt][1] = pack_bf16(o[nt][2] * inv[1], o[nt][3] * inv[1]);
            }
        }
        #pragma unroll
        for (int u = 0; u < 4; u += 2) {
            const int mi = lane >> 3, r = lane & 7;
            stsm_x4(addr(sq, r0 + (mi & 1) * 8 + r, hl * 4 + u + (mi >> 1)), ow[u][0], ow[u][1], ow[u + 1][0], ow[u + 1][1]);
        }
    }
}

constexpr uint32_t QKVB_TARGET = 12 * 8;
constexpr uint32_t PROGRESS_TARGET = 96;
constexpr uint32_t OA_TARGET = 64, OB_TARGET = 32;
#define ATT_B0 6
constexpr int ATT_TASKS = (NSEG + 16) * 32;
__device__ __forceinline__ int att_group(int g, bool& isb) {
    const int q = g - ATT_B0;
    isb = q >= 0 && q < 48 && q % 3 == 0;
    return q < 0 ? g : q >= 48 ? g - 16 : isb ? q / 3 : ATT_B0 + (q / 3) * 2 + q % 3 - 1;
}

__global__ void __launch_bounds__(ATT_THREADS, 1) attn_kernel(const __grid_constant__ AttnParams p) {
    extern __shared__ __align__(1024) uint8_t smem_raw[];
    const int tid = threadIdx.x, lane = tid & 31, warp = __shfl_sync(~0u, tid >> 5, 0);
    const int pair = warp >> 1, wi = warp & 1;
    const uint32_t base = smem_u32(smem_raw) + pair * ATT_SLOT, bar = smem_u32(smem_raw) + ATT_BAR + pair * 16, taskw = bar + 8;
    const bool leader = wi == 0 && lane == 0;
    if (tid == 0) pdl_launch_dependents();
    KENTER(3);
    const uint32_t cnt = smem_u32(smem_raw) + ATT_CNT;
    if (tid < 96) sts32(cnt + tid * 4, 0);
    __syncthreads();
    if (warp == 2 * ATT_PAIRS) {
        for (uint32_t n = 0; n < SPIN_LIMIT; n++) {
            const bool last = lds32_volatile(cnt + 320) == 2 * ATT_PAIRS;
            uint32_t v[3];
            #pragma unroll
            for (int i = 0; i < 3; i++) {
                v[i] = 0;
                if (i * 32 + lane < 80 && lds32_volatile(cnt + (i * 32 + lane) * 4) != 0)
                    asm volatile("atom.acquire.cta.shared.exch.b32 %0, [%1], 0;" : "=r"(v[i]) : "r"(cnt + (i * 32 + lane) * 4) : "memory");
            }
            if (v[0] | v[1] | v[2]) {
                asm volatile("fence.acq_rel.gpu;" ::: "memory");
                #pragma unroll
                for (int i = 0; i < 3; i++)
                    if (v[i]) asm volatile("red.relaxed.gpu.global.add.u32 [%0], %1;" ::"l"(p.flags + F_OB + i * 32 + lane), "r"(v[i]) : "memory");
                if (v[2] && lane == 15) KMARK(14);
            }
            __syncwarp();
            if (last) break;
            __nanosleep(40);
        }
        if (lane == 0) KEXIT(3);
        return;
    }
    uint32_t next = 0, phase = 0;
    if (leader) {
        mbar_init(bar, 1);
        asm volatile("fence.mbarrier_init.release.cluster;" ::: "memory");
        next = atomicAdd(p.flags + F_QUEUE3, 1u);
    }
    uint32_t pending = 0;
    auto flush = [&]() {
        if (pending) {
            bulk_wait_all();
            if (pending == cnt + 79 * 4) KMARK(13);
            asm volatile("red.release.cta.shared.add.u32 [%0], 1;" ::"r"(pending) : "memory");
            pending = 0;
        }
    };
    int ready_a = -1, ready_b = -1;
    while (true) {
        named_bar_sync(1 + pair, 64);
        if (leader) {
            const uint32_t task = next;
            sts32(taskw, task);
            if (task >= ATT_TASKS) {
                mbar_arrive(bar);
            } else {
                bool isb;
                const int grp = att_group(task >> 5, isb), i = task & 31;
                auto need = [&](const uint32_t* f, uint32_t target) {
                    if (ld_acquire_b32(f) < target) { flush(); wait_flag(f, target); }
                };
                if (isb) {
                    if (grp > ready_b) {
                        need(p.flags + F_QKVB + grp, QKVB_TARGET);
                        if (grp > 0) need(p.flags + F_QKVB + grp - 1, QKVB_TARGET);
                        asm volatile("fence.proxy.async.global;" ::: "memory");
                        ready_b = grp;
                    }
                    mbar_arrive_expect_tx(bar, 8192 + 2 * 9216);
                    tma_load_3d(base, &p.tmQb, (i >> 1) * 64, i & 1, grp * 64, bar);
                    tma_load_3d(base + 8192, &p.tmKb, DM + (i >> 1) * 64, i & 1, grp * 64 - 8, bar);
                    tma_load_3d(base + 8192 + 9216, &p.tmKb, 2 * DM + (i >> 1) * 64, i & 1, grp * 64 - 8, bar);
                } else {
                    if (grp > ready_a) {
                        need(p.flags + F_PROGRESS + grp, PROGRESS_TARGET);
                        asm volatile("fence.proxy.async.global;" ::: "memory");
                        ready_a = grp;
                    }
                    if (grp == 63) KMARK(10);
                    mbar_arrive_expect_tx(bar, ATT_SLOT);
                    #pragma unroll
                    for (int w = 0; w < 3; w++)
                        bulk_load(base + w * 8192, p.qkv_tok + (((size_t)w * NSEG + grp) * NH + i) * (SEG * DH), 8192, bar);
                    #pragma unroll
                    for (int w = 0; w < 2; w++)
                        bulk_load(base + 24576 + w * 2048, p.kv_mem + (((size_t)w * NSEG + grp) * NH + i) * (MROWS * DH), 2048, bar);
                }
                next = atomicAdd(p.flags + F_QUEUE3, 1u);
            }
        }
        if (lane == 0) flush();
        __syncwarp();
        mbar_wait_sleep(bar, phase);
        phase ^= 1;
        const uint32_t task = lds32_volatile(taskw);
        if (task >= ATT_TASKS) break;
        bool isb;
        const int grp = att_group(task >> 5, isb), i = task & 31;
        if (isb) {
            b_attn_warp(base, wi, grp * 64, lane);
            asm volatile("fence.proxy.async.shared::cta;" ::: "memory");
            named_bar_sync(1 + pair, 64);
            if (wi == 1 && lane == 0) {
                asm volatile("cp.async.bulk.tensor.3d.global.shared::cta.bulk_group [%0, {%2, %3, %4}], [%1];"
                             ::"l"(&p.tmOb), "r"(base), "r"((i >> 1) * 64), "r"(i & 1), "r"(grp * 64) : "memory");
                pending = cnt + grp * 4;
            }
        } else {
            if (grp == 63 && lane == 0) KMARK(11);
            tok_attn_warp(base, wi, lane);
            if (grp == 63 && lane == 0) KMARK(12);
            asm volatile("fence.proxy.async.shared::cta;" ::: "memory");
            __syncwarp();
            if (lane == 0) {
                #pragma unroll
                for (int h = 0; h < 2; h++) tma_store_2d(&p.tmOa, base + h * 4096 + wi * 2048, i * DH + h * 64, grp * SEG + wi * 16);
                pending = cnt + (16 + grp) * 4;
            }
        }
        if (lane == 0) { bulk_commit(); bulk_wait_read_all(); }
        __syncwarp();
    }
    if (lane == 0) asm volatile("red.release.cta.shared.add.u32 [%0], 1;" ::"r"(cnt + 320) : "memory");
}

typedef CUresult (*EncodeFn)(CUtensorMap*, CUtensorMapDataType, cuuint32_t, void*, const cuuint64_t*, const cuuint64_t*,
                             const cuuint32_t*, const cuuint32_t*, CUtensorMapInterleave, CUtensorMapSwizzle,
                             CUtensorMapL2promotion, CUtensorMapFloatOOBfill);

void make_map_2d(EncodeFn enc, CUtensorMap* m, const void* ptr, uint64_t rows, uint64_t cols, uint32_t box_rows) {
    cuuint64_t dims[2] = {cols, rows};
    cuuint64_t strides[1] = {cols * 2};
    cuuint32_t box[2] = {64, box_rows};
    cuuint32_t es[2] = {1, 1};
    enc(m, CU_TENSOR_MAP_DATA_TYPE_BFLOAT16, 2, const_cast<void*>(ptr), dims, strides, box, es,
        CU_TENSOR_MAP_INTERLEAVE_NONE, CU_TENSOR_MAP_SWIZZLE_128B, CU_TENSOR_MAP_L2_PROMOTION_L2_256B,
        CU_TENSOR_MAP_FLOAT_OOB_FILL_NONE);
}
void make_map_b(EncodeFn enc, CUtensorMap* m, const void* ptr, uint64_t k, uint64_t n, uint32_t nblk, uint32_t box_rows = 64,
                uint32_t bc = 64) {
    cuuint64_t dims[3] = {bc, k, n / bc};
    cuuint64_t strides[2] = {n * 2, bc * 2};
    cuuint32_t box[3] = {bc, box_rows, nblk};
    cuuint32_t es[3] = {1, 1, 1};
    enc(m, CU_TENSOR_MAP_DATA_TYPE_BFLOAT16, 3, const_cast<void*>(ptr), dims, strides, box, es,
        CU_TENSOR_MAP_INTERLEAVE_NONE, bc == 64 ? CU_TENSOR_MAP_SWIZZLE_128B : CU_TENSOR_MAP_SWIZZLE_64B, CU_TENSOR_MAP_L2_PROMOTION_L2_256B,
        CU_TENSOR_MAP_FLOAT_OOB_FILL_NONE);
}

void make_map_parity(EncodeFn enc, CUtensorMap* m, const void* ptr, uint64_t cols, uint32_t box_rows) {
    cuuint64_t dims[3] = {cols, 2, S_TOK / 2};
    cuuint64_t strides[2] = {cols * 2, cols * 4};
    cuuint32_t box[3] = {64, 1, box_rows};
    cuuint32_t es[3] = {1, 1, 1};
    enc(m, CU_TENSOR_MAP_DATA_TYPE_BFLOAT16, 3, const_cast<void*>(ptr), dims, strides, box, es,
        CU_TENSOR_MAP_INTERLEAVE_NONE, CU_TENSOR_MAP_SWIZZLE_128B, CU_TENSOR_MAP_L2_PROMOTION_L2_128B,
        CU_TENSOR_MAP_FLOAT_OOB_FILL_NONE);
}
void make_map_w(EncodeFn enc, CUtensorMap* m, const void* ptr) {
    cuuint64_t dims[3] = {HD, 64, DM / 64};
    cuuint64_t strides[2] = {HD * 2, 64 * HD * 2};
    cuuint32_t box[3] = {64, 16, 8};
    cuuint32_t es[3] = {1, 1, 1};
    enc(m, CU_TENSOR_MAP_DATA_TYPE_BFLOAT16, 3, const_cast<void*>(ptr), dims, strides, box, es,
        CU_TENSOR_MAP_INTERLEAVE_NONE, CU_TENSOR_MAP_SWIZZLE_128B, CU_TENSOR_MAP_L2_PROMOTION_L2_256B,
        CU_TENSOR_MAP_FLOAT_OOB_FILL_NONE);
}

#define OUTB_SIDE_BLOCKS 16
#define SIDE_ORDER 0
#define N_POST_ATT 0
#define SERIAL_ATT_CTAS h.n_sm
#define N_TAIL_CTAS 24
#define N_SIDE_CTAS 29
#define N_ATT_CTAS 7
#define TAIL_BLOCK0 12

struct HostState {
    bool ready;
    bool overlap;
    int n_side, n_att, n_sm;
    SideParams seq_a, seq_b;
    const void* key[11];
    RecParams rec;
    SideParams side, tail, outb;
    FinalParams fin;
    AttnParams attn;
    __nv_bfloat16 *qkv_tok, *kv_mem, *o_tok, *qkv_b, *o_b;
    uint8_t* xchg;
};
HostState g_host;

void setup(void* const* d_in, void* d_out) {
    HostState& h = g_host;
    void* fn = nullptr;
    cudaDriverEntryPointQueryResult qr;
    cudaGetDriverEntryPoint("cuTensorMapEncodeTiled", &fn, cudaEnableDefault, &qr);
    EncodeFn enc = reinterpret_cast<EncodeFn>(fn);
    void* ptr;
    cudaGetSymbolAddress(&ptr, g_qkv_tok); h.qkv_tok = (__nv_bfloat16*)ptr;
    cudaGetSymbolAddress(&ptr, g_kv_mem);  h.kv_mem = (__nv_bfloat16*)ptr;
    cudaGetSymbolAddress(&ptr, g_o_tok);   h.o_tok = (__nv_bfloat16*)ptr;
    cudaGetSymbolAddress(&ptr, g_qkv_b);   h.qkv_b = (__nv_bfloat16*)ptr;
    cudaGetSymbolAddress(&ptr, g_o_b);     h.o_b = (__nv_bfloat16*)ptr;
    cudaGetSymbolAddress(&ptr, g_xchg);    h.xchg = (uint8_t*)(((uint64_t)ptr + XCHG_BYTES - 1) & ~(uint64_t)(XCHG_BYTES - 1));
    cudaGetSymbolAddress(&ptr, g_flags);   uint32_t* flags = (uint32_t*)ptr;
    cudaGetSymbolAddress(&ptr, g_arrivals); uint32_t* arrivals = (uint32_t*)ptr;

    const void *xa = d_in[0], *mem0 = d_in[1], *wq = d_in[2], *wk = d_in[3], *wv = d_in[4], *wo = d_in[5];
    const void *xb = d_in[7], *wqkv = d_in[8], *wob = d_in[9];

    RecParams& r = h.rec;
    make_map_w(enc, &r.tmW[0], wq);
    make_map_w(enc, &r.tmW[1], wk);
    make_map_w(enc, &r.tmW[2], wv);
    make_map_b(enc, &r.tmWo, wo, HD, DM, 11, 128, 32);
    r.mem0 = (const __nv_bfloat16*)mem0;
    r.qkv_tok = h.qkv_tok; r.kv_mem = h.kv_mem; r.xchg = h.xchg;
    r.flags = flags; r.arrivals = arrivals; r.one[0] = r.one[1] = 1;
    make_map_b(enc, &r.tmX, xa, S_TOK, DM, 4, SEG);

    SideParams& sd = h.side;
    SideProb& p0 = sd.prob[0];
    make_map_2d(enc, &p0.tmA, xb, S_TOK, DM, BM);
    make_map_b(enc, &p0.tmB, wqkv, DM, 3 * DM, 4);
    make_map_2d(enc, &p0.tmC, h.qkv_b, S_TOK, 3 * DM, 16);
    p0.n_tiles = 3 * DM / 256; p0.k_blocks = DM / BK; p0.c_col0 = 0; p0.dep = nullptr; p0.dep_target = 0; p0.dep_n = 1; p0.sig = flags + F_QKVB;
    SideProb& p1 = sd.prob[1];
    make_map_2d(enc, &p1.tmA, h.o_tok, S_TOK, HD, BM);
    make_map_b(enc, &p1.tmB, wo, HD, DM, 4);
    make_map_2d(enc, &p1.tmC, d_out, S_TOK, 2 * DM, 16);
    p1.n_tiles = DM / 256; p1.k_blocks = HD / BK; p1.c_col0 = 0; p1.dep = flags + F_OA; p1.dep_target = OA_TARGET; p1.dep_n = 4; p1.sig = nullptr;
    SideProb& p2 = sd.prob[2];
    make_map_2d(enc, &p2.tmA, h.o_b, S_TOK, DM, BM);
    make_map_b(enc, &p2.tmB, wob, DM, DM, 4);
    p2.tmC = p1.tmC;
    p2.n_tiles = DM / 256; p2.k_blocks = DM / BK; p2.c_col0 = DM; p2.dep = flags + F_OB; p2.dep_target = OB_TARGET; p2.dep_n = 1; p2.sig = nullptr;
    p0.n_split = p1.n_split = p2.n_split = 1 << 20;
    p0.part = p1.part = p2.part = nullptr;
    if (SIDE_ORDER == 0) { sd.seg[0] = {0, 0, 16}; sd.seg[1] = {1, 0, TAIL_BLOCK0}; }
    else { sd.seg[0] = {1, 0, TAIL_BLOCK0}; sd.seg[1] = {0, 0, 16}; }
    sd.seg[2] = {2, 0, OUTB_SIDE_BLOCKS};
    sd.nseg = 3; sd.queue = flags + F_SIDEQ;
    h.outb = sd;
    h.outb.seg[0] = {2, OUTB_SIDE_BLOCKS, 16};
    h.outb.nseg = 1; h.outb.queue = flags + F_OUTBQ;

    SideParams& tl = h.tail;
    tl.prob[0] = p1;
    make_map_b(enc, &tl.prob[0].tmB, wo, HD, DM, 2);
    tl.prob[0].n_tiles = 2 * DM / 128; tl.prob[0].n_split = DM / 128; tl.prob[0].k_blocks = HD / BK / 2;
    cudaGetSymbolAddress(&ptr, g_part);
    tl.prob[0].part = (float*)ptr; tl.prob[0].part_flag = flags + F_PART;
    tl.prob[1] = tl.prob[2] = tl.prob[0];
    tl.seg[0] = {0, TAIL_BLOCK0, 15};
    tl.nseg = 1; tl.queue = flags + F_TAILQ;

    make_map_2d(enc, &h.fin.tmA, h.o_tok, S_TOK, HD, SEG);
    h.fin.tmB = tl.prob[0].tmB; h.fin.out = (__nv_bfloat16*)d_out;
    h.fin.dep = flags + F_OA + 60; h.fin.dep_target = OA_TARGET; h.fin.mt = 15;

    make_map_2d(enc, &h.attn.tmOa, h.o_tok, S_TOK, HD, 16);
    make_map_parity(enc, &h.attn.tmQb, h.qkv_b, 3 * DM, 64);
    make_map_parity(enc, &h.attn.tmKb, h.qkv_b, 3 * DM, 72);
    make_map_parity(enc, &h.attn.tmOb, h.o_b, DM, 64);
    h.attn.qkv_tok = h.qkv_tok; h.attn.kv_mem = h.kv_mem; h.attn.flags = flags;

    int dev = 0, nsm = 0;
    cudaGetDevice(&dev);
    cudaDeviceGetAttribute(&nsm, cudaDevAttrMultiProcessorCount, dev);
    h.n_sm = nsm;
    h.overlap = nsm - 96 >= N_SIDE_CTAS + N_ATT_CTAS;
    h.n_side = N_SIDE_CTAS; h.n_att = N_ATT_CTAS;
    h.seq_a = sd;
    h.seq_a.seg[0] = {0, 0, 16};
    h.seq_a.seg[1] = {0, 16, 16};
    h.seq_a.nseg = 2;
    h.seq_b = sd;
    h.seq_b.seg[0] = {1, 0, 16};
    h.seq_b.seg[1] = {2, 0, 16};
    h.seq_b.nseg = 2; h.seq_b.queue = flags + F_TAILQ;

    cudaFuncSetAttribute(side_gemm_kernel<256>, cudaFuncAttributeMaxDynamicSharedMemorySize, GemmCfg<256>::SMEM);
    cudaFuncSetAttribute(side_gemm_kernel<128>, cudaFuncAttributeMaxDynamicSharedMemorySize, GemmCfg<128>::SMEM);
    cudaFuncSetAttribute(final_gemm_kernel, cudaFuncAttributeMaxDynamicSharedMemorySize, FIN_SMEM);
    cudaFuncSetAttribute(rec_kernel, cudaFuncAttributeMaxDynamicSharedMemorySize, REC_SMEM);
    cudaFuncSetAttribute(attn_kernel, cudaFuncAttributeMaxDynamicSharedMemorySize, ATT_SMEM);
    for (int i = 0; i < 10; i++) h.key[i] = d_in[i];
    h.key[10] = d_out;
    h.ready = true;
}

template <typename K, typename P>
void launch(K kernel, int grid, int block, int smem, cudaStream_t st, const P& prm, int cluster, bool pdl) {
    cudaLaunchConfig_t cfg = {};
    cfg.gridDim = dim3(grid); cfg.blockDim = dim3(block); cfg.dynamicSmemBytes = smem; cfg.stream = st;
    cudaLaunchAttribute at[2];
    int n = 0;
    if (cluster > 1) {
        at[n].id = cudaLaunchAttributeClusterDimension;
        at[n].val.clusterDim.x = cluster; at[n].val.clusterDim.y = 1; at[n].val.clusterDim.z = 1;
        n++;
    }
    if (pdl) {
        at[n].id = cudaLaunchAttributeProgrammaticStreamSerialization;
        at[n].val.programmaticStreamSerializationAllowed = 1;
        n++;
    }
    cfg.attrs = at; cfg.numAttrs = n;
    cudaLaunchKernelEx(&cfg, kernel, prm);
}

}

extern "C" void kernel_launch(void* const* d_in, const int* in_sizes, int n_in, void* d_out, int out_size) {
    HostState& h = g_host;
    bool same = h.ready;
    for (int i = 0; same && i < 10; i++) same = h.key[i] == d_in[i];
    if (!same || h.key[10] != d_out) setup(d_in, d_out);
    cudaStream_t st = cudaStreamPerThread;

    launch(rec_kernel, 96, REC_THREADS, REC_SMEM, st, h.rec, 3, false);
    {
        if (!h.overlap) {
            launch(side_gemm_kernel<256>, h.n_sm, 384, GemmCfg<256>::SMEM, st, h.seq_a, 1, false);
            launch(attn_kernel, SERIAL_ATT_CTAS, ATT_THREADS, ATT_SMEM, st, h.attn, 1, false);
            launch(side_gemm_kernel<256>, h.n_sm, 384, GemmCfg<256>::SMEM, st, h.seq_b, 1, false);
            return;
        }
    }
    launch(side_gemm_kernel<256>, h.n_side, 384, GemmCfg<256>::SMEM, st, h.side, 1, true);
    launch(attn_kernel, h.n_att, ATT_THREADS, ATT_SMEM, st, h.attn, 1, true);
    launch(side_gemm_kernel<128>, N_TAIL_CTAS, 384, GemmCfg<128>::SMEM, st, h.tail, 1, true);
    if (N_POST_ATT > 0) launch(attn_kernel, N_POST_ATT, ATT_THREADS, ATT_SMEM, st, h.attn, 1, true);
    launch(final_gemm_kernel, 8 * FIN_SPLIT, 384, FIN_SMEM, st, h.fin, FIN_SPLIT, true);
    if (OUTB_SIDE_BLOCKS < 16)
        launch(side_gemm_kernel<256>, (16 - OUTB_SIDE_BLOCKS) * 4, 384, GemmCfg<256>::SMEM, st, h.outb, 1, true);
}
```

```cpp
#include <cuda_runtime.h>
#include <cuda_bf16.h>
#include <cuda.h>
#include <stdint.h>

namespace {

constexpr int S_TOK = 2048;
constexpr int DM = 1024;
constexpr int NH = 32;
constexpr int DH = 128;
constexpr int HD = NH * DH;
constexpr int NSEG = 64;
constexpr int SEG = 32;
constexpr int MROWS = 8;
constexpr uint32_t SENT = 0xFFFFFFFFu;
constexpr uint32_t SPIN_LIMIT = 1u << 24;

__device__ __align__(1024) __nv_bfloat16 g_qkv_tok[3ull * NSEG * NH * SEG * DH];
__device__ __align__(1024) __nv_bfloat16 g_kv_mem[2ull * NSEG * NH * MROWS * DH];
__device__ __align__(1024) __nv_bfloat16 g_o_tok[(size_t)S_TOK * HD];
__device__ __align__(1024) __nv_bfloat16 g_qkv_b[(size_t)S_TOK * 3 * DM];
__device__ __align__(1024) __nv_bfloat16 g_o_b[(size_t)S_TOK * DM];
__device__ __align__(1024) float g_part[32 * 128 * 128];
constexpr int PUB_BYTES = 32768;
constexpr int XCHG_SLOT = 1 << 20;
constexpr int XCHG_PUB = 0, XCHG_INBOX = 2 * PUB_BYTES;
constexpr int INBOX_MAX = 80;
constexpr int XCHG_BYTES = 2 * XCHG_SLOT;
__device__ __align__(8192) uint8_t g_xchg[2 * XCHG_BYTES];
enum { F_QUEUE3 = 3, F_QUEUE4 = 4, F_SIDEQ = 8, F_TAILQ = 16, F_OUTBQ = 24, F_PROGRESS = 32, F_QKVB = 96, F_OB = 112, F_OA = 128, F_PART = 192, F_COUNT = 224 };
__device__ uint32_t g_flags[F_COUNT];
__device__ __align__(16) uint32_t g_arrivals[4];

#define STAMP(k) do {} while (0)
#define STAMPD(k, x) do {} while (0)
#define PSTAMP(k) do {} while (0)
#define KENTER(k) do {} while (0)
#define APROF(k) do {} while (0)
#define KEXIT(k) do {} while (0)
#define KMARK(k) do {} while (0)

__device__ __forceinline__ uint32_t class_off(uint64_t a, uint32_t c) {
    return ((__popc((uint32_t)a & 0xB3000u) ^ c) & 1u) << 12;
}
__device__ __forceinline__ uint32_t smem_u32(const void* p) { return (uint32_t)__cvta_generic_to_shared(p); }
__device__ __forceinline__ uint32_t pack_bf16(float lo, float hi) {
    uint32_t r;
    asm("cvt.rn.bf16x2.f32 %0, %1, %2;" : "=r"(r) : "f"(hi), "f"(lo));
    return r;
}
__device__ __forceinline__ float ex2(float x) {
    float y;
    asm("ex2.approx.ftz.f32 %0, %1;" : "=f"(y) : "f"(x));
    return y;
}
__device__ __forceinline__ float rcp(float x) {
    float y;
    asm("rcp.approx.ftz.f32 %0, %1;" : "=f"(y) : "f"(x));
    return y;
}
__device__ __forceinline__ uint32_t clock32() {
    uint32_t t;
    asm volatile("mov.u32 %0, %%clock;" : "=r"(t));
    return t;
}
__device__ __forceinline__ void spin_clks(uint32_t n) {
    if (n == 0) return;
    const uint32_t t0 = clock32();
    while (clock32() - t0 < n) {}
}
__device__ __forceinline__ void spin_until(uint32_t t) {
    while ((int)(clock32() - t) < 0) {}
}
__device__ __forceinline__ uint32_t clock_after(uint32_t x) {
    uint32_t t;
    asm volatile("{\n.reg .pred p;\nsetp.eq.u32 p, %1, 0x12345678;\n@p exit;\nmov.u32 %0, %%clock;\n}" : "=r"(t) : "r"(x) : "memory");
    return t;
}
__device__ __forceinline__ uint32_t opaque(uint32_t x) { return __shfl_sync(~0u, x, threadIdx.x & 31); }
__device__ __forceinline__ uint32_t uniform(uint32_t x) { return __shfl_sync(~0u, x + (threadIdx.x & 31), 0); }
__device__ __forceinline__ float bf16_lo(uint32_t w) { return __uint_as_float(w << 16); }
__device__ __forceinline__ float bf16_hi(uint32_t w) { return __uint_as_float(w & 0xFFFF0000u); }

__device__ __forceinline__ void mbar_init(uint32_t bar, uint32_t cnt) {
    asm volatile("mbarrier.init.shared::cta.b64 [%0], %1;" ::"r"(bar), "r"(cnt) : "memory");
}
__device__ __forceinline__ void mbar_arrive(uint32_t bar) {
    asm volatile("mbarrier.arrive.shared::cta.b64 _, [%0];" ::"r"(bar) : "memory");
}
__device__ __forceinline__ void mbar_arrive_expect_tx(uint32_t bar, uint32_t bytes) {
    asm volatile("mbarrier.arrive.expect_tx.shared::cta.b64 _, [%0], %1;" ::"r"(bar), "r"(bytes) : "memory");
}
__device__ __forceinline__ bool mbar_try_wait(uint32_t bar, uint32_t parity) {
    uint32_t ok;
    asm volatile(
        "{\n.reg .pred p;\n"
        "mbarrier.try_wait.parity.shared::cta.b64 p, [%1], %2;\n"
        "selp.u32 %0, 1, 0, p;\n}"
        : "=r"(ok) : "r"(bar), "r"(parity) : "memory");
    return ok != 0;
}
__device__ __forceinline__ bool mbar_test_wait(uint32_t bar, uint32_t parity) {
    uint32_t ok;
    asm volatile(
        "{\n.reg .pred p;\n"
        "mbarrier.test_wait.parity.shared::cta.b64 p, [%1], %2;\n"
        "selp.u32 %0, 1, 0, p;\n}"
        : "=r"(ok) : "r"(bar), "r"(parity) : "memory");
    return ok != 0;
}
__device__ __forceinline__ void mbar_wait(uint32_t bar, uint32_t parity) {
    uint32_t n = 0;
    while (!mbar_try_wait(bar, parity)) {
        if (++n > SPIN_LIMIT) __trap();
    }
}
__device__ __forceinline__ void mbar_wait_sleep(uint32_t bar, uint32_t parity) {
    uint32_t n = 0;
    while (!mbar_try_wait(bar, parity)) {
        __nanosleep(20);
        if (++n > SPIN_LIMIT) __trap();
    }
}
__device__ __forceinline__ void mbar_wait_bounded(uint32_t bar, uint32_t parity) {
    for (uint32_t n = 0; n < (1u << 20) && !mbar_try_wait(bar, parity); n++) {}
}
__device__ __forceinline__ bool elect_one() {
    uint32_t ok;
    asm volatile("{\n.reg .pred p;\nelect.sync _|p, 0xFFFFFFFF;\nselp.u32 %0, 1, 0, p;\n}" : "=r"(ok));
    return ok != 0;
}
__device__ __forceinline__ void named_bar_sync(int id, int nthreads) {
    asm volatile("bar.sync %0, %1;" ::"r"(id), "r"(nthreads) : "memory");
}
__device__ __forceinline__ void named_bar_arrive(int id, int nthreads) {
    asm volatile("bar.arrive %0, %1;" ::"r"(id), "r"(nthreads) : "memory");
}
__device__ __forceinline__ void cluster_sync() {
    asm volatile("barrier.cluster.arrive.release.aligned;\nbarrier.cluster.wait.acquire.aligned;" ::: "memory");
}
__device__ __forceinline__ uint32_t mapa(uint32_t addr, uint32_t rank) {
    uint32_t r;
    asm volatile("mapa.shared::cluster.u32 %0, %1, %2;" : "=r"(r) : "r"(addr), "r"(rank));
    return r;
}

__device__ __forceinline__ void tma_load_2d(uint32_t dst, const CUtensorMap* tm, int c0, int c1, uint32_t bar) {
    asm volatile(
        "cp.async.bulk.tensor.2d.shared::cluster.global.mbarrier::complete_tx::bytes [%0], [%1, {%3, %4}], [%2];"
        ::"r"(dst), "l"(tm), "r"(bar), "r"(c0), "r"(c1) : "memory");
}
__device__ __forceinline__ void tma_load_3d(uint32_t dst, const CUtensorMap* tm, int c0, int c1, int c2, uint32_t bar) {
    asm volatile(
        "cp.async.bulk.tensor.3d.shared::cluster.global.mbarrier::complete_tx::bytes [%0], [%1, {%3, %4, %5}], [%2];"
        ::"r"(dst), "l"(tm), "r"(bar), "r"(c0), "r"(c1), "r"(c2) : "memory");
}
__device__ __forceinline__ void tma_load_3d_mc(uint32_t dst, const CUtensorMap* tm, int c0, int c1, int c2, uint32_t bar, uint16_t mask) {
    asm volatile(
        "cp.async.bulk.tensor.3d.shared::cluster.global.mbarrier::complete_tx::bytes.multicast::cluster [%0], [%1, {%3, %4, %5}], [%2], %6;"
        ::"r"(dst), "l"(tm), "r"(bar), "r"(c0), "r"(c1), "r"(c2), "h"(mask) : "memory");
}
__device__ __forceinline__ void tma_store_2d(const CUtensorMap* tm, uint32_t src, int c0, int c1) {
    asm volatile("cp.async.bulk.tensor.2d.global.shared::cta.bulk_group [%0, {%2, %3}], [%1];"
                 ::"l"(tm), "r"(src), "r"(c0), "r"(c1) : "memory");
}
__device__ __forceinline__ void bulk_store(void* dst, uint32_t src, uint32_t bytes) {
    asm volatile("cp.async.bulk.global.shared::cta.bulk_group [%0], [%1], %2;" ::"l"(dst), "r"(src), "r"(bytes) : "memory");
}
__device__ __forceinline__ void bulk_commit() { asm volatile("cp.async.bulk.commit_group;" ::: "memory"); }
__device__ __forceinline__ void bulk_wait_read_all() { asm volatile("cp.async.bulk.wait_group.read 0;" ::: "memory"); }
__device__ __forceinline__ void bulk_wait_all() { asm volatile("cp.async.bulk.wait_group 0;" ::: "memory"); }
__device__ __forceinline__ void bulk_load(uint32_t dst, const void* src, uint32_t bytes, uint32_t bar) {
    asm volatile("cp.async.bulk.shared::cluster.global.mbarrier::complete_tx::bytes [%0], [%1], %2, [%3];"
                 ::"r"(dst), "l"(src), "r"(bytes), "r"(bar) : "memory");
}
__device__ __forceinline__ void bulk_load_mc(uint32_t dst, const void* src, uint32_t bytes, uint32_t bar, uint16_t mask) {
    asm volatile(
        "cp.async.bulk.shared::cluster.global.mbarrier::complete_tx::bytes.multicast::cluster [%0], [%1], %2, [%3], %4;"
        ::"r"(dst), "l"(src), "r"(bytes), "r"(bar), "h"(mask) : "memory");
}
__device__ __forceinline__ void cp_async16(uint32_t dst, const void* src) {
    asm volatile("cp.async.cg.shared.global [%0], [%1], 16;" ::"r"(dst), "l"(src) : "memory");
}
__device__ __forceinline__ void cp_async_commit() { asm volatile("cp.async.commit_group;" ::: "memory"); }
template <int N> __device__ __forceinline__ void cp_async_wait() {
    asm volatile("cp.async.wait_group %0;" ::"n"(N) : "memory");
}

__device__ __forceinline__ void ldsm_x4(uint32_t addr, uint32_t& r0, uint32_t& r1, uint32_t& r2, uint32_t& r3) {
    asm volatile("ldmatrix.sync.aligned.m8n8.x4.shared.b16 {%0,%1,%2,%3}, [%4];"
                 : "=r"(r0), "=r"(r1), "=r"(r2), "=r"(r3) : "r"(addr) : "memory");
}
__device__ __forceinline__ void ldsm_x4_t(uint32_t addr, uint32_t& r0, uint32_t& r1, uint32_t& r2, uint32_t& r3) {
    asm volatile("ldmatrix.sync.aligned.m8n8.x4.trans.shared.b16 {%0,%1,%2,%3}, [%4];"
                 : "=r"(r0), "=r"(r1), "=r"(r2), "=r"(r3) : "r"(addr) : "memory");
}
__device__ __forceinline__ void stsm_x4(uint32_t addr, uint32_t r0, uint32_t r1, uint32_t r2, uint32_t r3) {
    asm volatile("stmatrix.sync.aligned.m8n8.x4.shared.b16 [%0], {%1,%2,%3,%4};"
                 ::"r"(addr), "r"(r0), "r"(r1), "r"(r2), "r"(r3) : "memory");
}
__device__ __forceinline__ uint32_t movmat(uint32_t a) {
    uint32_t d;
    asm volatile("movmatrix.sync.aligned.m8n8.trans.b16 %0, %1;" : "=r"(d) : "r"(a));
    return d;
}
__device__ __forceinline__ void mma16816(float* d, uint32_t a0, uint32_t a1, uint32_t a2, uint32_t a3,
                                         uint32_t b0, uint32_t b1) {
    asm volatile(
        "mma.sync.aligned.m16n8k16.row.col.f32.bf16.bf16.f32 {%0,%1,%2,%3}, {%4,%5,%6,%7}, {%8,%9}, {%0,%1,%2,%3};"
        : "+f"(d[0]), "+f"(d[1]), "+f"(d[2]), "+f"(d[3])
        : "r"(a0), "r"(a1), "r"(a2), "r"(a3), "r"(b0), "r"(b1));
}
__device__ __forceinline__ void mma1688(float* d, uint32_t a0, uint32_t a1, uint32_t b0) {
    asm volatile("mma.sync.aligned.m16n8k8.row.col.f32.bf16.bf16.f32 {%0,%1,%2,%3}, {%4,%5}, {%6}, {%0,%1,%2,%3};"
                 : "+f"(d[0]), "+f"(d[1]), "+f"(d[2]), "+f"(d[3]) : "r"(a0), "r"(a1), "r"(b0));
}
__device__ __forceinline__ uint32_t any_reg() {
    uint32_t r;
    asm volatile("" : "=r"(r));
    return r;
}
__device__ __forceinline__ uint2 lds64(uint32_t addr) {
    uint2 v;
    asm volatile("ld.volatile.shared.v2.b32 {%0,%1}, [%2];" : "=r"(v.x), "=r"(v.y) : "r"(addr) : "memory");
    return v;
}
__device__ __forceinline__ uint4 lds128(uint32_t addr) {
    uint4 v;
    asm volatile("ld.volatile.shared.v4.b32 {%0,%1,%2,%3}, [%4];" : "=r"(v.x), "=r"(v.y), "=r"(v.z), "=r"(v.w) : "r"(addr) : "memory");
    return v;
}
__device__ __forceinline__ void sts32(uint32_t addr, uint32_t x) {
    asm volatile("st.volatile.shared.b32 [%0], %1;" ::"r"(addr), "r"(x) : "memory");
}
__device__ __forceinline__ void sts64(uint32_t addr, uint32_t x, uint32_t y) {
    asm volatile("st.volatile.shared.v2.b32 [%0], {%1,%2};" ::"r"(addr), "r"(x), "r"(y) : "memory");
}
__device__ __forceinline__ void sts128(uint32_t addr, uint32_t x, uint32_t y, uint32_t z, uint32_t w) {
    asm volatile("st.volatile.shared.v4.b32 [%0], {%1,%2,%3,%4};" ::"r"(addr), "r"(x), "r"(y), "r"(z), "r"(w) : "memory");
}
__device__ __forceinline__ void st_async_v2(uint32_t addr, uint32_t x, uint32_t y, uint32_t bar) {
    asm volatile("st.async.weak.shared::cluster.mbarrier::complete_tx::bytes.v2.b32 [%0], {%1,%2}, [%3];"
                 ::"r"(addr), "r"(x), "r"(y), "r"(bar) : "memory");
}
__device__ __forceinline__ uint2 ld_relaxed_v2(const void* p) {
    uint2 v;
    asm volatile("ld.relaxed.gpu.global.v2.b32 {%0,%1}, [%2];" : "=r"(v.x), "=r"(v.y) : "l"(p) : "memory");
    return v;
}
__device__ __forceinline__ void st_relaxed_v2(void* p, uint32_t x, uint32_t y) {
    asm volatile("st.relaxed.gpu.global.v2.b32 [%0], {%1,%2};" ::"l"(p), "r"(x), "r"(y) : "memory");
}
__device__ __forceinline__ void st_relaxed_v4(void* p, uint32_t x) {
    asm volatile("st.relaxed.gpu.global.v4.b32 [%0], {%1,%1,%1,%1};" ::"l"(p), "r"(x) : "memory");
}
__device__ __forceinline__ uint32_t ld_relaxed_b32(const void* p) {
    uint32_t v;
    asm volatile("ld.relaxed.gpu.global.b32 %0, [%1];" : "=r"(v) : "l"(p) : "memory");
    return v;
}
__device__ __forceinline__ uint32_t lds32_volatile(uint32_t addr) {
    uint32_t v;
    asm volatile("ld.volatile.shared.b32 %0, [%1];" : "=r"(v) : "r"(addr) : "memory");
    return v;
}
__device__ __forceinline__ void st_relaxed_b32(void* p, uint32_t x) {
    asm volatile("st.relaxed.gpu.global.b32 [%0], %1;" ::"l"(p), "r"(x) : "memory");
}

__device__ __forceinline__ uint32_t ld_acquire_b32(const void* p) {
    uint32_t v;
    asm volatile("ld.acquire.gpu.global.b32 %0, [%1];" : "=r"(v) : "l"(p) : "memory");
    return v;
}
__device__ __forceinline__ void wait_flag(const uint32_t* p, uint32_t target) {
    uint32_t n = 0;
    while (ld_acquire_b32(p) < target) {
        __nanosleep(64);
        if (++n > SPIN_LIMIT) __trap();
    }
}
__device__ __forceinline__ void signal_flag(uint32_t* p) {
    asm volatile("red.release.gpu.global.add.u32 [%0], 1;" ::"l"(p) : "memory");
}
__device__ __forceinline__ void pdl_launch_dependents() { asm volatile("griddepcontrol.launch_dependents;" ::: "memory"); }

constexpr int BM = 128, BK = 64;
constexpr int A_STAGE = BM * BK * 2;
template <int BN> struct GemmCfg {
    static constexpr int STAGES = BN == 256 ? 3 : 6;
    static constexpr int STAGE = A_STAGE + BK * BN * 2;
    static constexpr int EPI_WARP = 16 * BN * 2;
    static constexpr int SMEM = STAGES * STAGE + 8 * EPI_WARP + 1024 + 512;
};

struct SideProb {
    CUtensorMap tmA, tmB, tmC;
    int n_split;
    int n_tiles, k_blocks, c_col0;
    const uint32_t* dep;
    uint32_t dep_target;
    int dep_n;
    uint32_t* sig;
    float* part;
    uint32_t* part_flag;
};
struct SideSeg { int prob, m0, m1; };
constexpr int SIDE_MAX_SEG = 6;
struct SideParams {
    SideProb prob[3];
    SideSeg seg[SIDE_MAX_SEG];
    int nseg;
    uint32_t* queue;
};
static_assert(sizeof(SideParams) <= 4096, "kernel parameter limit");

__device__ __forceinline__ uint64_t make_desc(uint32_t addr, uint32_t lbo, uint32_t sbo) {
    return (uint64_t)((addr & 0x3FFFF) >> 4) | ((uint64_t)(lbo >> 4) << 16) | ((uint64_t)(sbo >> 4) << 32) | (1ull << 62);
}

__device__ __forceinline__ void wgmma_m64n256k16(float (&d)[128], uint64_t da, uint64_t db, int scale_d) {
    asm volatile(
        "{\n.reg .pred p;\nsetp.ne.b32 p, %130, 0;\n"
        "wgmma.mma_async.sync.aligned.m64n256k16.f32.bf16.bf16 "
        "{%0,%1,%2,%3,%4,%5,%6,%7,%8,%9,%10,%11,%12,%13,%14,%15,"
        "%16,%17,%18,%19,%20,%21,%22,%23,%24,%25,%26,%27,%28,%29,%30,%31,"
        "%32,%33,%34,%35,%36,%37,%38,%39,%40,%41,%42,%43,%44,%45,%46,%47,"
        "%48,%49,%50,%51,%52,%53,%54,%55,%56,%57,%58,%59,%60,%61,%62,%63,"
        "%64,%65,%66,%67,%68,%69,%70,%71,%72,%73,%74,%75,%76,%77,%78,%79,"
        "%80,%81,%82,%83,%84,%85,%86,%87,%88,%89,%90,%91,%92,%93,%94,%95,"
        "%96,%97,%98,%99,%100,%101,%102,%103,%104,%105,%106,%107,%108,%109,%110,%111,"
        "%112,%113,%114,%115,%116,%117,%118,%119,%120,%121,%122,%123,%124,%125,%126,%127},"
        " %128, %129, p, 1, 1, 0, 1;\n}\n"
        : "+f"(d[0]), "+f"(d[1]), "+f"(d[2]), "+f"(d[3]), "+f"(d[4]), "+f"(d[5]), "+f"(d[6]), "+f"(d[7]),
          "+f"(d[8]), "+f"(d[9]), "+f"(d[10]), "+f"(d[11]), "+f"(d[12]), "+f"(d[13]), "+f"(d[14]), "+f"(d[15]),
          "+f"(d[16]), "+f"(d[17]), "+f"(d[18]), "+f"(d[19]), "+f"(d[20]), "+f"(d[21]), "+f"(d[22]), "+f"(d[23]),
          "+f"(d[24]), "+f"(d[25]), "+f"(d[26]), "+f"(d[27]), "+f"(d[28]), "+f"(d[29]), "+f"(d[30]), "+f"(d[31]),
          "+f"(d[32]), "+f"(d[33]), "+f"(d[34]), "+f"(d[35]), "+f"(d[36]), "+f"(d[37]), "+f"(d[38]), "+f"(d[39]),
          "+f"(d[40]), "+f"(d[41]), "+f"(d[42]), "+f"(d[43]), "+f"(d[44]), "+f"(d[45]), "+f"(d[46]), "+f"(d[47]),
          "+f"(d[48]), "+f"(d[49]), "+f"(d[50]), "+f"(d[51]), "+f"(d[52]), "+f"(d[53]), "+f"(d[54]), "+f"(d[55]),
          "+f"(d[56]), "+f"(d[57]), "+f"(d[58]), "+f"(d[59]), "+f"(d[60]), "+f"(d[61]), "+f"(d[62]), "+f"(d[63]),
          "+f"(d[64]), "+f"(d[65]), "+f"(d[66]), "+f"(d[67]), "+f"(d[68]), "+f"(d[69]), "+f"(d[70]), "+f"(d[71]),
          "+f"(d[72]), "+f"(d[73]), "+f"(d[74]), "+f"(d[75]), "+f"(d[76]), "+f"(d[77]), "+f"(d[78]), "+f"(d[79]),
          "+f"(d[80]), "+f"(d[81]), "+f"(d[82]), "+f"(d[83]), "+f"(d[84]), "+f"(d[85]), "+f"(d[86]), "+f"(d[87]),
          "+f"(d[88]), "+f"(d[89]), "+f"(d[90]), "+f"(d[91]), "+f"(d[92]), "+f"(d[93]), "+f"(d[94]), "+f"(d[95]),
          "+f"(d[96]), "+f"(d[97]), "+f"(d[98]), "+f"(d[99]), "+f"(d[100]), "+f"(d[101]), "+f"(d[102]), "+f"(d[103]),
          "+f"(d[104]), "+f"(d[105]), "+f"(d[106]), "+f"(d[107]), "+f"(d[108]), "+f"(d[109]), "+f"(d[110]), "+f"(d[111]),
          "+f"(d[112]), "+f"(d[113]), "+f"(d[114]), "+f"(d[115]), "+f"(d[116]), "+f"(d[117]), "+f"(d[118]), "+f"(d[119]),
          "+f"(d[120]), "+f"(d[121]), "+f"(d[122]), "+f"(d[123]), "+f"(d[124]), "+f"(d[125]), "+f"(d[126]), "+f"(d[127])
        : "l"(da), "l"(db), "r"(scale_d));
}

__device__ __forceinline__ void wgmma_m64n128k16(float (&d)[64], uint64_t da, uint64_t db, int scale_d) {
    asm volatile(
        "{\n.reg .pred p;\nsetp.ne.b32 p, %66, 0;\n"
        "wgmma.mma_async.sync.aligned.m64n128k16.f32.bf16.bf16 "
        "{%0,%1,%2,%3,%4,%5,%6,%7,%8,%9,%10,%11,%12,%13,%14,%15,"
        "%16,%17,%18,%19,%20,%21,%22,%23,%24,%25,%26,%27,%28,%29,%30,%31,"
        "%32,%33,%34,%35,%36,%37,%38,%39,%40,%41,%42,%43,%44,%45,%46,%47,"
        "%48,%49,%50,%51,%52,%53,%54,%55,%56,%57,%58,%59,%60,%61,%62,%63},"
        " %64, %65, p, 1, 1, 0, 1;\n}\n"
        : "+f"(d[0]), "+f"(d[1]), "+f"(d[2]), "+f"(d[3]), "+f"(d[4]), "+f"(d[5]), "+f"(d[6]), "+f"(d[7]),
          "+f"(d[8]), "+f"(d[9]), "+f"(d[10]), "+f"(d[11]), "+f"(d[12]), "+f"(d[13]), "+f"(d[14]), "+f"(d[15]),
          "+f"(d[16]), "+f"(d[17]), "+f"(d[18]), "+f"(d[19]), "+f"(d[20]), "+f"(d[21]), "+f"(d[22]), "+f"(d[23]),
          "+f"(d[24]), "+f"(d[25]), "+f"(d[26]), "+f"(d[27]), "+f"(d[28]), "+f"(d[29]), "+f"(d[30]), "+f"(d[31]),
          "+f"(d[32]), "+f"(d[33]), "+f"(d[34]), "+f"(d[35]), "+f"(d[36]), "+f"(d[37]), "+f"(d[38]), "+f"(d[39]),
          "+f"(d[40]), "+f"(d[41]), "+f"(d[42]), "+f"(d[43]), "+f"(d[44]), "+f"(d[45]), "+f"(d[46]), "+f"(d[47]),
          "+f"(d[48]), "+f"(d[49]), "+f"(d[50]), "+f"(d[51]), "+f"(d[52]), "+f"(d[53]), "+f"(d[54]), "+f"(d[55]),
          "+f"(d[56]), "+f"(d[57]), "+f"(d[58]), "+f"(d[59]), "+f"(d[60]), "+f"(d[61]), "+f"(d[62]), "+f"(d[63])
        : "l"(da), "l"(db), "r"(scale_d));
}
template <int BN> struct WgmmaOp;
template <> struct WgmmaOp<256> {
    static __device__ __forceinline__ void run(float (&d)[128], uint64_t a, uint64_t b, int sc) { wgmma_m64n256k16(d, a, b, sc); }
};
template <> struct WgmmaOp<128> {
    static __device__ __forceinline__ void run(float (&d)[64], uint64_t a, uint64_t b, int sc) { wgmma_m64n128k16(d, a, b, sc); }
};

struct StoreRec {
    uint64_t dst;
    uint64_t flag;
    int kind;
    int pad;
};
struct EpiCtx { uint32_t buf, rec, st_full, st_empty; uint32_t it; int lane; };
template <int N>
__device__ __forceinline__ void epi_hand_over(const float (&acc)[N], EpiCtx& e, uint64_t dst, uint64_t flag, int kind) {
    mbar_wait(e.st_empty, (e.it & 1) ^ 1);
    const int mi = e.lane >> 3, row = (mi & 1) * 8 + (e.lane & 7);
    #pragma unroll
    for (int j = 0; j < N / 4; j += 2) {
        const int chunk = (j & 7) + (mi >> 1);
        stsm_x4(e.buf + (j >> 3) * 2048 + row * 128 + ((chunk ^ (row & 7)) << 4),
                pack_bf16(acc[4 * j], acc[4 * j + 1]), pack_bf16(acc[4 * j + 2], acc[4 * j + 3]),
                pack_bf16(acc[4 * j + 4], acc[4 * j + 5]), pack_bf16(acc[4 * j + 6], acc[4 * j + 7]));
    }
    if (e.lane == 0) {
        asm volatile("st.shared.v2.b64 [%0], {%1, %2};" ::"r"(e.rec), "l"(dst), "l"(flag) : "memory");
        asm volatile("st.shared.b32 [%0], %1;" ::"r"(e.rec + 16), "r"(kind) : "memory");
    }
    asm volatile("fence.proxy.async.shared::cta;" ::: "memory");
    __syncwarp();
    if (e.lane == 0) mbar_arrive(e.st_full);
    e.it++;
}
__device__ __forceinline__ void epi_exit(EpiCtx& e) {
    mbar_wait(e.st_empty, (e.it & 1) ^ 1);
    if (e.lane == 0) {
        asm volatile("st.shared.b32 [%0], %1;" ::"r"(e.rec + 16), "r"(-1) : "memory");
        mbar_arrive(e.st_full);
    }
}
template <int BN, bool PAIR = false>
__device__ __forceinline__ void gemm_mainloop(float (&acc)[BN / 2], int k_blocks, uint32_t sbase, uint32_t bar_base, int cw,
                                              bool elected, int& stage, uint32_t& phase, uint32_t peer = 0) {
    using C = GemmCfg<BN>;
    auto release = [&](int st) {
        const uint32_t bar = bar_base + 8 * (C::STAGES + st);
        mbar_arrive(bar);
        if (PAIR) asm volatile("mbarrier.arrive.shared::cluster.b64 _, [%0];" ::"r"(mapa(bar, peer)) : "memory");
    };
    int prev_stage = -1;
    for (int kb = 0; kb < k_blocks; kb++) {
        mbar_wait(bar_base + 8 * stage, phase);
        const uint32_t sa = sbase + stage * C::STAGE + cw * (64 * 128);
        const uint32_t sb = sbase + stage * C::STAGE + A_STAGE;
        asm volatile("wgmma.fence.sync.aligned;" ::: "memory");
        #pragma unroll
        for (int kk = 0; kk < BK / 16; kk++)
            WgmmaOp<BN>::run(acc, make_desc(sa + kk * 32, 16, 1024), make_desc(sb + kk * 2048, 8192, 1024), (kb | kk) != 0);
        asm volatile("wgmma.commit_group.sync.aligned;" ::: "memory");
        asm volatile("wgmma.wait_group.sync.aligned 1;" ::: "memory");
        if (prev_stage >= 0 && elected) release(prev_stage);
        prev_stage = stage;
        if (++stage == C::STAGES) { stage = 0; phase ^= 1; }
    }
    asm volatile("wgmma.wait_group.sync.aligned 0;" ::: "memory");
    if (elected) release(prev_stage);
}
template <int BN>
__device__ __forceinline__ void store_warp(uint32_t epi_base, uint32_t rec_base, uint32_t st_full, uint32_t st_empty, int lane,
                                           const uint8_t* tmaps, int tstride) {
    for (uint32_t it = 0;; it++) {
        mbar_wait(st_full, it & 1);
        uint64_t dst = 0, flag = 0;
        int kind = -1;
        if (lane < 8) {
            const uint32_t rec = rec_base + lane * 32;
            asm volatile("ld.volatile.shared.v2.b64 {%0, %1}, [%2];" : "=l"(dst), "=l"(flag) : "r"(rec) : "memory");
            kind = (int)lds32_volatile(rec + 16);
        }
        if (__shfl_sync(~0u, kind, 0) < 0) break;
        if (lane < 8) {
            const uint32_t buf = epi_base + lane * GemmCfg<BN>::EPI_WARP;
            #pragma unroll
            for (int q = 0; q < BN / 64; q++) {
                tma_store_2d(reinterpret_cast<const CUtensorMap*>(tmaps + (kind - 1) * tstride), buf + q * 2048,
                                  (int)(uint32_t)dst + q * 64, (int)(dst >> 32));
            }
            bulk_commit();
            bulk_wait_read_all();
            mbar_arrive(st_empty);
            if (flag) {
                bulk_wait_all();
                signal_flag(reinterpret_cast<uint32_t*>(flag));
            }
        }
        __syncwarp();
    }
    if (lane < 8) bulk_wait_all();
}

#define SCHED_AHEAD 4
template <int BN>
__global__ void __launch_bounds__(384, 1) side_gemm_kernel(const __grid_constant__ SideParams p) {
    using C = GemmCfg<BN>;
    extern __shared__ uint8_t smem_raw[];
    const uint32_t sbase = (smem_u32(smem_raw) + 1023) & ~1023u;
    const uint32_t epi_base = sbase + C::STAGES * C::STAGE;
    const uint32_t bar_base = epi_base + 8 * C::EPI_WARP;
    const uint32_t tfull = bar_base + 16 * C::STAGES, tempty = tfull + 16, tslot = tempty + 16, twant = tslot + 8;
    const uint32_t st_full = bar_base + 192, st_empty = st_full + 8, rec_base = bar_base + 256;
    const int tid = threadIdx.x, wg = tid >> 7;
    if (tid == 0) {
        for (int s = 0; s < C::STAGES; s++) { mbar_init(bar_base + 8 * s, 1); mbar_init(bar_base + 8 * (C::STAGES + s), 2); }
        for (int s = 0; s < 2; s++) { mbar_init(tfull + 8 * s, 1); mbar_init(tempty + 8 * s, 3); }
        mbar_init(twant, 1);
        mbar_init(st_full, 8);
        mbar_init(st_empty, 8);
        asm volatile("fence.mbarrier_init.release.cluster;" ::: "memory");
        pdl_launch_dependents();
    }
    __syncthreads();
    KENTER(BN == 256 ? (p.nseg == 1 ? 6 : 2) : 4);

    if (wg == 0) {
        asm volatile("setmaxnreg.dec.sync.aligned.u32 40;");
        if (tid == 0) {
            int stage = 0; uint32_t phase = 1;
            for (uint32_t it = 0;; it++) {
                mbar_wait(tfull + 8 * (it & 1), (it >> 1) & 1);
                const int code = (int)lds32_volatile(tslot + 4 * (it & 1));
                mbar_arrive(tempty + 8 * (it & 1));
                if (code < 0) break;
                const SideProb& q = p.prob[code >> 16];
                const int mt = (code >> 8) & 255, nt = code & 255;
                asm volatile("fence.proxy.async.global;" ::: "memory");
                for (int kb = 0; kb < q.k_blocks; kb++) {
                    if (kb == q.k_blocks - SCHED_AHEAD) mbar_arrive(twant);
                    mbar_wait(bar_base + 8 * (C::STAGES + stage), phase);
                    const uint32_t sa = sbase + stage * C::STAGE, fb = bar_base + 8 * stage;
                    mbar_arrive_expect_tx(fb, C::STAGE);
                    const int k0 = (nt < q.n_split ? kb : kb + q.k_blocks) * BK;
                    tma_load_2d(sa, &q.tmA, k0, mt * BM, fb);
                    tma_load_3d(sa + A_STAGE, &q.tmB, 0, k0, (nt < q.n_split ? nt : nt - q.n_split) * (BN / 64), fb);
                    if (++stage == C::STAGES) { stage = 0; phase ^= 1; }
                }
            }
        } else if (tid >= 64 && tid < 96) {
            const int lane = tid & 31;
            const SideSeg sg = p.seg[lane < p.nseg ? lane : 0];
            const SideProb& mq = p.prob[sg.prob];
            const uint32_t total = lane < p.nseg ? (sg.m1 - sg.m0) * mq.n_tiles : 0;
            for (uint32_t it = 0;; it++) {
                if (it > 0) mbar_wait_sleep(twant, (it - 1) & 1);
                int code = -1;
                for (uint32_t tries = 0;; tries++) {
                    const uint32_t head = total ? ld_relaxed_b32(p.queue + lane) : 0;
                    const uint32_t left = __ballot_sync(~0u, head < total);
                    if (!left) break;
                    bool ready = head < total;
                    if (ready && mq.dep && (left & (left - 1)))
                        ready = ld_relaxed_b32(mq.dep + (sg.m0 + head / mq.n_tiles + 1) * mq.dep_n - 1) >= mq.dep_target;
                    const uint32_t rm = __ballot_sync(~0u, ready);
                    if (rm) {
                        const int g = __ffs(rm) - 1;
                        if (lane == g) {
                            const uint32_t idx = atomicAdd(p.queue + g, 1u);
                            if (idx < total) code = (sg.prob << 16) | ((sg.m0 + idx / mq.n_tiles) << 8) | (idx % mq.n_tiles);
                        }
                        code = __shfl_sync(~0u, code, g);
                        if (code >= 0) break;
                    } else {
                        __nanosleep(200);
                    }
                    if (tries > SPIN_LIMIT) __trap();
                }
                if (code >= 0) {
                    const SideProb& q = p.prob[code >> 16];
                    if (q.dep && lane < q.dep_n) wait_flag(q.dep + ((code >> 8) & 255) * q.dep_n + lane, q.dep_target);
                    __syncwarp();
                }
                if (lane == 0) {
                    mbar_wait(tempty + 8 * (it & 1), ((it >> 1) & 1) ^ 1);
                    asm volatile("st.shared.b32 [%0], %1;" ::"r"(tslot + 4 * (it & 1)), "r"(code) : "memory");
                    mbar_arrive(tfull + 8 * (it & 1));
                }
                __syncwarp();
                if (code < 0) break;
            }
        } else if (tid >= 32 && tid < 64) {
            store_warp<BN>(epi_base, rec_base, st_full, st_empty, tid & 31, reinterpret_cast<const uint8_t*>(&p.prob[0].tmC),
                           (int)sizeof(SideProb));
        }
    } else {
        asm volatile("setmaxnreg.inc.sync.aligned.u32 232;");
        const int cw = wg - 1, lane = tid & 31, wi = (tid >> 5) & 3;
        const bool elected = (tid & 127) == 0;
        int stage = 0; uint32_t phase = 0;
        float acc[BN / 2];
        EpiCtx ectx = {epi_base + (cw * 4 + wi) * C::EPI_WARP, rec_base + (cw * 4 + wi) * 32, st_full, st_empty, 0, lane};
        for (uint32_t it = 0;; it++) {
            mbar_wait(tfull + 8 * (it & 1), (it >> 1) & 1);
            const int code = (int)lds32_volatile(tslot + 4 * (it & 1));
            named_bar_sync(1 + cw, 128);
            if (elected) mbar_arrive(tempty + 8 * (it & 1));
            if (code < 0) break;
            const SideProb& q = p.prob[code >> 16];
            const int mt = (code >> 8) & 255, nt = code & 255;
            gemm_mainloop<BN>(acc, q.k_blocks, sbase, bar_base, cw, elected, stage, phase);
            const int row0 = mt * BM + cw * 64 + wi * 16, ntc = nt < q.n_split ? nt : nt - q.n_split;
            if (BN == 128 && q.part) {
                const int idx = (mt & 3) * q.n_split + ntc;
                float4* part = reinterpret_cast<float4*>(q.part) + (size_t)idx * (BM * BN / 4) + (tid - 128);
                if (nt < q.n_split) {
                    #pragma unroll
                    for (int j = 0; j < BN / 8; j++) __stcg(part + j * 256, make_float4(acc[4 * j], acc[4 * j + 1], acc[4 * j + 2], acc[4 * j + 3]));
                    __syncwarp();
                    if (lane == 0) signal_flag(q.part_flag + idx);
                    continue;
                }
                if (lane == 0) wait_flag(q.part_flag + idx, 8);
                __syncwarp();
                #pragma unroll
                for (int j = 0; j < BN / 8; j++) {
                    const float4 v = __ldcg(part + j * 256);
                    acc[4 * j] += v.x; acc[4 * j + 1] += v.y; acc[4 * j + 2] += v.z; acc[4 * j + 3] += v.w;
                }
            }
            epi_hand_over(acc, ectx, ((uint64_t)row0 << 32) | (uint32_t)(q.c_col0 + ntc * BN), q.sig ? (uint64_t)(q.sig + mt) : 0, 1 + (code >> 16));
        }
        epi_exit(ectx);
        if (elected) KEXIT(BN == 256 ? (p.nseg == 1 ? 6 : 2) : 4);
    }
}

constexpr int FIN_SPLIT = 8, FIN_KB = HD / BK / FIN_SPLIT;
constexpr int FIN_A1 = FIN_KB * 16384;
constexpr int FIN_A0 = FIN_A1 + FIN_KB * 8192;
constexpr int FIN_BAR = FIN_A0 + 4 * 8192, FIN_SMEM = FIN_BAR + 256;
enum { FB_B = 0, FB_A1 = 64, FB_A0 = 128, FB_E0 = 160, FB_RDY = 192, FB_RED = 208 };
struct FinalParams {
    CUtensorMap tmA, tmB;
    __nv_bfloat16* out;
    const uint32_t* dep;
    uint32_t dep_target;
    int mt;
};
__global__ void __launch_bounds__(384, 1) final_gemm_kernel(const __grid_constant__ FinalParams p) {
    extern __shared__ __align__(1024) uint8_t smem_raw[];
    const uint32_t sbase = smem_u32(smem_raw), bar = sbase + FIN_BAR;
    const int tid = threadIdx.x, wg = tid >> 7;
    const int rank = blockIdx.x % FIN_SPLIT, nt = blockIdx.x / FIN_SPLIT;
    KENTER(5);
    if (tid == 0) {
        for (int s = 0; s < FIN_KB; s++) { mbar_init(bar + FB_B + 8 * s, 1); mbar_init(bar + FB_A1 + 8 * s, 1); }
        for (int s = 0; s < 4; s++) { mbar_init(bar + FB_A0 + 8 * s, 1); mbar_init(bar + FB_E0 + 8 * s, 1); }
        for (int h = 0; h < 2; h++) { mbar_init(bar + FB_RDY + 8 * h, FIN_SPLIT); mbar_init(bar + FB_RED + 8 * h, 1); }
        asm volatile("fence.mbarrier_init.release.cluster;" ::: "memory");
        for (int h = 0; h < 2; h++) mbar_arrive_expect_tx(bar + FB_RED + 8 * h, (FIN_SPLIT - 1) * 4096);
        pdl_launch_dependents();
    }
    __syncthreads();
    asm volatile("barrier.cluster.arrive.relaxed.aligned;" ::: "memory");
    if (wg == 0) {
        auto need = [&](int i) {
            uint32_t n = 0;
            while (ld_acquire_b32(p.dep + i) < p.dep_target) { if (++n > SPIN_LIMIT) __trap(); }
            asm volatile("fence.proxy.async.global;" ::: "memory");
        };
        auto a_load = [&](uint32_t dst, int kb, int seg, uint32_t mb) { tma_load_2d(dst, &p.tmA, (rank * FIN_KB + kb) * BK, p.mt * BM + seg * SEG, mb); };
        if (tid == 0) {
            for (int kb = 0; kb < FIN_KB; kb++) {
                mbar_arrive_expect_tx(bar + FB_B + 8 * kb, 16384);
                tma_load_3d(sbase + kb * 16384, &p.tmB, 0, (rank * FIN_KB + kb) * BK, nt * 2, bar + FB_B + 8 * kb);
            }
        } else if (tid == 32) {
            need(0);
            need(1);
            for (int kb = 0; kb < FIN_KB; kb++) {
                if (kb >= 4) mbar_wait(bar + FB_E0 + 8 * (kb & 3), 0);
                mbar_arrive_expect_tx(bar + FB_A0 + 8 * (kb & 3), 8192);
                for (int u = 0; u < 2; u++) a_load(sbase + FIN_A0 + (kb & 3) * 8192 + u * 4096, kb, u, bar + FB_A0 + 8 * (kb & 3));
            }
        } else if (tid == 64) {
            need(2);
            for (int kb = 0; kb < FIN_KB; kb++) {
                mbar_arrive_expect_tx(bar + FB_A1 + 8 * kb, 8192);
                a_load(sbase + FIN_A1 + kb * 8192, kb, 2, bar + FB_A1 + 8 * kb);
            }
            need(3);
            KMARK(15);
            for (int kb = 0; kb < FIN_KB; kb++) a_load(sbase + FIN_A1 + kb * 8192 + 4096, kb, 3, bar + FB_A1 + 8 * kb);
        }
        __syncwarp();
        asm volatile("barrier.cluster.wait.aligned;" ::: "memory");
    } else {
        const int h = wg - 1, lane = tid & 31, wi = (tid >> 5) & 3, t128 = tid & 127;
        asm volatile("barrier.cluster.wait.aligned;" ::: "memory");
        float acc[64];
        for (int kb = 0; kb < FIN_KB; kb++) {
            mbar_wait(bar + FB_B + 8 * kb, 0);
            if (h == 0) mbar_wait(bar + FB_A0 + 8 * (kb & 3), kb >> 2); else mbar_wait(bar + FB_A1 + 8 * kb, 0);
            const uint32_t sa = sbase + (h == 0 ? FIN_A0 + (kb & 3) * 8192 : FIN_A1 + kb * 8192), sb = sbase + kb * 16384;
            asm volatile("wgmma.fence.sync.aligned;" ::: "memory");
            #pragma unroll
            for (int kk = 0; kk < BK / 16; kk++)
                wgmma_m64n128k16(acc, make_desc(sa + kk * 32, 16, 1024), make_desc(sb + kk * 2048, 8192, 1024), (kb | kk) != 0);
            asm volatile("wgmma.commit_group.sync.aligned;" ::: "memory");
            asm volatile("wgmma.wait_group.sync.aligned 1;" ::: "memory");
            if (h == 0 && kb >= 1 && kb <= 4 && t128 == 0) mbar_arrive(bar + FB_E0 + 8 * (kb - 1));
        }
        asm volatile("wgmma.wait_group.sync.aligned 0;" ::: "memory");
        const uint32_t red = sbase + (h == 0 ? FIN_A0 : FIN_A1);
        named_bar_sync(1 + h, 128);
        if (tid == 256) KMARK(16);
        if (tid == 128) KMARK(19);
        if (t128 < FIN_SPLIT)
            asm volatile("mbarrier.arrive.relaxed.cluster.shared::cluster.b64 _, [%0];" ::"r"(mapa(bar + FB_RDY + 8 * h, t128)) : "memory");
        mbar_wait(bar + FB_RDY + 8 * h, 0);
        if (tid == 256) KMARK(17);
        #pragma unroll
        for (int q = 0; q < FIN_SPLIT; q++) {
            if (q != rank) {
                const uint32_t dst = mapa(red + (rank - (rank > q ? 1 : 0)) * 4096 + t128 * 16, q), rb = mapa(bar + FB_RED + 8 * h, q);
                #pragma unroll
                for (int j = 0; j < 2; j++)
                    asm volatile("st.async.weak.shared::cluster.mbarrier::complete_tx::bytes.v4.f32 [%0], {%1,%2,%3,%4}, [%5];"
                                 ::"r"(dst + j * 2048), "f"(acc[8 * q + 4 * j]), "f"(acc[8 * q + 4 * j + 1]),
                                   "f"(acc[8 * q + 4 * j + 2]), "f"(acc[8 * q + 4 * j + 3]), "r"(rb) : "memory");
            }
        }
        float o[8];
        #pragma unroll
        for (int q = 0; q < FIN_SPLIT; q++)
            if (q == rank) {
                #pragma unroll
                for (int e = 0; e < 8; e++) o[e] = acc[8 * q + e];
            }
        mbar_wait(bar + FB_RED + 8 * h, 0);
        if (tid == 256) KMARK(18);
        if (tid == 128) KMARK(20);
        #pragma unroll
        for (int sl = 0; sl < FIN_SPLIT - 1; sl++) {
            #pragma unroll
            for (int j = 0; j < 2; j++) {
                const uint4 v = lds128(red + sl * 4096 + j * 2048 + t128 * 16);
                o[4 * j] += __uint_as_float(v.x); o[4 * j + 1] += __uint_as_float(v.y);
                o[4 * j + 2] += __uint_as_float(v.z); o[4 * j + 3] += __uint_as_float(v.w);
            }
        }
        __nv_bfloat16* dst = p.out + (size_t)(p.mt * BM + h * 64 + wi * 16 + (lane >> 2)) * (2 * DM) + nt * 128 + rank * 16 + (lane & 3) * 2;
        #pragma unroll
        for (int j = 0; j < 2; j++) {
            *reinterpret_cast<uint32_t*>(dst + j * 8) = pack_bf16(o[4 * j], o[4 * j + 1]);
            *reinterpret_cast<uint32_t*>(dst + (size_t)8 * (2 * DM) + j * 8) = pack_bf16(o[4 * j + 2], o[4 * j + 3]);
        }
        if (t128 == 0) KEXIT(5);
    }
}

#define POLL_DELAY 2
#define FETCH_DELAY 360
#define AT_PF 7
#define TOK_MOVED1 4
#define AT_POS0 0
#define FETCH_REL 1
#define REPOLL 1
#define V_EARLY 6
#define XB_POS 0
#define PARK_LATE 0
#define ST_POS 1
#define RST_POS 0
#define KV_POS 1
#define X0_POS 2
#define SPEC_SUM 0
#define AT_FIRST 4
#define AT_AHEAD 4
#define PRO_EARLY 0
#define PDL_POS 5
#define WO_FENCE 0
#define WO_PFA 4
#define WO_PFB_DELAY 60
#define EXP 0
#define NO_COMM 0
#define TOK_MOVED 8
#define XB_DELAY 0
#define WO_PF0 0
#define WO_PF1 11
#define WO_AHEAD 10
constexpr int REC_THREADS = 256;
constexpr uint32_t POLL_LIMIT = 1u << 16;
constexpr int NREG = 24;
__host__ __device__ constexpr int reg_idx(int j) { return ((j & 3) - 1) * 8 + (j >> 2); }
constexpr int SM_WQ = 0;
constexpr int SM_WO = 65536;
constexpr int SM_X = SM_WO + 11 * 8192;
constexpr int SM_PARK0 = SM_X, SM_PARK1 = SM_X + 8192;
constexpr int SM_MEM = SM_X + 4 * 4096;
constexpr int SM_RED = SM_X + 8 * 4096;
constexpr int SM_V = SM_X + 12 * 4096;
constexpr int SM_K = SM_X + 14 * 4096;
constexpr int SM_QS = SM_X + 15 * 4096;
constexpr int SM_QK = SM_X + 65536;
constexpr int SM_SP = SM_QK + 2048;
constexpr int SM_VM = SM_SP + 2560;
constexpr int SM_O = SM_VM + 2048;
constexpr int SM_SUM = SM_O + 2048;
constexpr int SM_TBL = SM_SUM + 128;
constexpr int SM_BAR = SM_TBL + 512;
constexpr int SM_STAMP = SM_BAR + 224;
constexpr int REC_SMEM = SM_STAMP;
static_assert(REC_SMEM <= 232448, "shared memory");
enum { BAR_V = 0, BAR_X = 8, BAR_P0 = 16, BAR_WQ = 40, BAR_WO = 48, BAR_XG = 56, BAR_F0 = 88, BAR_F3 = 96, BAR_VF = 104,
       BAR_M = 112, BAR_GO = 144, BAR_PK = 152, BAR_VM = 160, BAR_SELF = 168, BAR_TPUB = 176, BAR_MIN = 176, BAR_PUB = 192 };

template <int V> struct IntC { static constexpr int value = V; };
template <int I, int N, typename F> __device__ __forceinline__ void sfor(F&& f) {
    if constexpr (I < N) { f(IntC<I>{}); sfor<I + 1, N>(f); }
}

struct RecParams {
    CUtensorMap tmW[3];
    CUtensorMap tmWo;
    CUtensorMap tmX;
    const __nv_bfloat16* mem0;
    __nv_bfloat16* qkv_tok;
    __nv_bfloat16* kv_mem;
    uint8_t* xchg;
    uint32_t* flags;
    uint32_t one[2];
    uint32_t* arrivals;
};

__device__ __forceinline__ void mma_a(float* d, const uint32_t* a, uint32_t b0, uint32_t b1) {
    mma16816(d, a[0], a[1], a[2], a[3], b0, b1);
}
__device__ __forceinline__ void ldsm4(uint32_t addr, uint32_t* r) { ldsm_x4(addr, r[0], r[1], r[2], r[3]); }
__device__ __forceinline__ void ldsm4t(uint32_t addr, uint32_t* r) { ldsm_x4_t(addr, r[0], r[1], r[2], r[3]); }
template <int OFF> __device__ __forceinline__ void poll_v2(uint2& v, const uint8_t* p) {
    asm volatile("ld.relaxed.gpu.global.v2.b32 {%0,%1}, [%2+%3];" : "=r"(v.x), "=r"(v.y) : "l"(p), "n"(OFF) : "memory");
}
template <int OFF> __device__ __forceinline__ void repoll_v2(uint2& v, const uint8_t* p) {
    asm volatile("{\n.reg .pred q;\nsetp.eq.u32 q, %1, 0xFFFFFFFF;\n@q ld.relaxed.gpu.global.v2.b32 {%0,%1}, [%2+%3];\n}"
                 : "+r"(v.x), "+r"(v.y) : "l"(p), "n"(OFF) : "memory");
}
__device__ __forceinline__ uint32_t max3(uint32_t a, uint32_t b, uint32_t c) { return max(max(a, b), c); }
__device__ __forceinline__ uint32_t pub_slot(int s) { return (s & 1) * XCHG_SLOT + ((s >> 1) & 1) * PUB_BYTES; }

__device__ __forceinline__ uint8_t* xaddr(uint32_t lo, uint32_t hi) {
    uint64_t a;
    asm("mov.b64 %0, {%1, %2};" : "=l"(a) : "r"(lo), "r"(hi));
    return reinterpret_cast<uint8_t*>(a);
}
template <int N> __device__ __forceinline__ uint32_t delay_zero(uint32_t a) {
    uint32_t x = a;
    #pragma unroll
    for (int i = 0; i < N; i++) x = lds32_volatile(x);
    return x - a;
}
__device__ __forceinline__ uint32_t fresh(uint32_t x) { asm volatile("" : "+r"(x)); return x; }

template <int NT> __device__ __forceinline__ uint32_t wo_addr(uint32_t ao, uint32_t a3, int n) {
    return (n % NT == 2 ? a3 : ao + (n % NT) * 32768) + (n / NT) * 1024;
}
__device__ __forceinline__ void sched_fence(uint32_t& x, uint32_t zero) { x ^= clock32() & zero; }
template <int NT, int PF, typename F>
__device__ __forceinline__ void wo_phase(F&& hook, uint32_t (&st)[8 * NT][4], uint32_t ao, uint32_t a3, uint32_t l16, uint32_t tbl, uint32_t sums,
                                         uint32_t slot, uint32_t xhi, uint32_t third, uint32_t zero, uint32_t& tok, uint32_t xbar, uint32_t xpar, bool& x_ok) {
    constexpr int AHEAD = PF > WO_AHEAD ? PF - NT : WO_AHEAD;
    uint32_t of[4][4];
    uint2 sm;
    uint4 t;
    ldsm4t(l16 + SM_O, of[0]);
    #pragma unroll
    for (int n = PF; n < AHEAD; n++) {
        ldsm4t(wo_addr<NT>(ao, a3, n), st[n]);
        if (n == 2 * NT - 1) ldsm4t(l16 + SM_O + 512, of[1]);
    }
    if (PF >= 2 * NT) ldsm4t(l16 + SM_O + 512, of[1]);
    float acc[NT][4];
    #pragma unroll
    for (int i = 0; i < NT; i++) { acc[i][0] = acc[i][1] = acc[i][2] = acc[i][3] = 0.f; }
    #pragma unroll
    for (int kk = 0; kk < 8; kk++) {
        if (WO_FENCE && kk < 7) sched_fence(tok, zero);
        #pragma unroll
        for (int i = 0; i < NT; i++) {
            const int n = kk * NT + i;
            mma_a(acc[i], st[n], of[kk >> 1][(kk & 1) * 2], of[kk >> 1][(kk & 1) * 2 + 1]);
            if (n + AHEAD >= PF && n + AHEAD < 8 * NT) ldsm4t(wo_addr<NT>(ao, a3, n + AHEAD), st[n + AHEAD]);
        }
        if (kk == XB_POS - 1) hook();
        if (kk == 1 || kk == 3) ldsm4t(l16 + SM_O + ((kk >> 1) + 2) * 512, of[(kk >> 1) + 2]);
        if (kk == (NT == 3 ? 5 : 4)) {
            const uint32_t x = fresh(l16);
            sm = lds64(sums + ((x >> 1) & 0x18));
            t = lds128(tbl + ((x >> 3) & 0x30));
            x_ok = mbar_test_wait(xbar, xpar);
        }
    }
    const float i0 = rcp(__uint_as_float(sm.x)), i1 = rcp(__uint_as_float(sm.y));
    const uint32_t d = slot + ((fresh(l16) >> 1) & 0x38);
    const uint32_t pl[3] = {t.x + d, t.y + d, t.z + d};
    #pragma unroll
    for (int i = 0; i < NT; i++)
        asm volatile("{\n.reg .pred p;\nsetp.ne.u32 p, %3, 0;\n@p st.relaxed.gpu.global.v2.b32 [%0], {%1,%2};\n}"
                     ::"l"(xaddr(pl[i], xhi)), "r"(pack_bf16(acc[i][0] * i0, acc[i][1] * i1)), "r"(pack_bf16(acc[i][2] * i0, acc[i][3] * i1)),
                       "r"(i < 2 ? 1u : third) : "memory");
}

constexpr uint32_t SMEM_ORIGIN = 1024;
constexpr uint64_t DESC_BASE = (1ull << 16) | (0x40000040ull << 32);
template <int OFFB, int SCALE_D>
__device__ __forceinline__ void wgmma_n32_rs(float (&d)[16], const uint32_t* a, uint32_t one) {
    asm volatile(
        "{\n.reg .b64 db;\nmad.wide.u32 db, %20, %21, %22;\n"
        "wgmma.mma_async.sync.aligned.m64n32k16.f32.bf16.bf16 {%0,%1,%2,%3,%4,%5,%6,%7,%8,%9,%10,%11,%12,%13,%14,%15}, "
        "{%16,%17,%18,%19}, db, %23, 1, 1, 0;\n}"
        : "+f"(d[0]), "+f"(d[1]), "+f"(d[2]), "+f"(d[3]), "+f"(d[4]), "+f"(d[5]), "+f"(d[6]), "+f"(d[7]),
          "+f"(d[8]), "+f"(d[9]), "+f"(d[10]), "+f"(d[11]), "+f"(d[12]), "+f"(d[13]), "+f"(d[14]), "+f"(d[15])
        : "r"(a[0]), "r"(a[1]), "r"(a[2]), "r"(a[3]), "r"(one), "n"((SMEM_ORIGIN + OFFB) >> 4), "l"(DESC_BASE), "n"(SCALE_D));
}
template <int OFFA, int OFFB, int SCALE_D>
__device__ __forceinline__ void wgmma_n32_ss(float (&d)[16], uint32_t one) {
    asm volatile(
        "{\n.reg .b64 da, db;\nmad.wide.u32 da, %16, %17, %19;\nmad.wide.u32 db, %16, %18, %19;\n"
        "wgmma.mma_async.sync.aligned.m64n32k16.f32.bf16.bf16 {%0,%1,%2,%3,%4,%5,%6,%7,%8,%9,%10,%11,%12,%13,%14,%15}, "
        "da, db, %20, 1, 1, 1, 0;\n}"
        : "+f"(d[0]), "+f"(d[1]), "+f"(d[2]), "+f"(d[3]), "+f"(d[4]), "+f"(d[5]), "+f"(d[6]), "+f"(d[7]),
          "+f"(d[8]), "+f"(d[9]), "+f"(d[10]), "+f"(d[11]), "+f"(d[12]), "+f"(d[13]), "+f"(d[14]), "+f"(d[15])
        : "r"(one), "n"((SMEM_ORIGIN + OFFA) >> 4), "n"((SMEM_ORIGIN + OFFB) >> 4), "l"(DESC_BASE), "n"(SCALE_D));
}
template <int WG, int J0, int J1, int I, bool ACC, bool FENCE = true>
__device__ __forceinline__ void token_mma(float (&ta)[2][16], const uint32_t (&wr)[NREG][2][4], uint32_t one) {
    if (FENCE) asm volatile("wgmma.fence.sync.aligned;" ::: "memory");
    sfor<J0, J1>([&](auto J) {
        constexpr int j = J.value, c = j >> 2, offb = SM_X + WG * 32768 + c * 4096 + (j & 3) * 32, sc = (ACC || j != J0) ? 1 : 0;
        if constexpr ((j & 3) != 0) wgmma_n32_rs<offb, sc>(ta[I], wr[reg_idx(j)][I], one);
        else if constexpr (WG == 0 || c >= (I ? TOK_MOVED1 : TOK_MOVED)) wgmma_n32_ss<SM_WQ + WG * 32768 + I * 16384 + c * 2048, offb, sc>(ta[I], one);
        constexpr int m = I ? c : c - 4;
        if constexpr (WG == 0 && (j & 3) == 1 && m >= 0 && m < (I ? TOK_MOVED : TOK_MOVED1))
            wgmma_n32_ss<SM_WQ + 32768 + (1 - I) * 16384 + m * 2048, SM_X + 32768 + m * 4096, 1>(ta[I], one);
    });
    asm volatile("wgmma.commit_group.sync.aligned;" ::: "memory");
}
__device__ __forceinline__ void warp_arrive(uint32_t bar) {
    __syncwarp();
    if (elect_one()) mbar_arrive(bar);
}
__device__ __forceinline__ void remote_arrive(uint32_t bar, uint32_t rank) {
    asm volatile("mbarrier.arrive.relaxed.cluster.shared::cluster.b64 _, [%0];" ::"r"(mapa(bar, rank)) : "memory");
}
__device__ __forceinline__ void x_load(const RecParams& p, uint32_t sb, int sg, int g) {
    if ((EXP >> g) & 1) return;
    tma_load_3d_mc(sb + SM_X + g * 16384, &p.tmX, 0, sg * SEG, g * 4, sb + SM_BAR + BAR_XG + 8 * g, (uint16_t)7);
}

__device__ __forceinline__ void rec_steps(const RecParams& p, const uint32_t (&wr)[NREG][2][4], const uint32_t sb, const int warp,
                                          const int cta, const int head, const int rank) {
    const int wq = warp & 3, wg = warp >> 2;
    const uint32_t bar = sb + SM_BAR;
    const uint32_t xhi = (uint32_t)((uint64_t)p.xchg >> 32);
    const float sl2 = 0.08838834764831845f * 1.4426950408889634f;
    const bool has_unit = warp >= 5 && (warp < 7 || cta < 64);
    const bool qk = rank < 2;
    const uint32_t pa = rank == 2 ? 0 : rank + 1, pb = rank == 0 ? 2 : rank - 1;
    const uint32_t tbl = sb + SM_TBL + warp * 64;
    const bool att = (warp & 6) == 2;
    const int stile = warp < 5 ? warp : warp - 3;

    const uint32_t u_st = uniform(SM_QK - SM_WQ - wg * (32768 - 1024));
    const uint32_t u_xa = uniform(sb + (qk ? SM_SP + rank * 1280 + stile * 256 : SM_VM + warp * 256));
    const uint32_t u_key = uniform(!qk || att || warp == 7 ? 0 : sb + (warp == 4 ? SM_QK + 1024 : SM_K + stile * 1024));
    const uint32_t u_bx = uniform(bar + (qk ? BAR_X : BAR_VM)), u_bra = uniform(mapa(u_bx, pa)), u_brb = uniform(mapa(u_bx, pb));
    const uint32_t u_src = uniform(lds32_volatile(tbl + 44));
    const uint32_t u_kv = uniform(qk && wg == 0 ? ~0u : (((rank >> 1) * NSEG * NH + head) * 8 + (qk ? rank * 4 + wq : warp)) * 64);
    const uint32_t u_free = uniform(mapa(bar + (warp == 5 ? BAR_VF : BAR_F0), warp == 5 ? 2 : 0));
    const uint32_t u_role = uniform((has_unit ? 1 : 0) | (att ? 2 : 0) | (wg == 1 || qk ? 4 : 0) | (!qk && warp == 0 ? 8 : 0) | (rank != 0 && warp == (XB_POS ? 2 : 1) ? 16 : 0) |
                                    (warp == 5 || warp == 6 ? 32 : 0));
    uint32_t l16, aq, ao;
    {
        const int lane = threadIdx.x & 31, mi = lane >> 3, r8 = lane & 7, r16 = (mi >> 1) * 8 + r8;
        l16 = opaque(sb + lane * 16);
        aq = opaque(sb + SM_WQ + wg * 32768 + r16 * 128 + (((wq * 2 + (mi & 1)) ^ r8) << 4));
        ao = opaque(sb + SM_WO + (warp >> 1) * 8192 + r16 * 64 + ((((warp & 1) * 2 + (mi & 1)) ^ ((r8 >> 1) & 3)) << 4));
    }

    uint32_t mphase = 0;
    bool x0_ok = false;
    #pragma unroll 1
    for (int s = 0;; s++) {
        const uint32_t par = s & 1;
        uint32_t at[16][4];
        auto at_early = [](int i) { return i < 2 || ((i & 1) == 1 && (i >> 1) <= AT_PF - 2); };
        auto at_prefetch = [&](bool first) {
            #pragma unroll
            for (int i = 0; i < 16; i++)
                if (at_early(i) && first == ((i & 1) == 1 && (i >> 1) < AT_FIRST)) ldsm4t(aq + (i & 1) * 16384 + (i >> 1) * 2048, at[i]);
        };
        auto resets = [&](int late) {
            if ((u_role & 1) && (late || s > 0)) {
                const uint32_t lane = (fresh(l16) >> 4) & 31;
                uint8_t* ib = xaddr(lds32_volatile(tbl + 12) + (par ^ late) * XCHG_SLOT + lane * 16, xhi);
                #pragma unroll
                for (int i = 0; i < 4; i++) st_relaxed_v4(ib + i * 512, SENT);
                st_relaxed_b32(xaddr(lds32_volatile(tbl + 28) + pub_slot(s + 2 + late) + (lane & 16) * 256 + (lane & 8) * 16 + (lane & 7) * 4, xhi), SENT);
            }
        };
        if (wg == 0) {
            float ta[2][16];
            if (!x0_ok) mbar_wait_bounded(bar + BAR_XG, par);
            STAMP(6);
            auto park = [&](int i, uint32_t dst) {
                #pragma unroll
                for (int e = 0; e < 16; e++) asm volatile("" : "+f"(ta[i][e]));
                #pragma unroll
                for (int j = 0; j < ((EXP & 128) ? 2 : 4); j++)
                    sts128(l16 + dst + j * 2048 + wq * 512, __float_as_uint(ta[i][4 * j]), __float_as_uint(ta[i][4 * j + 1]),
                           __float_as_uint(ta[i][4 * j + 2]), __float_as_uint(ta[i][4 * j + 3]));
            };
            if (EXP & 64) spin_clks(1200);
            token_mma<0, 0, 16, 0, false>(ta, wr, 1);
            mbar_wait_bounded(bar + BAR_XG + 8, par);
            if (TOK_MOVED1 > 0) mbar_wait_bounded(bar + BAR_XG + 16, par);
            if (AT_POS0 == 0) at_prefetch(true);
            token_mma<0, 16, 32, 0, true>(ta, wr, p.one[1]);
            if (TOK_MOVED1 == 0) mbar_wait_bounded(bar + BAR_XG + 16, par);
            token_mma<0, 0, 16, 1, false, TOK_MOVED1 == 0>(ta, wr, p.one[0]);
            if (TOK_MOVED > 4) mbar_wait_bounded(bar + BAR_XG + 24, par);
            token_mma<0, 16, 32, 1, true, (TOK_MOVED > 4)>(ta, wr, 1);
            asm volatile("wgmma.wait_group.sync.aligned 1;" ::: "memory");
            if (PARK_LATE) mbar_wait_bounded(bar + BAR_PUB, par);
            park(0, SM_PARK0);
            warp_arrive(bar + BAR_GO);
            asm volatile("wgmma.wait_group.sync.aligned 0;" ::: "memory");
            park(1, SM_PARK1);
            if (TOK_MOVED <= 4) mbar_wait_bounded(bar + BAR_XG + 24, par);
            warp_arrive(bar + BAR_PK);
            const uint8_t* src = xaddr(u_src + pub_slot(s), xhi);
            auto fetch = [&]() {
                if (elect_one()) {
                    mbar_arrive_expect_tx(bar + BAR_M + 8 * wq, 4096);
                    bulk_load(sb + SM_MEM + wq * 4096, src, 4096, bar + BAR_M + 8 * wq);
                }
            };
            if (!PARK_LATE) named_bar_sync(7, REC_THREADS - 32);
            if (FETCH_REL) {
                const uint4 t = lds128(bar + BAR_TPUB);
                const uint32_t now = clock32();
                spin_until(now + FETCH_DELAY - min(min(min(now - t.y, now - t.z), now - t.w), (uint32_t)FETCH_DELAY));
            } else {
                spin_clks(FETCH_DELAY);
            }
            fetch();
            STAMP(12);
            if (warp == 0 && elect_one()) {
                if (qk) mbar_arrive_expect_tx(bar + BAR_V, (EXP & 16) ? 32 : 8192);
                mbar_arrive_expect_tx(bar + BAR_X, qk ? 1280 : 2560);
                mbar_arrive_expect_tx(bar + BAR_VM, qk ? 2048 : 0);
            }
            if (AT_POS0 == 1) at_prefetch(true);
            at_prefetch(false);
            const uint32_t x = fresh(l16) - sb;
            const uint32_t ca = sb + SM_MEM + wq * 4096 + x * 2 + ((x >> 4) & 0x1C);
            #pragma unroll 1
            for (uint32_t n = 0; n < POLL_LIMIT; n++) {
                mbar_wait_bounded(bar + BAR_M + 8 * wq, mphase);
                mphase ^= 1;
                const uint32_t c0 = lds32_volatile(ca), c1 = lds32_volatile(ca + 1024), c2 = lds32_volatile(ca + 2048), c3 = lds32_volatile(ca + 3072);
                if (!__any_sync(~0u, max(max3(c0, c1, c2), c3) == (NO_COMM ? 0x12345u : SENT))) break;
                fetch();
            }
            STAMP(0);
            named_bar_sync(0, REC_THREADS);
            if (X0_POS == 2 && warp == 0 && rank == 0 && s + 1 < NSEG) {
                mbar_wait_bounded(bar + BAR_F0, par);
                if (elect_one()) x_load(p, sb, s + 1, 0);
            }
            if (u_role & 8) {
                asm volatile("fence.proxy.async.shared::cta;" ::: "memory");
                mbar_wait_bounded(bar + BAR_VF, par);
                if (elect_one()) {
                    #pragma unroll
                    for (int r = 0; r < 2; r++)
                        asm volatile("cp.async.bulk.shared::cluster.shared::cta.mbarrier::complete_tx::bytes [%0], [%1], %2, [%3];"
                                     ::"r"(mapa(sb + SM_V, r)), "r"(sb + SM_V), "r"((EXP & 16) ? 32 : 8192), "r"(mapa(bar + BAR_V, r)) : "memory");
                }
            }
        } else {
            at_prefetch(true);
            if (RST_POS == 2) resets(0);
            if (s > 0) {
                if (u_role & 1) {
                    const uint32_t ln = (fresh(l16) >> 4) & 31;
                    const uint32_t ibl = lds32_volatile(tbl + 12) + (par ^ 1) * XCHG_SLOT + ln * 8;
                    const uint32_t publ = lds32_volatile(tbl + 28) + pub_slot(s) + (ln & 16) * 256 + (ln & 8) * 16 + (ln & 7) * 4;
                    const bool odd = ln & 8;
                    const uint8_t* ib = xaddr(ibl + delay_zero<POLL_DELAY>(bar + BAR_SELF), xhi);
                    STAMP(8);
                    uint2 v[8];
                    float a0, a1, a2, a3;
                    auto sum8 = [&]() {
                        a0 = ((bf16_lo(v[0].x) + bf16_lo(v[1].x)) + (bf16_lo(v[2].x) + bf16_lo(v[3].x))) +
                             ((bf16_lo(v[4].x) + bf16_lo(v[5].x)) + (bf16_lo(v[6].x) + bf16_lo(v[7].x)));
                        a1 = ((bf16_hi(v[0].x) + bf16_hi(v[1].x)) + (bf16_hi(v[2].x) + bf16_hi(v[3].x))) +
                             ((bf16_hi(v[4].x) + bf16_hi(v[5].x)) + (bf16_hi(v[6].x) + bf16_hi(v[7].x)));
                        a2 = ((bf16_lo(v[0].y) + bf16_lo(v[1].y)) + (bf16_lo(v[2].y) + bf16_lo(v[3].y))) +
                             ((bf16_lo(v[4].y) + bf16_lo(v[5].y)) + (bf16_lo(v[6].y) + bf16_lo(v[7].y)));
                        a3 = ((bf16_hi(v[0].y) + bf16_hi(v[1].y)) + (bf16_hi(v[2].y) + bf16_hi(v[3].y))) +
                             ((bf16_hi(v[4].y) + bf16_hi(v[5].y)) + (bf16_hi(v[6].y) + bf16_hi(v[7].y)));
                    };
                    if (REPOLL) {
                        #pragma unroll
                        for (int i = 0; i < 8; i++) v[i] = make_uint2(SENT, SENT);
                    }
                    #pragma unroll 1
                    for (uint32_t n = 0; n < POLL_LIMIT; n++) {
                        if (REPOLL) sfor<0, 8>([&](auto I) { repoll_v2<I.value * 256>(v[I.value], ib); });
                        else sfor<0, 8>([&](auto I) { poll_v2<I.value * 256>(v[I.value], ib); });
                        const uint32_t mx = max(max3(v[0].y, v[1].y, v[2].y), max3(max3(v[3].y, v[4].y, v[5].y), v[6].y, v[7].y));
                        if (SPEC_SUM) { sum8(); asm volatile("" : "+f"(a0), "+f"(a1), "+f"(a2), "+f"(a3)); }
                        if (!__any_sync(~0u, mx == (NO_COMM ? 0x12345u : SENT))) break;
                    }
                    STAMP(9);
                    if (!SPEC_SUM) sum8();
                    float k0 = odd ? a2 : a0, k1 = odd ? a3 : a1;
                    k0 += __shfl_xor_sync(~0u, odd ? a0 : a2, 8);
                    k1 += __shfl_xor_sync(~0u, odd ? a1 : a3, 8);
                    k0 += __shfl_xor_sync(~0u, k0, 16);
                    k1 += __shfl_xor_sync(~0u, k1, 16);
                    st_relaxed_b32(xaddr(publ, xhi), pack_bf16(k0, k1));
                    STAMP(11);
                } else if (warp == 4) {
                    bulk_wait_read_all();
                    if (elect_one()) remote_arrive(bar + BAR_F3, 2);
                    if (!qk) {
                        mbar_wait_bounded(bar + BAR_F3, par ^ 1);
                        if (elect_one()) x_load(p, sb, s, 3);
                    }
                    if (elect_one()) {
                        bulk_wait_all();
                        signal_flag(p.flags + F_PROGRESS + s - 1);
                    }
                    __syncwarp();
                    STAMP(10);
                }
            }
            float ta[2][16];
            uint32_t w[8];
            auto unpark = [&](int i, uint32_t src) {
                mbar_wait_bounded(bar + (i ? BAR_GO : BAR_PK), par);
                #pragma unroll
                for (int j = 0; j < 4; j++) {
                    uint4 v = make_uint4(0, 0, 0, 0);
                    if (!(EXP & 128) || j < 2) v = lds128(l16 + src + j * 2048 + wq * 512);
                    ta[i][4 * j] = __uint_as_float(v.x); ta[i][4 * j + 1] = __uint_as_float(v.y);
                    ta[i][4 * j + 2] = __uint_as_float(v.z); ta[i][4 * j + 3] = __uint_as_float(v.w);
                }
            };
            if (FETCH_REL) sts32(bar + BAR_TPUB + 4 * wq, clock32());
            if (warp != 4) { if (PARK_LATE) warp_arrive(bar + BAR_PUB); else named_bar_arrive(7, REC_THREADS - 32); }
            unpark(1, SM_PARK0);
            STAMP(6);
            token_mma<1, 0, 16, 1, true>(ta, wr, 1);
            if (RST_POS == 3) resets(0);
            unpark(0, SM_PARK1);
            token_mma<1, 16, 32, 1, true>(ta, wr, 1);
            token_mma<1, 16, 32, 0, true>(ta, wr, 1);
            token_mma<1, 0, 16, 0, true, false>(ta, wr, 1);
            auto put_tile = [&](int m, const uint32_t (&q)[8]) {
                #pragma unroll
                for (int h = 0; h < 2; h++) {
                    if (qk) asm volatile("stmatrix.sync.aligned.m8n8.x4.trans.shared.b16 [%0], {%1,%2,%3,%4};"
                                         ::"r"(aq - (SM_WQ + 32768) + (m ? SM_K : SM_QS) + h * 2048), "r"(q[4 * h]), "r"(q[4 * h + 1]),
                                           "r"(q[4 * h + 2]), "r"(q[4 * h + 3]) : "memory");
                    else sts128(l16 + SM_V + wq * 2048 + m * 1024 + h * 512, q[4 * h], q[4 * h + 1], q[4 * h + 2], q[4 * h + 3]);
                }
            };
            auto pack_tile = [&](int i) {
                #pragma unroll
                for (int e = 0; e < 16; e++) asm volatile("" : "+f"(ta[i][e]));
                #pragma unroll
                for (int j = 0; j < 8; j++) w[j] = pack_bf16(ta[i][2 * j], ta[i][2 * j + 1]);
            };
            asm volatile("wgmma.wait_group.sync.aligned 2;" ::: "memory");
            pack_tile(1);
            if (RST_POS == 4) resets(0);
            at_prefetch(false);
            asm volatile("wgmma.wait_group.sync.aligned 1;" ::: "memory");
            if ((u_role & 32) && elect_one())
                asm volatile("mbarrier.arrive.relaxed.cluster.shared::cluster.b64 _, [%0];" ::"r"(u_free) : "memory");
            put_tile(0, w);
            asm volatile("wgmma.wait_group.sync.aligned 0;" ::: "memory");
            pack_tile(0);
            put_tile(1, w);
            STAMP(0);
            named_bar_sync(0, REC_THREADS);
            STAMP(14);
        }
        const uint32_t mb = l16 + SM_MEM + wg * 8192;
        float acc[2][2][4];
        {
            uint32_t b[2][4];
            ldsm4t(mb, b[0]);
            ldsm4t(mb + 512, b[1]);
            #pragma unroll
            for (int i = 0; i < AT_AHEAD; i++)
                if (!at_early(i)) ldsm4t(aq + (i & 1) * 16384 + (i >> 1) * 2048, at[i]);
            STAMPD(1, b[0][0]);
            #pragma unroll
            for (int i = 0; i < 4; i++) { for (int e = 0; e < 4; e++) acc[i >> 1][i & 1][e] = 0.f; }
            #pragma unroll
            for (int u = 0; u < 16; u++) {
                #pragma unroll
                for (int h = 0; h < 2; h++) {
                    const int j = 2 * u + h;
                    #pragma unroll
                    for (int m = 0; m < 2; m++) {
                        if ((j & 3) == 0) mma_a(acc[h][m], at[(j >> 2) * 2 + m], b[u & 1][2 * h], b[u & 1][2 * h + 1]);
                        else mma_a(acc[h][m], wr[reg_idx(j)][m], b[u & 1][2 * h], b[u & 1][2 * h + 1]);
                    }
                }
                if (u + 2 < 16) ldsm4t(mb + (u + 2) * 512, b[u & 1]);
                if (u + AT_AHEAD < 16 && !at_early(u + AT_AHEAD))
                    ldsm4t(aq + ((u + AT_AHEAD) & 1) * 16384 + ((u + AT_AHEAD) >> 1) * 2048, at[u + AT_AHEAD]);
            }
        }
        sts128(l16 + SM_RED + warp * 512, __float_as_uint(acc[0][1][0] + acc[1][1][0]), __float_as_uint(acc[0][1][1] + acc[1][1][1]),
               __float_as_uint(acc[0][1][2] + acc[1][1][2]), __float_as_uint(acc[0][1][3] + acc[1][1][3]));
        #pragma unroll
        for (int e = 0; e < 4; e++) acc[0][0][e] += acc[1][0][e];
        const uint32_t x16 = fresh(l16);
        const uint32_t sa = fresh((x16 & 0x70) * 8 + ((((x16 >> 3) & 0x30) ^ x16) & 0x70));
        const uint32_t sq = fresh(sa ^ ((((x16 >> 7) ^ (x16 >> 8)) & 1) * 0x30));
        const uint32_t x8 = (x16 & 0x1F0) >> 1;
        const uint32_t xra = fresh(x8 + __byte_perm(u_xa, u_bra, 0x7210)), xrb = fresh(x8 + __byte_perm(u_xa, u_brb, 0x7210));
        STAMP(2);
        named_bar_sync(1 + wq, 64);
        uint32_t p0, p1;
        {
            const uint4 v = lds128(l16 + SM_RED + (warp ^ 4) * 512);
            p0 = pack_bf16(acc[0][0][0] + __uint_as_float(v.x), acc[0][0][1] + __uint_as_float(v.y));
            p1 = pack_bf16(acc[0][0][2] + __uint_as_float(v.z), acc[0][0][3] + __uint_as_float(v.w));
        }
        auto send = [&](uint32_t y0, uint32_t y1) {
            st_async_v2(xra, y0, y1, u_bra);
            st_async_v2(xrb, y0, y1, u_brb);
            sts64(x8 + u_xa, y0, y1);
            warp_arrive(u_bx);
        };
        if (qk) {
            asm volatile("stmatrix.sync.aligned.m8n8.x2.trans.shared.b16 [%0], {%1,%2};" ::"r"(aq + u_st), "r"(p0), "r"(p1) : "memory");
            named_bar_sync(5, REC_THREADS);
            if (u_key != 0) {
                uint32_t qa[2][4], kf[2][4];
                ldsm4(sq + sb + SM_QK, qa[0]);
                ldsm4(sa + u_key, kf[0]);
                ldsm4((sq ^ 64) + sb + SM_QK, qa[1]);
                ldsm4((sa ^ 64) + u_key, kf[1]);
                float se[4] = {0.f, 0.f, 0.f, 0.f}, so[4] = {0.f, 0.f, 0.f, 0.f};
                #pragma unroll
                for (int u = 0; u < 2; u++) {
                    mma_a(se, qa[u], kf[u][0], kf[u][1]);
                    mma_a(so, qa[u], kf[u][2], kf[u][3]);
                }
                send(__float_as_uint(se[0] + so[2]), __float_as_uint(se[1] + so[3]));
            }
        } else {
            send(p0, p1);
        }
        STAMP(3);
        const uint32_t lane = (fresh(l16) >> 4) & 31;
        auto kv_stores = [&]() {
            if (u_kv != ~0u) {
                uint32_t* dst = reinterpret_cast<uint32_t*>(p.kv_mem) + (u_kv + s * (NH * 512) + lane);
                dst[0] = p0;
                dst[32] = p1;
            }
        };
        auto tile_stores = [&]() {
            if (warp == 4) {
                asm volatile("fence.proxy.async.shared::cta;" ::: "memory");
                if (elect_one()) {
                    __nv_bfloat16* dst = p.qkv_tok + ((size_t)s * NH + head) * (SEG * DH);
                    constexpr size_t MAT = (size_t)NSEG * NH * SEG * DH;
                    bulk_store(dst + (qk ? rank * (SEG * 64) : 2 * MAT), sb + (qk ? SM_QS : SM_V), (EXP & 32) ? 32 : 4096);
                    bulk_store(dst + (qk ? MAT + rank * (SEG * 64) : 2 * MAT + SEG * 64), sb + (qk ? SM_K : SM_V + 4096), (EXP & 32) ? 32 : 4096);
                    bulk_commit();
                }
            }
        };
        if (((s + 1) & 62) == 0) {
            if (s == NSEG - 1) { kv_stores(); tile_stores(); break; }
            mbar_wait_bounded(bar + BAR_WO, 0);
            if (PDL_POS == 5) pdl_launch_dependents();
            PSTAMP(8);
        }
        const uint32_t slot = par * XCHG_SLOT;
        if (u_role & 2) {
            if (qk) mbar_wait_bounded(bar + BAR_V, par);
            uint32_t vt[2][4][4];
            auto v_load = [&](int i0, int i1) {
                #pragma unroll
                for (int i = i0; i < i1; i++) {
                    const uint4 v = lds128(l16 + SM_V + (warp & 1) * 1024 + (i & 3) * 2048 + (i >> 2) * 512);
                    vt[i >> 2][i & 3][0] = v.x; vt[i >> 2][i & 3][1] = v.y; vt[i >> 2][i & 3][2] = v.z; vt[i >> 2][i & 3][3] = v.w;
                }
            };
            v_load(0, V_EARLY);
            kv_stores();
            const uint32_t l8 = fresh(sb + lane * 8);
            mbar_wait_bounded(bar + BAR_X, par);
            STAMP(4);
            float sv[10];
            #pragma unroll
            for (int j = 0; j < 5; j++) {
                const uint2 a = lds64(l8 + SM_SP + j * 256), b = lds64(l8 + SM_SP + 1280 + j * 256);
                sv[2 * j] = __uint_as_float(a.x) + __uint_as_float(b.x);
                sv[2 * j + 1] = __uint_as_float(a.y) + __uint_as_float(b.y);
            }
            float mx = fmaxf(fmaxf(fmaxf(sv[0], sv[1]), fmaxf(sv[2], sv[3])), fmaxf(fmaxf(sv[4], sv[5]), fmaxf(sv[6], sv[7])));
            mx = fmaxf(mx, fmaxf(sv[8], sv[9]));
            const float m1 = __shfl_xor_sync(~0u, mx, 1), m2 = __shfl_xor_sync(~0u, mx, 2), m3 = __shfl_xor_sync(~0u, mx, 3);
            __syncwarp();
            v_load(V_EARLY, 8);
            const bool vm_ok = mbar_test_wait(bar + BAR_VM, par);
            mx = fmaxf(fmaxf(mx, m1), fmaxf(m2, m3));
            const float mo = mx * sl2;
            #pragma unroll
            for (int j = 0; j < 10; j++) sv[j] = ex2(fmaf(sv[j], sl2, -mo));
            const uint32_t e0 = pack_bf16(sv[0], sv[1]), e1 = pack_bf16(sv[2], sv[3]);
            const uint32_t e2 = pack_bf16(sv[4], sv[5]), e3 = pack_bf16(sv[6], sv[7]), em = pack_bf16(sv[8], sv[9]);
            float o[4][4];
            #pragma unroll
            for (int i = 0; i < 4; i++) {
                o[i][0] = o[i][1] = o[i][2] = o[i][3] = 0.f;
                mma_a(o[i], vt[0][i], e0, e1);
            }
            const float sum = (((sv[0] + sv[1]) + (sv[2] + sv[3])) + ((sv[4] + sv[5]) + (sv[6] + sv[7]))) + (sv[8] + sv[9]);
            if (!vm_ok) mbar_wait_bounded(bar + BAR_VM, par);
            uint2 vm[4];
            #pragma unroll
            for (int i = 0; i < 4; i++) {
                vm[i] = lds64(l8 + SM_VM + (warp & 1) * 1024 + i * 256);
                mma_a(o[i], vt[1][i], e2, e3);
            }
            #pragma unroll
            for (int i = 0; i < 4; i++) mma1688(o[i], vm[i].x, vm[i].y, em);
            {
                const float s1 = __shfl_xor_sync(~0u, sum, 1), s2 = __shfl_xor_sync(~0u, sum, 2), s3 = __shfl_xor_sync(~0u, sum, 3);
                sts32(sb + SM_SUM + (lane & 28), __float_as_uint((sum + s1) + (s2 + s3)));
            }
            #pragma unroll
            for (int i = 0; i < 4; i += 2)
                stsm_x4(l16 + SM_O + (warp & 1) * 1024 + i * 256, pack_bf16(o[i][0], o[i][1]), pack_bf16(o[i][2], o[i][3]),
                        pack_bf16(o[i + 1][0], o[i + 1][1]), pack_bf16(o[i + 1][2], o[i + 1][3]));
            STAMP(5);
            uint32_t st[16][4];
            #pragma unroll
            for (int n = 0; n < WO_PF0; n++) ldsm4t(wo_addr<2>(ao, 0, n), st[n]);
            named_bar_sync(6, REC_THREADS);
            wo_phase<2, WO_PF0>([&]() { if ((u_role & 16) && elect_one()) x_load(p, sb, s + 1, rank); }, st, ao, 0, l16, tbl, sb + SM_SUM, slot, xhi, 0, p.one[0] - 1, aq, bar + BAR_XG, par ^ 1, x0_ok);
        } else {
            const uint32_t a3 = fresh(ao) + (wg == 0 ? 10 : 6) * 8192;
            uint32_t st[24][4];
            #pragma unroll
            for (int n = 0; n < WO_PFA; n++) ldsm4t(wo_addr<3>(ao, a3, n), st[n]);
            if (KV_POS == 0) kv_stores();
            if (ST_POS == 0) tile_stores();
            if (RST_POS == 0) resets(1);
            if (warp == 1) {
                if (elect_one()) {
                    #pragma unroll
                    for (int g = 0; g < 4; g++) mbar_arrive_expect_tx(bar + BAR_XG + 8 * g, ((EXP >> g) & 1) ? 0 : 16384);
                }
                if (s + 2 < NSEG && cta < 4 && elect_one())
                    asm volatile("cp.async.bulk.prefetch.tensor.3d.L2.global [%0, {%1, %2, %3}];"
                                 ::"l"(&p.tmX), "r"(0), "r"((s + 2) * SEG), "r"(cta * 4) : "memory");
                if (X0_POS == 0 && rank == 0) {
                    mbar_wait_bounded(bar + BAR_F0, par);
                    if (elect_one()) x_load(p, sb, s + 1, 0);
                }
            }
            if (WO_PFA < WO_PF1 || (u_role & 16)) mbar_wait_bounded(bar + BAR_X, par);
            if (WO_PFA < WO_PF1) {
                spin_clks(WO_PFB_DELAY);
                #pragma unroll
                for (int n = WO_PFA; n < WO_PF1; n++) ldsm4t(wo_addr<3>(ao, a3, n), st[n]);
            }
            if (ST_POS == 1) tile_stores();
            if (RST_POS == 1) resets(1);
            if (KV_POS == 1) kv_stores();
            if (X0_POS == 1 && warp == 1 && rank == 0) {
                mbar_wait_bounded(bar + BAR_F0, par);
                if (elect_one()) x_load(p, sb, s + 1, 0);
            }
            if (XB_POS == 0 && (u_role & 16)) {
                spin_clks(XB_DELAY);
                mbar_wait_bounded(bar + BAR_VM, par);
                if (elect_one()) x_load(p, sb, s + 1, rank);
            }
            named_bar_sync(6, REC_THREADS);
            wo_phase<3, WO_PF1>([]() {}, st, ao, a3, l16, tbl, sb + SM_SUM, slot, xhi, u_role & 4, p.one[0] - 1, aq, bar + BAR_XG, par ^ 1, x0_ok);
        }
        STAMP(7);
        if (wg == 0) named_bar_sync(9, REC_THREADS); else named_bar_arrive(9, REC_THREADS);
    }
    if (threadIdx.x == 128) KMARK(8);
    mbar_wait(bar + BAR_X, 1);
    mbar_wait(bar + BAR_VM, 1);
    if (qk) mbar_wait(bar + BAR_V, 1);
    named_bar_sync(0, REC_THREADS);
    if (warp == 4 && elect_one()) {
        bulk_wait_all();
        signal_flag(p.flags + F_PROGRESS + NSEG - 1);
        KMARK(9);
    }
}

__global__ void __launch_bounds__(REC_THREADS, 1) rec_kernel(const __grid_constant__ RecParams p) {
    extern __shared__ __align__(1024) uint8_t smem_raw[];
    const uint32_t sb = smem_u32(smem_raw);
    const int tid = threadIdx.x, lane = tid & 31;
    const int warp = __shfl_sync(~0u, tid >> 5, 0);
    const int cta = blockIdx.x, head = cta / 3, rank = cta % 3;
    const int wg = warp >> 2, wq = warp & 3;
    const uint32_t bar = sb + SM_BAR;
    uint8_t* const xb = p.xchg;
    const uint32_t xlo = (uint32_t)(uint64_t)xb;
    if ((sb & 0x3FFFF) != SMEM_ORIGIN) __trap();
    KENTER(1);
    auto w_box = [&](int part, int g, int i, uint32_t dst, uint32_t mb) {
        const int m = i ^ g;
        const CUtensorMap* tm = &p.tmW[rank == 2 ? 2 : m];
        const int col = head * DH + (rank == 2 ? m : rank) * 64, row = ((part + 1) & 3) * 16;
        tma_load_3d(dst, tm, col, row, g * 8, mb);
    };
    if (tid == 0) {
        mbar_init(bar + BAR_V, 1);
        for (int i = 0; i < 4; i++) { mbar_init(bar + BAR_XG + 8 * i, 1); mbar_init(bar + BAR_M + 8 * i, 1); }
        mbar_init(bar + BAR_GO, 4);
        mbar_init(bar + BAR_PUB, 3);
        mbar_init(bar + BAR_PK, 4);
        mbar_init(bar + BAR_VM, rank < 2 ? 1 : 9);
        mbar_init(bar + BAR_F0, 3);
        mbar_init(bar + BAR_F3, 3);
        mbar_init(bar + BAR_VF, 3);
        sts64(bar + BAR_MIN, ~0u, ~0u);
        mbar_init(bar + BAR_X, rank < 2 ? 6 : 1);
        for (int i = 0; i < 3; i++) mbar_init(bar + BAR_P0 + 8 * i, 1);
        mbar_init(bar + BAR_WQ, 1);
        mbar_init(bar + BAR_WO, 1);
        sts32(bar + BAR_SELF, bar + BAR_SELF);
        asm volatile("fence.mbarrier_init.release.cluster;" ::: "memory");
    }
    auto build_tables = [&](uint32_t av) {
        for (uint32_t n = 0; !__all_sync(~0u, (av >> 24) == 24); n++) {
            av = ld_acquire_b32(p.arrivals + (lane & 3));
            if (n > SPIN_LIMIT) __trap();
        }
        uint32_t cm[3];
        #pragma unroll
        for (int i = 0; i < 3; i++) {
            const int o = i * 32 + lane;
            cm[i] = __ballot_sync(~0u, __popc((__shfl_sync(~0u, av, o / 24) >> (o % 24 / 3 * 3)) & 7) >= 2);
        }
        auto color_of = [&](int o) { return ((o < 32 ? cm[0] : o < 64 ? cm[1] : cm[2]) >> (o & 31)) & 1u; };
        auto inbox = [&](int o, int byte) {
            uint32_t c = color_of(o);
            int ones = 0;
            #pragma unroll
            for (int i = 0; i < 3; i++) ones += __popc(o >= i * 32 + 32 ? cm[i] : (o > i * 32 ? cm[i] & ((1u << (o - i * 32)) - 1) : 0u));
            int idx = c ? ones : o - ones;
            if (idx >= INBOX_MAX) { idx = 2 * INBOX_MAX - 1 - idx; c ^= 1; }
            const uint32_t lin = idx * 6144 + byte, q = XCHG_INBOX + (lin >> 12) * 8192;
            return q + class_off(xlo + q, c) + (lin & 4095);
        };
        uint32_t off = 0;
        const int grp = (warp + 3) & 3;
        if (lane < 12) {
            const int i = lane >> 2, lt0 = rank * 6;
            const int o = i < 2 ? rank * 32 + warp * 4 + (lane & 3) : (lt0 + ((warp + 4) & 7)) * 4 + (lane & 3);
            off = inbox(min(o, 95), i * 2048 + head * 64);
        } else if (lane == 12) {
            off = inbox(cta, (grp % 3) * 2048);
        } else if (lane == 13) {
            int T;
            if (grp < 2) {
                T = (cta >> 5) * 22 + 8 * grp + ((cta & 31) >> 2);
            } else {
                const int tl = (cta & 63) >> 2;
                T = (tl / 6) * 22 + 16 + tl % 6;
            }
            off = XCHG_PUB + (T >> 4) * 8192 + (T & 15) * 256 + (cta & 3) * 32;
        } else if (lane == 14) {
            const uint32_t q = XCHG_PUB + wq * 8192;
            off = q + class_off(xlo + q, color_of(cta));
        }
        if (lane < 16) asm volatile("st.shared.b32 [%0], %1;" ::"r"(sb + SM_TBL + warp * 64 + (lane & 3) * 16 + (lane >> 2) * 4), "r"(xlo + off) : "memory");
    };
    if (tid >= 32 && tid < 37) asm volatile("prefetch.tensormap [%0];" ::"l"(&p.tmW[0] + (tid - 32)) : "memory");
    if (cta == 0 && tid < F_COUNT) p.flags[tid] = 0;
    __syncthreads();
    auto stage = [](int part) { return ((part + 2) % 3) * 65536; };
    auto load_part = [&](int part) {
        mbar_arrive_expect_tx(bar + BAR_P0 + 8 * part, 65536);
        for (int u = 0; u < 4; u++) w_box(part, u >> 1, u & 1, sb + stage(part) + u * 16384, bar + BAR_P0 + 8 * part);
    };
    asm volatile("barrier.cluster.arrive.relaxed.aligned;" ::: "memory");
    uint4 img = make_uint4(SENT, SENT, SENT, SENT);
    if (cta >= 92) {
        const unsigned short* m = reinterpret_cast<const unsigned short*>(p.mem0) + (cta - 92) * 256 + tid;
        uint32_t w[4];
        #pragma unroll
        for (int i = 0; i < 4; i++) w[i] = (uint32_t)__ldg(m + 2 * i * DM) | ((uint32_t)__ldg(m + (2 * i + 1) * DM) << 16);
        img = make_uint4(w[0], w[1], w[2], w[3]);
    }
    {
        constexpr int NPAIR = (XCHG_SLOT + PUB_BYTES) / 8192;
        uint8_t* pr = xb + (4 + cta) * 8192;
        const uint32_t c0 = class_off(xlo + (4 + cta) * 8192, 0);
        #pragma unroll
        for (int c = 0; c < 2; c++) {
            const bool timed = lane == 0 || (lane == 8 && c == (warp & 1));
            reinterpret_cast<uint4*>(pr + (c0 ^ (c << 12)))[tid] = make_uint4(timed ? 0u : SENT, SENT, SENT, SENT);
        }
        __syncwarp();
        if (lane == 0) {
            uint32_t x = 0;
            for (int k = 0; k < 3; k++) {
                if (k == PRO_EARLY && warp == 0) load_part(0);
                const uint32_t c = (k + warp) & 1, t0 = clock_after(x);
                x = atomicExch(reinterpret_cast<uint32_t*>(pr + (c0 ^ (c << 12)) + warp * 512 + (k >> 1) * 128 + x), SENT);
                const uint32_t lat = clock_after(x) - t0;
                asm volatile("red.shared.min.u32 [%0], %1;" ::"r"(bar + BAR_MIN + 4 * c), "r"(lat) : "memory");
            }
        }
        __syncwarp();
        if (cta >= 92 || 100 + cta < NPAIR) {
            if (cta >= 92) {
                if (img.x == SENT) img.x = 0x7FFF7FFFu;
                if (img.y == SENT) img.y = 0x7FFF7FFFu;
                if (img.z == SENT) img.z = 0x7FFF7FFFu;
                if (img.w == SENT) img.w = 0x7FFF7FFFu;
            }
            uint8_t* q = xb + (cta >= 92 ? cta - 92 : 100 + cta) * 8192;
            reinterpret_cast<uint4*>(q)[tid] = img;
            reinterpret_cast<uint4*>(q + 4096)[tid] = img;
        }
    }
    __syncthreads();
    PSTAMP(4);
    if (tid == 0) {
        for (int part = PRO_EARLY < 3 ? 1 : 0; part < 3; part++) load_part(part);
    }
    if (tid == 224) {
        const uint32_t c = lds32_volatile(bar + BAR_MIN) > lds32_volatile(bar + BAR_MIN + 4) ? 1 : 0;
        asm volatile("red.release.gpu.global.add.u32 [%0], %1;" ::"l"(p.arrivals + cta / 24), "r"((1u << 24) | (c << (cta % 24))) : "memory");
        if (PDL_POS == 0) pdl_launch_dependents();
    }
    uint32_t wr[NREG][2][4];
    uint32_t arrived = 0;
    {
        const int mi = lane >> 3, r8 = lane & 7;
        const uint32_t a0 = sb + wg * 32768 + ((mi >> 1) * 8 + r8) * 128 + (((wq * 2 + (mi & 1)) ^ r8) << 4);
        #pragma unroll
        for (int part = 0; part < 3; part++) {
            mbar_wait_bounded(bar + BAR_P0 + 8 * part, 0);
            if (part == 0) arrived = ld_relaxed_b32(p.arrivals + (lane & 3));
            #pragma unroll
            for (int j = 0; j < 8; j++) {
                #pragma unroll
                for (int i = 0; i < 2; i++) ldsm4t(a0 + stage(part) + i * 16384 + j * 2048, wr[part * 8 + j][i]);
            }
            asm volatile("fence.proxy.async.shared::cta;" ::: "memory");
            __syncthreads();
            PSTAMP(5 + part);
            if (tid == 224 && PDL_POS == part + 1) pdl_launch_dependents();
            if (tid == 0) {
                if (part == 0) {
                    for (int g = 0; g < 4; g++) {
                        mbar_arrive_expect_tx(bar + BAR_XG + 8 * g, 16384);
                        tma_load_3d(sb + SM_X + g * 16384, &p.tmX, 0, 0, g * 4, bar + BAR_XG + 8 * g);
                    }
                } else if (part == 1) {
                    mbar_arrive_expect_tx(bar + BAR_WQ, 65536);
                    for (int u = 0; u < 4; u++) w_box(3, u >> 1, u & 1, sb + SM_WQ + u * 16384, bar + BAR_WQ);
                } else {
                    mbar_arrive_expect_tx(bar + BAR_WO, 11 * 8192);
                    tma_load_3d(sb + SM_WO, &p.tmWo, 0, head * DH, rank * 11, bar + BAR_WO);
                    if (cta < 4)
                        asm volatile("cp.async.bulk.prefetch.tensor.3d.L2.global [%0, {%1, %2, %3}];"
                                     ::"l"(&p.tmX), "r"(0), "r"(SEG), "r"(cta * 4) : "memory");
                }
            }
        }
    }
    build_tables(arrived);
    __syncwarp();
    PSTAMP(9);
    mbar_wait(bar + BAR_WQ, 0);
    if (PDL_POS == 4) pdl_launch_dependents();
    asm volatile("barrier.cluster.wait.aligned;" ::: "memory");

    rec_steps(p, wr, sb, warp, cta, head, rank);
    if (cta == 0 && tid < 4) p.arrivals[tid] = 0;
    cluster_sync();
    if (tid == 0) KEXIT(1);
}

constexpr int ATT_SLOT = 28672;
constexpr int ATT_PAIRS = 8;
constexpr int ATT_BAR = ATT_PAIRS * ATT_SLOT;
constexpr int ATT_CNT = ATT_BAR + ATT_PAIRS * 16;
constexpr int ATT_SMEM = ATT_CNT + 96 * 4;
constexpr int ATT_THREADS = ATT_PAIRS * 64 + 32;
static_assert(F_OA == F_OB + 16, "one range of flags");
struct AttnParams {
    CUtensorMap tmOa;
    CUtensorMap tmQb, tmKb;
    CUtensorMap tmOb;
    const __nv_bfloat16* qkv_tok;
    const __nv_bfloat16* kv_mem;
    uint32_t* flags;
};

__device__ __forceinline__ void tok_attn_warp(uint32_t base, int mh, int lane) {
    const uint32_t sq = base, sk = base + 8192, sv = base + 16384, skm = base + 24576, svm = skm + 2048;
    const int g = lane >> 2, c = lane & 3, mi = lane >> 3, r8 = lane & 7;
    const int ntile = mh ? 5 : 3;
    float sc[5][4];
    #pragma unroll
    for (int j = 0; j < 5; j++) { sc[j][0] = sc[j][1] = sc[j][2] = sc[j][3] = 0.f; }
    #pragma unroll
    for (int t2 = 0; t2 < 4; t2++) {
        uint32_t a[2][4];
        #pragma unroll
        for (int h = 0; h < 2; h++) {
            const int row = mh * 16 + (mi & 1) * 8 + r8, ch16 = 4 * t2 + 2 * h + (mi >> 1);
            ldsm_x4(sq + (ch16 >> 3) * 4096 + row * 128 + (((ch16 & 7) ^ r8) << 4), a[h][0], a[h][1], a[h][2], a[h][3]);
        }
        const int ch16 = 4 * t2 + mi;
        uint32_t b[5][4];
        #pragma unroll
        for (int j = 0; j < 5; j++) {
            if (j < ntile) {
                if (j == 0) ldsm_x4_t(skm + t2 * 512 + lane * 16, b[j][0], b[j][1], b[j][2], b[j][3]);
                else ldsm_x4(sk + (ch16 >> 3) * 4096 + ((j - 1) * 8 + r8) * 128 + (((ch16 & 7) ^ r8) << 4), b[j][0], b[j][1], b[j][2], b[j][3]);
            }
        }
        #pragma unroll
        for (int h = 0; h < 2; h++) {
            #pragma unroll
            for (int j = 0; j < 5; j++)
                if (j < ntile) mma16816(sc[j], a[h][0], a[h][1], a[h][2], a[h][3], b[j][2 * h], b[j][2 * h + 1]);
        }
    }
    const float sl2 = 0.08838834764831845f * 1.4426950408889634f;
    uint32_t pf[2][5];
    float inv[2];
    #pragma unroll
    for (int q = 0; q < 2; q++) {
        const int tok = mh * 16 + q * 8 + g;
        float v[10];
        #pragma unroll
        for (int j = 0; j < 5; j++) {
            #pragma unroll
            for (int e = 0; e < 2; e++) {
                const int key = (j - 1) * 8 + 2 * c + e;
                v[2 * j + e] = (j == 0 || key <= tok) ? sc[j][2 * q + e] : -INFINITY;
            }
        }
        float mx = v[0];
        #pragma unroll
        for (int j = 1; j < 10; j++) mx = fmaxf(mx, v[j]);
        mx = fmaxf(mx, __shfl_xor_sync(~0u, mx, 1));
        mx = fmaxf(mx, __shfl_xor_sync(~0u, mx, 2));
        const float mo = mx * sl2;
        float sum = 0.f;
        #pragma unroll
        for (int j = 0; j < 10; j++) { v[j] = ex2(fmaf(v[j], sl2, -mo)); sum += v[j]; }
        sum += __shfl_xor_sync(~0u, sum, 1);
        sum += __shfl_xor_sync(~0u, sum, 2);
        inv[q] = rcp(sum);
        #pragma unroll
        for (int j = 0; j < 5; j++) pf[q][j] = pack_bf16(v[2 * j], v[2 * j + 1]);
    }
    auto load_v = [&](int n4, uint32_t (&vm)[4], uint32_t (&vt)[4][4]) {
        ldsm_x4(svm + n4 * 512 + lane * 16, vm[0], vm[1], vm[2], vm[3]);
        #pragma unroll
        for (int u = 0; u < 4; u++) {
            const int dt = 2 * n4 + (u >> 1), kh = u & 1;
            const uint4 v = lds128(sv + (dt & 3) * 2048 + (dt >> 2) * 1024 + kh * 512 + lane * 16);
            vt[u & 2][2 * kh] = v.x; vt[u & 2][2 * kh + 1] = v.z;
            vt[(u & 2) + 1][2 * kh] = v.y; vt[(u & 2) + 1][2 * kh + 1] = v.w;
        }
    };
    uint32_t vm[2][4], vt[2][4][4];
    load_v(0, vm[0], vt[0]);
    #pragma unroll
    for (int n4 = 0; n4 < 4; n4++) {
        const int cur = n4 & 1;
        if (n4 + 1 < 4) load_v(n4 + 1, vm[cur ^ 1], vt[cur ^ 1]);
        float o[4][4];
        #pragma unroll
        for (int u = 0; u < 4; u++) {
            o[u][0] = o[u][1] = o[u][2] = o[u][3] = 0.f;
            mma16816(o[u], pf[0][1], pf[1][1], pf[0][2], pf[1][2], vt[cur][u][0], vt[cur][u][1]);
        }
        if (mh) {
            #pragma unroll
            for (int u = 0; u < 4; u++) mma16816(o[u], pf[0][3], pf[1][3], pf[0][4], pf[1][4], vt[cur][u][2], vt[cur][u][3]);
        }
        #pragma unroll
        for (int u = 0; u < 4; u++) mma1688(o[u], pf[0][0], pf[1][0], vm[cur][u]);
        #pragma unroll
        for (int u = 0; u < 4; u += 2) {
            const int row = mh * 16 + (mi & 1) * 8 + r8, nt = 4 * n4 + u + (mi >> 1);
            stsm_x4(sq + (nt >> 3) * 4096 + row * 128 + (((nt & 7) ^ r8) << 4),
                    pack_bf16(o[u][0] * inv[0], o[u][1] * inv[0]), pack_bf16(o[u][2] * inv[1], o[u][3] * inv[1]),
                    pack_bf16(o[u + 1][0] * inv[0], o[u + 1][1] * inv[0]), pack_bf16(o[u + 1][2] * inv[1], o[u + 1][3] * inv[1]));
        }
    }
}

__device__ __forceinline__ void b_attn_warp(uint32_t base, int hl, int idx0, int lane) {
    const uint32_t sq = base, sk = base + 8192, sv = base + 8192 + 9216;
    const int g = lane >> 2, c = lane & 3;
    auto addr = [&](uint32_t t, int row, int ch) { return t + row * 128 + ((ch ^ (row & 7)) << 4); };
    const float sl2 = 0.17677669529663687f * 1.4426950408889634f;
    #pragma unroll 2
    for (int blk = 0; blk < 4; blk++) {
        const int r0 = blk * 16;
        float sc[3][4];
        #pragma unroll
        for (int j = 0; j < 3; j++) { sc[j][0] = sc[j][1] = sc[j][2] = sc[j][3] = 0.f; }
        #pragma unroll
        for (int t = 0; t < 2; t++) {
            uint32_t a0, a1, a2, a3, b0, b1, b2, b3, d0, d1, d2, d3;
            const int mi = lane >> 3, r = lane & 7;
            ldsm_x4(addr(sq, r0 + (mi & 1) * 8 + r, hl * 4 + 2 * t + (mi >> 1)), a0, a1, a2, a3);
            ldsm_x4(addr(sk, r0 + (mi >> 1) * 8 + r, hl * 4 + 2 * t + (mi & 1)), b0, b1, b2, b3);
            ldsm_x4(addr(sk, r0 + 16 + r, hl * 4 + 2 * t + (mi & 1)), d0, d1, d2, d3);
            mma16816(sc[0], a0, a1, a2, a3, b0, b1);
            mma16816(sc[1], a0, a1, a2, a3, b2, b3);
            mma16816(sc[2], a0, a1, a2, a3, d0, d1);
        }
        uint32_t pf[2][3];
        float inv[2];
        #pragma unroll
        for (int r = 0; r < 2; r++) {
            const int u = r * 8 + g;
            float v[6];
            #pragma unroll
            for (int j = 0; j < 3; j++) {
                #pragma unroll
                for (int e = 0; e < 2; e++) {
                    const int key = j * 8 + 2 * c + e;
                    const bool ok = key > u && key <= u + 8 && idx0 + r0 - 8 + key >= 0;
                    v[2 * j + e] = ok ? sc[j][2 * r + e] : -INFINITY;
                }
            }
            float mx = fmaxf(fmaxf(fmaxf(v[0], v[1]), fmaxf(v[2], v[3])), fmaxf(v[4], v[5]));
            mx = fmaxf(mx, __shfl_xor_sync(~0u, mx, 1));
            mx = fmaxf(mx, __shfl_xor_sync(~0u, mx, 2));
            const float mo = mx * sl2;
            float sum = 0.f;
            #pragma unroll
            for (int j = 0; j < 6; j++) { v[j] = ex2(fmaf(v[j], sl2, -mo)); sum += v[j]; }
            sum += __shfl_xor_sync(~0u, sum, 1);
            sum += __shfl_xor_sync(~0u, sum, 2);
            inv[r] = rcp(sum);
            #pragma unroll
            for (int j = 0; j < 3; j++) pf[r][j] = pack_bf16(v[2 * j], v[2 * j + 1]);
        }
        uint32_t ow[4][2];
        {
            const int mi = lane >> 3, r = lane & 7;
            uint32_t vv[4][4];
            #pragma unroll
            for (int nt = 0; nt < 4; nt++)
                ldsm_x4_t(addr(sv, r0 + min(mi, 2) * 8 + r, hl * 4 + nt), vv[nt][0], vv[nt][1], vv[nt][2], vv[nt][3]);
            float o[4][4];
            #pragma unroll
            for (int nt = 0; nt < 4; nt++) {
                o[nt][0] = o[nt][1] = o[nt][2] = o[nt][3] = 0.f;
                mma16816(o[nt], pf[0][0], pf[1][0], pf[0][1], pf[1][1], vv[nt][0], vv[nt][1]);
            }
            #pragma unroll
            for (int nt = 0; nt < 4; nt++) mma1688(o[nt], pf[0][2], pf[1][2], vv[nt][2]);
            #pragma unroll
            for (int nt = 0; nt < 4; nt++) {
                ow[nt][0] = pack_bf16(o[nt][0] * inv[0], o[nt][1] * inv[0]);
                ow[nt][1] = pack_bf16(o[nt][2] * inv[1], o[nt][3] * inv[1]);
            }
        }
        #pragma unroll
        for (int u = 0; u < 4; u += 2) {
            const int mi = lane >> 3, r = lane & 7;
            stsm_x4(addr(sq, r0 + (mi & 1) * 8 + r, hl * 4 + u + (mi >> 1)), ow[u][0], ow[u][1], ow[u + 1][0], ow[u + 1][1]);
        }
    }
}

constexpr uint32_t QKVB_TARGET = 12 * 8;
constexpr uint32_t PROGRESS_TARGET = 96;
constexpr uint32_t OA_TARGET = 64, OB_TARGET = 32;
#define ATT_B0 6
constexpr int ATT_TASKS = (NSEG + 16) * 32;
__device__ __forceinline__ int att_group(int g, bool& isb) {
    const int q = g - ATT_B0;
    isb = q >= 0 && q < 48 && q % 3 == 0;
    return q < 0 ? g : q >= 48 ? g - 16 : isb ? q / 3 : ATT_B0 + (q / 3) * 2 + q % 3 - 1;
}

__global__ void __launch_bounds__(ATT_THREADS, 1) attn_kernel(const __grid_constant__ AttnParams p) {
    extern __shared__ __align__(1024) uint8_t smem_raw[];
    const int tid = threadIdx.x, lane = tid & 31, warp = __shfl_sync(~0u, tid >> 5, 0);
    const int pair = warp >> 1, wi = warp & 1;
    const uint32_t base = smem_u32(smem_raw) + pair * ATT_SLOT, bar = smem_u32(smem_raw) + ATT_BAR + pair * 16, taskw = bar + 8;
    const bool leader = wi == 0 && lane == 0;
    if (tid == 0) pdl_launch_dependents();
    KENTER(3);
    const uint32_t cnt = smem_u32(smem_raw) + ATT_CNT;
    if (tid < 96) sts32(cnt + tid * 4, 0);
    __syncthreads();
    if (warp == 2 * ATT_PAIRS) {
        for (uint32_t n = 0; n < SPIN_LIMIT; n++) {
            const bool last = lds32_volatile(cnt + 320) == 2 * ATT_PAIRS;
            uint32_t v[3];
            #pragma unroll
            for (int i = 0; i < 3; i++) {
                v[i] = 0;
                if (i * 32 + lane < 80 && lds32_volatile(cnt + (i * 32 + lane) * 4) != 0)
                    asm volatile("atom.acquire.cta.shared.exch.b32 %0, [%1], 0;" : "=r"(v[i]) : "r"(cnt + (i * 32 + lane) * 4) : "memory");
            }
            if (v[0] | v[1] | v[2]) {
                asm volatile("fence.acq_rel.gpu;" ::: "memory");
                #pragma unroll
                for (int i = 0; i < 3; i++)
                    if (v[i]) asm volatile("red.relaxed.gpu.global.add.u32 [%0], %1;" ::"l"(p.flags + F_OB + i * 32 + lane), "r"(v[i]) : "memory");
                if (v[2] && lane == 15) KMARK(14);
            }
            __syncwarp();
            if (last) break;
            __nanosleep(40);
        }
        if (lane == 0) KEXIT(3);
        return;
    }
    uint32_t next = 0, phase = 0;
    if (leader) {
        mbar_init(bar, 1);
        asm volatile("fence.mbarrier_init.release.cluster;" ::: "memory");
        next = atomicAdd(p.flags + F_QUEUE3, 1u);
    }
    uint32_t pending = 0;
    auto flush = [&]() {
        if (pending) {
            bulk_wait_all();
            if (pending == cnt + 79 * 4) KMARK(13);
            asm volatile("red.release.cta.shared.add.u32 [%0], 1;" ::"r"(pending) : "memory");
            pending = 0;
        }
    };
    int ready_a = -1, ready_b = -1;
    while (true) {
        named_bar_sync(1 + pair, 64);
        if (leader) {
            const uint32_t task = next;
            sts32(taskw, task);
            if (task >= ATT_TASKS) {
                mbar_arrive(bar);
            } else {
                bool isb;
                const int grp = att_group(task >> 5, isb), i = task & 31;
                auto need = [&](const uint32_t* f, uint32_t target) {
                    if (ld_acquire_b32(f) < target) { flush(); wait_flag(f, target); }
                };
                if (isb) {
                    if (grp > ready_b) {
                        need(p.flags + F_QKVB + grp, QKVB_TARGET);
                        if (grp > 0) need(p.flags + F_QKVB + grp - 1, QKVB_TARGET);
                        asm volatile("fence.proxy.async.global;" ::: "memory");
                        ready_b = grp;
                    }
                    mbar_arrive_expect_tx(bar, 8192 + 2 * 9216);
                    tma_load_3d(base, &p.tmQb, (i >> 1) * 64, i & 1, grp * 64, bar);
                    tma_load_3d(base + 8192, &p.tmKb, DM + (i >> 1) * 64, i & 1, grp * 64 - 8, bar);
                    tma_load_3d(base + 8192 + 9216, &p.tmKb, 2 * DM + (i >> 1) * 64, i & 1, grp * 64 - 8, bar);
                } else {
                    if (grp > ready_a) {
                        need(p.flags + F_PROGRESS + grp, PROGRESS_TARGET);
                        asm volatile("fence.proxy.async.global;" ::: "memory");
                        ready_a = grp;
                    }
                    if (grp == 63) KMARK(10);
                    mbar_arrive_expect_tx(bar, ATT_SLOT);
                    #pragma unroll
                    for (int w = 0; w < 3; w++)
                        bulk_load(base + w * 8192, p.qkv_tok + (((size_t)w * NSEG + grp) * NH + i) * (SEG * DH), 8192, bar);
                    #pragma unroll
                    for (int w = 0; w < 2; w++)
                        bulk_load(base + 24576 + w * 2048, p.kv_mem + (((size_t)w * NSEG + grp) * NH + i) * (MROWS * DH), 2048, bar);
                }
                next = atomicAdd(p.flags + F_QUEUE3, 1u);
            }
        }
        if (lane == 0) flush();
        __syncwarp();
        mbar_wait_sleep(bar, phase);
        phase ^= 1;
        const uint32_t task = lds32_volatile(taskw);
        if (task >= ATT_TASKS) break;
        bool isb;
        const int grp = att_group(task >> 5, isb), i = task & 31;
        if (isb) {
            b_attn_warp(base, wi, grp * 64, lane);
            asm volatile("fence.proxy.async.shared::cta;" ::: "memory");
            named_bar_sync(1 + pair, 64);
            if (wi == 1 && lane == 0) {
                asm volatile("cp.async.bulk.tensor.3d.global.shared::cta.bulk_group [%0, {%2, %3, %4}], [%1];"
                             ::"l"(&p.tmOb), "r"(base), "r"((i >> 1) * 64), "r"(i & 1), "r"(grp * 64) : "memory");
                pending = cnt + grp * 4;
            }
        } else {
            if (grp == 63 && lane == 0) KMARK(11);
            tok_attn_warp(base, wi, lane);
            if (grp == 63 && lane == 0) KMARK(12);
            asm volatile("fence.proxy.async.shared::cta;" ::: "memory");
            __syncwarp();
            if (lane == 0) {
                #pragma unroll
                for (int h = 0; h < 2; h++) tma_store_2d(&p.tmOa, base + h * 4096 + wi * 2048, i * DH + h * 64, grp * SEG + wi * 16);
                pending = cnt + (16 + grp) * 4;
            }
        }
        if (lane == 0) { bulk_commit(); bulk_wait_read_all(); }
        __syncwarp();
    }
    if (lane == 0) asm volatile("red.release.cta.shared.add.u32 [%0], 1;" ::"r"(cnt + 320) : "memory");
}

typedef CUresult (*EncodeFn)(CUtensorMap*, CUtensorMapDataType, cuuint32_t, void*, const cuuint64_t*, const cuuint64_t*,
                             const cuuint32_t*, const cuuint32_t*, CUtensorMapInterleave, CUtensorMapSwizzle,
                             CUtensorMapL2promotion, CUtensorMapFloatOOBfill);

void make_map_2d(EncodeFn enc, CUtensorMap* m, const void* ptr, uint64_t rows, uint64_t cols, uint32_t box_rows) {
    cuuint64_t dims[2] = {cols, rows};
    cuuint64_t strides[1] = {cols * 2};
    cuuint32_t box[2] = {64, box_rows};
    cuuint32_t es[2] = {1, 1};
    enc(m, CU_TENSOR_MAP_DATA_TYPE_BFLOAT16, 2, const_cast<void*>(ptr), dims, strides, box, es,
        CU_TENSOR_MAP_INTERLEAVE_NONE, CU_TENSOR_MAP_SWIZZLE_128B, CU_TENSOR_MAP_L2_PROMOTION_L2_256B,
        CU_TENSOR_MAP_FLOAT_OOB_FILL_NONE);
}
void make_map_b(EncodeFn enc, CUtensorMap* m, const void* ptr, uint64_t k, uint64_t n, uint32_t nblk, uint32_t box_rows = 64,
                uint32_t bc = 64) {
    cuuint64_t dims[3] = {bc, k, n / bc};
    cuuint64_t strides[2] = {n * 2, bc * 2};
    cuuint32_t box[3] = {bc, box_rows, nblk};
    cuuint32_t es[3] = {1, 1, 1};
    enc(m, CU_TENSOR_MAP_DATA_TYPE_BFLOAT16, 3, const_cast<void*>(ptr), dims, strides, box, es,
        CU_TENSOR_MAP_INTERLEAVE_NONE, bc == 64 ? CU_TENSOR_MAP_SWIZZLE_128B : CU_TENSOR_MAP_SWIZZLE_64B, CU_TENSOR_MAP_L2_PROMOTION_L2_256B,
        CU_TENSOR_MAP_FLOAT_OOB_FILL_NONE);
}

void make_map_parity(EncodeFn enc, CUtensorMap* m, const void* ptr, uint64_t cols, uint32_t box_rows) {
    cuuint64_t dims[3] = {cols, 2, S_TOK / 2};
    cuuint64_t strides[2] = {cols * 2, cols * 4};
    cuuint32_t box[3] = {64, 1, box_rows};
    cuuint32_t es[3] = {1, 1, 1};
    enc(m, CU_TENSOR_MAP_DATA_TYPE_BFLOAT16, 3, const_cast<void*>(ptr), dims, strides, box, es,
        CU_TENSOR_MAP_INTERLEAVE_NONE, CU_TENSOR_MAP_SWIZZLE_128B, CU_TENSOR_MAP_L2_PROMOTION_L2_128B,
        CU_TENSOR_MAP_FLOAT_OOB_FILL_NONE);
}
void make_map_w(EncodeFn enc, CUtensorMap* m, const void* ptr) {
    cuuint64_t dims[3] = {HD, 64, DM / 64};
    cuuint64_t strides[2] = {HD * 2, 64 * HD * 2};
    cuuint32_t box[3] = {64, 16, 8};
    cuuint32_t es[3] = {1, 1, 1};
    enc(m, CU_TENSOR_MAP_DATA_TYPE_BFLOAT16, 3, const_cast<void*>(ptr), dims, strides, box, es,
        CU_TENSOR_MAP_INTERLEAVE_NONE, CU_TENSOR_MAP_SWIZZLE_128B, CU_TENSOR_MAP_L2_PROMOTION_L2_256B,
        CU_TENSOR_MAP_FLOAT_OOB_FILL_NONE);
}

#define OUTB_SIDE_BLOCKS 16
#define SIDE_ORDER 0
#define N_POST_ATT 0
#define SERIAL_ATT_CTAS h.n_sm
#define N_TAIL_CTAS 24
#define N_SIDE_CTAS 29
#define N_ATT_CTAS 7
#define TAIL_BLOCK0 12

struct HostState {
    bool ready;
    bool overlap;
    int n_side, n_att, n_sm;
    SideParams seq_a, seq_b;
    const void* key[11];
    RecParams rec;
    SideParams side, tail, outb;
    FinalParams fin;
    AttnParams attn;
    __nv_bfloat16 *qkv_tok, *kv_mem, *o_tok, *qkv_b, *o_b;
    uint8_t* xchg;
};
HostState g_host;

void setup(void* const* d_in, void* d_out) {
    HostState& h = g_host;
    void* fn = nullptr;
    cudaDriverEntryPointQueryResult qr;
    cudaGetDriverEntryPoint("cuTensorMapEncodeTiled", &fn, cudaEnableDefault, &qr);
    EncodeFn enc = reinterpret_cast<EncodeFn>(fn);
    void* ptr;
    cudaGetSymbolAddress(&ptr, g_qkv_tok); h.qkv_tok = (__nv_bfloat16*)ptr;
    cudaGetSymbolAddress(&ptr, g_kv_mem);  h.kv_mem = (__nv_bfloat16*)ptr;
    cudaGetSymbolAddress(&ptr, g_o_tok);   h.o_tok = (__nv_bfloat16*)ptr;
    cudaGetSymbolAddress(&ptr, g_qkv_b);   h.qkv_b = (__nv_bfloat16*)ptr;
    cudaGetSymbolAddress(&ptr, g_o_b);     h.o_b = (__nv_bfloat16*)ptr;
    cudaGetSymbolAddress(&ptr, g_xchg);    h.xchg = (uint8_t*)(((uint64_t)ptr + XCHG_BYTES - 1) & ~(uint64_t)(XCHG_BYTES - 1));
    cudaGetSymbolAddress(&ptr, g_flags);   uint32_t* flags = (uint32_t*)ptr;
    cudaGetSymbolAddress(&ptr, g_arrivals); uint32_t* arrivals = (uint32_t*)ptr;

    const void *xa = d_in[0], *mem0 = d_in[1], *wq = d_in[2], *wk = d_in[3], *wv = d_in[4], *wo = d_in[5];
    const void *xb = d_in[7], *wqkv = d_in[8], *wob = d_in[9];

    RecParams& r = h.rec;
    make_map_w(enc, &r.tmW[0], wq);
    make_map_w(enc, &r.tmW[1], wk);
    make_map_w(enc, &r.tmW[2], wv);
    make_map_b(enc, &r.tmWo, wo, HD, DM, 11, 128, 32);
    r.mem0 = (const __nv_bfloat16*)mem0;
    r.qkv_tok = h.qkv_tok; r.kv_mem = h.kv_mem; r.xchg = h.xchg;
    r.flags = flags; r.arrivals = arrivals; r.one[0] = r.one[1] = 1;
    make_map_b(enc, &r.tmX, xa, S_TOK, DM, 4, SEG);

    SideParams& sd = h.side;
    SideProb& p0 = sd.prob[0];
    make_map_2d(enc, &p0.tmA, xb, S_TOK, DM, BM);
    make_map_b(enc, &p0.tmB, wqkv, DM, 3 * DM, 4);
    make_map_2d(enc, &p0.tmC, h.qkv_b, S_TOK, 3 * DM, 16);
    p0.n_tiles = 3 * DM / 256; p0.k_blocks = DM / BK; p0.c_col0 = 0; p0.dep = nullptr; p0.dep_target = 0; p0.dep_n = 1; p0.sig = flags + F_QKVB;
    SideProb& p1 = sd.prob[1];
    make_map_2d(enc, &p1.tmA, h.o_tok, S_TOK, HD, BM);
    make_map_b(enc, &p1.tmB, wo, HD, DM, 4);
    make_map_2d(enc, &p1.tmC, d_out, S_TOK, 2 * DM, 16);
    p1.n_tiles = DM / 256; p1.k_blocks = HD / BK; p1.c_col0 = 0; p1.dep = flags + F_OA; p1.dep_target = OA_TARGET; p1.dep_n = 4; p1.sig = nullptr;
    SideProb& p2 = sd.prob[2];
    make_map_2d(enc, &p2.tmA, h.o_b, S_TOK, DM, BM);
    make_map_b(enc, &p2.tmB, wob, DM, DM, 4);
    p2.tmC = p1.tmC;
    p2.n_tiles = DM / 256; p2.k_blocks = DM / BK; p2.c_col0 = DM; p2.dep = flags + F_OB; p2.dep_target = OB_TARGET; p2.dep_n = 1; p2.sig = nullptr;
    p0.n_split = p1.n_split = p2.n_split = 1 << 20;
    p0.part = p1.part = p2.part = nullptr;
    if (SIDE_ORDER == 0) { sd.seg[0] = {0, 0, 16}; sd.seg[1] = {1, 0, TAIL_BLOCK0}; }
    else { sd.seg[0] = {1, 0, TAIL_BLOCK0}; sd.seg[1] = {0, 0, 16}; }
    sd.seg[2] = {2, 0, OUTB_SIDE_BLOCKS};
    sd.nseg = 3; sd.queue = flags + F_SIDEQ;
    h.outb = sd;
    h.outb.seg[0] = {2, OUTB_SIDE_BLOCKS, 16};
    h.outb.nseg = 1; h.outb.queue = flags + F_OUTBQ;

    SideParams& tl = h.tail;
    tl.prob[0] = p1;
    make_map_b(enc, &tl.prob[0].tmB, wo, HD, DM, 2);
    tl.prob[0].n_tiles = 2 * DM / 128; tl.prob[0].n_split = DM / 128; tl.prob[0].k_blocks = HD / BK / 2;
    cudaGetSymbolAddress(&ptr, g_part);
    tl.prob[0].part = (float*)ptr; tl.prob[0].part_flag = flags + F_PART;
    tl.prob[1] = tl.prob[2] = tl.prob[0];
    tl.seg[0] = {0, TAIL_BLOCK0, 15};
    tl.nseg = 1; tl.queue = flags + F_TAILQ;

    make_map_2d(enc, &h.fin.tmA, h.o_tok, S_TOK, HD, SEG);
    h.fin.tmB = tl.prob[0].tmB; h.fin.out = (__nv_bfloat16*)d_out;
    h.fin.dep = flags + F_OA + 60; h.fin.dep_target = OA_TARGET; h.fin.mt = 15;

    make_map_2d(enc, &h.attn.tmOa, h.o_tok, S_TOK, HD, 16);
    make_map_parity(enc, &h.attn.tmQb, h.qkv_b, 3 * DM, 64);
    make_map_parity(enc, &h.attn.tmKb, h.qkv_b, 3 * DM, 72);
    make_map_parity(enc, &h.attn.tmOb, h.o_b, DM, 64);
    h.attn.qkv_tok = h.qkv_tok; h.attn.kv_mem = h.kv_mem; h.attn.flags = flags;

    int dev = 0, nsm = 0;
    cudaGetDevice(&dev);
    cudaDeviceGetAttribute(&nsm, cudaDevAttrMultiProcessorCount, dev);
    h.n_sm = nsm;
    h.overlap = nsm - 96 >= N_SIDE_CTAS + N_ATT_CTAS;
    h.n_side = N_SIDE_CTAS; h.n_att = N_ATT_CTAS;
    h.seq_a = sd;
    h.seq_a.seg[0] = {0, 0, 16};
    h.seq_a.seg[1] = {0, 16, 16};
    h.seq_a.nseg = 2;
    h.seq_b = sd;
    h.seq_b.seg[0] = {1, 0, 16};
    h.seq_b.seg[1] = {2, 0, 16};
    h.seq_b.nseg = 2; h.seq_b.queue = flags + F_TAILQ;

    cudaFuncSetAttribute(side_gemm_kernel<256>, cudaFuncAttributeMaxDynamicSharedMemorySize, GemmCfg<256>::SMEM);
    cudaFuncSetAttribute(side_gemm_kernel<128>, cudaFuncAttributeMaxDynamicSharedMemorySize, GemmCfg<128>::SMEM);
    cudaFuncSetAttribute(final_gemm_kernel, cudaFuncAttributeMaxDynamicSharedMemorySize, FIN_SMEM);
    cudaFuncSetAttribute(rec_kernel, cudaFuncAttributeMaxDynamicSharedMemorySize, REC_SMEM);
    cudaFuncSetAttribute(attn_kernel, cudaFuncAttributeMaxDynamicSharedMemorySize, ATT_SMEM);
    for (int i = 0; i < 10; i++) h.key[i] = d_in[i];
    h.key[10] = d_out;
    h.ready = true;
}

template <typename K, typename P>
void launch(K kernel, int grid, int block, int smem, cudaStream_t st, const P& prm, int cluster, bool pdl) {
    cudaLaunchConfig_t cfg = {};
    cfg.gridDim = dim3(grid); cfg.blockDim = dim3(block); cfg.dynamicSmemBytes = smem; cfg.stream = st;
    cudaLaunchAttribute at[2];
    int n = 0;
    if (cluster > 1) {
        at[n].id = cudaLaunchAttributeClusterDimension;
        at[n].val.clusterDim.x = cluster; at[n].val.clusterDim.y = 1; at[n].val.clusterDim.z = 1;
        n++;
    }
    if (pdl) {
        at[n].id = cudaLaunchAttributeProgrammaticStreamSerialization;
        at[n].val.programmaticStreamSerializationAllowed = 1;
        n++;
    }
    cfg.attrs = at; cfg.numAttrs = n;
    cudaLaunchKernelEx(&cfg, kernel, prm);
}

}

extern "C" void kernel_launch(void* const* d_in, const int* in_sizes, int n_in, void* d_out, int out_size) {
    HostState& h = g_host;
    bool same = h.ready;
    for (int i = 0; same && i < 10; i++) same = h.key[i] == d_in[i];
    if (!same || h.key[10] != d_out) setup(d_in, d_out);
    cudaStream_t st = cudaStreamPerThread;

    launch(rec_kernel, 96, REC_THREADS, REC_SMEM, st, h.rec, 3, false);
    {
        if (!h.overlap) {
            launch(side_gemm_kernel<256>, h.n_sm, 384, GemmCfg<256>::SMEM, st, h.seq_a, 1, false);
            launch(attn_kernel, SERIAL_ATT_CTAS, ATT_THREADS, ATT_SMEM, st, h.attn, 1, false);
            launch(side_gemm_kernel<256>, h.n_sm, 384, GemmCfg<256>::SMEM, st, h.seq_b, 1, false);
            return;
        }
    }
    launch(side_gemm_kernel<256>, h.n_side, 384, GemmCfg<256>::SMEM, st, h.side, 1, true);
    launch(attn_kernel, h.n_att, ATT_THREADS, ATT_SMEM, st, h.attn, 1, true);
    launch(side_gemm_kernel<128>, N_TAIL_CTAS, 384, GemmCfg<128>::SMEM, st, h.tail, 1, true);
    if (N_POST_ATT > 0) launch(attn_kernel, N_POST_ATT, ATT_THREADS, ATT_SMEM, st, h.attn, 1, true);
    launch(final_gemm_kernel, 8 * FIN_SPLIT, 384, FIN_SMEM, st, h.fin, FIN_SPLIT, true);
    if (OUTB_SIDE_BLOCKS < 16)
        launch(side_gemm_kernel<256>, (16 - OUTB_SIDE_BLOCKS) * 4, 384, GemmCfg<256>::SMEM, st, h.outb, 1, true);
}
```

```cpp
#include <cuda_runtime.h>
#include <cuda_bf16.h>
#include <cuda.h>
#include <stdint.h>

namespace {

constexpr int S_TOK = 2048;
constexpr int DM = 1024;
constexpr int NH = 32;
constexpr int DH = 128;
constexpr int HD = NH * DH;
constexpr int NSEG = 64;
constexpr int SEG = 32;
constexpr int MROWS = 8;
constexpr uint32_t SENT = 0xFFFFFFFFu;
constexpr uint32_t SPIN_LIMIT = 1u << 24;

__device__ __align__(1024) __nv_bfloat16 g_qkv_tok[3ull * NSEG * NH * SEG * DH];
__device__ __align__(1024) __nv_bfloat16 g_kv_mem[2ull * NSEG * NH * MROWS * DH];
__device__ __align__(1024) __nv_bfloat16 g_o_tok[(size_t)S_TOK * HD];
__device__ __align__(1024) __nv_bfloat16 g_qkv_b[(size_t)S_TOK * 3 * DM];
__device__ __align__(1024) __nv_bfloat16 g_o_b[(size_t)S_TOK * DM];
__device__ __align__(1024) float g_part[32 * 2 * 128 * 128];
constexpr int PUB_BYTES = 32768;
constexpr int XCHG_SLOT = 1 << 20;
constexpr int XCHG_PUB = 0, XCHG_INBOX = 2 * PUB_BYTES;
constexpr int INBOX_MAX = 80;
constexpr int XCHG_BYTES = 2 * XCHG_SLOT;
__device__ __align__(8192) uint8_t g_xchg[2 * XCHG_BYTES];
enum { F_RECSM = 4, F_PROGRESS = 16, F_QKVB = 80, F_OB = 96, F_OA = 112, F_PART = 176, F_SIDEQ = 208, F_TAILQ = 256, F_OUTBQ = 304, F_COUNT = 352 };
__device__ uint32_t g_flags[F_COUNT];
__device__ __align__(16) uint32_t g_arrivals[4];

#define STAMP(k) do {} while (0)
#define STAMPD(k, x) do {} while (0)
#define PSTAMP(k) do {} while (0)
#define KENTER(k) do {} while (0)
#define APROF(k) do {} while (0)
#define KEXIT(k) do {} while (0)
#define KMARK(k) do {} while (0)

__device__ __forceinline__ uint32_t class_off(uint64_t a, uint32_t c) {
    return ((__popc((uint32_t)a & 0xB3000u) ^ c) & 1u) << 12;
}
__device__ __forceinline__ uint32_t smem_u32(const void* p) { return (uint32_t)__cvta_generic_to_shared(p); }
__device__ __forceinline__ uint32_t pack_bf16(float lo, float hi) {
    uint32_t r;
    asm("cvt.rn.bf16x2.f32 %0, %1, %2;" : "=r"(r) : "f"(hi), "f"(lo));
    return r;
}
__device__ __forceinline__ float ex2(float x) {
    float y;
    asm("ex2.approx.ftz.f32 %0, %1;" : "=f"(y) : "f"(x));
    return y;
}
__device__ __forceinline__ float rcp(float x) {
    float y;
    asm("rcp.approx.ftz.f32 %0, %1;" : "=f"(y) : "f"(x));
    return y;
}
__device__ __forceinline__ uint32_t clock32() {
    uint32_t t;
    asm volatile("mov.u32 %0, %%clock;" : "=r"(t));
    return t;
}
__device__ __forceinline__ void spin_clks(uint32_t n) {
    if (n == 0) return;
    const uint32_t t0 = clock32();
    while (clock32() - t0 < n) {}
}
__device__ __forceinline__ void spin_until(uint32_t t) {
    while ((int)(clock32() - t) < 0) {}
}
__device__ __forceinline__ uint32_t clock_after(uint32_t x) {
    uint32_t t;
    asm volatile("{\n.reg .pred p;\nsetp.eq.u32 p, %1, 0x12345678;\n@p exit;\nmov.u32 %0, %%clock;\n}" : "=r"(t) : "r"(x) : "memory");
    return t;
}
__device__ __forceinline__ uint32_t opaque(uint32_t x) { return __shfl_sync(~0u, x, threadIdx.x & 31); }
__device__ __forceinline__ uint32_t uniform(uint32_t x) { return __shfl_sync(~0u, x + (threadIdx.x & 31), 0); }
__device__ __forceinline__ float bf16_lo(uint32_t w) { return __uint_as_float(w << 16); }
__device__ __forceinline__ float bf16_hi(uint32_t w) { return __uint_as_float(w & 0xFFFF0000u); }

__device__ __forceinline__ void mbar_init(uint32_t bar, uint32_t cnt) {
    asm volatile("mbarrier.init.shared::cta.b64 [%0], %1;" ::"r"(bar), "r"(cnt) : "memory");
}
__device__ __forceinline__ void mbar_arrive(uint32_t bar) {
    asm volatile("mbarrier.arrive.shared::cta.b64 _, [%0];" ::"r"(bar) : "memory");
}
__device__ __forceinline__ void mbar_arrive_expect_tx(uint32_t bar, uint32_t bytes) {
    asm volatile("mbarrier.arrive.expect_tx.shared::cta.b64 _, [%0], %1;" ::"r"(bar), "r"(bytes) : "memory");
}
__device__ __forceinline__ bool mbar_try_wait(uint32_t bar, uint32_t parity) {
    uint32_t ok;
    asm volatile(
        "{\n.reg .pred p;\n"
        "mbarrier.try_wait.parity.shared::cta.b64 p, [%1], %2;\n"
        "selp.u32 %0, 1, 0, p;\n}"
        : "=r"(ok) : "r"(bar), "r"(parity) : "memory");
    return ok != 0;
}
__device__ __forceinline__ bool mbar_test_wait(uint32_t bar, uint32_t parity) {
    uint32_t ok;
    asm volatile(
        "{\n.reg .pred p;\n"
        "mbarrier.test_wait.parity.shared::cta.b64 p, [%1], %2;\n"
        "selp.u32 %0, 1, 0, p;\n}"
        : "=r"(ok) : "r"(bar), "r"(parity) : "memory");
    return ok != 0;
}
__device__ __forceinline__ void mbar_wait(uint32_t bar, uint32_t parity) {
    uint32_t n = 0;
    while (!mbar_try_wait(bar, parity)) {
        if (++n > SPIN_LIMIT) __trap();
    }
}
__device__ __forceinline__ void mbar_wait_sleep(uint32_t bar, uint32_t parity) {
    uint32_t n = 0;
    while (!mbar_try_wait(bar, parity)) {
        __nanosleep(20);
        if (++n > SPIN_LIMIT) __trap();
    }
}
__device__ __forceinline__ void mbar_wait_bounded(uint32_t bar, uint32_t parity) {
    for (uint32_t n = 0; n < (1u << 20) && !mbar_try_wait(bar, parity); n++) {}
}
__device__ __forceinline__ bool elect_one() {
    uint32_t ok;
    asm volatile("{\n.reg .pred p;\nelect.sync _|p, 0xFFFFFFFF;\nselp.u32 %0, 1, 0, p;\n}" : "=r"(ok));
    return ok != 0;
}
__device__ __forceinline__ void named_bar_sync(int id, int nthreads) {
    asm volatile("bar.sync %0, %1;" ::"r"(id), "r"(nthreads) : "memory");
}
__device__ __forceinline__ void named_bar_arrive(int id, int nthreads) {
    asm volatile("bar.arrive %0, %1;" ::"r"(id), "r"(nthreads) : "memory");
}
__device__ __forceinline__ void cluster_sync() {
    asm volatile("barrier.cluster.arrive.release.aligned;\nbarrier.cluster.wait.acquire.aligned;" ::: "memory");
}
__device__ __forceinline__ uint32_t mapa(uint32_t addr, uint32_t rank) {
    uint32_t r;
    asm volatile("mapa.shared::cluster.u32 %0, %1, %2;" : "=r"(r) : "r"(addr), "r"(rank));
    return r;
}

__device__ __forceinline__ void tma_load_2d(uint32_t dst, const CUtensorMap* tm, int c0, int c1, uint32_t bar) {
    asm volatile(
        "cp.async.bulk.tensor.2d.shared::cluster.global.mbarrier::complete_tx::bytes [%0], [%1, {%3, %4}], [%2];"
        ::"r"(dst), "l"(tm), "r"(bar), "r"(c0), "r"(c1) : "memory");
}
__device__ __forceinline__ void tma_load_3d(uint32_t dst, const CUtensorMap* tm, int c0, int c1, int c2, uint32_t bar) {
    asm volatile(
        "cp.async.bulk.tensor.3d.shared::cluster.global.mbarrier::complete_tx::bytes [%0], [%1, {%3, %4, %5}], [%2];"
        ::"r"(dst), "l"(tm), "r"(bar), "r"(c0), "r"(c1), "r"(c2) : "memory");
}
__device__ __forceinline__ void tma_load_3d_mc(uint32_t dst, const CUtensorMap* tm, int c0, int c1, int c2, uint32_t bar, uint16_t mask) {
    asm volatile(
        "cp.async.bulk.tensor.3d.shared::cluster.global.mbarrier::complete_tx::bytes.multicast::cluster [%0], [%1, {%3, %4, %5}], [%2], %6;"
        ::"r"(dst), "l"(tm), "r"(bar), "r"(c0), "r"(c1), "r"(c2), "h"(mask) : "memory");
}
__device__ __forceinline__ void tma_store_2d(const CUtensorMap* tm, uint32_t src, int c0, int c1) {
    asm volatile("cp.async.bulk.tensor.2d.global.shared::cta.bulk_group [%0, {%2, %3}], [%1];"
                 ::"l"(tm), "r"(src), "r"(c0), "r"(c1) : "memory");
}
__device__ __forceinline__ void bulk_store(void* dst, uint32_t src, uint32_t bytes) {
    asm volatile("cp.async.bulk.global.shared::cta.bulk_group [%0], [%1], %2;" ::"l"(dst), "r"(src), "r"(bytes) : "memory");
}
__device__ __forceinline__ void bulk_commit() { asm volatile("cp.async.bulk.commit_group;" ::: "memory"); }
__device__ __forceinline__ void bulk_wait_read_all() { asm volatile("cp.async.bulk.wait_group.read 0;" ::: "memory"); }
__device__ __forceinline__ void bulk_wait_all() { asm volatile("cp.async.bulk.wait_group 0;" ::: "memory"); }
__device__ __forceinline__ void bulk_load(uint32_t dst, const void* src, uint32_t bytes, uint32_t bar) {
    asm volatile("cp.async.bulk.shared::cluster.global.mbarrier::complete_tx::bytes [%0], [%1], %2, [%3];"
                 ::"r"(dst), "l"(src), "r"(bytes), "r"(bar) : "memory");
}
__device__ __forceinline__ void bulk_load_mc(uint32_t dst, const void* src, uint32_t bytes, uint32_t bar, uint16_t mask) {
    asm volatile(
        "cp.async.bulk.shared::cluster.global.mbarrier::complete_tx::bytes.multicast::cluster [%0], [%1], %2, [%3], %4;"
        ::"r"(dst), "l"(src), "r"(bytes), "r"(bar), "h"(mask) : "memory");
}
__device__ __forceinline__ void cp_async16(uint32_t dst, const void* src) {
    asm volatile("cp.async.cg.shared.global [%0], [%1], 16;" ::"r"(dst), "l"(src) : "memory");
}
__device__ __forceinline__ void cp_async_commit() { asm volatile("cp.async.commit_group;" ::: "memory"); }
template <int N> __device__ __forceinline__ void cp_async_wait() {
    asm volatile("cp.async.wait_group %0;" ::"n"(N) : "memory");
}

__device__ __forceinline__ void ldsm_x4(uint32_t addr, uint32_t& r0, uint32_t& r1, uint32_t& r2, uint32_t& r3) {
    asm volatile("ldmatrix.sync.aligned.m8n8.x4.shared.b16 {%0,%1,%2,%3}, [%4];"
                 : "=r"(r0), "=r"(r1), "=r"(r2), "=r"(r3) : "r"(addr) : "memory");
}
__device__ __forceinline__ void ldsm_x4_t(uint32_t addr, uint32_t& r0, uint32_t& r1, uint32_t& r2, uint32_t& r3) {
    asm volatile("ldmatrix.sync.aligned.m8n8.x4.trans.shared.b16 {%0,%1,%2,%3}, [%4];"
                 : "=r"(r0), "=r"(r1), "=r"(r2), "=r"(r3) : "r"(addr) : "memory");
}
__device__ __forceinline__ void stsm_x4(uint32_t addr, uint32_t r0, uint32_t r1, uint32_t r2, uint32_t r3) {
    asm volatile("stmatrix.sync.aligned.m8n8.x4.shared.b16 [%0], {%1,%2,%3,%4};"
                 ::"r"(addr), "r"(r0), "r"(r1), "r"(r2), "r"(r3) : "memory");
}
__device__ __forceinline__ uint32_t movmat(uint32_t a) {
    uint32_t d;
    asm volatile("movmatrix.sync.aligned.m8n8.trans.b16 %0, %1;" : "=r"(d) : "r"(a));
    return d;
}
__device__ __forceinline__ void mma16816(float* d, uint32_t a0, uint32_t a1, uint32_t a2, uint32_t a3,
                                         uint32_t b0, uint32_t b1) {
    asm volatile(
        "mma.sync.aligned.m16n8k16.row.col.f32.bf16.bf16.f32 {%0,%1,%2,%3}, {%4,%5,%6,%7}, {%8,%9}, {%0,%1,%2,%3};"
        : "+f"(d[0]), "+f"(d[1]), "+f"(d[2]), "+f"(d[3])
        : "r"(a0), "r"(a1), "r"(a2), "r"(a3), "r"(b0), "r"(b1));
}
__device__ __forceinline__ void mma1688(float* d, uint32_t a0, uint32_t a1, uint32_t b0) {
    asm volatile("mma.sync.aligned.m16n8k8.row.col.f32.bf16.bf16.f32 {%0,%1,%2,%3}, {%4,%5}, {%6}, {%0,%1,%2,%3};"
                 : "+f"(d[0]), "+f"(d[1]), "+f"(d[2]), "+f"(d[3]) : "r"(a0), "r"(a1), "r"(b0));
}
__device__ __forceinline__ uint32_t any_reg() {
    uint32_t r;
    asm volatile("" : "=r"(r));
    return r;
}
__device__ __forceinline__ uint2 lds64(uint32_t addr) {
    uint2 v;
    asm volatile("ld.volatile.shared.v2.b32 {%0,%1}, [%2];" : "=r"(v.x), "=r"(v.y) : "r"(addr) : "memory");
    return v;
}
__device__ __forceinline__ uint4 lds128(uint32_t addr) {
    uint4 v;
    asm volatile("ld.volatile.shared.v4.b32 {%0,%1,%2,%3}, [%4];" : "=r"(v.x), "=r"(v.y), "=r"(v.z), "=r"(v.w) : "r"(addr) : "memory");
    return v;
}
__device__ __forceinline__ void sts32(uint32_t addr, uint32_t x) {
    asm volatile("st.volatile.shared.b32 [%0], %1;" ::"r"(addr), "r"(x) : "memory");
}
__device__ __forceinline__ void sts64(uint32_t addr, uint32_t x, uint32_t y) {
    asm volatile("st.volatile.shared.v2.b32 [%0], {%1,%2};" ::"r"(addr), "r"(x), "r"(y) : "memory");
}
__device__ __forceinline__ void sts128(uint32_t addr, uint32_t x, uint32_t y, uint32_t z, uint32_t w) {
    asm volatile("st.volatile.shared.v4.b32 [%0], {%1,%2,%3,%4};" ::"r"(addr), "r"(x), "r"(y), "r"(z), "r"(w) : "memory");
}
__device__ __forceinline__ void st_async_v2(uint32_t addr, uint32_t x, uint32_t y, uint32_t bar) {
    asm volatile("st.async.weak.shared::cluster.mbarrier::complete_tx::bytes.v2.b32 [%0], {%1,%2}, [%3];"
                 ::"r"(addr), "r"(x), "r"(y), "r"(bar) : "memory");
}
__device__ __forceinline__ uint2 ld_relaxed_v2(const void* p) {
    uint2 v;
    asm volatile("ld.relaxed.gpu.global.v2.b32 {%0,%1}, [%2];" : "=r"(v.x), "=r"(v.y) : "l"(p) : "memory");
    return v;
}
__device__ __forceinline__ void st_relaxed_v2(void* p, uint32_t x, uint32_t y) {
    asm volatile("st.relaxed.gpu.global.v2.b32 [%0], {%1,%2};" ::"l"(p), "r"(x), "r"(y) : "memory");
}
__device__ __forceinline__ void st_relaxed_v4(void* p, uint32_t x) {
    asm volatile("st.relaxed.gpu.global.v4.b32 [%0], {%1,%1,%1,%1};" ::"l"(p), "r"(x) : "memory");
}
__device__ __forceinline__ uint32_t ld_relaxed_b32(const void* p) {
    uint32_t v;
    asm volatile("ld.relaxed.gpu.global.b32 %0, [%1];" : "=r"(v) : "l"(p) : "memory");
    return v;
}
__device__ __forceinline__ uint32_t lds32_volatile(uint32_t addr) {
    uint32_t v;
    asm volatile("ld.volatile.shared.b32 %0, [%1];" : "=r"(v) : "r"(addr) : "memory");
    return v;
}
__device__ __forceinline__ void st_relaxed_b32(void* p, uint32_t x) {
    asm volatile("st.relaxed.gpu.global.b32 [%0], %1;" ::"l"(p), "r"(x) : "memory");
}

__device__ __forceinline__ uint32_t ld_acquire_b32(const void* p) {
    uint32_t v;
    asm volatile("ld.acquire.gpu.global.b32 %0, [%1];" : "=r"(v) : "l"(p) : "memory");
    return v;
}
__device__ __forceinline__ void wait_flag(const uint32_t* p, uint32_t target) {
    uint32_t n = 0;
    while (ld_acquire_b32(p) < target) {
        __nanosleep(64);
        if (++n > SPIN_LIMIT) __trap();
    }
}
__device__ __forceinline__ void signal_flag(uint32_t* p) {
    asm volatile("red.release.gpu.global.add.u32 [%0], 1;" ::"l"(p) : "memory");
}
__device__ __forceinline__ bool next_to_rec(const uint32_t* flags) {
    uint32_t smid;
    asm volatile("mov.u32 %0, %%smid;" : "=r"(smid));
    smid ^= 1;
    return smid < 384 && ((ld_relaxed_b32(flags + F_RECSM + (smid >> 5)) >> (smid & 31)) & 1);
}
__device__ __forceinline__ void pdl_launch_dependents() { asm volatile("griddepcontrol.launch_dependents;" ::: "memory"); }

constexpr int BM = 128, BK = 64;
constexpr int A_STAGE = BM * BK * 2;
template <int BN> struct GemmCfg {
    static constexpr int STAGES = BN == 256 ? 3 : 6;
    static constexpr int STAGE = A_STAGE + BK * BN * 2;
    static constexpr int EPI_WARP = 16 * BN * 2;
    static constexpr int SMEM = STAGES * STAGE + 8 * EPI_WARP + 1024 + 512;
};

struct SideProb {
    CUtensorMap tmA, tmB, tmC;
    int n_split;
    int n_tiles, k_blocks, k_total, c_col0;
    const uint32_t* dep;
    uint32_t dep_target;
    int dep_n;
    uint32_t* sig;
    float* part;
    uint32_t* part_flag;
};
struct SideSeg { int prob, m0, m1; };
constexpr int SIDE_MAX_SEG = 3;
struct SideParams {
    SideProb prob[3];
    SideSeg seg[SIDE_MAX_SEG];
    int nseg;
    int spare_seg;
    const uint32_t* flags;
    uint32_t* queue;
};
static_assert(sizeof(SideParams) <= 4096, "kernel parameter limit");

__device__ __forceinline__ uint64_t make_desc(uint32_t addr, uint32_t lbo, uint32_t sbo) {
    return (uint64_t)((addr & 0x3FFFF) >> 4) | ((uint64_t)(lbo >> 4) << 16) | ((uint64_t)(sbo >> 4) << 32) | (1ull << 62);
}

__device__ __forceinline__ void wgmma_m64n256k16(float (&d)[128], uint64_t da, uint64_t db, int scale_d) {
    asm volatile(
        "{\n.reg .pred p;\nsetp.ne.b32 p, %130, 0;\n"
        "wgmma.mma_async.sync.aligned.m64n256k16.f32.bf16.bf16 "
        "{%0,%1,%2,%3,%4,%5,%6,%7,%8,%9,%10,%11,%12,%13,%14,%15,"
        "%16,%17,%18,%19,%20,%21,%22,%23,%24,%25,%26,%27,%28,%29,%30,%31,"
        "%32,%33,%34,%35,%36,%37,%38,%39,%40,%41,%42,%43,%44,%45,%46,%47,"
        "%48,%49,%50,%51,%52,%53,%54,%55,%56,%57,%58,%59,%60,%61,%62,%63,"
        "%64,%65,%66,%67,%68,%69,%70,%71,%72,%73,%74,%75,%76,%77,%78,%79,"
        "%80,%81,%82,%83,%84,%85,%86,%87,%88,%89,%90,%91,%92,%93,%94,%95,"
        "%96,%97,%98,%99,%100,%101,%102,%103,%104,%105,%106,%107,%108,%109,%110,%111,"
        "%112,%113,%114,%115,%116,%117,%118,%119,%120,%121,%122,%123,%124,%125,%126,%127},"
        " %128, %129, p, 1, 1, 0, 1;\n}\n"
        : "+f"(d[0]), "+f"(d[1]), "+f"(d[2]), "+f"(d[3]), "+f"(d[4]), "+f"(d[5]), "+f"(d[6]), "+f"(d[7]),
          "+f"(d[8]), "+f"(d[9]), "+f"(d[10]), "+f"(d[11]), "+f"(d[12]), "+f"(d[13]), "+f"(d[14]), "+f"(d[15]),
          "+f"(d[16]), "+f"(d[17]), "+f"(d[18]), "+f"(d[19]), "+f"(d[20]), "+f"(d[21]), "+f"(d[22]), "+f"(d[23]),
          "+f"(d[24]), "+f"(d[25]), "+f"(d[26]), "+f"(d[27]), "+f"(d[28]), "+f"(d[29]), "+f"(d[30]), "+f"(d[31]),
          "+f"(d[32]), "+f"(d[33]), "+f"(d[34]), "+f"(d[35]), "+f"(d[36]), "+f"(d[37]), "+f"(d[38]), "+f"(d[39]),
          "+f"(d[40]), "+f"(d[41]), "+f"(d[42]), "+f"(d[43]), "+f"(d[44]), "+f"(d[45]), "+f"(d[46]), "+f"(d[47]),
          "+f"(d[48]), "+f"(d[49]), "+f"(d[50]), "+f"(d[51]), "+f"(d[52]), "+f"(d[53]), "+f"(d[54]), "+f"(d[55]),
          "+f"(d[56]), "+f"(d[57]), "+f"(d[58]), "+f"(d[59]), "+f"(d[60]), "+f"(d[61]), "+f"(d[62]), "+f"(d[63]),
          "+f"(d[64]), "+f"(d[65]), "+f"(d[66]), "+f"(d[67]), "+f"(d[68]), "+f"(d[69]), "+f"(d[70]), "+f"(d[71]),
          "+f"(d[72]), "+f"(d[73]), "+f"(d[74]), "+f"(d[75]), "+f"(d[76]), "+f"(d[77]), "+f"(d[78]), "+f"(d[79]),
          "+f"(d[80]), "+f"(d[81]), "+f"(d[82]), "+f"(d[83]), "+f"(d[84]), "+f"(d[85]), "+f"(d[86]), "+f"(d[87]),
          "+f"(d[88]), "+f"(d[89]), "+f"(d[90]), "+f"(d[91]), "+f"(d[92]), "+f"(d[93]), "+f"(d[94]), "+f"(d[95]),
          "+f"(d[96]), "+f"(d[97]), "+f"(d[98]), "+f"(d[99]), "+f"(d[100]), "+f"(d[101]), "+f"(d[102]), "+f"(d[103]),
          "+f"(d[104]), "+f"(d[105]), "+f"(d[106]), "+f"(d[107]), "+f"(d[108]), "+f"(d[109]), "+f"(d[110]), "+f"(d[111]),
          "+f"(d[112]), "+f"(d[113]), "+f"(d[114]), "+f"(d[115]), "+f"(d[116]), "+f"(d[117]), "+f"(d[118]), "+f"(d[119]),
          "+f"(d[120]), "+f"(d[121]), "+f"(d[122]), "+f"(d[123]), "+f"(d[124]), "+f"(d[125]), "+f"(d[126]), "+f"(d[127])
        : "l"(da), "l"(db), "r"(scale_d));
}

__device__ __forceinline__ void wgmma_m64n128k16(float (&d)[64], uint64_t da, uint64_t db, int scale_d) {
    asm volatile(
        "{\n.reg .pred p;\nsetp.ne.b32 p, %66, 0;\n"
        "wgmma.mma_async.sync.aligned.m64n128k16.f32.bf16.bf16 "
        "{%0,%1,%2,%3,%4,%5,%6,%7,%8,%9,%10,%11,%12,%13,%14,%15,"
        "%16,%17,%18,%19,%20,%21,%22,%23,%24,%25,%26,%27,%28,%29,%30,%31,"
        "%32,%33,%34,%35,%36,%37,%38,%39,%40,%41,%42,%43,%44,%45,%46,%47,"
        "%48,%49,%50,%51,%52,%53,%54,%55,%56,%57,%58,%59,%60,%61,%62,%63},"
        " %64, %65, p, 1, 1, 0, 1;\n}\n"
        : "+f"(d[0]), "+f"(d[1]), "+f"(d[2]), "+f"(d[3]), "+f"(d[4]), "+f"(d[5]), "+f"(d[6]), "+f"(d[7]),
          "+f"(d[8]), "+f"(d[9]), "+f"(d[10]), "+f"(d[11]), "+f"(d[12]), "+f"(d[13]), "+f"(d[14]), "+f"(d[15]),
          "+f"(d[16]), "+f"(d[17]), "+f"(d[18]), "+f"(d[19]), "+f"(d[20]), "+f"(d[21]), "+f"(d[22]), "+f"(d[23]),
          "+f"(d[24]), "+f"(d[25]), "+f"(d[26]), "+f"(d[27]), "+f"(d[28]), "+f"(d[29]), "+f"(d[30]), "+f"(d[31]),
          "+f"(d[32]), "+f"(d[33]), "+f"(d[34]), "+f"(d[35]), "+f"(d[36]), "+f"(d[37]), "+f"(d[38]), "+f"(d[39]),
          "+f"(d[40]), "+f"(d[41]), "+f"(d[42]), "+f"(d[43]), "+f"(d[44]), "+f"(d[45]), "+f"(d[46]), "+f"(d[47]),
          "+f"(d[48]), "+f"(d[49]), "+f"(d[50]), "+f"(d[51]), "+f"(d[52]), "+f"(d[53]), "+f"(d[54]), "+f"(d[55]),
          "+f"(d[56]), "+f"(d[57]), "+f"(d[58]), "+f"(d[59]), "+f"(d[60]), "+f"(d[61]), "+f"(d[62]), "+f"(d[63])
        : "l"(da), "l"(db), "r"(scale_d));
}
template <int BN> struct WgmmaOp;
template <> struct WgmmaOp<256> {
    static __device__ __forceinline__ void run(float (&d)[128], uint64_t a, uint64_t b, int sc) { wgmma_m64n256k16(d, a, b, sc); }
};
template <> struct WgmmaOp<128> {
    static __device__ __forceinline__ void run(float (&d)[64], uint64_t a, uint64_t b, int sc) { wgmma_m64n128k16(d, a, b, sc); }
};

struct StoreRec {
    uint64_t dst;
    uint64_t flag;
    int kind;
    int pad;
};
struct EpiCtx { uint32_t buf, rec, st_full, st_empty; uint32_t it; int lane; };
template <int N>
__device__ __forceinline__ void epi_hand_over(const float (&acc)[N], EpiCtx& e, uint64_t dst, uint64_t flag, int kind) {
    mbar_wait(e.st_empty, (e.it & 1) ^ 1);
    const int mi = e.lane >> 3, row = (mi & 1) * 8 + (e.lane & 7);
    #pragma unroll
    for (int j = 0; j < N / 4; j += 2) {
        const int chunk = (j & 7) + (mi >> 1);
        stsm_x4(e.buf + (j >> 3) * 2048 + row * 128 + ((chunk ^ (row & 7)) << 4),
                pack_bf16(acc[4 * j], acc[4 * j + 1]), pack_bf16(acc[4 * j + 2], acc[4 * j + 3]),
                pack_bf16(acc[4 * j + 4], acc[4 * j + 5]), pack_bf16(acc[4 * j + 6], acc[4 * j + 7]));
    }
    if (e.lane == 0) {
        asm volatile("st.shared.v2.b64 [%0], {%1, %2};" ::"r"(e.rec), "l"(dst), "l"(flag) : "memory");
        asm volatile("st.shared.b32 [%0], %1;" ::"r"(e.rec + 16), "r"(kind) : "memory");
    }
    asm volatile("fence.proxy.async.shared::cta;" ::: "memory");
    __syncwarp();
    if (e.lane == 0) mbar_arrive(e.st_full);
    e.it++;
}
__device__ __forceinline__ void epi_exit(EpiCtx& e) {
    mbar_wait(e.st_empty, (e.it & 1) ^ 1);
    if (e.lane == 0) {
        asm volatile("st.shared.b32 [%0], %1;" ::"r"(e.rec + 16), "r"(-1) : "memory");
        mbar_arrive(e.st_full);
    }
}
template <int BN, bool PAIR = false>
__device__ __forceinline__ void gemm_mainloop(float (&acc)[BN / 2], int k_blocks, uint32_t sbase, uint32_t bar_base, int cw,
                                              bool elected, int& stage, uint32_t& phase, uint32_t peer = 0) {
    using C = GemmCfg<BN>;
    auto release = [&](int st) {
        const uint32_t bar = bar_base + 8 * (C::STAGES + st);
        mbar_arrive(bar);
        if (PAIR) asm volatile("mbarrier.arrive.shared::cluster.b64 _, [%0];" ::"r"(mapa(bar, peer)) : "memory");
    };
    int prev_stage = -1;
    for (int kb = 0; kb < k_blocks; kb++) {
        mbar_wait(bar_base + 8 * stage, phase);
        const uint32_t sa = sbase + stage * C::STAGE + cw * (64 * 128);
        const uint32_t sb = sbase + stage * C::STAGE + A_STAGE;
        asm volatile("wgmma.fence.sync.aligned;" ::: "memory");
        #pragma unroll
        for (int kk = 0; kk < BK / 16; kk++)
            WgmmaOp<BN>::run(acc, make_desc(sa + kk * 32, 16, 1024), make_desc(sb + kk * 2048, 8192, 1024), (kb | kk) != 0);
        asm volatile("wgmma.commit_group.sync.aligned;" ::: "memory");
        asm volatile("wgmma.wait_group.sync.aligned 1;" ::: "memory");
        if (prev_stage >= 0 && elected) release(prev_stage);
        prev_stage = stage;
        if (++stage == C::STAGES) { stage = 0; phase ^= 1; }
    }
    asm volatile("wgmma.wait_group.sync.aligned 0;" ::: "memory");
    if (elected) release(prev_stage);
}
template <int BN>
__device__ __forceinline__ void store_warp(uint32_t epi_base, uint32_t rec_base, uint32_t st_full, uint32_t st_empty, int lane,
                                           const uint8_t* tmaps, int tstride) {
    for (uint32_t it = 0;; it++) {
        mbar_wait(st_full, it & 1);
        uint64_t dst = 0, flag = 0;
        int kind = -1;
        if (lane < 8) {
            const uint32_t rec = rec_base + lane * 32;
            asm volatile("ld.volatile.shared.v2.b64 {%0, %1}, [%2];" : "=l"(dst), "=l"(flag) : "r"(rec) : "memory");
            kind = (int)lds32_volatile(rec + 16);
        }
        if (__shfl_sync(~0u, kind, 0) < 0) break;
        if (lane < 8) {
            const uint32_t buf = epi_base + lane * GemmCfg<BN>::EPI_WARP;
            #pragma unroll
            for (int q = 0; q < BN / 64; q++) {
                tma_store_2d(reinterpret_cast<const CUtensorMap*>(tmaps + (kind - 1) * tstride), buf + q * 2048,
                                  (int)(uint32_t)dst + q * 64, (int)(dst >> 32));
            }
            bulk_commit();
            bulk_wait_read_all();
            mbar_arrive(st_empty);
            if (flag) {
                bulk_wait_all();
                signal_flag(reinterpret_cast<uint32_t*>(flag));
            }
        }
        __syncwarp();
    }
    if (lane < 8) bulk_wait_all();
}

#define SCHED_AHEAD 4
template <int BN>
__global__ void __launch_bounds__(384, 1) side_gemm_kernel(const __grid_constant__ SideParams p) {
    using C = GemmCfg<BN>;
    extern __shared__ uint8_t smem_raw[];
    const uint32_t sbase = (smem_u32(smem_raw) + 1023) & ~1023u;
    const uint32_t epi_base = sbase + C::STAGES * C::STAGE;
    const uint32_t bar_base = epi_base + 8 * C::EPI_WARP;
    const uint32_t tfull = bar_base + 16 * C::STAGES, tempty = tfull + 16, tslot = tempty + 16, twant = tslot + 8;
    const uint32_t st_full = bar_base + 192, st_empty = st_full + 8, rec_base = bar_base + 256;
    const int tid = threadIdx.x, wg = tid >> 7;
    if (tid == 0) {
        for (int s = 0; s < C::STAGES; s++) { mbar_init(bar_base + 8 * s, 1); mbar_init(bar_base + 8 * (C::STAGES + s), 2); }
        for (int s = 0; s < 2; s++) { mbar_init(tfull + 8 * s, 1); mbar_init(tempty + 8 * s, 3); }
        mbar_init(twant, 1);
        mbar_init(st_full, 8);
        mbar_init(st_empty, 8);
        asm volatile("fence.mbarrier_init.release.cluster;" ::: "memory");
        pdl_launch_dependents();
    }
    __syncthreads();
    KENTER(BN == 256 ? (p.nseg == 1 ? 6 : 2) : 4);

    if (wg == 0) {
        asm volatile("setmaxnreg.dec.sync.aligned.u32 40;");
        if (tid == 0) {
            int stage = 0; uint32_t phase = 1;
            for (uint32_t it = 0;; it++) {
                mbar_wait(tfull + 8 * (it & 1), (it >> 1) & 1);
                const int code = (int)lds32_volatile(tslot + 4 * (it & 1));
                mbar_arrive(tempty + 8 * (it & 1));
                if (code < 0) break;
                const SideProb& q = p.prob[code >> 16];
                const int mt = (code >> 8) & 255, nt = code & 255;
                asm volatile("fence.proxy.async.global;" ::: "memory");
                const int kb0 = nt / q.n_split * q.k_blocks, nkb = nt + q.n_split < q.n_tiles ? q.k_blocks : q.k_total - kb0;
                for (int kb = 0; kb < nkb; kb++) {
                    if (kb == nkb - SCHED_AHEAD) mbar_arrive(twant);
                    mbar_wait(bar_base + 8 * (C::STAGES + stage), phase);
                    const uint32_t sa = sbase + stage * C::STAGE, fb = bar_base + 8 * stage;
                    mbar_arrive_expect_tx(fb, C::STAGE);
                    const int k0 = (kb0 + kb) * BK;
                    tma_load_2d(sa, &q.tmA, k0, mt * BM, fb);
                    tma_load_3d(sa + A_STAGE, &q.tmB, 0, k0, nt % q.n_split * (BN / 64), fb);
                    if (++stage == C::STAGES) { stage = 0; phase ^= 1; }
                }
            }
        } else if (tid >= 64 && tid < 96) {
            const int lane = tid & 31;
            const bool spare = p.spare_seg < 3 && next_to_rec(p.flags);
            uint32_t ntl[2], tgt[2], prb[2];
            const uint32_t* dp[2];
            #pragma unroll
            for (int u = 0; u < 2; u++) {
                const int g = u * 2 + (lane >> 4), mt = lane & 15;
                const bool on = g < p.nseg && mt >= p.seg[g < p.nseg ? g : 0].m0 && mt < p.seg[g < p.nseg ? g : 0].m1;
                prb[u] = p.seg[on ? g : 0].prob;
                const SideProb& q = p.prob[prb[u]];
                ntl[u] = on && !(g >= p.spare_seg && spare) ? q.n_tiles : 0;
                tgt[u] = on && q.dep ? q.dep_target : 0;
                dp[u] = tgt[u] ? q.dep + (mt + 1) * q.dep_n - 1 : p.queue;
            }
            for (uint32_t it = 0;; it++) {
                if (it > 0) mbar_wait_sleep(twant, (it - 1) & 1);
                int code = -1;
                for (uint32_t tries = 0; code < 0; tries++) {
                    const uint32_t c0 = ld_relaxed_b32(p.queue + lane), c1 = ld_relaxed_b32(p.queue + 32 + (lane & 15));
                    const uint32_t d0 = ld_relaxed_b32(dp[0]), d1 = ld_relaxed_b32(dp[1]);
                    const uint64_t left = __ballot_sync(~0u, c0 < ntl[0]) | (uint64_t)__ballot_sync(~0u, c1 < ntl[1]) << 32;
                    uint64_t ready = left & (__ballot_sync(~0u, d0 >= tgt[0]) | (uint64_t)__ballot_sync(~0u, d1 >= tgt[1]) << 32);
                    if (!left) break;
                    if (!ready && (BN == 128 || (left >> (((__ffsll(left) - 1) & ~15) + 16)) == 0)) ready = left;
                    if (!ready) __nanosleep(200);
                    while (ready) {
                        const int e = __ffsll(ready) - 1;
                        const uint32_t n = __shfl_sync(~0u, e < 32 ? ntl[0] : ntl[1], e & 31), pr = __shfl_sync(~0u, e < 32 ? prb[0] : prb[1], e & 31);
                        uint32_t idx = 0;
                        if (lane == 0) idx = atomicAdd(p.queue + e, 1u);
                        idx = __shfl_sync(~0u, idx, 0);
                        if (idx < n) { code = (pr << 16) | ((e & 15) << 8) | idx; break; }
                        for (uint32_t k = idx / n; k > 0; k--) ready &= ready - 1;
                    }
                    if (tries > SPIN_LIMIT) __trap();
                }
                if (code >= 0) {
                    const SideProb& q = p.prob[code >> 16];
                    if (q.dep && lane < q.dep_n) wait_flag(q.dep + ((code >> 8) & 255) * q.dep_n + lane, q.dep_target);
                    __syncwarp();
                }
                if (lane == 0) {
                    mbar_wait(tempty + 8 * (it & 1), ((it >> 1) & 1) ^ 1);
                    asm volatile("st.shared.b32 [%0], %1;" ::"r"(tslot + 4 * (it & 1)), "r"(code) : "memory");
                    mbar_arrive(tfull + 8 * (it & 1));
                }
                __syncwarp();
                if (code < 0) break;
            }
        } else if (tid >= 32 && tid < 64) {
            store_warp<BN>(epi_base, rec_base, st_full, st_empty, tid & 31, reinterpret_cast<const uint8_t*>(&p.prob[0].tmC),
                           (int)sizeof(SideProb));
        }
    } else {
        asm volatile("setmaxnreg.inc.sync.aligned.u32 232;");
        const int cw = wg - 1, lane = tid & 31, wi = (tid >> 5) & 3;
        const bool elected = (tid & 127) == 0;
        int stage = 0; uint32_t phase = 0;
        float acc[BN / 2];
        EpiCtx ectx = {epi_base + (cw * 4 + wi) * C::EPI_WARP, rec_base + (cw * 4 + wi) * 32, st_full, st_empty, 0, lane};
        for (uint32_t it = 0;; it++) {
            mbar_wait(tfull + 8 * (it & 1), (it >> 1) & 1);
            const int code = (int)lds32_volatile(tslot + 4 * (it & 1));
            named_bar_sync(1 + cw, 128);
            if (elected) mbar_arrive(tempty + 8 * (it & 1));
            if (code < 0) break;
            const SideProb& q = p.prob[code >> 16];
            const int mt = (code >> 8) & 255, nt = code & 255;
            gemm_mainloop<BN>(acc, nt + q.n_split < q.n_tiles ? q.k_blocks : q.k_total - nt / q.n_split * q.k_blocks, sbase, bar_base, cw, elected, stage, phase);
            const int row0 = mt * BM + cw * 64 + wi * 16, ntc = nt % q.n_split;
            if (BN == 128 && q.part) {
                const int idx = (mt & 3) * q.n_split + ntc, item = nt / q.n_split, nprev = q.n_tiles / q.n_split - 1;
                float4* part = reinterpret_cast<float4*>(q.part) + (size_t)idx * 2 * (BM * BN / 4) + (tid - 128);
                if (mt == 14 && elected) KMARK(21);
                if (item < nprev) {
                    #pragma unroll
                    for (int j = 0; j < BN / 8; j++)
                        __stcg(part + item * (BM * BN / 4) + j * 256, make_float4(acc[4 * j], acc[4 * j + 1], acc[4 * j + 2], acc[4 * j + 3]));
                    __syncwarp();
                    if (lane == 0) signal_flag(q.part_flag + idx);
                    continue;
                }
                if (lane == 0) wait_flag(q.part_flag + idx, 8 * nprev);
                __syncwarp();
                if (mt == 14 && elected) KMARK(22);
                for (int u = 0; u < nprev; u++) {
                    #pragma unroll
                    for (int j = 0; j < BN / 8; j++) {
                        const float4 v = __ldcg(part + u * (BM * BN / 4) + j * 256);
                        acc[4 * j] += v.x; acc[4 * j + 1] += v.y; acc[4 * j + 2] += v.z; acc[4 * j + 3] += v.w;
                    }
                }
            }
            if (BN == 128 && mt == 14 && elected) KMARK(23);
            epi_hand_over(acc, ectx, ((uint64_t)row0 << 32) | (uint32_t)(q.c_col0 + ntc * BN), q.sig ? (uint64_t)(q.sig + mt) : 0, 1 + (code >> 16));
        }
        epi_exit(ectx);
        if (elected) KEXIT(BN == 256 ? (p.nseg == 1 ? 6 : 2) : 4);
    }
}

constexpr int FIN_SPLIT = 8, FIN_KB = HD / BK / FIN_SPLIT;
constexpr int FIN_A1 = FIN_KB * 16384;
constexpr int FIN_A0 = FIN_A1 + FIN_KB * 8192;
constexpr int FIN_BAR = FIN_A0 + 4 * 8192, FIN_SMEM = FIN_BAR + 256;
enum { FB_B = 0, FB_A1 = 64, FB_A0 = 128, FB_E0 = 160, FB_RDY = 192, FB_RED = 208 };
struct FinalParams {
    CUtensorMap tmA, tmB;
    __nv_bfloat16* out;
    const uint32_t* dep;
    uint32_t dep_target;
    int mt;
};
__global__ void __launch_bounds__(384, 1) final_gemm_kernel(const __grid_constant__ FinalParams p) {
    extern __shared__ __align__(1024) uint8_t smem_raw[];
    const uint32_t sbase = smem_u32(smem_raw), bar = sbase + FIN_BAR;
    const int tid = threadIdx.x, wg = tid >> 7;
    const int rank = blockIdx.x % FIN_SPLIT, nt = blockIdx.x / FIN_SPLIT;
    KENTER(5);
    if (tid == 0) {
        for (int s = 0; s < FIN_KB; s++) { mbar_init(bar + FB_B + 8 * s, 1); mbar_init(bar + FB_A1 + 8 * s, 1); }
        for (int s = 0; s < 4; s++) { mbar_init(bar + FB_A0 + 8 * s, 1); mbar_init(bar + FB_E0 + 8 * s, 1); }
        for (int h = 0; h < 2; h++) { mbar_init(bar + FB_RDY + 8 * h, FIN_SPLIT); mbar_init(bar + FB_RED + 8 * h, 1); }
        asm volatile("fence.mbarrier_init.release.cluster;" ::: "memory");
        for (int h = 0; h < 2; h++) mbar_arrive_expect_tx(bar + FB_RED + 8 * h, (FIN_SPLIT - 1) * 4096);
        pdl_launch_dependents();
    }
    __syncthreads();
    asm volatile("barrier.cluster.arrive.relaxed.aligned;" ::: "memory");
    if (wg == 0) {
        auto need = [&](int i) {
            uint32_t n = 0;
            while (ld_acquire_b32(p.dep + i) < p.dep_target) { if (++n > SPIN_LIMIT) __trap(); }
            asm volatile("fence.proxy.async.global;" ::: "memory");
        };
        auto a_load = [&](uint32_t dst, int kb, int seg, uint32_t mb) { tma_load_2d(dst, &p.tmA, (rank * FIN_KB + kb) * BK, p.mt * BM + seg * SEG, mb); };
        if (tid == 0) {
            for (int kb = 0; kb < FIN_KB; kb++) {
                mbar_arrive_expect_tx(bar + FB_B + 8 * kb, 16384);
                tma_load_3d(sbase + kb * 16384, &p.tmB, 0, (rank * FIN_KB + kb) * BK, nt * 2, bar + FB_B + 8 * kb);
            }
        } else if (tid == 32) {
            need(0);
            need(1);
            for (int kb = 0; kb < FIN_KB; kb++) {
                if (kb >= 4) mbar_wait(bar + FB_E0 + 8 * (kb & 3), 0);
                mbar_arrive_expect_tx(bar + FB_A0 + 8 * (kb & 3), 8192);
                for (int u = 0; u < 2; u++) a_load(sbase + FIN_A0 + (kb & 3) * 8192 + u * 4096, kb, u, bar + FB_A0 + 8 * (kb & 3));
            }
        } else if (tid == 96) {
            need(3);
            for (int kb = 1; kb < FIN_KB; kb += 2) a_load(sbase + FIN_A1 + kb * 8192 + 4096, kb, 3, bar + FB_A1 + 8 * kb);
        } else if (tid == 64) {
            need(2);
            for (int kb = 0; kb < FIN_KB; kb++) {
                mbar_arrive_expect_tx(bar + FB_A1 + 8 * kb, 8192);
                a_load(sbase + FIN_A1 + kb * 8192, kb, 2, bar + FB_A1 + 8 * kb);
            }
            need(3);
            KMARK(15);
            for (int kb = 0; kb < FIN_KB; kb += 2) a_load(sbase + FIN_A1 + kb * 8192 + 4096, kb, 3, bar + FB_A1 + 8 * kb);
        }
        __syncwarp();
        asm volatile("barrier.cluster.wait.aligned;" ::: "memory");
    } else {
        const int h = wg - 1, lane = tid & 31, wi = (tid >> 5) & 3, t128 = tid & 127;
        asm volatile("barrier.cluster.wait.aligned;" ::: "memory");
        float acc[64];
        for (int kb = 0; kb < FIN_KB; kb++) {
            mbar_wait(bar + FB_B + 8 * kb, 0);
            if (h == 0) mbar_wait(bar + FB_A0 + 8 * (kb & 3), kb >> 2); else mbar_wait(bar + FB_A1 + 8 * kb, 0);
            const uint32_t sa = sbase + (h == 0 ? FIN_A0 + (kb & 3) * 8192 : FIN_A1 + kb * 8192), sb = sbase + kb * 16384;
            asm volatile("wgmma.fence.sync.aligned;" ::: "memory");
            #pragma unroll
            for (int kk = 0; kk < BK / 16; kk++)
                wgmma_m64n128k16(acc, make_desc(sa + kk * 32, 16, 1024), make_desc(sb + kk * 2048, 8192, 1024), (kb | kk) != 0);
            asm volatile("wgmma.commit_group.sync.aligned;" ::: "memory");
            asm volatile("wgmma.wait_group.sync.aligned 1;" ::: "memory");
            if (h == 0 && kb >= 1 && kb <= 4 && t128 == 0) mbar_arrive(bar + FB_E0 + 8 * (kb - 1));
        }
        asm volatile("wgmma.wait_group.sync.aligned 0;" ::: "memory");
        const uint32_t red = sbase + FIN_A0;
        auto ready = [&](int i) {
            named_bar_sync(1, 128);
            if (t128 < FIN_SPLIT)
                asm volatile("mbarrier.arrive.relaxed.cluster.shared::cluster.b64 _, [%0];" ::"r"(mapa(bar + FB_RDY + 8 * i, t128)) : "memory");
        };
        if (tid == 256) KMARK(16);
        if (tid == 128) KMARK(19);
        if (h == 0) ready(0);
        mbar_wait(bar + FB_RDY + 8 * h, 0);
        if (tid == 256) KMARK(17);
        #pragma unroll
        for (int q = 0; q < FIN_SPLIT; q++) {
            if (q != rank) {
                const uint32_t dst = mapa(red + (rank - (rank > q ? 1 : 0)) * 4096 + t128 * 16, q), rb = mapa(bar + FB_RED + 8 * h, q);
                #pragma unroll
                for (int j = 0; j < 2; j++)
                    asm volatile("st.async.weak.shared::cluster.mbarrier::complete_tx::bytes.v4.f32 [%0], {%1,%2,%3,%4}, [%5];"
                                 ::"r"(dst + j * 2048), "f"(acc[8 * q + 4 * j]), "f"(acc[8 * q + 4 * j + 1]),
                                   "f"(acc[8 * q + 4 * j + 2]), "f"(acc[8 * q + 4 * j + 3]), "r"(rb) : "memory");
            }
        }
        float o[8];
        #pragma unroll
        for (int q = 0; q < FIN_SPLIT; q++)
            if (q == rank) {
                #pragma unroll
                for (int e = 0; e < 8; e++) o[e] = acc[8 * q + e];
            }
        mbar_wait(bar + FB_RED + 8 * h, 0);
        if (tid == 256) KMARK(18);
        if (tid == 128) KMARK(20);
        #pragma unroll
        for (int sl = 0; sl < FIN_SPLIT - 1; sl++) {
            #pragma unroll
            for (int j = 0; j < 2; j++) {
                const uint4 v = lds128(red + sl * 4096 + j * 2048 + t128 * 16);
                o[4 * j] += __uint_as_float(v.x); o[4 * j + 1] += __uint_as_float(v.y);
                o[4 * j + 2] += __uint_as_float(v.z); o[4 * j + 3] += __uint_as_float(v.w);
            }
        }
        if (h == 0) ready(1);
        __nv_bfloat16* dst = p.out + (size_t)(p.mt * BM + h * 64 + wi * 16 + (lane >> 2)) * (2 * DM) + nt * 128 + rank * 16 + (lane & 3) * 2;
        #pragma unroll
        for (int j = 0; j < 2; j++) {
            *reinterpret_cast<uint32_t*>(dst + j * 8) = pack_bf16(o[4 * j], o[4 * j + 1]);
            *reinterpret_cast<uint32_t*>(dst + (size_t)8 * (2 * DM) + j * 8) = pack_bf16(o[4 * j + 2], o[4 * j + 3]);
        }
        if (t128 == 0) KEXIT(5);
    }
}

#define POLL_DELAY 2
#define FETCH_DELAY 360
#define AT_PF 7
#define TOK_MOVED1 4
#define AT_POS0 0
#define FETCH_REL 1
#define REPOLL 1
#define V_EARLY 6
#define XB_POS 0
#define PARK_LATE 0
#define ST_POS 1
#define RST_POS 0
#define KV_POS 1
#define X0_POS 2
#define SPEC_SUM 0
#define AT_FIRST 4
#define AT_AHEAD 4
#define PRO_EARLY 0
#define PDL_POS 5
#define WO_FENCE 0
#define WO_PFA 4
#define WO_PFB_DELAY 60
#define EXP 0
#define NO_COMM 0
#define TOK_MOVED 8
#define XB_DELAY 0
#define WO_PF0 0
#define WO_PF1 11
#define WO_AHEAD 10
constexpr int REC_THREADS = 256;
constexpr uint32_t POLL_LIMIT = 1u << 16;
constexpr int NREG = 24;
__host__ __device__ constexpr int reg_idx(int j) { return ((j & 3) - 1) * 8 + (j >> 2); }
constexpr int SM_WQ = 0;
constexpr int SM_WO = 65536;
constexpr int SM_X = SM_WO + 11 * 8192;
constexpr int SM_PARK0 = SM_X, SM_PARK1 = SM_X + 8192;
constexpr int SM_MEM = SM_X + 4 * 4096;
constexpr int SM_RED = SM_X + 8 * 4096;
constexpr int SM_V = SM_X + 12 * 4096;
constexpr int SM_K = SM_X + 14 * 4096;
constexpr int SM_QS = SM_X + 15 * 4096;
constexpr int SM_QK = SM_X + 65536;
constexpr int SM_SP = SM_QK + 2048;
constexpr int SM_VM = SM_SP + 2560;
constexpr int SM_O = SM_VM + 2048;
constexpr int SM_SUM = SM_O + 2048;
constexpr int SM_TBL = SM_SUM + 128;
constexpr int SM_BAR = SM_TBL + 512;
constexpr int SM_STAMP = SM_BAR + 224;
constexpr int REC_SMEM = SM_STAMP;
static_assert(REC_SMEM <= 232448, "shared memory");
enum { BAR_V = 0, BAR_X = 8, BAR_P0 = 16, BAR_WQ = 40, BAR_WO = 48, BAR_XG = 56, BAR_F0 = 88, BAR_F3 = 96, BAR_VF = 104,
       BAR_M = 112, BAR_GO = 144, BAR_PK = 152, BAR_VM = 160, BAR_SELF = 168, BAR_TPUB = 176, BAR_MIN = 176, BAR_PUB = 192 };

template <int V> struct IntC { static constexpr int value = V; };
template <int I, int N, typename F> __device__ __forceinline__ void sfor(F&& f) {
    if constexpr (I < N) { f(IntC<I>{}); sfor<I + 1, N>(f); }
}

struct RecParams {
    CUtensorMap tmW[3];
    CUtensorMap tmWo;
    CUtensorMap tmX;
    const __nv_bfloat16* mem0;
    __nv_bfloat16* qkv_tok;
    __nv_bfloat16* kv_mem;
    uint8_t* xchg;
    uint32_t* flags;
    uint32_t one[2];
    uint32_t* arrivals;
};

__device__ __forceinline__ void mma_a(float* d, const uint32_t* a, uint32_t b0, uint32_t b1) {
    mma16816(d, a[0], a[1], a[2], a[3], b0, b1);
}
__device__ __forceinline__ void ldsm4(uint32_t addr, uint32_t* r) { ldsm_x4(addr, r[0], r[1], r[2], r[3]); }
__device__ __forceinline__ void ldsm4t(uint32_t addr, uint32_t* r) { ldsm_x4_t(addr, r[0], r[1], r[2], r[3]); }
template <int OFF> __device__ __forceinline__ void poll_v2(uint2& v, const uint8_t* p) {
    asm volatile("ld.relaxed.gpu.global.v2.b32 {%0,%1}, [%2+%3];" : "=r"(v.x), "=r"(v.y) : "l"(p), "n"(OFF) : "memory");
}
template <int OFF> __device__ __forceinline__ void repoll_v2(uint2& v, const uint8_t* p) {
    asm volatile("{\n.reg .pred q;\nsetp.eq.u32 q, %1, 0xFFFFFFFF;\n@q ld.relaxed.gpu.global.v2.b32 {%0,%1}, [%2+%3];\n}"
                 : "+r"(v.x), "+r"(v.y) : "l"(p), "n"(OFF) : "memory");
}
__device__ __forceinline__ uint32_t max3(uint32_t a, uint32_t b, uint32_t c) { return max(max(a, b), c); }
__device__ __forceinline__ uint32_t pub_slot(int s) { return (s & 1) * XCHG_SLOT + ((s >> 1) & 1) * PUB_BYTES; }

__device__ __forceinline__ uint8_t* xaddr(uint32_t lo, uint32_t hi) {
    uint64_t a;
    asm("mov.b64 %0, {%1, %2};" : "=l"(a) : "r"(lo), "r"(hi));
    return reinterpret_cast<uint8_t*>(a);
}
template <int N> __device__ __forceinline__ uint32_t delay_zero(uint32_t a) {
    uint32_t x = a;
    #pragma unroll
    for (int i = 0; i < N; i++) x = lds32_volatile(x);
    return x - a;
}
__device__ __forceinline__ uint32_t fresh(uint32_t x) { asm volatile("" : "+r"(x)); return x; }

template <int NT> __device__ __forceinline__ uint32_t wo_addr(uint32_t ao, uint32_t a3, int n) {
    return (n % NT == 2 ? a3 : ao + (n % NT) * 32768) + (n / NT) * 1024;
}
__device__ __forceinline__ void sched_fence(uint32_t& x, uint32_t zero) { x ^= clock32() & zero; }
template <int NT, int PF, typename F>
__device__ __forceinline__ void wo_phase(F&& hook, uint32_t (&st)[8 * NT][4], uint32_t ao, uint32_t a3, uint32_t l16, uint32_t tbl, uint32_t sums,
                                         uint32_t slot, uint32_t xhi, uint32_t third, uint32_t zero, uint32_t& tok, uint32_t xbar, uint32_t xpar, bool& x_ok) {
    constexpr int AHEAD = PF > WO_AHEAD ? PF - NT : WO_AHEAD;
    uint32_t of[4][4];
    uint2 sm;
    uint4 t;
    ldsm4t(l16 + SM_O, of[0]);
    #pragma unroll
    for (int n = PF; n < AHEAD; n++) {
        ldsm4t(wo_addr<NT>(ao, a3, n), st[n]);
        if (n == 2 * NT - 1) ldsm4t(l16 + SM_O + 512, of[1]);
    }
    if (PF >= 2 * NT) ldsm4t(l16 + SM_O + 512, of[1]);
    float acc[NT][4];
    #pragma unroll
    for (int i = 0; i < NT; i++) { acc[i][0] = acc[i][1] = acc[i][2] = acc[i][3] = 0.f; }
    #pragma unroll
    for (int kk = 0; kk < 8; kk++) {
        if (WO_FENCE && kk < 7) sched_fence(tok, zero);
        #pragma unroll
        for (int i = 0; i < NT; i++) {
            const int n = kk * NT + i;
            mma_a(acc[i], st[n], of[kk >> 1][(kk & 1) * 2], of[kk >> 1][(kk & 1) * 2 + 1]);
            if (n + AHEAD >= PF && n + AHEAD < 8 * NT) ldsm4t(wo_addr<NT>(ao, a3, n + AHEAD), st[n + AHEAD]);
        }
        if (kk == XB_POS - 1) hook();
        if (kk == 1 || kk == 3) ldsm4t(l16 + SM_O + ((kk >> 1) + 2) * 512, of[(kk >> 1) + 2]);
        if (kk == (NT == 3 ? 5 : 4)) {
            const uint32_t x = fresh(l16);
            sm = lds64(sums + ((x >> 1) & 0x18));
            t = lds128(tbl + ((x >> 3) & 0x30));
            x_ok = mbar_test_wait(xbar, xpar);
        }
    }
    const float i0 = rcp(__uint_as_float(sm.x)), i1 = rcp(__uint_as_float(sm.y));
    const uint32_t d = slot + ((fresh(l16) >> 1) & 0x38);
    const uint32_t pl[3] = {t.x + d, t.y + d, t.z + d};
    #pragma unroll
    for (int i = 0; i < NT; i++)
        asm volatile("{\n.reg .pred p;\nsetp.ne.u32 p, %3, 0;\n@p st.relaxed.gpu.global.v2.b32 [%0], {%1,%2};\n}"
                     ::"l"(xaddr(pl[i], xhi)), "r"(pack_bf16(acc[i][0] * i0, acc[i][1] * i1)), "r"(pack_bf16(acc[i][2] * i0, acc[i][3] * i1)),
                       "r"(i < 2 ? 1u : third) : "memory");
}

constexpr uint32_t SMEM_ORIGIN = 1024;
constexpr uint64_t DESC_BASE = (1ull << 16) | (0x40000040ull << 32);
template <int OFFB, int SCALE_D>
__device__ __forceinline__ void wgmma_n32_rs(float (&d)[16], const uint32_t* a, uint32_t one) {
    asm volatile(
        "{\n.reg .b64 db;\nmad.wide.u32 db, %20, %21, %22;\n"
        "wgmma.mma_async.sync.aligned.m64n32k16.f32.bf16.bf16 {%0,%1,%2,%3,%4,%5,%6,%7,%8,%9,%10,%11,%12,%13,%14,%15}, "
        "{%16,%17,%18,%19}, db, %23, 1, 1, 0;\n}"
        : "+f"(d[0]), "+f"(d[1]), "+f"(d[2]), "+f"(d[3]), "+f"(d[4]), "+f"(d[5]), "+f"(d[6]), "+f"(d[7]),
          "+f"(d[8]), "+f"(d[9]), "+f"(d[10]), "+f"(d[11]), "+f"(d[12]), "+f"(d[13]), "+f"(d[14]), "+f"(d[15])
        : "r"(a[0]), "r"(a[1]), "r"(a[2]), "r"(a[3]), "r"(one), "n"((SMEM_ORIGIN + OFFB) >> 4), "l"(DESC_BASE), "n"(SCALE_D));
}
template <int OFFA, int OFFB, int SCALE_D>
__device__ __forceinline__ void wgmma_n32_ss(float (&d)[16], uint32_t one) {
    asm volatile(
        "{\n.reg .b64 da, db;\nmad.wide.u32 da, %16, %17, %19;\nmad.wide.u32 db, %16, %18, %19;\n"
        "wgmma.mma_async.sync.aligned.m64n32k16.f32.bf16.bf16 {%0,%1,%2,%3,%4,%5,%6,%7,%8,%9,%10,%11,%12,%13,%14,%15}, "
        "da, db, %20, 1, 1, 1, 0;\n}"
        : "+f"(d[0]), "+f"(d[1]), "+f"(d[2]), "+f"(d[3]), "+f"(d[4]), "+f"(d[5]), "+f"(d[6]), "+f"(d[7]),
          "+f"(d[8]), "+f"(d[9]), "+f"(d[10]), "+f"(d[11]), "+f"(d[12]), "+f"(d[13]), "+f"(d[14]), "+f"(d[15])
        : "r"(one), "n"((SMEM_ORIGIN + OFFA) >> 4), "n"((SMEM_ORIGIN + OFFB) >> 4), "l"(DESC_BASE), "n"(SCALE_D));
}
template <int WG, int J0, int J1, int I, bool ACC, bool FENCE = true>
__device__ __forceinline__ void token_mma(float (&ta)[2][16], const uint32_t (&wr)[NREG][2][4], uint32_t one) {
    if (FENCE) asm volatile("wgmma.fence.sync.aligned;" ::: "memory");
    sfor<J0, J1>([&](auto J) {
        constexpr int j = J.value, c = j >> 2, offb = SM_X + WG * 32768 + c * 4096 + (j & 3) * 32, sc = (ACC || j != J0) ? 1 : 0;
        if constexpr ((j & 3) != 0) wgmma_n32_rs<offb, sc>(ta[I], wr[reg_idx(j)][I], one);
        else if constexpr (WG == 0 || c >= (I ? TOK_MOVED1 : TOK_MOVED)) wgmma_n32_ss<SM_WQ + WG * 32768 + I * 16384 + c * 2048, offb, sc>(ta[I], one);
        constexpr int m = I ? c : c - 4;
        if constexpr (WG == 0 && (j & 3) == 1 && m >= 0 && m < (I ? TOK_MOVED : TOK_MOVED1))
            wgmma_n32_ss<SM_WQ + 32768 + (1 - I) * 16384 + m * 2048, SM_X + 32768 + m * 4096, 1>(ta[I], one);
    });
    asm volatile("wgmma.commit_group.sync.aligned;" ::: "memory");
}
__device__ __forceinline__ void warp_arrive(uint32_t bar) {
    __syncwarp();
    if (elect_one()) mbar_arrive(bar);
}
__device__ __forceinline__ void remote_arrive(uint32_t bar, uint32_t rank) {
    asm volatile("mbarrier.arrive.relaxed.cluster.shared::cluster.b64 _, [%0];" ::"r"(mapa(bar, rank)) : "memory");
}
__device__ __forceinline__ void x_load(const RecParams& p, uint32_t sb, int sg, int g) {
    if ((EXP >> g) & 1) return;
    tma_load_3d_mc(sb + SM_X + g * 16384, &p.tmX, 0, sg * SEG, g * 4, sb + SM_BAR + BAR_XG + 8 * g, (uint16_t)7);
}

__device__ __forceinline__ void rec_steps(const RecParams& p, const uint32_t (&wr)[NREG][2][4], const uint32_t sb, const int warp,
                                          const int cta, const int head, const int rank) {
    const int wq = warp & 3, wg = warp >> 2;
    const uint32_t bar = sb + SM_BAR;
    const uint32_t xhi = (uint32_t)((uint64_t)p.xchg >> 32);
    const float sl2 = 0.08838834764831845f * 1.4426950408889634f;
    const bool has_unit = warp >= 5 && (warp < 7 || cta < 64);
    const bool qk = rank < 2;
    const uint32_t pa = rank == 2 ? 0 : rank + 1, pb = rank == 0 ? 2 : rank - 1;
    const uint32_t tbl = sb + SM_TBL + warp * 64;
    const bool att = (warp & 6) == 2;
    const int stile = warp < 5 ? warp : warp - 3;

    const uint32_t u_st = uniform(SM_QK - SM_WQ - wg * (32768 - 1024));
    const uint32_t u_xa = uniform(sb + (qk ? SM_SP + rank * 1280 + stile * 256 : SM_VM + warp * 256));
    const uint32_t u_key = uniform(!qk || att || warp == 7 ? 0 : sb + (warp == 4 ? SM_QK + 1024 : SM_K + stile * 1024));
    const uint32_t u_bx = uniform(bar + (qk ? BAR_X : BAR_VM)), u_bra = uniform(mapa(u_bx, pa)), u_brb = uniform(mapa(u_bx, pb));
    const uint32_t u_src = uniform(lds32_volatile(tbl + 44));
    const uint32_t u_kv = uniform(qk && wg == 0 ? ~0u : (((rank >> 1) * NSEG * NH + head) * 8 + (qk ? rank * 4 + wq : warp)) * 64);
    const uint32_t u_free = uniform(mapa(bar + (warp == 5 ? BAR_VF : BAR_F0), warp == 5 ? 2 : 0));
    const uint32_t u_role = uniform((has_unit ? 1 : 0) | (att ? 2 : 0) | (wg == 1 || qk ? 4 : 0) | (!qk && warp == 0 ? 8 : 0) | (rank != 0 && warp == (XB_POS ? 2 : 1) ? 16 : 0) |
                                    (warp == 5 || warp == 6 ? 32 : 0));
    uint32_t l16, aq, ao;
    {
        const int lane = threadIdx.x & 31, mi = lane >> 3, r8 = lane & 7, r16 = (mi >> 1) * 8 + r8;
        l16 = opaque(sb + lane * 16);
        aq = opaque(sb + SM_WQ + wg * 32768 + r16 * 128 + (((wq * 2 + (mi & 1)) ^ r8) << 4));
        ao = opaque(sb + SM_WO + (warp >> 1) * 8192 + r16 * 64 + ((((warp & 1) * 2 + (mi & 1)) ^ ((r8 >> 1) & 3)) << 4));
    }

    uint32_t mphase = 0;
    bool x0_ok = false;
    #pragma unroll 1
    for (int s = 0;; s++) {
        const uint32_t par = s & 1;
        uint32_t at[16][4];
        auto at_early = [](int i) { return i < 2 || ((i & 1) == 1 && (i >> 1) <= AT_PF - 2); };
        auto at_prefetch = [&](bool first) {
            #pragma unroll
            for (int i = 0; i < 16; i++)
                if (at_early(i) && first == ((i & 1) == 1 && (i >> 1) < AT_FIRST)) ldsm4t(aq + (i & 1) * 16384 + (i >> 1) * 2048, at[i]);
        };
        auto resets = [&](int late) {
            if ((u_role & 1) && (late || s > 0)) {
                const uint32_t lane = (fresh(l16) >> 4) & 31;
                uint8_t* ib = xaddr(lds32_volatile(tbl + 12) + (par ^ late) * XCHG_SLOT + lane * 16, xhi);
                #pragma unroll
                for (int i = 0; i < 4; i++) st_relaxed_v4(ib + i * 512, SENT);
                st_relaxed_b32(xaddr(lds32_volatile(tbl + 28) + pub_slot(s + 2 + late) + (lane & 16) * 256 + (lane & 8) * 16 + (lane & 7) * 4, xhi), SENT);
            }
        };
        auto tile_stores = [&]() {
            if (warp == 4) {
                asm volatile("fence.proxy.async.shared::cta;" ::: "memory");
                if (elect_one()) {
                    __nv_bfloat16* dst = p.qkv_tok + ((size_t)s * NH + head) * (SEG * DH);
                    constexpr size_t MAT = (size_t)NSEG * NH * SEG * DH;
                    bulk_store(dst + (qk ? rank * (SEG * 64) : 2 * MAT), sb + (qk ? SM_QS : SM_V), (EXP & 32) ? 32 : 4096);
                    bulk_store(dst + (qk ? MAT + rank * (SEG * 64) : 2 * MAT + SEG * 64), sb + (qk ? SM_K : SM_V + 4096), (EXP & 32) ? 32 : 4096);
                    bulk_commit();
                }
            }
        };
        if (wg == 0) {
            float ta[2][16];
            if (!x0_ok) mbar_wait_bounded(bar + BAR_XG, par);
            STAMP(6);
            auto park = [&](int i, uint32_t dst) {
                #pragma unroll
                for (int e = 0; e < 16; e++) asm volatile("" : "+f"(ta[i][e]));
                #pragma unroll
                for (int j = 0; j < ((EXP & 128) ? 2 : 4); j++)
                    sts128(l16 + dst + j * 2048 + wq * 512, __float_as_uint(ta[i][4 * j]), __float_as_uint(ta[i][4 * j + 1]),
                           __float_as_uint(ta[i][4 * j + 2]), __float_as_uint(ta[i][4 * j + 3]));
            };
            if (EXP & 64) spin_clks(1200);
            token_mma<0, 0, 16, 0, false>(ta, wr, 1);
            mbar_wait_bounded(bar + BAR_XG + 8, par);
            if (TOK_MOVED1 > 0) mbar_wait_bounded(bar + BAR_XG + 16, par);
            if (AT_POS0 == 0) at_prefetch(true);
            token_mma<0, 16, 32, 0, true>(ta, wr, p.one[1]);
            if (TOK_MOVED1 == 0) mbar_wait_bounded(bar + BAR_XG + 16, par);
            token_mma<0, 0, 16, 1, false, TOK_MOVED1 == 0>(ta, wr, p.one[0]);
            if (TOK_MOVED > 4) mbar_wait_bounded(bar + BAR_XG + 24, par);
            token_mma<0, 16, 32, 1, true, (TOK_MOVED > 4)>(ta, wr, 1);
            asm volatile("wgmma.wait_group.sync.aligned 1;" ::: "memory");
            if (PARK_LATE) mbar_wait_bounded(bar + BAR_PUB, par);
            park(0, SM_PARK0);
            warp_arrive(bar + BAR_GO);
            asm volatile("wgmma.wait_group.sync.aligned 0;" ::: "memory");
            park(1, SM_PARK1);
            if (TOK_MOVED <= 4) mbar_wait_bounded(bar + BAR_XG + 24, par);
            warp_arrive(bar + BAR_PK);
            const uint8_t* src = xaddr(u_src + pub_slot(s), xhi);
            auto fetch = [&]() {
                if (elect_one()) {
                    mbar_arrive_expect_tx(bar + BAR_M + 8 * wq, 4096);
                    bulk_load(sb + SM_MEM + wq * 4096, src, 4096, bar + BAR_M + 8 * wq);
                }
            };
            if (!PARK_LATE) named_bar_sync(7, REC_THREADS - 32);
            if (FETCH_REL) {
                const uint4 t = lds128(bar + BAR_TPUB);
                const uint32_t now = clock32();
                spin_until(now + FETCH_DELAY - min(min(min(now - t.y, now - t.z), now - t.w), (uint32_t)FETCH_DELAY));
            } else {
                spin_clks(FETCH_DELAY);
            }
            fetch();
            STAMP(12);
            if (warp == 0 && elect_one()) {
                if (qk) mbar_arrive_expect_tx(bar + BAR_V, (EXP & 16) ? 32 : 8192);
                mbar_arrive_expect_tx(bar + BAR_X, qk ? 1280 : 2560);
                mbar_arrive_expect_tx(bar + BAR_VM, qk ? 2048 : 0);
            }
            if (AT_POS0 == 1) at_prefetch(true);
            at_prefetch(false);
            const uint32_t x = fresh(l16) - sb;
            const uint32_t ca = sb + SM_MEM + wq * 4096 + x * 2 + ((x >> 4) & 0x1C);
            #pragma unroll 1
            for (uint32_t n = 0; n < POLL_LIMIT; n++) {
                mbar_wait_bounded(bar + BAR_M + 8 * wq, mphase);
                mphase ^= 1;
                const uint32_t c0 = lds32_volatile(ca), c1 = lds32_volatile(ca + 1024), c2 = lds32_volatile(ca + 2048), c3 = lds32_volatile(ca + 3072);
                if (!__any_sync(~0u, max(max3(c0, c1, c2), c3) == (NO_COMM ? 0x12345u : SENT))) break;
                fetch();
            }
            STAMP(0);
            named_bar_sync(0, REC_THREADS);
            if (X0_POS == 2 && warp == 0 && rank == 0 && s + 1 < NSEG) {
                mbar_wait_bounded(bar + BAR_F0, par);
                if (elect_one()) x_load(p, sb, s + 1, 0);
            }
            if (u_role & 8) {
                asm volatile("fence.proxy.async.shared::cta;" ::: "memory");
                mbar_wait_bounded(bar + BAR_VF, par);
                if (s < NSEG - 1 && elect_one()) {
                    #pragma unroll
                    for (int r = 0; r < 2; r++)
                        asm volatile("cp.async.bulk.shared::cluster.shared::cta.mbarrier::complete_tx::bytes [%0], [%1], %2, [%3];"
                                     ::"r"(mapa(sb + SM_V, r)), "r"(sb + SM_V), "r"((EXP & 16) ? 32 : 8192), "r"(mapa(bar + BAR_V, r)) : "memory");
                }
            }
        } else {
            at_prefetch(true);
            if (RST_POS == 2) resets(0);
            if (s > 0) {
                if (u_role & 1) {
                    const uint32_t ln = (fresh(l16) >> 4) & 31;
                    const uint32_t ibl = lds32_volatile(tbl + 12) + (par ^ 1) * XCHG_SLOT + ln * 8;
                    const uint32_t publ = lds32_volatile(tbl + 28) + pub_slot(s) + (ln & 16) * 256 + (ln & 8) * 16 + (ln & 7) * 4;
                    const bool odd = ln & 8;
                    const uint8_t* ib = xaddr(ibl + delay_zero<POLL_DELAY>(bar + BAR_SELF), xhi);
                    STAMP(8);
                    uint2 v[8];
                    float a0, a1, a2, a3;
                    auto sum8 = [&]() {
                        a0 = ((bf16_lo(v[0].x) + bf16_lo(v[1].x)) + (bf16_lo(v[2].x) + bf16_lo(v[3].x))) +
                             ((bf16_lo(v[4].x) + bf16_lo(v[5].x)) + (bf16_lo(v[6].x) + bf16_lo(v[7].x)));
                        a1 = ((bf16_hi(v[0].x) + bf16_hi(v[1].x)) + (bf16_hi(v[2].x) + bf16_hi(v[3].x))) +
                             ((bf16_hi(v[4].x) + bf16_hi(v[5].x)) + (bf16_hi(v[6].x) + bf16_hi(v[7].x)));
                        a2 = ((bf16_lo(v[0].y) + bf16_lo(v[1].y)) + (bf16_lo(v[2].y) + bf16_lo(v[3].y))) +
                             ((bf16_lo(v[4].y) + bf16_lo(v[5].y)) + (bf16_lo(v[6].y) + bf16_lo(v[7].y)));
                        a3 = ((bf16_hi(v[0].y) + bf16_hi(v[1].y)) + (bf16_hi(v[2].y) + bf16_hi(v[3].y))) +
                             ((bf16_hi(v[4].y) + bf16_hi(v[5].y)) + (bf16_hi(v[6].y) + bf16_hi(v[7].y)));
                    };
                    if (REPOLL) {
                        #pragma unroll
                        for (int i = 0; i < 8; i++) v[i] = make_uint2(SENT, SENT);
                    }
                    #pragma unroll 1
                    for (uint32_t n = 0; n < POLL_LIMIT; n++) {
                        if (REPOLL) sfor<0, 8>([&](auto I) { repoll_v2<I.value * 256>(v[I.value], ib); });
                        else sfor<0, 8>([&](auto I) { poll_v2<I.value * 256>(v[I.value], ib); });
                        const uint32_t mx = max(max3(v[0].y, v[1].y, v[2].y), max3(max3(v[3].y, v[4].y, v[5].y), v[6].y, v[7].y));
                        if (SPEC_SUM) { sum8(); asm volatile("" : "+f"(a0), "+f"(a1), "+f"(a2), "+f"(a3)); }
                        if (!__any_sync(~0u, mx == (NO_COMM ? 0x12345u : SENT))) break;
                    }
                    STAMP(9);
                    if (!SPEC_SUM) sum8();
                    float k0 = odd ? a2 : a0, k1 = odd ? a3 : a1;
                    k0 += __shfl_xor_sync(~0u, odd ? a0 : a2, 8);
                    k1 += __shfl_xor_sync(~0u, odd ? a1 : a3, 8);
                    k0 += __shfl_xor_sync(~0u, k0, 16);
                    k1 += __shfl_xor_sync(~0u, k1, 16);
                    st_relaxed_b32(xaddr(publ, xhi), pack_bf16(k0, k1));
                    STAMP(11);
                } else if (warp == 4) {
                    bulk_wait_read_all();
                    if (elect_one()) remote_arrive(bar + BAR_F3, 2);
                    if (!qk) {
                        mbar_wait_bounded(bar + BAR_F3, par ^ 1);
                        if (elect_one()) x_load(p, sb, s, 3);
                    }
                    if (elect_one()) {
                        bulk_wait_all();
                        signal_flag(p.flags + F_PROGRESS + s - 1);
                    }
                    __syncwarp();
                    STAMP(10);
                }
            }
            float ta[2][16];
            uint32_t w[8];
            auto unpark = [&](int i, uint32_t src) {
                mbar_wait_bounded(bar + (i ? BAR_GO : BAR_PK), par);
                #pragma unroll
                for (int j = 0; j < 4; j++) {
                    uint4 v = make_uint4(0, 0, 0, 0);
                    if (!(EXP & 128) || j < 2) v = lds128(l16 + src + j * 2048 + wq * 512);
                    ta[i][4 * j] = __uint_as_float(v.x); ta[i][4 * j + 1] = __uint_as_float(v.y);
                    ta[i][4 * j + 2] = __uint_as_float(v.z); ta[i][4 * j + 3] = __uint_as_float(v.w);
                }
            };
            if (FETCH_REL) sts32(bar + BAR_TPUB + 4 * wq, clock32());
            if (warp != 4) { if (PARK_LATE) warp_arrive(bar + BAR_PUB); else named_bar_arrive(7, REC_THREADS - 32); }
            unpark(1, SM_PARK0);
            STAMP(6);
            token_mma<1, 0, 16, 1, true>(ta, wr, 1);
            if (RST_POS == 3) resets(0);
            unpark(0, SM_PARK1);
            token_mma<1, 16, 32, 1, true>(ta, wr, 1);
            token_mma<1, 16, 32, 0, true>(ta, wr, 1);
            token_mma<1, 0, 16, 0, true, false>(ta, wr, 1);
            auto put_tile = [&](int m, const uint32_t (&q)[8]) {
                #pragma unroll
                for (int h = 0; h < 2; h++) {
                    if (qk) asm volatile("stmatrix.sync.aligned.m8n8.x4.trans.shared.b16 [%0], {%1,%2,%3,%4};"
                                         ::"r"(aq - (SM_WQ + 32768) + (m ? SM_K : SM_QS) + h * 2048), "r"(q[4 * h]), "r"(q[4 * h + 1]),
                                           "r"(q[4 * h + 2]), "r"(q[4 * h + 3]) : "memory");
                    else sts128(l16 + SM_V + wq * 2048 + m * 1024 + h * 512, q[4 * h], q[4 * h + 1], q[4 * h + 2], q[4 * h + 3]);
                }
            };
            auto pack_tile = [&](int i) {
                #pragma unroll
                for (int e = 0; e < 16; e++) asm volatile("" : "+f"(ta[i][e]));
                #pragma unroll
                for (int j = 0; j < 8; j++) w[j] = pack_bf16(ta[i][2 * j], ta[i][2 * j + 1]);
            };
            asm volatile("wgmma.wait_group.sync.aligned 2;" ::: "memory");
            pack_tile(1);
            if (RST_POS == 4) resets(0);
            at_prefetch(false);
            asm volatile("wgmma.wait_group.sync.aligned 1;" ::: "memory");
            if ((u_role & 32) && elect_one())
                asm volatile("mbarrier.arrive.relaxed.cluster.shared::cluster.b64 _, [%0];" ::"r"(u_free) : "memory");
            put_tile(0, w);
            asm volatile("wgmma.wait_group.sync.aligned 0;" ::: "memory");
            pack_tile(0);
            put_tile(1, w);
            STAMP(0);
            named_bar_sync(0, REC_THREADS);
            if (s == NSEG - 1) tile_stores();
            STAMP(14);
        }
        const uint32_t mb = l16 + SM_MEM + wg * 8192;
        float acc[2][2][4];
        {
            uint32_t b[2][4];
            ldsm4t(mb, b[0]);
            ldsm4t(mb + 512, b[1]);
            #pragma unroll
            for (int i = 0; i < AT_AHEAD; i++)
                if (!at_early(i)) ldsm4t(aq + (i & 1) * 16384 + (i >> 1) * 2048, at[i]);
            STAMPD(1, b[0][0]);
            #pragma unroll
            for (int i = 0; i < 4; i++) { for (int e = 0; e < 4; e++) acc[i >> 1][i & 1][e] = 0.f; }
            #pragma unroll
            for (int u = 0; u < 16; u++) {
                #pragma unroll
                for (int h = 0; h < 2; h++) {
                    const int j = 2 * u + h;
                    #pragma unroll
                    for (int m = 0; m < 2; m++) {
                        if ((j & 3) == 0) mma_a(acc[h][m], at[(j >> 2) * 2 + m], b[u & 1][2 * h], b[u & 1][2 * h + 1]);
                        else mma_a(acc[h][m], wr[reg_idx(j)][m], b[u & 1][2 * h], b[u & 1][2 * h + 1]);
                    }
                }
                if (u + 2 < 16) ldsm4t(mb + (u + 2) * 512, b[u & 1]);
                if (u + AT_AHEAD < 16 && !at_early(u + AT_AHEAD))
                    ldsm4t(aq + ((u + AT_AHEAD) & 1) * 16384 + ((u + AT_AHEAD) >> 1) * 2048, at[u + AT_AHEAD]);
            }
        }
        sts128(l16 + SM_RED + warp * 512, __float_as_uint(acc[0][1][0] + acc[1][1][0]), __float_as_uint(acc[0][1][1] + acc[1][1][1]),
               __float_as_uint(acc[0][1][2] + acc[1][1][2]), __float_as_uint(acc[0][1][3] + acc[1][1][3]));
        #pragma unroll
        for (int e = 0; e < 4; e++) acc[0][0][e] += acc[1][0][e];
        const uint32_t x16 = fresh(l16);
        const uint32_t sa = fresh((x16 & 0x70) * 8 + ((((x16 >> 3) & 0x30) ^ x16) & 0x70));
        const uint32_t sq = fresh(sa ^ ((((x16 >> 7) ^ (x16 >> 8)) & 1) * 0x30));
        const uint32_t x8 = (x16 & 0x1F0) >> 1;
        const uint32_t xra = fresh(x8 + __byte_perm(u_xa, u_bra, 0x7210)), xrb = fresh(x8 + __byte_perm(u_xa, u_brb, 0x7210));
        STAMP(2);
        named_bar_sync(1 + wq, 64);
        uint32_t p0, p1;
        {
            const uint4 v = lds128(l16 + SM_RED + (warp ^ 4) * 512);
            p0 = pack_bf16(acc[0][0][0] + __uint_as_float(v.x), acc[0][0][1] + __uint_as_float(v.y));
            p1 = pack_bf16(acc[0][0][2] + __uint_as_float(v.z), acc[0][0][3] + __uint_as_float(v.w));
        }
        auto send = [&](uint32_t y0, uint32_t y1) {
            st_async_v2(xra, y0, y1, u_bra);
            st_async_v2(xrb, y0, y1, u_brb);
            sts64(x8 + u_xa, y0, y1);
            warp_arrive(u_bx);
        };
        if (qk) {
            asm volatile("stmatrix.sync.aligned.m8n8.x2.trans.shared.b16 [%0], {%1,%2};" ::"r"(aq + u_st), "r"(p0), "r"(p1) : "memory");
            named_bar_sync(5, REC_THREADS);
            if (u_key != 0) {
                uint32_t qa[2][4], kf[2][4];
                ldsm4(sq + sb + SM_QK, qa[0]);
                ldsm4(sa + u_key, kf[0]);
                ldsm4((sq ^ 64) + sb + SM_QK, qa[1]);
                ldsm4((sa ^ 64) + u_key, kf[1]);
                float se[4] = {0.f, 0.f, 0.f, 0.f}, so[4] = {0.f, 0.f, 0.f, 0.f};
                #pragma unroll
                for (int u = 0; u < 2; u++) {
                    mma_a(se, qa[u], kf[u][0], kf[u][1]);
                    mma_a(so, qa[u], kf[u][2], kf[u][3]);
                }
                send(__float_as_uint(se[0] + so[2]), __float_as_uint(se[1] + so[3]));
            }
        } else {
            send(p0, p1);
        }
        STAMP(3);
        const uint32_t lane = (fresh(l16) >> 4) & 31;
        auto kv_stores = [&]() {
            if (u_kv != ~0u) {
                uint32_t* dst = reinterpret_cast<uint32_t*>(p.kv_mem) + (u_kv + s * (NH * 512) + lane);
                dst[0] = p0;
                dst[32] = p1;
            }
        };
        if (((s + 1) & 62) == 0) {
            if (s == NSEG - 1) { kv_stores(); break; }
            mbar_wait_bounded(bar + BAR_WO, 0);
            if (PDL_POS == 5) pdl_launch_dependents();
            PSTAMP(8);
        }
        const uint32_t slot = par * XCHG_SLOT;
        if (u_role & 2) {
            if (qk) mbar_wait_bounded(bar + BAR_V, par);
            uint32_t vt[2][4][4];
            auto v_load = [&](int i0, int i1) {
                #pragma unroll
                for (int i = i0; i < i1; i++) {
                    const uint4 v = lds128(l16 + SM_V + (warp & 1) * 1024 + (i & 3) * 2048 + (i >> 2) * 512);
                    vt[i >> 2][i & 3][0] = v.x; vt[i >> 2][i & 3][1] = v.y; vt[i >> 2][i & 3][2] = v.z; vt[i >> 2][i & 3][3] = v.w;
                }
            };
            v_load(0, V_EARLY);
            kv_stores();
            const uint32_t l8 = fresh(sb + lane * 8);
            mbar_wait_bounded(bar + BAR_X, par);
            STAMP(4);
            float sv[10];
            #pragma unroll
            for (int j = 0; j < 5; j++) {
                const uint2 a = lds64(l8 + SM_SP + j * 256), b = lds64(l8 + SM_SP + 1280 + j * 256);
                sv[2 * j] = __uint_as_float(a.x) + __uint_as_float(b.x);
                sv[2 * j + 1] = __uint_as_float(a.y) + __uint_as_float(b.y);
            }
            float mx = fmaxf(fmaxf(fmaxf(sv[0], sv[1]), fmaxf(sv[2], sv[3])), fmaxf(fmaxf(sv[4], sv[5]), fmaxf(sv[6], sv[7])));
            mx = fmaxf(mx, fmaxf(sv[8], sv[9]));
            const float m1 = __shfl_xor_sync(~0u, mx, 1), m2 = __shfl_xor_sync(~0u, mx, 2), m3 = __shfl_xor_sync(~0u, mx, 3);
            __syncwarp();
            v_load(V_EARLY, 8);
            const bool vm_ok = mbar_test_wait(bar + BAR_VM, par);
            mx = fmaxf(fmaxf(mx, m1), fmaxf(m2, m3));
            const float mo = mx * sl2;
            #pragma unroll
            for (int j = 0; j < 10; j++) sv[j] = ex2(fmaf(sv[j], sl2, -mo));
            const uint32_t e0 = pack_bf16(sv[0], sv[1]), e1 = pack_bf16(sv[2], sv[3]);
            const uint32_t e2 = pack_bf16(sv[4], sv[5]), e3 = pack_bf16(sv[6], sv[7]), em = pack_bf16(sv[8], sv[9]);
            float o[4][4];
            #pragma unroll
            for (int i = 0; i < 4; i++) {
                o[i][0] = o[i][1] = o[i][2] = o[i][3] = 0.f;
                mma_a(o[i], vt[0][i], e0, e1);
            }
            const float sum = (((sv[0] + sv[1]) + (sv[2] + sv[3])) + ((sv[4] + sv[5]) + (sv[6] + sv[7]))) + (sv[8] + sv[9]);
            if (!vm_ok) mbar_wait_bounded(bar + BAR_VM, par);
            uint2 vm[4];
            #pragma unroll
            for (int i = 0; i < 4; i++) {
                vm[i] = lds64(l8 + SM_VM + (warp & 1) * 1024 + i * 256);
                mma_a(o[i], vt[1][i], e2, e3);
            }
            #pragma unroll
            for (int i = 0; i < 4; i++) mma1688(o[i], vm[i].x, vm[i].y, em);
            {
                const float s1 = __shfl_xor_sync(~0u, sum, 1), s2 = __shfl_xor_sync(~0u, sum, 2), s3 = __shfl_xor_sync(~0u, sum, 3);
                sts32(sb + SM_SUM + (lane & 28), __float_as_uint((sum + s1) + (s2 + s3)));
            }
            #pragma unroll
            for (int i = 0; i < 4; i += 2)
                stsm_x4(l16 + SM_O + (warp & 1) * 1024 + i * 256, pack_bf16(o[i][0], o[i][1]), pack_bf16(o[i][2], o[i][3]),
                        pack_bf16(o[i + 1][0], o[i + 1][1]), pack_bf16(o[i + 1][2], o[i + 1][3]));
            STAMP(5);
            uint32_t st[16][4];
            #pragma unroll
            for (int n = 0; n < WO_PF0; n++) ldsm4t(wo_addr<2>(ao, 0, n), st[n]);
            named_bar_sync(6, REC_THREADS);
            wo_phase<2, WO_PF0>([&]() { if ((u_role & 16) && elect_one()) x_load(p, sb, s + 1, rank); }, st, ao, 0, l16, tbl, sb + SM_SUM, slot, xhi, 0, p.one[0] - 1, aq, bar + BAR_XG, par ^ 1, x0_ok);
        } else {
            const uint32_t a3 = fresh(ao) + (wg == 0 ? 10 : 6) * 8192;
            uint32_t st[24][4];
            #pragma unroll
            for (int n = 0; n < WO_PFA; n++) ldsm4t(wo_addr<3>(ao, a3, n), st[n]);
            if (KV_POS == 0) kv_stores();
            if (ST_POS == 0) tile_stores();
            if (RST_POS == 0) resets(1);
            if (warp == 1) {
                if (elect_one()) {
                    #pragma unroll
                    for (int g = 0; g < 4; g++) mbar_arrive_expect_tx(bar + BAR_XG + 8 * g, ((EXP >> g) & 1) ? 0 : 16384);
                }
                if (s + 2 < NSEG && cta < 4 && elect_one())
                    asm volatile("cp.async.bulk.prefetch.tensor.3d.L2.global [%0, {%1, %2, %3}];"
                                 ::"l"(&p.tmX), "r"(0), "r"((s + 2) * SEG), "r"(cta * 4) : "memory");
                if (X0_POS == 0 && rank == 0) {
                    mbar_wait_bounded(bar + BAR_F0, par);
                    if (elect_one()) x_load(p, sb, s + 1, 0);
                }
            }
            if (WO_PFA < WO_PF1 || (u_role & 16)) mbar_wait_bounded(bar + BAR_X, par);
            if (WO_PFA < WO_PF1) {
                spin_clks(WO_PFB_DELAY);
                #pragma unroll
                for (int n = WO_PFA; n < WO_PF1; n++) ldsm4t(wo_addr<3>(ao, a3, n), st[n]);
            }
            if (ST_POS == 1) tile_stores();
            if (RST_POS == 1) resets(1);
            if (KV_POS == 1) kv_stores();
            if (X0_POS == 1 && warp == 1 && rank == 0) {
                mbar_wait_bounded(bar + BAR_F0, par);
                if (elect_one()) x_load(p, sb, s + 1, 0);
            }
            if (XB_POS == 0 && (u_role & 16)) {
                spin_clks(XB_DELAY);
                mbar_wait_bounded(bar + BAR_VM, par);
                if (elect_one()) x_load(p, sb, s + 1, rank);
            }
            named_bar_sync(6, REC_THREADS);
            wo_phase<3, WO_PF1>([]() {}, st, ao, a3, l16, tbl, sb + SM_SUM, slot, xhi, u_role & 4, p.one[0] - 1, aq, bar + BAR_XG, par ^ 1, x0_ok);
        }
        STAMP(7);
        if (wg == 0) named_bar_sync(9, REC_THREADS); else named_bar_arrive(9, REC_THREADS);
    }
    if (threadIdx.x == 128) KMARK(8);
    named_bar_sync(0, REC_THREADS);
    if (warp == 4) {
        if (elect_one()) {
            bulk_wait_all();
            signal_flag(p.flags + F_PROGRESS + NSEG - 1);
            KMARK(9);
        }
    } else if (warp == 0) {
        mbar_wait(bar + BAR_X, 1);
        mbar_wait(bar + BAR_VM, 1);
        if (rank == 0) mbar_wait(bar + BAR_F0, 1);
    }
}

__global__ void __launch_bounds__(REC_THREADS, 1) rec_kernel(const __grid_constant__ RecParams p) {
    extern __shared__ __align__(1024) uint8_t smem_raw[];
    const uint32_t sb = smem_u32(smem_raw);
    const int tid = threadIdx.x, lane = tid & 31;
    const int warp = __shfl_sync(~0u, tid >> 5, 0);
    const int cta = blockIdx.x, head = cta / 3, rank = cta % 3;
    const int wg = warp >> 2, wq = warp & 3;
    const uint32_t bar = sb + SM_BAR;
    uint8_t* const xb = p.xchg;
    const uint32_t xlo = (uint32_t)(uint64_t)xb;
    if ((sb & 0x3FFFF) != SMEM_ORIGIN) __trap();
    KENTER(1);
    auto w_box = [&](int part, int g, int i, uint32_t dst, uint32_t mb) {
        const int m = i ^ g;
        const CUtensorMap* tm = &p.tmW[rank == 2 ? 2 : m];
        const int col = head * DH + (rank == 2 ? m : rank) * 64, row = ((part + 1) & 3) * 16;
        tma_load_3d(dst, tm, col, row, g * 8, mb);
    };
    if (tid == 0) {
        mbar_init(bar + BAR_V, 1);
        for (int i = 0; i < 4; i++) { mbar_init(bar + BAR_XG + 8 * i, 1); mbar_init(bar + BAR_M + 8 * i, 1); }
        mbar_init(bar + BAR_GO, 4);
        mbar_init(bar + BAR_PUB, 3);
        mbar_init(bar + BAR_PK, 4);
        mbar_init(bar + BAR_VM, rank < 2 ? 1 : 9);
        mbar_init(bar + BAR_F0, 3);
        mbar_init(bar + BAR_F3, 3);
        mbar_init(bar + BAR_VF, 3);
        sts64(bar + BAR_MIN, ~0u, ~0u);
        mbar_init(bar + BAR_X, rank < 2 ? 6 : 1);
        for (int i = 0; i < 3; i++) mbar_init(bar + BAR_P0 + 8 * i, 1);
        mbar_init(bar + BAR_WQ, 1);
        mbar_init(bar + BAR_WO, 1);
        sts32(bar + BAR_SELF, bar + BAR_SELF);
        asm volatile("fence.mbarrier_init.release.cluster;" ::: "memory");
    }
    auto build_tables = [&](uint32_t av) {
        for (uint32_t n = 0; !__all_sync(~0u, (av >> 24) == 24); n++) {
            av = ld_acquire_b32(p.arrivals + (lane & 3));
            if (n > SPIN_LIMIT) __trap();
        }
        uint32_t cm[3];
        #pragma unroll
        for (int i = 0; i < 3; i++) {
            const int o = i * 32 + lane;
            cm[i] = __ballot_sync(~0u, __popc((__shfl_sync(~0u, av, o / 24) >> (o % 24 / 3 * 3)) & 7) >= 2);
        }
        auto color_of = [&](int o) { return ((o < 32 ? cm[0] : o < 64 ? cm[1] : cm[2]) >> (o & 31)) & 1u; };
        auto inbox = [&](int o, int byte) {
            uint32_t c = color_of(o);
            int ones = 0;
            #pragma unroll
            for (int i = 0; i < 3; i++) ones += __popc(o >= i * 32 + 32 ? cm[i] : (o > i * 32 ? cm[i] & ((1u << (o - i * 32)) - 1) : 0u));
            int idx = c ? ones : o - ones;
            if (idx >= INBOX_MAX) { idx = 2 * INBOX_MAX - 1 - idx; c ^= 1; }
            const uint32_t lin = idx * 6144 + byte, q = XCHG_INBOX + (lin >> 12) * 8192;
            return q + class_off(xlo + q, c) + (lin & 4095);
        };
        uint32_t off = 0;
        const int grp = (warp + 3) & 3;
        if (lane < 12) {
            const int i = lane >> 2, lt0 = rank * 6;
            const int o = i < 2 ? rank * 32 + warp * 4 + (lane & 3) : (lt0 + ((warp + 4) & 7)) * 4 + (lane & 3);
            off = inbox(min(o, 95), i * 2048 + head * 64);
        } else if (lane == 12) {
            off = inbox(cta, (grp % 3) * 2048);
        } else if (lane == 13) {
            int T;
            if (grp < 2) {
                T = (cta >> 5) * 22 + 8 * grp + ((cta & 31) >> 2);
            } else {
                const int tl = (cta & 63) >> 2;
                T = (tl / 6) * 22 + 16 + tl % 6;
            }
            off = XCHG_PUB + (T >> 4) * 8192 + (T & 15) * 256 + (cta & 3) * 32;
        } else if (lane == 14) {
            const uint32_t q = XCHG_PUB + wq * 8192;
            off = q + class_off(xlo + q, color_of(cta));
        }
        if (lane < 16) asm volatile("st.shared.b32 [%0], %1;" ::"r"(sb + SM_TBL + warp * 64 + (lane & 3) * 16 + (lane >> 2) * 4), "r"(xlo + off) : "memory");
    };
    if (tid >= 32 && tid < 37) asm volatile("prefetch.tensormap [%0];" ::"l"(&p.tmW[0] + (tid - 32)) : "memory");
    if (cta == 0) for (int i = tid; i < F_COUNT; i += REC_THREADS) p.flags[i] = 0;
    __syncthreads();
    auto stage = [](int part) { return ((part + 2) % 3) * 65536; };
    auto load_part = [&](int part) {
        mbar_arrive_expect_tx(bar + BAR_P0 + 8 * part, 65536);
        for (int u = 0; u < 4; u++) w_box(part, u >> 1, u & 1, sb + stage(part) + u * 16384, bar + BAR_P0 + 8 * part);
    };
    asm volatile("barrier.cluster.arrive.relaxed.aligned;" ::: "memory");
    uint4 img = make_uint4(SENT, SENT, SENT, SENT);
    if (cta >= 92) {
        const unsigned short* m = reinterpret_cast<const unsigned short*>(p.mem0) + (cta - 92) * 256 + tid;
        uint32_t w[4];
        #pragma unroll
        for (int i = 0; i < 4; i++) w[i] = (uint32_t)__ldg(m + 2 * i * DM) | ((uint32_t)__ldg(m + (2 * i + 1) * DM) << 16);
        img = make_uint4(w[0], w[1], w[2], w[3]);
    }
    {
        constexpr int NPAIR = (XCHG_SLOT + PUB_BYTES) / 8192;
        uint8_t* pr = xb + (4 + cta) * 8192;
        const uint32_t c0 = class_off(xlo + (4 + cta) * 8192, 0);
        #pragma unroll
        for (int c = 0; c < 2; c++) {
            const bool timed = lane == 0 || (lane == 8 && c == (warp & 1));
            reinterpret_cast<uint4*>(pr + (c0 ^ (c << 12)))[tid] = make_uint4(timed ? 0u : SENT, SENT, SENT, SENT);
        }
        __syncwarp();
        if (lane == 0) {
            uint32_t x = 0;
            for (int k = 0; k < 3; k++) {
                if (k == PRO_EARLY && warp == 0) load_part(0);
                const uint32_t c = (k + warp) & 1, t0 = clock_after(x);
                x = atomicExch(reinterpret_cast<uint32_t*>(pr + (c0 ^ (c << 12)) + warp * 512 + (k >> 1) * 128 + x), SENT);
                const uint32_t lat = clock_after(x) - t0;
                asm volatile("red.shared.min.u32 [%0], %1;" ::"r"(bar + BAR_MIN + 4 * c), "r"(lat) : "memory");
            }
        }
        __syncwarp();
        if (cta >= 92 || 100 + cta < NPAIR) {
            if (cta >= 92) {
                if (img.x == SENT) img.x = 0x7FFF7FFFu;
                if (img.y == SENT) img.y = 0x7FFF7FFFu;
                if (img.z == SENT) img.z = 0x7FFF7FFFu;
                if (img.w == SENT) img.w = 0x7FFF7FFFu;
            }
            uint8_t* q = xb + (cta >= 92 ? cta - 92 : 100 + cta) * 8192;
            reinterpret_cast<uint4*>(q)[tid] = img;
            reinterpret_cast<uint4*>(q + 4096)[tid] = img;
        }
    }
    __syncthreads();
    PSTAMP(4);
    if (tid == 0) {
        for (int part = PRO_EARLY < 3 ? 1 : 0; part < 3; part++) load_part(part);
    }
    if (tid == 224) {
        const uint32_t c = lds32_volatile(bar + BAR_MIN) > lds32_volatile(bar + BAR_MIN + 4) ? 1 : 0;
        asm volatile("red.release.gpu.global.add.u32 [%0], %1;" ::"l"(p.arrivals + cta / 24), "r"((1u << 24) | (c << (cta % 24))) : "memory");
        if (PDL_POS == 0) pdl_launch_dependents();
    }
    uint32_t wr[NREG][2][4];
    uint32_t arrived = 0;
    {
        const int mi = lane >> 3, r8 = lane & 7;
        const uint32_t a0 = sb + wg * 32768 + ((mi >> 1) * 8 + r8) * 128 + (((wq * 2 + (mi & 1)) ^ r8) << 4);
        #pragma unroll
        for (int part = 0; part < 3; part++) {
            mbar_wait_bounded(bar + BAR_P0 + 8 * part, 0);
            if (part == 0) arrived = ld_relaxed_b32(p.arrivals + (lane & 3));
            #pragma unroll
            for (int j = 0; j < 8; j++) {
                #pragma unroll
                for (int i = 0; i < 2; i++) ldsm4t(a0 + stage(part) + i * 16384 + j * 2048, wr[part * 8 + j][i]);
            }
            asm volatile("fence.proxy.async.shared::cta;" ::: "memory");
            __syncthreads();
            PSTAMP(5 + part);
            if (tid == 224 && PDL_POS == part + 1) pdl_launch_dependents();
            if (tid == 0) {
                if (part == 0) {
                    for (int g = 0; g < 4; g++) {
                        mbar_arrive_expect_tx(bar + BAR_XG + 8 * g, 16384);
                        tma_load_3d(sb + SM_X + g * 16384, &p.tmX, 0, 0, g * 4, bar + BAR_XG + 8 * g);
                    }
                } else if (part == 1) {
                    mbar_arrive_expect_tx(bar + BAR_WQ, 65536);
                    for (int u = 0; u < 4; u++) w_box(3, u >> 1, u & 1, sb + SM_WQ + u * 16384, bar + BAR_WQ);
                } else {
                    mbar_arrive_expect_tx(bar + BAR_WO, 11 * 8192);
                    tma_load_3d(sb + SM_WO, &p.tmWo, 0, head * DH, rank * 11, bar + BAR_WO);
                    if (cta < 4)
                        asm volatile("cp.async.bulk.prefetch.tensor.3d.L2.global [%0, {%1, %2, %3}];"
                                     ::"l"(&p.tmX), "r"(0), "r"(SEG), "r"(cta * 4) : "memory");
                }
            }
        }
    }
    build_tables(arrived);
    if (tid == 64) {
        uint32_t smid;
        asm volatile("mov.u32 %0, %%smid;" : "=r"(smid));
        if (smid < 384) atomicOr(p.flags + F_RECSM + (smid >> 5), 1u << (smid & 31));
    }
    __syncwarp();
    PSTAMP(9);
    mbar_wait(bar + BAR_WQ, 0);
    if (PDL_POS == 4) pdl_launch_dependents();
    asm volatile("barrier.cluster.wait.aligned;" ::: "memory");

    rec_steps(p, wr, sb, warp, cta, head, rank);
    if (cta == 0 && tid < 4) p.arrivals[tid] = 0;
    if (tid == 128) KEXIT(1);
}

constexpr int ATT_SLOT = 28672;
constexpr int ATT_PAIRS = 8;
constexpr int ATT_BAR = ATT_PAIRS * ATT_SLOT;
constexpr int ATT_CNT = ATT_BAR + ATT_PAIRS * 16;
constexpr int ATT_SMEM = ATT_CNT + 96 * 4;
constexpr int ATT_THREADS = ATT_PAIRS * 64 + 32;
static_assert(F_OA == F_OB + 16, "one range of flags");
struct AttnParams {
    CUtensorMap tmOa;
    CUtensorMap tmQb, tmKb;
    CUtensorMap tmOb;
    const __nv_bfloat16* qkv_tok;
    const __nv_bfloat16* kv_mem;
    uint32_t* flags;
};

__device__ __forceinline__ void tok_attn_warp(uint32_t base, int mh, int lane) {
    const uint32_t sq = base, sk = base + 8192, sv = base + 16384, skm = base + 24576, svm = skm + 2048;
    const int g = lane >> 2, c = lane & 3, mi = lane >> 3, r8 = lane & 7;
    const int ntile = mh ? 5 : 3;
    float sc[5][4];
    #pragma unroll
    for (int j = 0; j < 5; j++) { sc[j][0] = sc[j][1] = sc[j][2] = sc[j][3] = 0.f; }
    #pragma unroll
    for (int t2 = 0; t2 < 4; t2++) {
        uint32_t a[2][4];
        #pragma unroll
        for (int h = 0; h < 2; h++) {
            const int row = mh * 16 + (mi & 1) * 8 + r8, ch16 = 4 * t2 + 2 * h + (mi >> 1);
            ldsm_x4(sq + (ch16 >> 3) * 4096 + row * 128 + (((ch16 & 7) ^ r8) << 4), a[h][0], a[h][1], a[h][2], a[h][3]);
        }
        const int ch16 = 4 * t2 + mi;
        uint32_t b[5][4];
        #pragma unroll
        for (int j = 0; j < 5; j++) {
            if (j < ntile) {
                if (j == 0) ldsm_x4_t(skm + t2 * 512 + lane * 16, b[j][0], b[j][1], b[j][2], b[j][3]);
                else ldsm_x4(sk + (ch16 >> 3) * 4096 + ((j - 1) * 8 + r8) * 128 + (((ch16 & 7) ^ r8) << 4), b[j][0], b[j][1], b[j][2], b[j][3]);
            }
        }
        #pragma unroll
        for (int h = 0; h < 2; h++) {
            #pragma unroll
            for (int j = 0; j < 5; j++)
                if (j < ntile) mma16816(sc[j], a[h][0], a[h][1], a[h][2], a[h][3], b[j][2 * h], b[j][2 * h + 1]);
        }
    }
    const float sl2 = 0.08838834764831845f * 1.4426950408889634f;
    uint32_t pf[2][5];
    float inv[2];
    #pragma unroll
    for (int q = 0; q < 2; q++) {
        const int tok = mh * 16 + q * 8 + g;
        float v[10];
        #pragma unroll
        for (int j = 0; j < 5; j++) {
            #pragma unroll
            for (int e = 0; e < 2; e++) {
                const int key = (j - 1) * 8 + 2 * c + e;
                v[2 * j + e] = (j == 0 || key <= tok) ? sc[j][2 * q + e] : -INFINITY;
            }
        }
        float mx = v[0];
        #pragma unroll
        for (int j = 1; j < 10; j++) mx = fmaxf(mx, v[j]);
        mx = fmaxf(mx, __shfl_xor_sync(~0u, mx, 1));
        mx = fmaxf(mx, __shfl_xor_sync(~0u, mx, 2));
        const float mo = mx * sl2;
        float sum = 0.f;
        #pragma unroll
        for (int j = 0; j < 10; j++) { v[j] = ex2(fmaf(v[j], sl2, -mo)); sum += v[j]; }
        sum += __shfl_xor_sync(~0u, sum, 1);
        sum += __shfl_xor_sync(~0u, sum, 2);
        inv[q] = rcp(sum);
        #pragma unroll
        for (int j = 0; j < 5; j++) pf[q][j] = pack_bf16(v[2 * j], v[2 * j + 1]);
    }
    auto load_v = [&](int n4, uint32_t (&vm)[4], uint32_t (&vt)[4][4]) {
        ldsm_x4(svm + n4 * 512 + lane * 16, vm[0], vm[1], vm[2], vm[3]);
        #pragma unroll
        for (int u = 0; u < 4; u++) {
            const int dt = 2 * n4 + (u >> 1), kh = u & 1;
            const uint4 v = lds128(sv + (dt & 3) * 2048 + (dt >> 2) * 1024 + kh * 512 + lane * 16);
            vt[u & 2][2 * kh] = v.x; vt[u & 2][2 * kh + 1] = v.z;
            vt[(u & 2) + 1][2 * kh] = v.y; vt[(u & 2) + 1][2 * kh + 1] = v.w;
        }
    };
    uint32_t vm[2][4], vt[2][4][4];
    load_v(0, vm[0], vt[0]);
    #pragma unroll
    for (int n4 = 0; n4 < 4; n4++) {
        const int cur = n4 & 1;
        if (n4 + 1 < 4) load_v(n4 + 1, vm[cur ^ 1], vt[cur ^ 1]);
        float o[4][4];
        #pragma unroll
        for (int u = 0; u < 4; u++) {
            o[u][0] = o[u][1] = o[u][2] = o[u][3] = 0.f;
            mma16816(o[u], pf[0][1], pf[1][1], pf[0][2], pf[1][2], vt[cur][u][0], vt[cur][u][1]);
        }
        if (mh) {
            #pragma unroll
            for (int u = 0; u < 4; u++) mma16816(o[u], pf[0][3], pf[1][3], pf[0][4], pf[1][4], vt[cur][u][2], vt[cur][u][3]);
        }
        #pragma unroll
        for (int u = 0; u < 4; u++) mma1688(o[u], pf[0][0], pf[1][0], vm[cur][u]);
        #pragma unroll
        for (int u = 0; u < 4; u += 2) {
            const int row = mh * 16 + (mi & 1) * 8 + r8, nt = 4 * n4 + u + (mi >> 1);
            stsm_x4(sq + (nt >> 3) * 4096 + row * 128 + (((nt & 7) ^ r8) << 4),
                    pack_bf16(o[u][0] * inv[0], o[u][1] * inv[0]), pack_bf16(o[u][2] * inv[1], o[u][3] * inv[1]),
                    pack_bf16(o[u + 1][0] * inv[0], o[u + 1][1] * inv[0]), pack_bf16(o[u + 1][2] * inv[1], o[u + 1][3] * inv[1]));
        }
    }
}

__device__ __forceinline__ void b_attn_warp(uint32_t base, int hl, int idx0, int lane) {
    const uint32_t sq = base, sk = base + 8192, sv = base + 8192 + 9216;
    const int g = lane >> 2, c = lane & 3;
    auto addr = [&](uint32_t t, int row, int ch) { return t + row * 128 + ((ch ^ (row & 7)) << 4); };
    const float sl2 = 0.17677669529663687f * 1.4426950408889634f;
    #pragma unroll 2
    for (int blk = 0; blk < 4; blk++) {
        const int r0 = blk * 16;
        float sc[3][4];
        #pragma unroll
        for (int j = 0; j < 3; j++) { sc[j][0] = sc[j][1] = sc[j][2] = sc[j][3] = 0.f; }
        #pragma unroll
        for (int t = 0; t < 2; t++) {
            uint32_t a0, a1, a2, a3, b0, b1, b2, b3, d0, d1, d2, d3;
            const int mi = lane >> 3, r = lane & 7;
            ldsm_x4(addr(sq, r0 + (mi & 1) * 8 + r, hl * 4 + 2 * t + (mi >> 1)), a0, a1, a2, a3);
            ldsm_x4(addr(sk, r0 + (mi >> 1) * 8 + r, hl * 4 + 2 * t + (mi & 1)), b0, b1, b2, b3);
            ldsm_x4(addr(sk, r0 + 16 + r, hl * 4 + 2 * t + (mi & 1)), d0, d1, d2, d3);
            mma16816(sc[0], a0, a1, a2, a3, b0, b1);
            mma16816(sc[1], a0, a1, a2, a3, b2, b3);
            mma16816(sc[2], a0, a1, a2, a3, d0, d1);
        }
        uint32_t pf[2][3];
        float inv[2];
        #pragma unroll
        for (int r = 0; r < 2; r++) {
            const int u = r * 8 + g;
            float v[6];
            #pragma unroll
            for (int j = 0; j < 3; j++) {
                #pragma unroll
                for (int e = 0; e < 2; e++) {
                    const int key = j * 8 + 2 * c + e;
                    const bool ok = key > u && key <= u + 8 && idx0 + r0 - 8 + key >= 0;
                    v[2 * j + e] = ok ? sc[j][2 * r + e] : -INFINITY;
                }
            }
            float mx = fmaxf(fmaxf(fmaxf(v[0], v[1]), fmaxf(v[2], v[3])), fmaxf(v[4], v[5]));
            mx = fmaxf(mx, __shfl_xor_sync(~0u, mx, 1));
            mx = fmaxf(mx, __shfl_xor_sync(~0u, mx, 2));
            const float mo = mx * sl2;
            float sum = 0.f;
            #pragma unroll
            for (int j = 0; j < 6; j++) { v[j] = ex2(fmaf(v[j], sl2, -mo)); sum += v[j]; }
            sum += __shfl_xor_sync(~0u, sum, 1);
            sum += __shfl_xor_sync(~0u, sum, 2);
            inv[r] = rcp(sum);
            #pragma unroll
            for (int j = 0; j < 3; j++) pf[r][j] = pack_bf16(v[2 * j], v[2 * j + 1]);
        }
        uint32_t ow[4][2];
        {
            const int mi = lane >> 3, r = lane & 7;
            uint32_t vv[4][4];
            #pragma unroll
            for (int nt = 0; nt < 4; nt++)
                ldsm_x4_t(addr(sv, r0 + min(mi, 2) * 8 + r, hl * 4 + nt), vv[nt][0], vv[nt][1], vv[nt][2], vv[nt][3]);
            float o[4][4];
            #pragma unroll
            for (int nt = 0; nt < 4; nt++) {
                o[nt][0] = o[nt][1] = o[nt][2] = o[nt][3] = 0.f;
                mma16816(o[nt], pf[0][0], pf[1][0], pf[0][1], pf[1][1], vv[nt][0], vv[nt][1]);
            }
            #pragma unroll
            for (int nt = 0; nt < 4; nt++) mma1688(o[nt], pf[0][2], pf[1][2], vv[nt][2]);
            #pragma unroll
            for (int nt = 0; nt < 4; nt++) {
                ow[nt][0] = pack_bf16(o[nt][0] * inv[0], o[nt][1] * inv[0]);
                ow[nt][1] = pack_bf16(o[nt][2] * inv[1], o[nt][3] * inv[1]);
            }
        }
        #pragma unroll
        for (int u = 0; u < 4; u += 2) {
            const int mi = lane >> 3, r = lane & 7;
            stsm_x4(addr(sq, r0 + (mi & 1) * 8 + r, hl * 4 + u + (mi >> 1)), ow[u][0], ow[u][1], ow[u + 1][0], ow[u + 1][1]);
        }
    }
}

constexpr uint32_t QKVB_TARGET = 12 * 8;
constexpr uint32_t PROGRESS_TARGET = 96;
constexpr uint32_t OA_TARGET = 64, OB_TARGET = 32;
#define ATT_RELAXED 1
#define ATT_B0 8
#define ATT_BSTEP 2
constexpr int ATT_TASKS = (NSEG + 16) * 32;
static_assert(ATT_B0 + 16 * ATT_BSTEP <= NSEG, "order of the task groups");
__device__ __forceinline__ int att_group(int g, bool& isb) {
    constexpr int P = ATT_BSTEP + 1;
    const int q = g - ATT_B0;
    isb = q >= 0 && q < 16 * P && q % P == 0;
    return q < 0 ? g : q >= 16 * P ? g - 16 : isb ? q / P : g - q / P - 1;
}

__global__ void __launch_bounds__(ATT_THREADS, 1) attn_kernel(const __grid_constant__ AttnParams p) {
    extern __shared__ __align__(1024) uint8_t smem_raw[];
    const int tid = threadIdx.x, lane = tid & 31, warp = __shfl_sync(~0u, tid >> 5, 0);
    const int pair = warp >> 1, wi = warp & 1;
    const uint32_t base = smem_u32(smem_raw) + pair * ATT_SLOT, bar = smem_u32(smem_raw) + ATT_BAR + pair * 16;
    const bool leader = wi == 0 && lane == 0;
    if (tid == 0) pdl_launch_dependents();
    KENTER(3);
    const uint32_t cnt = smem_u32(smem_raw) + ATT_CNT;
    if (tid < 96) sts32(cnt + tid * 4, 0);
    __syncthreads();
    if (warp == 2 * ATT_PAIRS) {
        for (uint32_t n = 0; n < SPIN_LIMIT; n++) {
            const bool last = lds32_volatile(cnt + 320) == 2 * ATT_PAIRS;
            uint32_t v[3];
            #pragma unroll
            for (int i = 0; i < 3; i++) {
                v[i] = 0;
                if (i * 32 + lane < 80 && lds32_volatile(cnt + (i * 32 + lane) * 4) != 0)
                    asm volatile("atom.acquire.cta.shared.exch.b32 %0, [%1], 0;" : "=r"(v[i]) : "r"(cnt + (i * 32 + lane) * 4) : "memory");
            }
            if (v[0] | v[1] | v[2]) {
                if (!ATT_RELAXED) asm volatile("fence.acq_rel.gpu;" ::: "memory");
                #pragma unroll
                for (int i = 0; i < 3; i++)
                    if (v[i]) asm volatile("red.relaxed.gpu.global.add.u32 [%0], %1;" ::"l"(p.flags + F_OB + i * 32 + lane), "r"(v[i]) : "memory");
                if (v[2] && lane == 15) KMARK(14);
            }
            __syncwarp();
            if (last) break;
            __nanosleep(40);
        }
        if (lane == 0) KEXIT(3);
        return;
    }
    uint32_t phase = 0;
    if (leader) {
        mbar_init(bar, 1);
        asm volatile("fence.mbarrier_init.release.cluster;" ::: "memory");
    }
    uint32_t pending = 0;
    auto flush = [&]() {
        if (pending) {
            bulk_wait_all();
            if (pending == cnt + 79 * 4) KMARK(13);
            asm volatile("red.release.cta.shared.add.u32 [%0], 1;" ::"r"(pending) : "memory");
            pending = 0;
        }
    };
    int ready_a = -1, ready_b = -1;
    for (int task = pair * gridDim.x + blockIdx.x; task < ATT_TASKS; task += ATT_PAIRS * gridDim.x) {
        bool isb;
        const int grp = att_group(task >> 5, isb), i = task & 31;
        named_bar_sync(1 + pair, 64);
        if (leader) {
            {
                auto need = [&](const uint32_t* f, uint32_t target) {
                    if (ld_acquire_b32(f) < target) { flush(); wait_flag(f, target); }
                };
                if (isb) {
                    if (grp > ready_b) {
                        need(p.flags + F_QKVB + grp, QKVB_TARGET);
                        if (grp > 0) need(p.flags + F_QKVB + grp - 1, QKVB_TARGET);
                        asm volatile("fence.proxy.async.global;" ::: "memory");
                        ready_b = grp;
                    }
                    mbar_arrive_expect_tx(bar, 8192 + 2 * 9216);
                    tma_load_3d(base, &p.tmQb, (i >> 1) * 64, i & 1, grp * 64, bar);
                    tma_load_3d(base + 8192, &p.tmKb, DM + (i >> 1) * 64, i & 1, grp * 64 - 8, bar);
                    tma_load_3d(base + 8192 + 9216, &p.tmKb, 2 * DM + (i >> 1) * 64, i & 1, grp * 64 - 8, bar);
                } else {
                    if (grp > ready_a) {
                        need(p.flags + F_PROGRESS + grp, PROGRESS_TARGET);
                        asm volatile("fence.proxy.async.global;" ::: "memory");
                        ready_a = grp;
                    }
                    if (grp == 63) KMARK(10);
                    mbar_arrive_expect_tx(bar, ATT_SLOT);
                    #pragma unroll
                    for (int w = 0; w < 3; w++)
                        bulk_load(base + w * 8192, p.qkv_tok + (((size_t)w * NSEG + grp) * NH + i) * (SEG * DH), 8192, bar);
                    #pragma unroll
                    for (int w = 0; w < 2; w++)
                        bulk_load(base + 24576 + w * 2048, p.kv_mem + (((size_t)w * NSEG + grp) * NH + i) * (MROWS * DH), 2048, bar);
                }
            }
        }
        if (lane == 0) flush();
        __syncwarp();
        mbar_wait_sleep(bar, phase);
        phase ^= 1;
        if (isb) {
            b_attn_warp(base, wi, grp * 64, lane);
            asm volatile("fence.proxy.async.shared::cta;" ::: "memory");
            named_bar_sync(1 + pair, 64);
            if (wi == 1 && lane == 0) {
                asm volatile("cp.async.bulk.tensor.3d.global.shared::cta.bulk_group [%0, {%2, %3, %4}], [%1];"
                             ::"l"(&p.tmOb), "r"(base), "r"((i >> 1) * 64), "r"(i & 1), "r"(grp * 64) : "memory");
                pending = cnt + grp * 4;
            }
        } else {
            if (grp == 63 && lane == 0) KMARK(11);
            tok_attn_warp(base, wi, lane);
            if (grp == 63 && lane == 0) KMARK(12);
            asm volatile("fence.proxy.async.shared::cta;" ::: "memory");
            __syncwarp();
            if (lane == 0) {
                #pragma unroll
                for (int h = 0; h < 2; h++) tma_store_2d(&p.tmOa, base + h * 4096 + wi * 2048, i * DH + h * 64, grp * SEG + wi * 16);
                pending = cnt + (16 + grp) * 4;
            }
        }
        if (lane == 0) { bulk_commit(); bulk_wait_read_all(); }
        __syncwarp();
    }
    if (lane == 0) {
        flush();
        asm volatile("red.release.cta.shared.add.u32 [%0], 1;" ::"r"(cnt + 320) : "memory");
    }
}

typedef CUresult (*EncodeFn)(CUtensorMap*, CUtensorMapDataType, cuuint32_t, void*, const cuuint64_t*, const cuuint64_t*,
                             const cuuint32_t*, const cuuint32_t*, CUtensorMapInterleave, CUtensorMapSwizzle,
                             CUtensorMapL2promotion, CUtensorMapFloatOOBfill);

void make_map_2d(EncodeFn enc, CUtensorMap* m, const void* ptr, uint64_t rows, uint64_t cols, uint32_t box_rows) {
    cuuint64_t dims[2] = {cols, rows};
    cuuint64_t strides[1] = {cols * 2};
    cuuint32_t box[2] = {64, box_rows};
    cuuint32_t es[2] = {1, 1};
    enc(m, CU_TENSOR_MAP_DATA_TYPE_BFLOAT16, 2, const_cast<void*>(ptr), dims, strides, box, es,
        CU_TENSOR_MAP_INTERLEAVE_NONE, CU_TENSOR_MAP_SWIZZLE_128B, CU_TENSOR_MAP_L2_PROMOTION_L2_256B,
        CU_TENSOR_MAP_FLOAT_OOB_FILL_NONE);
}
void make_map_b(EncodeFn enc, CUtensorMap* m, const void* ptr, uint64_t k, uint64_t n, uint32_t nblk, uint32_t box_rows = 64,
                uint32_t bc = 64) {
    cuuint64_t dims[3] = {bc, k, n / bc};
    cuuint64_t strides[2] = {n * 2, bc * 2};
    cuuint32_t box[3] = {bc, box_rows, nblk};
    cuuint32_t es[3] = {1, 1, 1};
    enc(m, CU_TENSOR_MAP_DATA_TYPE_BFLOAT16, 3, const_cast<void*>(ptr), dims, strides, box, es,
        CU_TENSOR_MAP_INTERLEAVE_NONE, bc == 64 ? CU_TENSOR_MAP_SWIZZLE_128B : CU_TENSOR_MAP_SWIZZLE_64B, CU_TENSOR_MAP_L2_PROMOTION_L2_256B,
        CU_TENSOR_MAP_FLOAT_OOB_FILL_NONE);
}

void make_map_parity(EncodeFn enc, CUtensorMap* m, const void* ptr, uint64_t cols, uint32_t box_rows) {
    cuuint64_t dims[3] = {cols, 2, S_TOK / 2};
    cuuint64_t strides[2] = {cols * 2, cols * 4};
    cuuint32_t box[3] = {64, 1, box_rows};
    cuuint32_t es[3] = {1, 1, 1};
    enc(m, CU_TENSOR_MAP_DATA_TYPE_BFLOAT16, 3, const_cast<void*>(ptr), dims, strides, box, es,
        CU_TENSOR_MAP_INTERLEAVE_NONE, CU_TENSOR_MAP_SWIZZLE_128B, CU_TENSOR_MAP_L2_PROMOTION_L2_128B,
        CU_TENSOR_MAP_FLOAT_OOB_FILL_NONE);
}
void make_map_w(EncodeFn enc, CUtensorMap* m, const void* ptr) {
    cuuint64_t dims[3] = {HD, 64, DM / 64};
    cuuint64_t strides[2] = {HD * 2, 64 * HD * 2};
    cuuint32_t box[3] = {64, 16, 8};
    cuuint32_t es[3] = {1, 1, 1};
    enc(m, CU_TENSOR_MAP_DATA_TYPE_BFLOAT16, 3, const_cast<void*>(ptr), dims, strides, box, es,
        CU_TENSOR_MAP_INTERLEAVE_NONE, CU_TENSOR_MAP_SWIZZLE_128B, CU_TENSOR_MAP_L2_PROMOTION_L2_256B,
        CU_TENSOR_MAP_FLOAT_OOB_FILL_NONE);
}

#define OUTB_SIDE_BLOCKS 16
#define SIDE_ORDER 0
#define SERIAL_ATT_CTAS h.n_sm
#define N_TAIL_CTAS 28
#define N_SIDE_CTAS 28
#define N_ATT_CTAS 8
#define TAIL_BLOCK0 11

#define TAIL_SPARE 2
#define TAIL_KB2 30
#define TAIL_KB3 20
#define TAIL_BLOCK1 13
#define TAIL_BLOCK2 14

struct HostState {
    bool ready;
    bool overlap;
    int n_side, n_att, n_sm;
    SideParams seq_a, seq_b;
    const void* key[11];
    RecParams rec;
    SideParams side, tail, outb;
    FinalParams fin;
    AttnParams attn;
    __nv_bfloat16 *qkv_tok, *kv_mem, *o_tok, *qkv_b, *o_b;
    uint8_t* xchg;
};
HostState g_host;

void setup(void* const* d_in, void* d_out) {
    HostState& h = g_host;
    void* fn = nullptr;
    cudaDriverEntryPointQueryResult qr;
    cudaGetDriverEntryPoint("cuTensorMapEncodeTiled", &fn, cudaEnableDefault, &qr);
    EncodeFn enc = reinterpret_cast<EncodeFn>(fn);
    void* ptr;
    cudaGetSymbolAddress(&ptr, g_qkv_tok); h.qkv_tok = (__nv_bfloat16*)ptr;
    cudaGetSymbolAddress(&ptr, g_kv_mem);  h.kv_mem = (__nv_bfloat16*)ptr;
    cudaGetSymbolAddress(&ptr, g_o_tok);   h.o_tok = (__nv_bfloat16*)ptr;
    cudaGetSymbolAddress(&ptr, g_qkv_b);   h.qkv_b = (__nv_bfloat16*)ptr;
    cudaGetSymbolAddress(&ptr, g_o_b);     h.o_b = (__nv_bfloat16*)ptr;
    cudaGetSymbolAddress(&ptr, g_xchg);    h.xchg = (uint8_t*)(((uint64_t)ptr + XCHG_BYTES - 1) & ~(uint64_t)(XCHG_BYTES - 1));
    cudaGetSymbolAddress(&ptr, g_flags);   uint32_t* flags = (uint32_t*)ptr;
    cudaGetSymbolAddress(&ptr, g_arrivals); uint32_t* arrivals = (uint32_t*)ptr;

    const void *xa = d_in[0], *mem0 = d_in[1], *wq = d_in[2], *wk = d_in[3], *wv = d_in[4], *wo = d_in[5];
    const void *xb = d_in[7], *wqkv = d_in[8], *wob = d_in[9];

    RecParams& r = h.rec;
    make_map_w(enc, &r.tmW[0], wq);
    make_map_w(enc, &r.tmW[1], wk);
    make_map_w(enc, &r.tmW[2], wv);
    make_map_b(enc, &r.tmWo, wo, HD, DM, 11, 128, 32);
    r.mem0 = (const __nv_bfloat16*)mem0;
    r.qkv_tok = h.qkv_tok; r.kv_mem = h.kv_mem; r.xchg = h.xchg;
    r.flags = flags; r.arrivals = arrivals; r.one[0] = r.one[1] = 1;
    make_map_b(enc, &r.tmX, xa, S_TOK, DM, 4, SEG);

    SideParams& sd = h.side;
    SideProb& p0 = sd.prob[0];
    make_map_2d(enc, &p0.tmA, xb, S_TOK, DM, BM);
    make_map_b(enc, &p0.tmB, wqkv, DM, 3 * DM, 4);
    make_map_2d(enc, &p0.tmC, h.qkv_b, S_TOK, 3 * DM, 16);
    p0.n_tiles = 3 * DM / 256; p0.k_blocks = DM / BK; p0.c_col0 = 0; p0.dep = nullptr; p0.dep_target = 0; p0.dep_n = 1; p0.sig = flags + F_QKVB;
    SideProb& p1 = sd.prob[1];
    make_map_2d(enc, &p1.tmA, h.o_tok, S_TOK, HD, BM);
    make_map_b(enc, &p1.tmB, wo, HD, DM, 4);
    make_map_2d(enc, &p1.tmC, d_out, S_TOK, 2 * DM, 16);
    p1.n_tiles = DM / 256; p1.k_blocks = HD / BK; p1.c_col0 = 0; p1.dep = flags + F_OA; p1.dep_target = OA_TARGET; p1.dep_n = 4; p1.sig = nullptr;
    SideProb& p2 = sd.prob[2];
    make_map_2d(enc, &p2.tmA, h.o_b, S_TOK, DM, BM);
    make_map_b(enc, &p2.tmB, wob, DM, DM, 4);
    p2.tmC = p1.tmC;
    p2.n_tiles = DM / 256; p2.k_blocks = DM / BK; p2.c_col0 = DM; p2.dep = flags + F_OB; p2.dep_target = OB_TARGET; p2.dep_n = 1; p2.sig = nullptr;
    p0.n_split = p0.n_tiles; p1.n_split = p1.n_tiles; p2.n_split = p2.n_tiles;
    p0.part = p1.part = p2.part = nullptr;
    p0.k_total = p0.k_blocks; p1.k_total = p1.k_blocks; p2.k_total = p2.k_blocks;
    if (SIDE_ORDER == 0) { sd.seg[0] = {0, 0, 16}; sd.seg[1] = {1, 0, TAIL_BLOCK0}; }
    else { sd.seg[0] = {1, 0, TAIL_BLOCK0}; sd.seg[1] = {0, 0, 16}; }
    sd.seg[2] = {2, 0, OUTB_SIDE_BLOCKS};
    sd.nseg = 3; sd.queue = flags + F_SIDEQ; sd.spare_seg = 3; sd.flags = flags;
    h.outb = sd;
    h.outb.seg[0] = {2, OUTB_SIDE_BLOCKS, 16};
    h.outb.nseg = 1; h.outb.queue = flags + F_OUTBQ;

    SideParams& tl = h.tail;
    tl.prob[0] = p1;
    make_map_b(enc, &tl.prob[0].tmB, wo, HD, DM, 2);
    cudaGetSymbolAddress(&ptr, g_part);
    for (int i = 0; i < 3; i++) {
        SideProb& q = tl.prob[i];
        q = tl.prob[0];
        q.n_tiles = (i + 1) * DM / 128; q.n_split = DM / 128; q.k_blocks = i == 0 ? HD / BK : i == 1 ? TAIL_KB2 : TAIL_KB3;
        q.part = i ? (float*)ptr : nullptr; q.part_flag = flags + F_PART;
    }
    tl.seg[0] = {0, TAIL_BLOCK0, TAIL_BLOCK1};
    tl.seg[1] = {1, TAIL_BLOCK1, TAIL_BLOCK2};
    tl.seg[2] = {2, TAIL_BLOCK2, 15};
    tl.nseg = 3; tl.queue = flags + F_TAILQ; tl.spare_seg = TAIL_SPARE; tl.flags = flags;

    make_map_2d(enc, &h.fin.tmA, h.o_tok, S_TOK, HD, SEG);
    h.fin.tmB = tl.prob[0].tmB; h.fin.out = (__nv_bfloat16*)d_out;
    h.fin.dep = flags + F_OA + 60; h.fin.dep_target = OA_TARGET; h.fin.mt = 15;

    make_map_2d(enc, &h.attn.tmOa, h.o_tok, S_TOK, HD, 16);
    make_map_parity(enc, &h.attn.tmQb, h.qkv_b, 3 * DM, 64);
    make_map_parity(enc, &h.attn.tmKb, h.qkv_b, 3 * DM, 72);
    make_map_parity(enc, &h.attn.tmOb, h.o_b, DM, 64);
    h.attn.qkv_tok = h.qkv_tok; h.attn.kv_mem = h.kv_mem; h.attn.flags = flags;

    int dev = 0, nsm = 0;
    cudaGetDevice(&dev);
    cudaDeviceGetAttribute(&nsm, cudaDevAttrMultiProcessorCount, dev);
    h.n_sm = nsm;
    h.overlap = nsm - 96 >= N_SIDE_CTAS + N_ATT_CTAS;
    h.n_side = N_SIDE_CTAS; h.n_att = N_ATT_CTAS;
    h.seq_a = sd;
    h.seq_a.seg[0] = {0, 0, 16};
    h.seq_a.nseg = 1;
    h.seq_b = sd;
    h.seq_b.seg[0] = {1, 0, 16};
    h.seq_b.seg[1] = {2, 0, 16};
    h.seq_b.nseg = 2; h.seq_b.queue = flags + F_TAILQ;

    cudaFuncSetAttribute(side_gemm_kernel<256>, cudaFuncAttributeMaxDynamicSharedMemorySize, GemmCfg<256>::SMEM);
    cudaFuncSetAttribute(side_gemm_kernel<128>, cudaFuncAttributeMaxDynamicSharedMemorySize, GemmCfg<128>::SMEM);
    cudaFuncSetAttribute(final_gemm_kernel, cudaFuncAttributeMaxDynamicSharedMemorySize, FIN_SMEM);
    cudaFuncSetAttribute(rec_kernel, cudaFuncAttributeMaxDynamicSharedMemorySize, REC_SMEM);
    cudaFuncSetAttribute(attn_kernel, cudaFuncAttributeMaxDynamicSharedMemorySize, ATT_SMEM);
    for (int i = 0; i < 10; i++) h.key[i] = d_in[i];
    h.key[10] = d_out;
    h.ready = true;
}

template <typename K, typename P>
void launch(K kernel, int grid, int block, int smem, cudaStream_t st, const P& prm, int cluster, bool pdl) {
    cudaLaunchConfig_t cfg = {};
    cfg.gridDim = dim3(grid); cfg.blockDim = dim3(block); cfg.dynamicSmemBytes = smem; cfg.stream = st;
    cudaLaunchAttribute at[2];
    int n = 0;
    if (cluster > 1) {
        at[n].id = cudaLaunchAttributeClusterDimension;
        at[n].val.clusterDim.x = cluster; at[n].val.clusterDim.y = 1; at[n].val.clusterDim.z = 1;
        n++;
    }
    if (pdl) {
        at[n].id = cudaLaunchAttributeProgrammaticStreamSerialization;
        at[n].val.programmaticStreamSerializationAllowed = 1;
        n++;
    }
    cfg.attrs = at; cfg.numAttrs = n;
    cudaLaunchKernelEx(&cfg, kernel, prm);
}

}

extern "C" void kernel_launch(void* const* d_in, const int* in_sizes, int n_in, void* d_out, int out_size) {
    HostState& h = g_host;
    bool same = h.ready;
    for (int i = 0; same && i < 10; i++) same = h.key[i] == d_in[i];
    if (!same || h.key[10] != d_out) setup(d_in, d_out);
    cudaStream_t st = cudaStreamPerThread;

    launch(rec_kernel, 96, REC_THREADS, REC_SMEM, st, h.rec, 3, false);
    {
        if (!h.overlap) {
            launch(side_gemm_kernel<256>, h.n_sm, 384, GemmCfg<256>::SMEM, st, h.seq_a, 1, false);
            launch(attn_kernel, SERIAL_ATT_CTAS, ATT_THREADS, ATT_SMEM, st, h.attn, 1, false);
            launch(side_gemm_kernel<256>, h.n_sm, 384, GemmCfg<256>::SMEM, st, h.seq_b, 1, false);
            return;
        }
    }
    launch(side_gemm_kernel<256>, h.n_side, 384, GemmCfg<256>::SMEM, st, h.side, 1, true);
    launch(attn_kernel, h.n_att, ATT_THREADS, ATT_SMEM, st, h.attn, 1, true);
    launch(side_gemm_kernel<128>, N_TAIL_CTAS, 384, GemmCfg<128>::SMEM, st, h.tail, 1, true);
    launch(final_gemm_kernel, 8 * FIN_SPLIT, 384, FIN_SMEM, st, h.fin, FIN_SPLIT, true);
    if (OUTB_SIDE_BLOCKS < 16)
        launch(side_gemm_kernel<256>, (16 - OUTB_SIDE_BLOCKS) * 4, 384, GemmCfg<256>::SMEM, st, h.outb, 1, true);
}
```

```cpp
#include <cuda_runtime.h>
#include <cuda_bf16.h>
#include <cuda.h>
#include <stdint.h>

namespace {

constexpr int S_TOK = 2048;
constexpr int DM = 1024;
constexpr int NH = 32;
constexpr int DH = 128;
constexpr int HD = NH * DH;
constexpr int NSEG = 64;
constexpr int SEG = 32;
constexpr int MROWS = 8;
constexpr uint32_t SENT = 0xFFFFFFFFu;
constexpr uint32_t SPIN_LIMIT = 1u << 24;

__device__ __align__(1024) __nv_bfloat16 g_qkv_tok[3ull * NSEG * NH * SEG * DH];
__device__ __align__(1024) __nv_bfloat16 g_kv_mem[2ull * NSEG * NH * MROWS * DH];
__device__ __align__(1024) __nv_bfloat16 g_o_tok[(size_t)S_TOK * HD];
__device__ __align__(1024) __nv_bfloat16 g_qkv_b[(size_t)S_TOK * 3 * DM];
__device__ __align__(1024) __nv_bfloat16 g_o_b[(size_t)S_TOK * DM];
__device__ __align__(1024) float g_part[32 * 2 * 128 * 128];
constexpr int PUB_BYTES = 32768;
constexpr int XCHG_SLOT = 1 << 20;
constexpr int XCHG_PUB = 0, XCHG_INBOX = 2 * PUB_BYTES;
constexpr int INBOX_MAX = 80;
constexpr int XCHG_BYTES = 2 * XCHG_SLOT;
__device__ __align__(8192) uint8_t g_xchg[2 * XCHG_BYTES];
enum { F_LASTTOK = 0, F_RECSM = 4, F_PROGRESS = 16, F_QKVB = 80, F_OB = 96, F_OA = 112, F_PART = 176, F_SIDEQ = 208, F_TAILQ = 256, F_OUTBQ = 304, F_COUNT = 352 };
__device__ uint32_t g_flags[F_COUNT];
__device__ __align__(16) uint32_t g_arrivals[4];

#define STAMP(k) do {} while (0)
#define STAMPD(k, x) do {} while (0)
#define PSTAMP(k) do {} while (0)
#define KENTER(k) do {} while (0)
#define APROF(k) do {} while (0)
#define KEXIT(k) do {} while (0)
#define KMARK(k) do {} while (0)

__device__ __forceinline__ uint32_t class_off(uint64_t a, uint32_t c) {
    return ((__popc((uint32_t)a & 0xB3000u) ^ c) & 1u) << 12;
}
__device__ __forceinline__ uint32_t smem_u32(const void* p) { return (uint32_t)__cvta_generic_to_shared(p); }
__device__ __forceinline__ uint32_t pack_bf16(float lo, float hi) {
    uint32_t r;
    asm("cvt.rn.bf16x2.f32 %0, %1, %2;" : "=r"(r) : "f"(hi), "f"(lo));
    return r;
}
__device__ __forceinline__ float ex2(float x) {
    float y;
    asm("ex2.approx.ftz.f32 %0, %1;" : "=f"(y) : "f"(x));
    return y;
}
__device__ __forceinline__ float rcp(float x) {
    float y;
    asm("rcp.approx.ftz.f32 %0, %1;" : "=f"(y) : "f"(x));
    return y;
}
__device__ __forceinline__ uint32_t clock32() {
    uint32_t t;
    asm volatile("mov.u32 %0, %%clock;" : "=r"(t));
    return t;
}
__device__ __forceinline__ void spin_clks(uint32_t n) {
    if (n == 0) return;
    const uint32_t t0 = clock32();
    while (clock32() - t0 < n) {}
}
__device__ __forceinline__ void spin_until(uint32_t t) {
    while ((int)(clock32() - t) < 0) {}
}
__device__ __forceinline__ uint32_t clock_after(uint32_t x) {
    uint32_t t;
    asm volatile("{\n.reg .pred p;\nsetp.eq.u32 p, %1, 0x12345678;\n@p exit;\nmov.u32 %0, %%clock;\n}" : "=r"(t) : "r"(x) : "memory");
    return t;
}
__device__ __forceinline__ uint32_t opaque(uint32_t x) { return __shfl_sync(~0u, x, threadIdx.x & 31); }
__device__ __forceinline__ uint32_t uniform(uint32_t x) { return __shfl_sync(~0u, x + (threadIdx.x & 31), 0); }
__device__ __forceinline__ float bf16_lo(uint32_t w) { return __uint_as_float(w << 16); }
__device__ __forceinline__ float bf16_hi(uint32_t w) { return __uint_as_float(w & 0xFFFF0000u); }

__device__ __forceinline__ void mbar_init(uint32_t bar, uint32_t cnt) {
    asm volatile("mbarrier.init.shared::cta.b64 [%0], %1;" ::"r"(bar), "r"(cnt) : "memory");
}
__device__ __forceinline__ void mbar_arrive(uint32_t bar) {
    asm volatile("mbarrier.arrive.shared::cta.b64 _, [%0];" ::"r"(bar) : "memory");
}
__device__ __forceinline__ void mbar_arrive_expect_tx(uint32_t bar, uint32_t bytes) {
    asm volatile("mbarrier.arrive.expect_tx.shared::cta.b64 _, [%0], %1;" ::"r"(bar), "r"(bytes) : "memory");
}
__device__ __forceinline__ bool mbar_try_wait(uint32_t bar, uint32_t parity) {
    uint32_t ok;
    asm volatile(
        "{\n.reg .pred p;\n"
        "mbarrier.try_wait.parity.shared::cta.b64 p, [%1], %2;\n"
        "selp.u32 %0, 1, 0, p;\n}"
        : "=r"(ok) : "r"(bar), "r"(parity) : "memory");
    return ok != 0;
}
__device__ __forceinline__ bool mbar_test_wait(uint32_t bar, uint32_t parity) {
    uint32_t ok;
    asm volatile(
        "{\n.reg .pred p;\n"
        "mbarrier.test_wait.parity.shared::cta.b64 p, [%1], %2;\n"
        "selp.u32 %0, 1, 0, p;\n}"
        : "=r"(ok) : "r"(bar), "r"(parity) : "memory");
    return ok != 0;
}
__device__ __forceinline__ void mbar_wait(uint32_t bar, uint32_t parity) {
    uint32_t n = 0;
    while (!mbar_try_wait(bar, parity)) {
        if (++n > SPIN_LIMIT) __trap();
    }
}
__device__ __forceinline__ void mbar_wait_sleep(uint32_t bar, uint32_t parity) {
    uint32_t n = 0;
    while (!mbar_try_wait(bar, parity)) {
        __nanosleep(20);
        if (++n > SPIN_LIMIT) __trap();
    }
}
__device__ __forceinline__ void mbar_wait_bounded(uint32_t bar, uint32_t parity) {
    for (uint32_t n = 0; n < (1u << 20) && !mbar_try_wait(bar, parity); n++) {}
}
__device__ __forceinline__ bool elect_one() {
    uint32_t ok;
    asm volatile("{\n.reg .pred p;\nelect.sync _|p, 0xFFFFFFFF;\nselp.u32 %0, 1, 0, p;\n}" : "=r"(ok));
    return ok != 0;
}
__device__ __forceinline__ void named_bar_sync(int id, int nthreads) {
    asm volatile("bar.sync %0, %1;" ::"r"(id), "r"(nthreads) : "memory");
}
__device__ __forceinline__ void named_bar_arrive(int id, int nthreads) {
    asm volatile("bar.arrive %0, %1;" ::"r"(id), "r"(nthreads) : "memory");
}
__device__ __forceinline__ void cluster_sync() {
    asm volatile("barrier.cluster.arrive.release.aligned;\nbarrier.cluster.wait.acquire.aligned;" ::: "memory");
}
__device__ __forceinline__ uint32_t mapa(uint32_t addr, uint32_t rank) {
    uint32_t r;
    asm volatile("mapa.shared::cluster.u32 %0, %1, %2;" : "=r"(r) : "r"(addr), "r"(rank));
    return r;
}

__device__ __forceinline__ void tma_load_2d(uint32_t dst, const CUtensorMap* tm, int c0, int c1, uint32_t bar) {
    asm volatile(
        "cp.async.bulk.tensor.2d.shared::cluster.global.mbarrier::complete_tx::bytes [%0], [%1, {%3, %4}], [%2];"
        ::"r"(dst), "l"(tm), "r"(bar), "r"(c0), "r"(c1) : "memory");
}
__device__ __forceinline__ void tma_load_3d(uint32_t dst, const CUtensorMap* tm, int c0, int c1, int c2, uint32_t bar) {
    asm volatile(
        "cp.async.bulk.tensor.3d.shared::cluster.global.mbarrier::complete_tx::bytes [%0], [%1, {%3, %4, %5}], [%2];"
        ::"r"(dst), "l"(tm), "r"(bar), "r"(c0), "r"(c1), "r"(c2) : "memory");
}
__device__ __forceinline__ void tma_load_3d_mc(uint32_t dst, const CUtensorMap* tm, int c0, int c1, int c2, uint32_t bar, uint16_t mask) {
    asm volatile(
        "cp.async.bulk.tensor.3d.shared::cluster.global.mbarrier::complete_tx::bytes.multicast::cluster [%0], [%1, {%3, %4, %5}], [%2], %6;"
        ::"r"(dst), "l"(tm), "r"(bar), "r"(c0), "r"(c1), "r"(c2), "h"(mask) : "memory");
}
__device__ __forceinline__ void tma_store_2d(const CUtensorMap* tm, uint32_t src, int c0, int c1) {
    asm volatile("cp.async.bulk.tensor.2d.global.shared::cta.bulk_group [%0, {%2, %3}], [%1];"
                 ::"l"(tm), "r"(src), "r"(c0), "r"(c1) : "memory");
}
__device__ __forceinline__ void bulk_store(void* dst, uint32_t src, uint32_t bytes) {
    asm volatile("cp.async.bulk.global.shared::cta.bulk_group [%0], [%1], %2;" ::"l"(dst), "r"(src), "r"(bytes) : "memory");
}
__device__ __forceinline__ void bulk_commit() { asm volatile("cp.async.bulk.commit_group;" ::: "memory"); }
__device__ __forceinline__ void bulk_wait_read_all() { asm volatile("cp.async.bulk.wait_group.read 0;" ::: "memory"); }
__device__ __forceinline__ void bulk_wait_all() { asm volatile("cp.async.bulk.wait_group 0;" ::: "memory"); }
__device__ __forceinline__ void bulk_load(uint32_t dst, const void* src, uint32_t bytes, uint32_t bar) {
    asm volatile("cp.async.bulk.shared::cluster.global.mbarrier::complete_tx::bytes [%0], [%1], %2, [%3];"
                 ::"r"(dst), "l"(src), "r"(bytes), "r"(bar) : "memory");
}
__device__ __forceinline__ void bulk_load_mc(uint32_t dst, const void* src, uint32_t bytes, uint32_t bar, uint16_t mask) {
    asm volatile(
        "cp.async.bulk.shared::cluster.global.mbarrier::complete_tx::bytes.multicast::cluster [%0], [%1], %2, [%3], %4;"
        ::"r"(dst), "l"(src), "r"(bytes), "r"(bar), "h"(mask) : "memory");
}
__device__ __forceinline__ void cp_async16(uint32_t dst, const void* src) {
    asm volatile("cp.async.cg.shared.global [%0], [%1], 16;" ::"r"(dst), "l"(src) : "memory");
}
__device__ __forceinline__ void cp_async_commit() { asm volatile("cp.async.commit_group;" ::: "memory"); }
template <int N> __device__ __forceinline__ void cp_async_wait() {
    asm volatile("cp.async.wait_group %0;" ::"n"(N) : "memory");
}

__device__ __forceinline__ void ldsm_x4(uint32_t addr, uint32_t& r0, uint32_t& r1, uint32_t& r2, uint32_t& r3) {
    asm volatile("ldmatrix.sync.aligned.m8n8.x4.shared.b16 {%0,%1,%2,%3}, [%4];"
                 : "=r"(r0), "=r"(r1), "=r"(r2), "=r"(r3) : "r"(addr) : "memory");
}
__device__ __forceinline__ void ldsm_x4_t(uint32_t addr, uint32_t& r0, uint32_t& r1, uint32_t& r2, uint32_t& r3) {
    asm volatile("ldmatrix.sync.aligned.m8n8.x4.trans.shared.b16 {%0,%1,%2,%3}, [%4];"
                 : "=r"(r0), "=r"(r1), "=r"(r2), "=r"(r3) : "r"(addr) : "memory");
}
__device__ __forceinline__ void stsm_x4(uint32_t addr, uint32_t r0, uint32_t r1, uint32_t r2, uint32_t r3) {
    asm volatile("stmatrix.sync.aligned.m8n8.x4.shared.b16 [%0], {%1,%2,%3,%4};"
                 ::"r"(addr), "r"(r0), "r"(r1), "r"(r2), "r"(r3) : "memory");
}
__device__ __forceinline__ uint32_t movmat(uint32_t a) {
    uint32_t d;
    asm volatile("movmatrix.sync.aligned.m8n8.trans.b16 %0, %1;" : "=r"(d) : "r"(a));
    return d;
}
__device__ __forceinline__ void mma16816(float* d, uint32_t a0, uint32_t a1, uint32_t a2, uint32_t a3,
                                         uint32_t b0, uint32_t b1) {
    asm volatile(
        "mma.sync.aligned.m16n8k16.row.col.f32.bf16.bf16.f32 {%0,%1,%2,%3}, {%4,%5,%6,%7}, {%8,%9}, {%0,%1,%2,%3};"
        : "+f"(d[0]), "+f"(d[1]), "+f"(d[2]), "+f"(d[3])
        : "r"(a0), "r"(a1), "r"(a2), "r"(a3), "r"(b0), "r"(b1));
}
__device__ __forceinline__ void mma1688(float* d, uint32_t a0, uint32_t a1, uint32_t b0) {
    asm volatile("mma.sync.aligned.m16n8k8.row.col.f32.bf16.bf16.f32 {%0,%1,%2,%3}, {%4,%5}, {%6}, {%0,%1,%2,%3};"
                 : "+f"(d[0]), "+f"(d[1]), "+f"(d[2]), "+f"(d[3]) : "r"(a0), "r"(a1), "r"(b0));
}
__device__ __forceinline__ uint32_t any_reg() {
    uint32_t r;
    asm volatile("" : "=r"(r));
    return r;
}
__device__ __forceinline__ uint2 lds64(uint32_t addr) {
    uint2 v;
    asm volatile("ld.volatile.shared.v2.b32 {%0,%1}, [%2];" : "=r"(v.x), "=r"(v.y) : "r"(addr) : "memory");
    return v;
}
__device__ __forceinline__ uint4 lds128(uint32_t addr) {
    uint4 v;
    asm volatile("ld.volatile.shared.v4.b32 {%0,%1,%2,%3}, [%4];" : "=r"(v.x), "=r"(v.y), "=r"(v.z), "=r"(v.w) : "r"(addr) : "memory");
    return v;
}
__device__ __forceinline__ void sts32(uint32_t addr, uint32_t x) {
    asm volatile("st.volatile.shared.b32 [%0], %1;" ::"r"(addr), "r"(x) : "memory");
}
__device__ __forceinline__ void sts64(uint32_t addr, uint32_t x, uint32_t y) {
    asm volatile("st.volatile.shared.v2.b32 [%0], {%1,%2};" ::"r"(addr), "r"(x), "r"(y) : "memory");
}
__device__ __forceinline__ void sts128(uint32_t addr, uint32_t x, uint32_t y, uint32_t z, uint32_t w) {
    asm volatile("st.volatile.shared.v4.b32 [%0], {%1,%2,%3,%4};" ::"r"(addr), "r"(x), "r"(y), "r"(z), "r"(w) : "memory");
}
__device__ __forceinline__ void st_async_v2(uint32_t addr, uint32_t x, uint32_t y, uint32_t bar) {
    asm volatile("st.async.weak.shared::cluster.mbarrier::complete_tx::bytes.v2.b32 [%0], {%1,%2}, [%3];"
                 ::"r"(addr), "r"(x), "r"(y), "r"(bar) : "memory");
}
__device__ __forceinline__ uint2 ld_relaxed_v2(const void* p) {
    uint2 v;
    asm volatile("ld.relaxed.gpu.global.v2.b32 {%0,%1}, [%2];" : "=r"(v.x), "=r"(v.y) : "l"(p) : "memory");
    return v;
}
__device__ __forceinline__ void st_relaxed_v2(void* p, uint32_t x, uint32_t y) {
    asm volatile("st.relaxed.gpu.global.v2.b32 [%0], {%1,%2};" ::"l"(p), "r"(x), "r"(y) : "memory");
}
__device__ __forceinline__ void st_relaxed_v4(void* p, uint32_t x) {
    asm volatile("st.relaxed.gpu.global.v4.b32 [%0], {%1,%1,%1,%1};" ::"l"(p), "r"(x) : "memory");
}
__device__ __forceinline__ uint32_t ld_relaxed_b32(const void* p) {
    uint32_t v;
    asm volatile("ld.relaxed.gpu.global.b32 %0, [%1];" : "=r"(v) : "l"(p) : "memory");
    return v;
}
__device__ __forceinline__ uint32_t lds32_volatile(uint32_t addr) {
    uint32_t v;
    asm volatile("ld.volatile.shared.b32 %0, [%1];" : "=r"(v) : "r"(addr) : "memory");
    return v;
}
__device__ __forceinline__ void st_relaxed_b32(void* p, uint32_t x) {
    asm volatile("st.relaxed.gpu.global.b32 [%0], %1;" ::"l"(p), "r"(x) : "memory");
}

__device__ __forceinline__ uint32_t ld_acquire_b32(const void* p) {
    uint32_t v;
    asm volatile("ld.acquire.gpu.global.b32 %0, [%1];" : "=r"(v) : "l"(p) : "memory");
    return v;
}
__device__ __forceinline__ void wait_flag(const uint32_t* p, uint32_t target) {
    uint32_t n = 0;
    while (ld_acquire_b32(p) < target) {
        __nanosleep(64);
        if (++n > SPIN_LIMIT) __trap();
    }
}
__device__ __forceinline__ void signal_flag(uint32_t* p) {
    asm volatile("red.release.gpu.global.add.u32 [%0], 1;" ::"l"(p) : "memory");
}
__device__ __forceinline__ bool next_to_rec(const uint32_t* flags) {
    uint32_t smid;
    asm volatile("mov.u32 %0, %%smid;" : "=r"(smid));
    smid ^= 1;
    return smid < 384 && ((ld_relaxed_b32(flags + F_RECSM + (smid >> 5)) >> (smid & 31)) & 1);
}
__device__ __forceinline__ void pdl_launch_dependents() { asm volatile("griddepcontrol.launch_dependents;" ::: "memory"); }

constexpr int BM = 128, BK = 64;
constexpr int A_STAGE = BM * BK * 2;
template <int BN> struct GemmCfg {
    static constexpr int STAGES = BN == 256 ? 3 : 6;
    static constexpr int STAGE = A_STAGE + BK * BN * 2;
    static constexpr int EPI_WARP = 16 * BN * 2;
    static constexpr int SMEM = STAGES * STAGE + 8 * EPI_WARP + 1024 + 512;
};

struct SideProb {
    CUtensorMap tmA, tmB, tmC;
    int n_split;
    int n_tiles, k_blocks, k_total, c_col0;
    const uint32_t* dep;
    uint32_t dep_target;
    int dep_n;
    uint32_t* sig;
    float* part;
    uint32_t* part_flag;
};
struct SideSeg { int prob, m0, m1; };
constexpr int SIDE_MAX_SEG = 3;
struct SideParams {
    SideProb prob[3];
    SideSeg seg[SIDE_MAX_SEG];
    int nseg;
    int spare_seg;
    const uint32_t* flags;
    uint32_t* queue;
};
static_assert(sizeof(SideParams) <= 4096, "kernel parameter limit");

__device__ __forceinline__ uint64_t make_desc(uint32_t addr, uint32_t lbo, uint32_t sbo) {
    return (uint64_t)((addr & 0x3FFFF) >> 4) | ((uint64_t)(lbo >> 4) << 16) | ((uint64_t)(sbo >> 4) << 32) | (1ull << 62);
}

__device__ __forceinline__ void wgmma_m64n256k16(float (&d)[128], uint64_t da, uint64_t db, int scale_d) {
    asm volatile(
        "{\n.reg .pred p;\nsetp.ne.b32 p, %130, 0;\n"
        "wgmma.mma_async.sync.aligned.m64n256k16.f32.bf16.bf16 "
        "{%0,%1,%2,%3,%4,%5,%6,%7,%8,%9,%10,%11,%12,%13,%14,%15,"
        "%16,%17,%18,%19,%20,%21,%22,%23,%24,%25,%26,%27,%28,%29,%30,%31,"
        "%32,%33,%34,%35,%36,%37,%38,%39,%40,%41,%42,%43,%44,%45,%46,%47,"
        "%48,%49,%50,%51,%52,%53,%54,%55,%56,%57,%58,%59,%60,%61,%62,%63,"
        "%64,%65,%66,%67,%68,%69,%70,%71,%72,%73,%74,%75,%76,%77,%78,%79,"
        "%80,%81,%82,%83,%84,%85,%86,%87,%88,%89,%90,%91,%92,%93,%94,%95,"
        "%96,%97,%98,%99,%100,%101,%102,%103,%104,%105,%106,%107,%108,%109,%110,%111,"
        "%112,%113,%114,%115,%116,%117,%118,%119,%120,%121,%122,%123,%124,%125,%126,%127},"
        " %128, %129, p, 1, 1, 0, 1;\n}\n"
        : "+f"(d[0]), "+f"(d[1]), "+f"(d[2]), "+f"(d[3]), "+f"(d[4]), "+f"(d[5]), "+f"(d[6]), "+f"(d[7]),
          "+f"(d[8]), "+f"(d[9]), "+f"(d[10]), "+f"(d[11]), "+f"(d[12]), "+f"(d[13]), "+f"(d[14]), "+f"(d[15]),
          "+f"(d[16]), "+f"(d[17]), "+f"(d[18]), "+f"(d[19]), "+f"(d[20]), "+f"(d[21]), "+f"(d[22]), "+f"(d[23]),
          "+f"(d[24]), "+f"(d[25]), "+f"(d[26]), "+f"(d[27]), "+f"(d[28]), "+f"(d[29]), "+f"(d[30]), "+f"(d[31]),
          "+f"(d[32]), "+f"(d[33]), "+f"(d[34]), "+f"(d[35]), "+f"(d[36]), "+f"(d[37]), "+f"(d[38]), "+f"(d[39]),
          "+f"(d[40]), "+f"(d[41]), "+f"(d[42]), "+f"(d[43]), "+f"(d[44]), "+f"(d[45]), "+f"(d[46]), "+f"(d[47]),
          "+f"(d[48]), "+f"(d[49]), "+f"(d[50]), "+f"(d[51]), "+f"(d[52]), "+f"(d[53]), "+f"(d[54]), "+f"(d[55]),
          "+f"(d[56]), "+f"(d[57]), "+f"(d[58]), "+f"(d[59]), "+f"(d[60]), "+f"(d[61]), "+f"(d[62]), "+f"(d[63]),
          "+f"(d[64]), "+f"(d[65]), "+f"(d[66]), "+f"(d[67]), "+f"(d[68]), "+f"(d[69]), "+f"(d[70]), "+f"(d[71]),
          "+f"(d[72]), "+f"(d[73]), "+f"(d[74]), "+f"(d[75]), "+f"(d[76]), "+f"(d[77]), "+f"(d[78]), "+f"(d[79]),
          "+f"(d[80]), "+f"(d[81]), "+f"(d[82]), "+f"(d[83]), "+f"(d[84]), "+f"(d[85]), "+f"(d[86]), "+f"(d[87]),
          "+f"(d[88]), "+f"(d[89]), "+f"(d[90]), "+f"(d[91]), "+f"(d[92]), "+f"(d[93]), "+f"(d[94]), "+f"(d[95]),
          "+f"(d[96]), "+f"(d[97]), "+f"(d[98]), "+f"(d[99]), "+f"(d[100]), "+f"(d[101]), "+f"(d[102]), "+f"(d[103]),
          "+f"(d[104]), "+f"(d[105]), "+f"(d[106]), "+f"(d[107]), "+f"(d[108]), "+f"(d[109]), "+f"(d[110]), "+f"(d[111]),
          "+f"(d[112]), "+f"(d[113]), "+f"(d[114]), "+f"(d[115]), "+f"(d[116]), "+f"(d[117]), "+f"(d[118]), "+f"(d[119]),
          "+f"(d[120]), "+f"(d[121]), "+f"(d[122]), "+f"(d[123]), "+f"(d[124]), "+f"(d[125]), "+f"(d[126]), "+f"(d[127])
        : "l"(da), "l"(db), "r"(scale_d));
}

__device__ __forceinline__ void wgmma_m64n128k16(float (&d)[64], uint64_t da, uint64_t db, int scale_d) {
    asm volatile(
        "{\n.reg .pred p;\nsetp.ne.b32 p, %66, 0;\n"
        "wgmma.mma_async.sync.aligned.m64n128k16.f32.bf16.bf16 "
        "{%0,%1,%2,%3,%4,%5,%6,%7,%8,%9,%10,%11,%12,%13,%14,%15,"
        "%16,%17,%18,%19,%20,%21,%22,%23,%24,%25,%26,%27,%28,%29,%30,%31,"
        "%32,%33,%34,%35,%36,%37,%38,%39,%40,%41,%42,%43,%44,%45,%46,%47,"
        "%48,%49,%50,%51,%52,%53,%54,%55,%56,%57,%58,%59,%60,%61,%62,%63},"
        " %64, %65, p, 1, 1, 0, 1;\n}\n"
        : "+f"(d[0]), "+f"(d[1]), "+f"(d[2]), "+f"(d[3]), "+f"(d[4]), "+f"(d[5]), "+f"(d[6]), "+f"(d[7]),
          "+f"(d[8]), "+f"(d[9]), "+f"(d[10]), "+f"(d[11]), "+f"(d[12]), "+f"(d[13]), "+f"(d[14]), "+f"(d[15]),
          "+f"(d[16]), "+f"(d[17]), "+f"(d[18]), "+f"(d[19]), "+f"(d[20]), "+f"(d[21]), "+f"(d[22]), "+f"(d[23]),
          "+f"(d[24]), "+f"(d[25]), "+f"(d[26]), "+f"(d[27]), "+f"(d[28]), "+f"(d[29]), "+f"(d[30]), "+f"(d[31]),
          "+f"(d[32]), "+f"(d[33]), "+f"(d[34]), "+f"(d[35]), "+f"(d[36]), "+f"(d[37]), "+f"(d[38]), "+f"(d[39]),
          "+f"(d[40]), "+f"(d[41]), "+f"(d[42]), "+f"(d[43]), "+f"(d[44]), "+f"(d[45]), "+f"(d[46]), "+f"(d[47]),
          "+f"(d[48]), "+f"(d[49]), "+f"(d[50]), "+f"(d[51]), "+f"(d[52]), "+f"(d[53]), "+f"(d[54]), "+f"(d[55]),
          "+f"(d[56]), "+f"(d[57]), "+f"(d[58]), "+f"(d[59]), "+f"(d[60]), "+f"(d[61]), "+f"(d[62]), "+f"(d[63])
        : "l"(da), "l"(db), "r"(scale_d));
}
template <int BN> struct WgmmaOp;
template <> struct WgmmaOp<256> {
    static __device__ __forceinline__ void run(float (&d)[128], uint64_t a, uint64_t b, int sc) { wgmma_m64n256k16(d, a, b, sc); }
};
template <> struct WgmmaOp<128> {
    static __device__ __forceinline__ void run(float (&d)[64], uint64_t a, uint64_t b, int sc) { wgmma_m64n128k16(d, a, b, sc); }
};

struct StoreRec {
    uint64_t dst;
    uint64_t flag;
    int kind;
    int pad;
};
struct EpiCtx { uint32_t buf, rec, st_full, st_empty; uint32_t it; int lane; };
template <int N>
__device__ __forceinline__ void epi_hand_over(const float (&acc)[N], EpiCtx& e, uint64_t dst, uint64_t flag, int kind) {
    mbar_wait(e.st_empty, (e.it & 1) ^ 1);
    const int mi = e.lane >> 3, row = (mi & 1) * 8 + (e.lane & 7);
    #pragma unroll
    for (int j = 0; j < N / 4; j += 2) {
        const int chunk = (j & 7) + (mi >> 1);
        stsm_x4(e.buf + (j >> 3) * 2048 + row * 128 + ((chunk ^ (row & 7)) << 4),
                pack_bf16(acc[4 * j], acc[4 * j + 1]), pack_bf16(acc[4 * j + 2], acc[4 * j + 3]),
                pack_bf16(acc[4 * j + 4], acc[4 * j + 5]), pack_bf16(acc[4 * j + 6], acc[4 * j + 7]));
    }
    if (e.lane == 0) {
        asm volatile("st.shared.v2.b64 [%0], {%1, %2};" ::"r"(e.rec), "l"(dst), "l"(flag) : "memory");
        asm volatile("st.shared.b32 [%0], %1;" ::"r"(e.rec + 16), "r"(kind) : "memory");
    }
    asm volatile("fence.proxy.async.shared::cta;" ::: "memory");
    __syncwarp();
    if (e.lane == 0) mbar_arrive(e.st_full);
    e.it++;
}
__device__ __forceinline__ void epi_exit(EpiCtx& e) {
    mbar_wait(e.st_empty, (e.it & 1) ^ 1);
    if (e.lane == 0) {
        asm volatile("st.shared.b32 [%0], %1;" ::"r"(e.rec + 16), "r"(-1) : "memory");
        mbar_arrive(e.st_full);
    }
}
template <int BN, bool PAIR = false>
__device__ __forceinline__ void gemm_mainloop(float (&acc)[BN / 2], int k_blocks, uint32_t sbase, uint32_t bar_base, int cw,
                                              bool elected, int& stage, uint32_t& phase, uint32_t peer = 0) {
    using C = GemmCfg<BN>;
    auto release = [&](int st) {
        const uint32_t bar = bar_base + 8 * (C::STAGES + st);
        mbar_arrive(bar);
        if (PAIR) asm volatile("mbarrier.arrive.shared::cluster.b64 _, [%0];" ::"r"(mapa(bar, peer)) : "memory");
    };
    int prev_stage = -1;
    for (int kb = 0; kb < k_blocks; kb++) {
        mbar_wait(bar_base + 8 * stage, phase);
        const uint32_t sa = sbase + stage * C::STAGE + cw * (64 * 128);
        const uint32_t sb = sbase + stage * C::STAGE + A_STAGE;
        asm volatile("wgmma.fence.sync.aligned;" ::: "memory");
        #pragma unroll
        for (int kk = 0; kk < BK / 16; kk++)
            WgmmaOp<BN>::run(acc, make_desc(sa + kk * 32, 16, 1024), make_desc(sb + kk * 2048, 8192, 1024), (kb | kk) != 0);
        asm volatile("wgmma.commit_group.sync.aligned;" ::: "memory");
        asm volatile("wgmma.wait_group.sync.aligned 1;" ::: "memory");
        if (prev_stage >= 0 && elected) release(prev_stage);
        prev_stage = stage;
        if (++stage == C::STAGES) { stage = 0; phase ^= 1; }
    }
    asm volatile("wgmma.wait_group.sync.aligned 0;" ::: "memory");
    if (elected) release(prev_stage);
}
template <int BN>
__device__ __forceinline__ void store_warp(uint32_t epi_base, uint32_t rec_base, uint32_t st_full, uint32_t st_empty, int lane,
                                           const uint8_t* tmaps, int tstride) {
    for (uint32_t it = 0;; it++) {
        mbar_wait(st_full, it & 1);
        uint64_t dst = 0, flag = 0;
        int kind = -1;
        if (lane < 8) {
            const uint32_t rec = rec_base + lane * 32;
            asm volatile("ld.volatile.shared.v2.b64 {%0, %1}, [%2];" : "=l"(dst), "=l"(flag) : "r"(rec) : "memory");
            kind = (int)lds32_volatile(rec + 16);
        }
        if (__shfl_sync(~0u, kind, 0) < 0) break;
        if (lane < 8) {
            const uint32_t buf = epi_base + lane * GemmCfg<BN>::EPI_WARP;
            #pragma unroll
            for (int q = 0; q < BN / 64; q++) {
                tma_store_2d(reinterpret_cast<const CUtensorMap*>(tmaps + (kind - 1) * tstride), buf + q * 2048,
                                  (int)(uint32_t)dst + q * 64, (int)(dst >> 32));
            }
            bulk_commit();
            bulk_wait_read_all();
            mbar_arrive(st_empty);
            if (flag) {
                bulk_wait_all();
                signal_flag(reinterpret_cast<uint32_t*>(flag));
            }
        }
        __syncwarp();
    }
    if (lane < 8) bulk_wait_all();
}

#define SCHED_AHEAD 4
template <int BN>
__global__ void __launch_bounds__(384, 1) side_gemm_kernel(const __grid_constant__ SideParams p) {
    using C = GemmCfg<BN>;
    extern __shared__ uint8_t smem_raw[];
    const uint32_t sbase = (smem_u32(smem_raw) + 1023) & ~1023u;
    const uint32_t epi_base = sbase + C::STAGES * C::STAGE;
    const uint32_t bar_base = epi_base + 8 * C::EPI_WARP;
    const uint32_t tfull = bar_base + 16 * C::STAGES, tempty = tfull + 16, tslot = tempty + 16, twant = tslot + 8;
    const uint32_t st_full = bar_base + 192, st_empty = st_full + 8, rec_base = bar_base + 256;
    const int tid = threadIdx.x, wg = tid >> 7;
    if (tid == 0) {
        for (int s = 0; s < C::STAGES; s++) { mbar_init(bar_base + 8 * s, 1); mbar_init(bar_base + 8 * (C::STAGES + s), 2); }
        for (int s = 0; s < 2; s++) { mbar_init(tfull + 8 * s, 1); mbar_init(tempty + 8 * s, 3); }
        mbar_init(twant, 1);
        mbar_init(st_full, 8);
        mbar_init(st_empty, 8);
        asm volatile("fence.mbarrier_init.release.cluster;" ::: "memory");
        pdl_launch_dependents();
    }
    __syncthreads();
    KENTER(BN == 256 ? (p.nseg == 1 ? 6 : 2) : 4);

    if (wg == 0) {
        asm volatile("setmaxnreg.dec.sync.aligned.u32 40;");
        if (tid == 0) {
            int stage = 0; uint32_t phase = 1;
            for (uint32_t it = 0;; it++) {
                mbar_wait(tfull + 8 * (it & 1), (it >> 1) & 1);
                const int code = (int)lds32_volatile(tslot + 4 * (it & 1));
                mbar_arrive(tempty + 8 * (it & 1));
                if (code < 0) break;
                const SideProb& q = p.prob[code >> 16];
                const int mt = (code >> 8) & 255, nt = code & 255;
                asm volatile("fence.proxy.async.global;" ::: "memory");
                const int kb0 = nt / q.n_split * q.k_blocks, nkb = nt + q.n_split < q.n_tiles ? q.k_blocks : q.k_total - kb0;
                for (int kb = 0; kb < nkb; kb++) {
                    if (kb == nkb - SCHED_AHEAD) mbar_arrive(twant);
                    mbar_wait(bar_base + 8 * (C::STAGES + stage), phase);
                    const uint32_t sa = sbase + stage * C::STAGE, fb = bar_base + 8 * stage;
                    mbar_arrive_expect_tx(fb, C::STAGE);
                    const int k0 = (kb0 + kb) * BK;
                    tma_load_2d(sa, &q.tmA, k0, mt * BM, fb);
                    tma_load_3d(sa + A_STAGE, &q.tmB, 0, k0, nt % q.n_split * (BN / 64), fb);
                    if (++stage == C::STAGES) { stage = 0; phase ^= 1; }
                }
            }
        } else if (tid >= 64 && tid < 96) {
            const int lane = tid & 31;
            const bool spare = p.spare_seg < 3 && next_to_rec(p.flags);
            uint32_t ntl[2], tgt[2], prb[2];
            const uint32_t* dp[2];
            #pragma unroll
            for (int u = 0; u < 2; u++) {
                const int g = u * 2 + (lane >> 4), mt = lane & 15;
                const bool on = g < p.nseg && mt >= p.seg[g < p.nseg ? g : 0].m0 && mt < p.seg[g < p.nseg ? g : 0].m1;
                prb[u] = p.seg[on ? g : 0].prob;
                const SideProb& q = p.prob[prb[u]];
                ntl[u] = on && !(g >= p.spare_seg && spare) ? q.n_tiles : 0;
                tgt[u] = on && q.dep ? q.dep_target : 0;
                dp[u] = tgt[u] ? q.dep + (mt + 1) * q.dep_n - 1 : p.queue;
            }
            for (uint32_t it = 0;; it++) {
                if (it > 0) mbar_wait_sleep(twant, (it - 1) & 1);
                int code = -1;
                for (uint32_t tries = 0; code < 0; tries++) {
                    const uint32_t c0 = ld_relaxed_b32(p.queue + lane), c1 = ld_relaxed_b32(p.queue + 32 + (lane & 15));
                    const uint32_t d0 = ld_relaxed_b32(dp[0]), d1 = ld_relaxed_b32(dp[1]);
                    const uint64_t left = __ballot_sync(~0u, c0 < ntl[0]) | (uint64_t)__ballot_sync(~0u, c1 < ntl[1]) << 32;
                    uint64_t ready = left & (__ballot_sync(~0u, d0 >= tgt[0]) | (uint64_t)__ballot_sync(~0u, d1 >= tgt[1]) << 32);
                    if (!left) break;
                    if (!ready && (BN == 128 || (left >> (((__ffsll(left) - 1) & ~15) + 16)) == 0)) ready = left;
                    if (!ready) __nanosleep(200);
                    while (ready) {
                        const int e = __ffsll(ready) - 1;
                        const uint32_t n = __shfl_sync(~0u, e < 32 ? ntl[0] : ntl[1], e & 31), pr = __shfl_sync(~0u, e < 32 ? prb[0] : prb[1], e & 31);
                        uint32_t idx = 0;
                        if (lane == 0) idx = atomicAdd(p.queue + e, 1u);
                        idx = __shfl_sync(~0u, idx, 0);
                        if (idx < n) { code = (pr << 16) | ((e & 15) << 8) | idx; break; }
                        for (uint32_t k = idx / n; k > 0; k--) ready &= ready - 1;
                    }
                    if (tries > SPIN_LIMIT) __trap();
                }
                if (code >= 0) {
                    const SideProb& q = p.prob[code >> 16];
                    if (q.dep && lane < q.dep_n) wait_flag(q.dep + ((code >> 8) & 255) * q.dep_n + lane, q.dep_target);
                    __syncwarp();
                }
                if (lane == 0) {
                    mbar_wait(tempty + 8 * (it & 1), ((it >> 1) & 1) ^ 1);
                    asm volatile("st.shared.b32 [%0], %1;" ::"r"(tslot + 4 * (it & 1)), "r"(code) : "memory");
                    mbar_arrive(tfull + 8 * (it & 1));
                }
                __syncwarp();
                if (code < 0) break;
            }
        } else if (tid >= 32 && tid < 64) {
            store_warp<BN>(epi_base, rec_base, st_full, st_empty, tid & 31, reinterpret_cast<const uint8_t*>(&p.prob[0].tmC),
                           (int)sizeof(SideProb));
        }
    } else {
        asm volatile("setmaxnreg.inc.sync.aligned.u32 232;");
        const int cw = wg - 1, lane = tid & 31, wi = (tid >> 5) & 3;
        const bool elected = (tid & 127) == 0;
        int stage = 0; uint32_t phase = 0;
        float acc[BN / 2];
        EpiCtx ectx = {epi_base + (cw * 4 + wi) * C::EPI_WARP, rec_base + (cw * 4 + wi) * 32, st_full, st_empty, 0, lane};
        for (uint32_t it = 0;; it++) {
            mbar_wait(tfull + 8 * (it & 1), (it >> 1) & 1);
            const int code = (int)lds32_volatile(tslot + 4 * (it & 1));
            named_bar_sync(1 + cw, 128);
            if (elected) mbar_arrive(tempty + 8 * (it & 1));
            if (code < 0) break;
            const SideProb& q = p.prob[code >> 16];
            const int mt = (code >> 8) & 255, nt = code & 255;
            gemm_mainloop<BN>(acc, nt + q.n_split < q.n_tiles ? q.k_blocks : q.k_total - nt / q.n_split * q.k_blocks, sbase, bar_base, cw, elected, stage, phase);
            const int row0 = mt * BM + cw * 64 + wi * 16, ntc = nt % q.n_split;
            if (BN == 128 && q.part) {
                const int idx = (mt & 3) * q.n_split + ntc, item = nt / q.n_split, nprev = q.n_tiles / q.n_split - 1;
                float4* part = reinterpret_cast<float4*>(q.part) + (size_t)idx * 2 * (BM * BN / 4) + (tid - 128);
                if (mt == 14 && elected) KMARK(21);
                if (item < nprev) {
                    #pragma unroll
                    for (int j = 0; j < BN / 8; j++)
                        __stcg(part + item * (BM * BN / 4) + j * 256, make_float4(acc[4 * j], acc[4 * j + 1], acc[4 * j + 2], acc[4 * j + 3]));
                    __syncwarp();
                    if (lane == 0) signal_flag(q.part_flag + idx);
                    continue;
                }
                if (lane == 0) wait_flag(q.part_flag + idx, 8 * nprev);
                __syncwarp();
                if (mt == 14 && elected) KMARK(22);
                for (int u = 0; u < nprev; u++) {
                    #pragma unroll
                    for (int j = 0; j < BN / 8; j++) {
                        const float4 v = __ldcg(part + u * (BM * BN / 4) + j * 256);
                        acc[4 * j] += v.x; acc[4 * j + 1] += v.y; acc[4 * j + 2] += v.z; acc[4 * j + 3] += v.w;
                    }
                }
            }
            if (BN == 128 && mt == 14 && elected) KMARK(23);
            epi_hand_over(acc, ectx, ((uint64_t)row0 << 32) | (uint32_t)(q.c_col0 + ntc * BN), q.sig ? (uint64_t)(q.sig + mt) : 0, 1 + (code >> 16));
        }
        epi_exit(ectx);
        if (elected) KEXIT(BN == 256 ? (p.nseg == 1 ? 6 : 2) : 4);
    }
}

#define FIN_LATE 3
constexpr int FIN_SPLIT = 8, FIN_KB = HD / BK / FIN_SPLIT;
constexpr int FIN_A1 = FIN_KB * 16384;
constexpr int FIN_A0 = FIN_A1 + FIN_KB * 8192;
constexpr int FIN_BAR = FIN_A0 + 4 * 8192, FIN_SMEM = FIN_BAR + 256;
enum { FB_B = 0, FB_A1 = 64, FB_A0 = 128, FB_E0 = 160, FB_RDY = 192, FB_RED = 208 };
struct FinalParams {
    CUtensorMap tmA, tmB;
    __nv_bfloat16* out;
    const uint32_t* dep;
    uint32_t dep_target;
    int mt;
};
__global__ void __launch_bounds__(384, 1) final_gemm_kernel(const __grid_constant__ FinalParams p) {
    extern __shared__ __align__(1024) uint8_t smem_raw[];
    const uint32_t sbase = smem_u32(smem_raw), bar = sbase + FIN_BAR;
    const int tid = threadIdx.x, wg = tid >> 7;
    const int rank = blockIdx.x % FIN_SPLIT, nt = blockIdx.x / FIN_SPLIT;
    KENTER(5);
    if (tid == 0) {
        for (int s = 0; s < FIN_KB; s++) { mbar_init(bar + FB_B + 8 * s, 1); mbar_init(bar + FB_A1 + 8 * s, 1); }
        for (int s = 0; s < 4; s++) { mbar_init(bar + FB_A0 + 8 * s, 1); mbar_init(bar + FB_E0 + 8 * s, 1); }
        for (int h = 0; h < 2; h++) { mbar_init(bar + FB_RDY + 8 * h, FIN_SPLIT); mbar_init(bar + FB_RED + 8 * h, 1); }
        asm volatile("fence.mbarrier_init.release.cluster;" ::: "memory");
        for (int h = 0; h < 2; h++) mbar_arrive_expect_tx(bar + FB_RED + 8 * h, (FIN_SPLIT - 1) * 4096);
        pdl_launch_dependents();
    }
    __syncthreads();
    asm volatile("barrier.cluster.arrive.relaxed.aligned;" ::: "memory");
    if (wg == 0) {
        auto need = [&](int i) {
            uint32_t n = 0;
            while (ld_acquire_b32(p.dep + i) < p.dep_target) { if (++n > SPIN_LIMIT) __trap(); }
            asm volatile("fence.proxy.async.global;" ::: "memory");
        };
        auto a_load = [&](uint32_t dst, int kb, int seg, uint32_t mb) { tma_load_2d(dst, &p.tmA, (rank * FIN_KB + kb) * BK, p.mt * BM + seg * SEG, mb); };
        if (tid == 0) {
            auto b_load = [&](int kb) {
                mbar_arrive_expect_tx(bar + FB_B + 8 * kb, 16384);
                tma_load_3d(sbase + kb * 16384, &p.tmB, 0, (rank * FIN_KB + kb) * BK, nt * 2, bar + FB_B + 8 * kb);
            };
            const uint32_t f0 = ld_relaxed_b32(p.dep);
            b_load(0);
            need(1);
            if (f0 < p.dep_target) need(0);
            for (int kb = 0; kb < FIN_KB; kb++) {
                if (kb >= 4) mbar_wait(bar + FB_E0 + 8 * (kb & 3), 0);
                mbar_arrive_expect_tx(bar + FB_A0 + 8 * (kb & 3), 8192);
                for (int u = 0; u < 2; u++) a_load(sbase + FIN_A0 + (kb & 3) * 8192 + u * 4096, kb, u, bar + FB_A0 + 8 * (kb & 3));
                if (kb < 3) b_load(kb + 1);
                if (kb == 3) { b_load(4); b_load(5); }
                if (kb == 4 || kb == 5) b_load(kb + 2);
            }
        } else if (tid == 96) {
            need(3);
            for (int kb = 1; kb < FIN_KB; kb += 2) a_load(sbase + FIN_A1 + kb * 8192 + 4096, kb, 3, bar + FB_A1 + 8 * kb);
        } else if (tid == 64) {
            if (FIN_LATE >= 0) mbar_wait(bar + FB_B + 8 * FIN_LATE, 0);
            need(2);
            for (int kb = 0; kb < FIN_KB; kb++) {
                mbar_arrive_expect_tx(bar + FB_A1 + 8 * kb, 8192);
                a_load(sbase + FIN_A1 + kb * 8192, kb, 2, bar + FB_A1 + 8 * kb);
            }
            need(3);
            KMARK(15);
            for (int kb = 0; kb < FIN_KB; kb += 2) a_load(sbase + FIN_A1 + kb * 8192 + 4096, kb, 3, bar + FB_A1 + 8 * kb);
        }
        __syncwarp();
        asm volatile("barrier.cluster.wait.aligned;" ::: "memory");
    } else {
        const int h = wg - 1, lane = tid & 31, wi = (tid >> 5) & 3, t128 = tid & 127;
        asm volatile("barrier.cluster.wait.aligned;" ::: "memory");
        float acc[64];
        for (int kb = 0; kb < FIN_KB; kb++) {
            mbar_wait(bar + FB_B + 8 * kb, 0);
            if (h == 0) mbar_wait(bar + FB_A0 + 8 * (kb & 3), kb >> 2); else mbar_wait(bar + FB_A1 + 8 * kb, 0);
            const uint32_t sa = sbase + (h == 0 ? FIN_A0 + (kb & 3) * 8192 : FIN_A1 + kb * 8192), sb = sbase + kb * 16384;
            asm volatile("wgmma.fence.sync.aligned;" ::: "memory");
            #pragma unroll
            for (int kk = 0; kk < BK / 16; kk++)
                wgmma_m64n128k16(acc, make_desc(sa + kk * 32, 16, 1024), make_desc(sb + kk * 2048, 8192, 1024), (kb | kk) != 0);
            asm volatile("wgmma.commit_group.sync.aligned;" ::: "memory");
            asm volatile("wgmma.wait_group.sync.aligned 1;" ::: "memory");
            if (h == 0 && kb >= 1 && kb <= 4 && t128 == 0) mbar_arrive(bar + FB_E0 + 8 * (kb - 1));
        }
        asm volatile("wgmma.wait_group.sync.aligned 0;" ::: "memory");
        const uint32_t red = sbase + FIN_A0;
        auto ready = [&](int i) {
            named_bar_sync(1, 128);
            if (t128 < FIN_SPLIT)
                asm volatile("mbarrier.arrive.relaxed.cluster.shared::cluster.b64 _, [%0];" ::"r"(mapa(bar + FB_RDY + 8 * i, t128)) : "memory");
        };
        if (tid == 256) KMARK(16);
        if (tid == 128) KMARK(19);
        if (h == 0) ready(0);
        mbar_wait(bar + FB_RDY + 8 * h, 0);
        if (tid == 256) KMARK(17);
        #pragma unroll
        for (int q = 0; q < FIN_SPLIT; q++) {
            if (q != rank) {
                const uint32_t dst = mapa(red + (rank - (rank > q ? 1 : 0)) * 4096 + t128 * 16, q), rb = mapa(bar + FB_RED + 8 * h, q);
                #pragma unroll
                for (int j = 0; j < 2; j++)
                    asm volatile("st.async.weak.shared::cluster.mbarrier::complete_tx::bytes.v4.f32 [%0], {%1,%2,%3,%4}, [%5];"
                                 ::"r"(dst + j * 2048), "f"(acc[8 * q + 4 * j]), "f"(acc[8 * q + 4 * j + 1]),
                                   "f"(acc[8 * q + 4 * j + 2]), "f"(acc[8 * q + 4 * j + 3]), "r"(rb) : "memory");
            }
        }
        float o[8];
        #pragma unroll
        for (int q = 0; q < FIN_SPLIT; q++)
            if (q == rank) {
                #pragma unroll
                for (int e = 0; e < 8; e++) o[e] = acc[8 * q + e];
            }
        mbar_wait(bar + FB_RED + 8 * h, 0);
        if (tid == 256) KMARK(18);
        if (tid == 128) KMARK(20);
        #pragma unroll
        for (int sl = 0; sl < FIN_SPLIT - 1; sl++) {
            #pragma unroll
            for (int j = 0; j < 2; j++) {
                const uint4 v = lds128(red + sl * 4096 + j * 2048 + t128 * 16);
                o[4 * j] += __uint_as_float(v.x); o[4 * j + 1] += __uint_as_float(v.y);
                o[4 * j + 2] += __uint_as_float(v.z); o[4 * j + 3] += __uint_as_float(v.w);
            }
        }
        if (h == 0) ready(1);
        __nv_bfloat16* dst = p.out + (size_t)(p.mt * BM + h * 64 + wi * 16 + (lane >> 2)) * (2 * DM) + nt * 128 + rank * 16 + (lane & 3) * 2;
        #pragma unroll
        for (int j = 0; j < 2; j++) {
            *reinterpret_cast<uint32_t*>(dst + j * 8) = pack_bf16(o[4 * j], o[4 * j + 1]);
            *reinterpret_cast<uint32_t*>(dst + (size_t)8 * (2 * DM) + j * 8) = pack_bf16(o[4 * j + 2], o[4 * j + 3]);
        }
        if (t128 == 0) KEXIT(5);
    }
}

#define POLL_DELAY 2
#define FETCH_DELAY 360
#define AT_PF 7
#define TOK_MOVED1 4
#define AT_POS0 0
#define FETCH_REL 1
#define REPOLL 1
#define V_EARLY 6
#define XB_POS 0
#define PARK_LATE 0
#define ST_POS 1
#define RST_POS 0
#define KV_POS 1
#define X0_POS 2
#define SPEC_SUM 0
#define AT_FIRST 4
#define AT_AHEAD 4
#define PRO_EARLY 0
#define PDL_POS 5
#define WO_FENCE 0
#define WO_PFA 4
#define WO_PFB_DELAY 60
#define EXP 0
#define NO_COMM 0
#define TOK_MOVED 8
#define XB_DELAY 0
#define WO_PF0 0
#define WO_PF1 11
#define WO_AHEAD 10
constexpr int REC_THREADS = 256;
constexpr uint32_t POLL_LIMIT = 1u << 16;
constexpr int NREG = 24;
__host__ __device__ constexpr int reg_idx(int j) { return ((j & 3) - 1) * 8 + (j >> 2); }
constexpr int SM_WQ = 0;
constexpr int SM_WO = 65536;
constexpr int SM_X = SM_WO + 11 * 8192;
constexpr int SM_PARK0 = SM_X, SM_PARK1 = SM_X + 8192;
constexpr int SM_MEM = SM_X + 4 * 4096;
constexpr int SM_RED = SM_X + 8 * 4096;
constexpr int SM_V = SM_X + 12 * 4096;
constexpr int SM_K = SM_X + 14 * 4096;
constexpr int SM_QS = SM_X + 15 * 4096;
constexpr int SM_QK = SM_X + 65536;
constexpr int SM_SP = SM_QK + 2048;
constexpr int SM_VM = SM_SP + 2560;
constexpr int SM_O = SM_VM + 2048;
constexpr int SM_SUM = SM_O + 2048;
constexpr int SM_TBL = SM_SUM + 128;
constexpr int SM_BAR = SM_TBL + 512;
constexpr int SM_STAMP = SM_BAR + 224;
constexpr int REC_SMEM = SM_STAMP;
static_assert(REC_SMEM <= 232448, "shared memory");
enum { BAR_V = 0, BAR_X = 8, BAR_P0 = 16, BAR_WQ = 40, BAR_WO = 48, BAR_XG = 56, BAR_F0 = 88, BAR_F3 = 96, BAR_VF = 104,
       BAR_M = 112, BAR_GO = 144, BAR_PK = 152, BAR_VM = 160, BAR_SELF = 168, BAR_TPUB = 176, BAR_MIN = 176, BAR_PUB = 192 };

template <int V> struct IntC { static constexpr int value = V; };
template <int I, int N, typename F> __device__ __forceinline__ void sfor(F&& f) {
    if constexpr (I < N) { f(IntC<I>{}); sfor<I + 1, N>(f); }
}

struct RecParams {
    CUtensorMap tmW[3];
    CUtensorMap tmWo;
    CUtensorMap tmX;
    const __nv_bfloat16* mem0;
    __nv_bfloat16* qkv_tok;
    __nv_bfloat16* kv_mem;
    uint8_t* xchg;
    uint32_t* flags;
    uint32_t one[2];
    uint32_t* arrivals;
};

__device__ __forceinline__ void mma_a(float* d, const uint32_t* a, uint32_t b0, uint32_t b1) {
    mma16816(d, a[0], a[1], a[2], a[3], b0, b1);
}
__device__ __forceinline__ void ldsm4(uint32_t addr, uint32_t* r) { ldsm_x4(addr, r[0], r[1], r[2], r[3]); }
__device__ __forceinline__ void ldsm4t(uint32_t addr, uint32_t* r) { ldsm_x4_t(addr, r[0], r[1], r[2], r[3]); }
template <int OFF> __device__ __forceinline__ void poll_v2(uint2& v, const uint8_t* p) {
    asm volatile("ld.relaxed.gpu.global.v2.b32 {%0,%1}, [%2+%3];" : "=r"(v.x), "=r"(v.y) : "l"(p), "n"(OFF) : "memory");
}
template <int OFF> __device__ __forceinline__ void repoll_v2(uint2& v, const uint8_t* p) {
    asm volatile("{\n.reg .pred q;\nsetp.eq.u32 q, %1, 0xFFFFFFFF;\n@q ld.relaxed.gpu.global.v2.b32 {%0,%1}, [%2+%3];\n}"
                 : "+r"(v.x), "+r"(v.y) : "l"(p), "n"(OFF) : "memory");
}
__device__ __forceinline__ uint32_t max3(uint32_t a, uint32_t b, uint32_t c) { return max(max(a, b), c); }
__device__ __forceinline__ uint32_t pub_slot(int s) { return (s & 1) * XCHG_SLOT + ((s >> 1) & 1) * PUB_BYTES; }

__device__ __forceinline__ uint8_t* xaddr(uint32_t lo, uint32_t hi) {
    uint64_t a;
    asm("mov.b64 %0, {%1, %2};" : "=l"(a) : "r"(lo), "r"(hi));
    return reinterpret_cast<uint8_t*>(a);
}
template <int N> __device__ __forceinline__ uint32_t delay_zero(uint32_t a) {
    uint32_t x = a;
    #pragma unroll
    for (int i = 0; i < N; i++) x = lds32_volatile(x);
    return x - a;
}
__device__ __forceinline__ uint32_t fresh(uint32_t x) { asm volatile("" : "+r"(x)); return x; }

template <int NT> __device__ __forceinline__ uint32_t wo_addr(uint32_t ao, uint32_t a3, int n) {
    return (n % NT == 2 ? a3 : ao + (n % NT) * 32768) + (n / NT) * 1024;
}
__device__ __forceinline__ void sched_fence(uint32_t& x, uint32_t zero) { x ^= clock32() & zero; }
template <int NT, int PF, typename F>
__device__ __forceinline__ void wo_phase(F&& hook, uint32_t (&st)[8 * NT][4], uint32_t ao, uint32_t a3, uint32_t l16, uint32_t tbl, uint32_t sums,
                                         uint32_t slot, uint32_t xhi, uint32_t third, uint32_t zero, uint32_t& tok, uint32_t xbar, uint32_t xpar, bool& x_ok) {
    constexpr int AHEAD = PF > WO_AHEAD ? PF - NT : WO_AHEAD;
    uint32_t of[4][4];
    uint2 sm;
    uint4 t;
    ldsm4t(l16 + SM_O, of[0]);
    #pragma unroll
    for (int n = PF; n < AHEAD; n++) {
        ldsm4t(wo_addr<NT>(ao, a3, n), st[n]);
        if (n == 2 * NT - 1) ldsm4t(l16 + SM_O + 512, of[1]);
    }
    if (PF >= 2 * NT) ldsm4t(l16 + SM_O + 512, of[1]);
    float acc[NT][4];
    #pragma unroll
    for (int i = 0; i < NT; i++) { acc[i][0] = acc[i][1] = acc[i][2] = acc[i][3] = 0.f; }
    #pragma unroll
    for (int kk = 0; kk < 8; kk++) {
        if (WO_FENCE && kk < 7) sched_fence(tok, zero);
        #pragma unroll
        for (int i = 0; i < NT; i++) {
            const int n = kk * NT + i;
            mma_a(acc[i], st[n], of[kk >> 1][(kk & 1) * 2], of[kk >> 1][(kk & 1) * 2 + 1]);
            if (n + AHEAD >= PF && n + AHEAD < 8 * NT) ldsm4t(wo_addr<NT>(ao, a3, n + AHEAD), st[n + AHEAD]);
        }
        if (kk == XB_POS - 1) hook();
        if (kk == 1 || kk == 3) ldsm4t(l16 + SM_O + ((kk >> 1) + 2) * 512, of[(kk >> 1) + 2]);
        if (kk == (NT == 3 ? 5 : 4)) {
            const uint32_t x = fresh(l16);
            sm = lds64(sums + ((x >> 1) & 0x18));
            t = lds128(tbl + ((x >> 3) & 0x30));
            x_ok = mbar_test_wait(xbar, xpar);
        }
    }
    const float i0 = rcp(__uint_as_float(sm.x)), i1 = rcp(__uint_as_float(sm.y));
    const uint32_t d = slot + ((fresh(l16) >> 1) & 0x38);
    const uint32_t pl[3] = {t.x + d, t.y + d, t.z + d};
    #pragma unroll
    for (int i = 0; i < NT; i++)
        asm volatile("{\n.reg .pred p;\nsetp.ne.u32 p, %3, 0;\n@p st.relaxed.gpu.global.v2.b32 [%0], {%1,%2};\n}"
                     ::"l"(xaddr(pl[i], xhi)), "r"(pack_bf16(acc[i][0] * i0, acc[i][1] * i1)), "r"(pack_bf16(acc[i][2] * i0, acc[i][3] * i1)),
                       "r"(i < 2 ? 1u : third) : "memory");
}

constexpr uint32_t SMEM_ORIGIN = 1024;
constexpr uint64_t DESC_BASE = (1ull << 16) | (0x40000040ull << 32);
template <int OFFB, int SCALE_D>
__device__ __forceinline__ void wgmma_n32_rs(float (&d)[16], const uint32_t* a, uint32_t one) {
    asm volatile(
        "{\n.reg .b64 db;\nmad.wide.u32 db, %20, %21, %22;\n"
        "wgmma.mma_async.sync.aligned.m64n32k16.f32.bf16.bf16 {%0,%1,%2,%3,%4,%5,%6,%7,%8,%9,%10,%11,%12,%13,%14,%15}, "
        "{%16,%17,%18,%19}, db, %23, 1, 1, 0;\n}"
        : "+f"(d[0]), "+f"(d[1]), "+f"(d[2]), "+f"(d[3]), "+f"(d[4]), "+f"(d[5]), "+f"(d[6]), "+f"(d[7]),
          "+f"(d[8]), "+f"(d[9]), "+f"(d[10]), "+f"(d[11]), "+f"(d[12]), "+f"(d[13]), "+f"(d[14]), "+f"(d[15])
        : "r"(a[0]), "r"(a[1]), "r"(a[2]), "r"(a[3]), "r"(one), "n"((SMEM_ORIGIN + OFFB) >> 4), "l"(DESC_BASE), "n"(SCALE_D));
}
template <int OFFA, int OFFB, int SCALE_D>
__device__ __forceinline__ void wgmma_n32_ss(float (&d)[16], uint32_t one) {
    asm volatile(
        "{\n.reg .b64 da, db;\nmad.wide.u32 da, %16, %17, %19;\nmad.wide.u32 db, %16, %18, %19;\n"
        "wgmma.mma_async.sync.aligned.m64n32k16.f32.bf16.bf16 {%0,%1,%2,%3,%4,%5,%6,%7,%8,%9,%10,%11,%12,%13,%14,%15}, "
        "da, db, %20, 1, 1, 1, 0;\n}"
        : "+f"(d[0]), "+f"(d[1]), "+f"(d[2]), "+f"(d[3]), "+f"(d[4]), "+f"(d[5]), "+f"(d[6]), "+f"(d[7]),
          "+f"(d[8]), "+f"(d[9]), "+f"(d[10]), "+f"(d[11]), "+f"(d[12]), "+f"(d[13]), "+f"(d[14]), "+f"(d[15])
        : "r"(one), "n"((SMEM_ORIGIN + OFFA) >> 4), "n"((SMEM_ORIGIN + OFFB) >> 4), "l"(DESC_BASE), "n"(SCALE_D));
}
template <int WG, int J0, int J1, int I, bool ACC, bool FENCE = true>
__device__ __forceinline__ void token_mma(float (&ta)[2][16], const uint32_t (&wr)[NREG][2][4], uint32_t one) {
    if (FENCE) asm volatile("wgmma.fence.sync.aligned;" ::: "memory");
    sfor<J0, J1>([&](auto J) {
        constexpr int j = J.value, c = j >> 2, offb = SM_X + WG * 32768 + c * 4096 + (j & 3) * 32, sc = (ACC || j != J0) ? 1 : 0;
        if constexpr ((j & 3) != 0) wgmma_n32_rs<offb, sc>(ta[I], wr[reg_idx(j)][I], one);
        else if constexpr (WG == 0 || c >= (I ? TOK_MOVED1 : TOK_MOVED)) wgmma_n32_ss<SM_WQ + WG * 32768 + I * 16384 + c * 2048, offb, sc>(ta[I], one);
        constexpr int m = I ? c : c - 4;
        if constexpr (WG == 0 && (j & 3) == 1 && m >= 0 && m < (I ? TOK_MOVED : TOK_MOVED1))
            wgmma_n32_ss<SM_WQ + 32768 + (1 - I) * 16384 + m * 2048, SM_X + 32768 + m * 4096, 1>(ta[I], one);
    });
    asm volatile("wgmma.commit_group.sync.aligned;" ::: "memory");
}
__device__ __forceinline__ void warp_arrive(uint32_t bar) {
    __syncwarp();
    if (elect_one()) mbar_arrive(bar);
}
__device__ __forceinline__ void remote_arrive(uint32_t bar, uint32_t rank) {
    asm volatile("mbarrier.arrive.relaxed.cluster.shared::cluster.b64 _, [%0];" ::"r"(mapa(bar, rank)) : "memory");
}
__device__ __forceinline__ void x_load(const RecParams& p, uint32_t sb, int sg, int g) {
    if ((EXP >> g) & 1) return;
    tma_load_3d_mc(sb + SM_X + g * 16384, &p.tmX, 0, sg * SEG, g * 4, sb + SM_BAR + BAR_XG + 8 * g, (uint16_t)7);
}

__device__ __forceinline__ void rec_steps(const RecParams& p, const uint32_t (&wr)[NREG][2][4], const uint32_t sb, const int warp,
                                          const int cta, const int head, const int rank) {
    const int wq = warp & 3, wg = warp >> 2;
    const uint32_t bar = sb + SM_BAR;
    const uint32_t xhi = (uint32_t)((uint64_t)p.xchg >> 32);
    const float sl2 = 0.08838834764831845f * 1.4426950408889634f;
    const bool has_unit = warp >= 5 && (warp < 7 || cta < 64);
    const bool qk = rank < 2;
    const uint32_t pa = rank == 2 ? 0 : rank + 1, pb = rank == 0 ? 2 : rank - 1;
    const uint32_t tbl = sb + SM_TBL + warp * 64;
    const bool att = (warp & 6) == 2;
    const int stile = warp < 5 ? warp : warp - 3;

    const uint32_t u_st = uniform(SM_QK - SM_WQ - wg * (32768 - 1024));
    const uint32_t u_xa = uniform(sb + (qk ? SM_SP + rank * 1280 + stile * 256 : SM_VM + warp * 256));
    const uint32_t u_key = uniform(!qk || att || warp == 7 ? 0 : sb + (warp == 4 ? SM_QK + 1024 : SM_K + stile * 1024));
    const uint32_t u_bx = uniform(bar + (qk ? BAR_X : BAR_VM)), u_bra = uniform(mapa(u_bx, pa)), u_brb = uniform(mapa(u_bx, pb));
    const uint32_t u_src = uniform(lds32_volatile(tbl + 44));
    const uint32_t u_kv = uniform(qk && wg == 0 ? ~0u : (((rank >> 1) * NSEG * NH + head) * 8 + (qk ? rank * 4 + wq : warp)) * 64);
    const uint32_t u_free = uniform(mapa(bar + (warp == 5 ? BAR_VF : BAR_F0), warp == 5 ? 2 : 0));
    const uint32_t u_role = uniform((has_unit ? 1 : 0) | (att ? 2 : 0) | (wg == 1 || qk ? 4 : 0) | (!qk && warp == 0 ? 8 : 0) | (rank != 0 && warp == (XB_POS ? 2 : 1) ? 16 : 0) |
                                    (warp == 5 || warp == 6 ? 32 : 0));
    uint32_t l16, aq, ao;
    {
        const int lane = threadIdx.x & 31, mi = lane >> 3, r8 = lane & 7, r16 = (mi >> 1) * 8 + r8;
        l16 = opaque(sb + lane * 16);
        aq = opaque(sb + SM_WQ + wg * 32768 + r16 * 128 + (((wq * 2 + (mi & 1)) ^ r8) << 4));
        ao = opaque(sb + SM_WO + (warp >> 1) * 8192 + r16 * 64 + ((((warp & 1) * 2 + (mi & 1)) ^ ((r8 >> 1) & 3)) << 4));
    }

    uint32_t mphase = 0;
    bool x0_ok = false;
    #pragma unroll 1
    for (int s = 0;; s++) {
        const uint32_t par = s & 1;
        uint32_t at[16][4];
        auto at_early = [](int i) { return i < 2 || ((i & 1) == 1 && (i >> 1) <= AT_PF - 2); };
        auto at_prefetch = [&](bool first) {
            #pragma unroll
            for (int i = 0; i < 16; i++)
                if (at_early(i) && first == ((i & 1) == 1 && (i >> 1) < AT_FIRST)) ldsm4t(aq + (i & 1) * 16384 + (i >> 1) * 2048, at[i]);
        };
        auto resets = [&](int late) {
            if ((u_role & 1) && (late || s > 0)) {
                const uint32_t lane = (fresh(l16) >> 4) & 31;
                uint8_t* ib = xaddr(lds32_volatile(tbl + 12) + (par ^ late) * XCHG_SLOT + lane * 16, xhi);
                #pragma unroll
                for (int i = 0; i < 4; i++) st_relaxed_v4(ib + i * 512, SENT);
                st_relaxed_b32(xaddr(lds32_volatile(tbl + 28) + pub_slot(s + 2 + late) + (lane & 16) * 256 + (lane & 8) * 16 + (lane & 7) * 4, xhi), SENT);
            }
        };
        auto tile_stores = [&]() {
            if (warp == 4) {
                asm volatile("fence.proxy.async.shared::cta;" ::: "memory");
                if (elect_one()) {
                    __nv_bfloat16* dst = p.qkv_tok + ((size_t)s * NH + head) * (SEG * DH);
                    constexpr size_t MAT = (size_t)NSEG * NH * SEG * DH;
                    bulk_store(dst + (qk ? rank * (SEG * 64) : 2 * MAT), sb + (qk ? SM_QS : SM_V), (EXP & 32) ? 32 : 4096);
                    bulk_store(dst + (qk ? MAT + rank * (SEG * 64) : 2 * MAT + SEG * 64), sb + (qk ? SM_K : SM_V + 4096), (EXP & 32) ? 32 : 4096);
                    bulk_commit();
                }
            }
        };
        if (wg == 0) {
            float ta[2][16];
            if (!x0_ok) mbar_wait_bounded(bar + BAR_XG, par);
            STAMP(6);
            auto park = [&](int i, uint32_t dst) {
                #pragma unroll
                for (int e = 0; e < 16; e++) asm volatile("" : "+f"(ta[i][e]));
                #pragma unroll
                for (int j = 0; j < ((EXP & 128) ? 2 : 4); j++)
                    sts128(l16 + dst + j * 2048 + wq * 512, __float_as_uint(ta[i][4 * j]), __float_as_uint(ta[i][4 * j + 1]),
                           __float_as_uint(ta[i][4 * j + 2]), __float_as_uint(ta[i][4 * j + 3]));
            };
            if (EXP & 64) spin_clks(1200);
            token_mma<0, 0, 16, 0, false>(ta, wr, 1);
            mbar_wait_bounded(bar + BAR_XG + 8, par);
            if (TOK_MOVED1 > 0) mbar_wait_bounded(bar + BAR_XG + 16, par);
            if (AT_POS0 == 0) at_prefetch(true);
            token_mma<0, 16, 32, 0, true>(ta, wr, p.one[1]);
            if (TOK_MOVED1 == 0) mbar_wait_bounded(bar + BAR_XG + 16, par);
            token_mma<0, 0, 16, 1, false, TOK_MOVED1 == 0>(ta, wr, p.one[0]);
            if (TOK_MOVED > 4) mbar_wait_bounded(bar + BAR_XG + 24, par);
            token_mma<0, 16, 32, 1, true, (TOK_MOVED > 4)>(ta, wr, 1);
            asm volatile("wgmma.wait_group.sync.aligned 1;" ::: "memory");
            if (PARK_LATE) mbar_wait_bounded(bar + BAR_PUB, par);
            park(0, SM_PARK0);
            warp_arrive(bar + BAR_GO);
            asm volatile("wgmma.wait_group.sync.aligned 0;" ::: "memory");
            park(1, SM_PARK1);
            if (TOK_MOVED <= 4) mbar_wait_bounded(bar + BAR_XG + 24, par);
            warp_arrive(bar + BAR_PK);
            const uint8_t* src = xaddr(u_src + pub_slot(s), xhi);
            auto fetch = [&]() {
                if (elect_one()) {
                    mbar_arrive_expect_tx(bar + BAR_M + 8 * wq, 4096);
                    bulk_load(sb + SM_MEM + wq * 4096, src, 4096, bar + BAR_M + 8 * wq);
                }
            };
            if (!PARK_LATE) named_bar_sync(7, REC_THREADS - 32);
            if (FETCH_REL) {
                const uint4 t = lds128(bar + BAR_TPUB);
                const uint32_t now = clock32();
                spin_until(now + FETCH_DELAY - min(min(min(now - t.y, now - t.z), now - t.w), (uint32_t)FETCH_DELAY));
            } else {
                spin_clks(FETCH_DELAY);
            }
            fetch();
            STAMP(12);
            if (warp == 0 && elect_one()) {
                if (qk) mbar_arrive_expect_tx(bar + BAR_V, (EXP & 16) ? 32 : 8192);
                mbar_arrive_expect_tx(bar + BAR_X, qk ? 1280 : 2560);
                mbar_arrive_expect_tx(bar + BAR_VM, qk ? 2048 : 0);
            }
            if (AT_POS0 == 1) at_prefetch(true);
            at_prefetch(false);
            const uint32_t x = fresh(l16) - sb;
            const uint32_t ca = sb + SM_MEM + wq * 4096 + x * 2 + ((x >> 4) & 0x1C);
            #pragma unroll 1
            for (uint32_t n = 0; n < POLL_LIMIT; n++) {
                mbar_wait_bounded(bar + BAR_M + 8 * wq, mphase);
                mphase ^= 1;
                const uint32_t c0 = lds32_volatile(ca), c1 = lds32_volatile(ca + 1024), c2 = lds32_volatile(ca + 2048), c3 = lds32_volatile(ca + 3072);
                if (!__any_sync(~0u, max(max3(c0, c1, c2), c3) == (NO_COMM ? 0x12345u : SENT))) break;
                fetch();
            }
            STAMP(0);
            named_bar_sync(0, REC_THREADS);
            if (X0_POS == 2 && warp == 0 && rank == 0 && s + 1 < NSEG) {
                mbar_wait_bounded(bar + BAR_F0, par);
                if (elect_one()) x_load(p, sb, s + 1, 0);
            }
            if (u_role & 8) {
                asm volatile("fence.proxy.async.shared::cta;" ::: "memory");
                mbar_wait_bounded(bar + BAR_VF, par);
                if (s < NSEG - 1 && elect_one()) {
                    #pragma unroll
                    for (int r = 0; r < 2; r++)
                        asm volatile("cp.async.bulk.shared::cluster.shared::cta.mbarrier::complete_tx::bytes [%0], [%1], %2, [%3];"
                                     ::"r"(mapa(sb + SM_V, r)), "r"(sb + SM_V), "r"((EXP & 16) ? 32 : 8192), "r"(mapa(bar + BAR_V, r)) : "memory");
                }
            }
        } else {
            at_prefetch(true);
            if (RST_POS == 2) resets(0);
            if (s > 0) {
                if (u_role & 1) {
                    const uint32_t ln = (fresh(l16) >> 4) & 31;
                    const uint32_t ibl = lds32_volatile(tbl + 12) + (par ^ 1) * XCHG_SLOT + ln * 8;
                    const uint32_t publ = lds32_volatile(tbl + 28) + pub_slot(s) + (ln & 16) * 256 + (ln & 8) * 16 + (ln & 7) * 4;
                    const bool odd = ln & 8;
                    const uint8_t* ib = xaddr(ibl + delay_zero<POLL_DELAY>(bar + BAR_SELF), xhi);
                    STAMP(8);
                    uint2 v[8];
                    float a0, a1, a2, a3;
                    auto sum8 = [&]() {
                        a0 = ((bf16_lo(v[0].x) + bf16_lo(v[1].x)) + (bf16_lo(v[2].x) + bf16_lo(v[3].x))) +
                             ((bf16_lo(v[4].x) + bf16_lo(v[5].x)) + (bf16_lo(v[6].x) + bf16_lo(v[7].x)));
                        a1 = ((bf16_hi(v[0].x) + bf16_hi(v[1].x)) + (bf16_hi(v[2].x) + bf16_hi(v[3].x))) +
                             ((bf16_hi(v[4].x) + bf16_hi(v[5].x)) + (bf16_hi(v[6].x) + bf16_hi(v[7].x)));
                        a2 = ((bf16_lo(v[0].y) + bf16_lo(v[1].y)) + (bf16_lo(v[2].y) + bf16_lo(v[3].y))) +
                             ((bf16_lo(v[4].y) + bf16_lo(v[5].y)) + (bf16_lo(v[6].y) + bf16_lo(v[7].y)));
                        a3 = ((bf16_hi(v[0].y) + bf16_hi(v[1].y)) + (bf16_hi(v[2].y) + bf16_hi(v[3].y))) +
                             ((bf16_hi(v[4].y) + bf16_hi(v[5].y)) + (bf16_hi(v[6].y) + bf16_hi(v[7].y)));
                    };
                    if (REPOLL) {
                        #pragma unroll
                        for (int i = 0; i < 8; i++) v[i] = make_uint2(SENT, SENT);
                    }
                    #pragma unroll 1
                    for (uint32_t n = 0; n < POLL_LIMIT; n++) {
                        if (REPOLL) sfor<0, 8>([&](auto I) { repoll_v2<I.value * 256>(v[I.value], ib); });
                        else sfor<0, 8>([&](auto I) { poll_v2<I.value * 256>(v[I.value], ib); });
                        const uint32_t mx = max(max3(v[0].y, v[1].y, v[2].y), max3(max3(v[3].y, v[4].y, v[5].y), v[6].y, v[7].y));
                        if (SPEC_SUM) { sum8(); asm volatile("" : "+f"(a0), "+f"(a1), "+f"(a2), "+f"(a3)); }
                        if (!__any_sync(~0u, mx == (NO_COMM ? 0x12345u : SENT))) break;
                    }
                    STAMP(9);
                    if (!SPEC_SUM) sum8();
                    float k0 = odd ? a2 : a0, k1 = odd ? a3 : a1;
                    k0 += __shfl_xor_sync(~0u, odd ? a0 : a2, 8);
                    k1 += __shfl_xor_sync(~0u, odd ? a1 : a3, 8);
                    k0 += __shfl_xor_sync(~0u, k0, 16);
                    k1 += __shfl_xor_sync(~0u, k1, 16);
                    st_relaxed_b32(xaddr(publ, xhi), pack_bf16(k0, k1));
                    STAMP(11);
                } else if (warp == 4) {
                    bulk_wait_read_all();
                    if (elect_one()) remote_arrive(bar + BAR_F3, 2);
                    if (!qk) {
                        mbar_wait_bounded(bar + BAR_F3, par ^ 1);
                        if (elect_one()) x_load(p, sb, s, 3);
                    }
                    if (elect_one()) {
                        bulk_wait_all();
                        signal_flag(p.flags + F_PROGRESS + s - 1);
                    }
                    __syncwarp();
                    STAMP(10);
                }
            }
            float ta[2][16];
            uint32_t w[8];
            auto unpark = [&](int i, uint32_t src) {
                mbar_wait_bounded(bar + (i ? BAR_GO : BAR_PK), par);
                #pragma unroll
                for (int j = 0; j < 4; j++) {
                    uint4 v = make_uint4(0, 0, 0, 0);
                    if (!(EXP & 128) || j < 2) v = lds128(l16 + src + j * 2048 + wq * 512);
                    ta[i][4 * j] = __uint_as_float(v.x); ta[i][4 * j + 1] = __uint_as_float(v.y);
                    ta[i][4 * j + 2] = __uint_as_float(v.z); ta[i][4 * j + 3] = __uint_as_float(v.w);
                }
            };
            if (FETCH_REL) sts32(bar + BAR_TPUB + 4 * wq, clock32());
            if (warp != 4) { if (PARK_LATE) warp_arrive(bar + BAR_PUB); else named_bar_arrive(7, REC_THREADS - 32); }
            unpark(1, SM_PARK0);
            STAMP(6);
            token_mma<1, 0, 16, 1, true>(ta, wr, 1);
            if (RST_POS == 3) resets(0);
            unpark(0, SM_PARK1);
            token_mma<1, 16, 32, 1, true>(ta, wr, 1);
            token_mma<1, 16, 32, 0, true>(ta, wr, 1);
            token_mma<1, 0, 16, 0, true, false>(ta, wr, 1);
            auto put_tile = [&](int m, const uint32_t (&q)[8]) {
                #pragma unroll
                for (int h = 0; h < 2; h++) {
                    if (qk) asm volatile("stmatrix.sync.aligned.m8n8.x4.trans.shared.b16 [%0], {%1,%2,%3,%4};"
                                         ::"r"(aq - (SM_WQ + 32768) + (m ? SM_K : SM_QS) + h * 2048), "r"(q[4 * h]), "r"(q[4 * h + 1]),
                                           "r"(q[4 * h + 2]), "r"(q[4 * h + 3]) : "memory");
                    else sts128(l16 + SM_V + wq * 2048 + m * 1024 + h * 512, q[4 * h], q[4 * h + 1], q[4 * h + 2], q[4 * h + 3]);
                }
            };
            auto pack_tile = [&](int i) {
                #pragma unroll
                for (int e = 0; e < 16; e++) asm volatile("" : "+f"(ta[i][e]));
                #pragma unroll
                for (int j = 0; j < 8; j++) w[j] = pack_bf16(ta[i][2 * j], ta[i][2 * j + 1]);
            };
            asm volatile("wgmma.wait_group.sync.aligned 2;" ::: "memory");
            pack_tile(1);
            if (RST_POS == 4) resets(0);
            at_prefetch(false);
            asm volatile("wgmma.wait_group.sync.aligned 1;" ::: "memory");
            if ((u_role & 32) && elect_one())
                asm volatile("mbarrier.arrive.relaxed.cluster.shared::cluster.b64 _, [%0];" ::"r"(u_free) : "memory");
            put_tile(0, w);
            asm volatile("wgmma.wait_group.sync.aligned 0;" ::: "memory");
            pack_tile(0);
            put_tile(1, w);
            STAMP(0);
            named_bar_sync(0, REC_THREADS);
            if (s == NSEG - 1) tile_stores();
            STAMP(14);
        }
        const uint32_t mb = l16 + SM_MEM + wg * 8192;
        float acc[2][2][4];
        {
            uint32_t b[2][4];
            ldsm4t(mb, b[0]);
            ldsm4t(mb + 512, b[1]);
            #pragma unroll
            for (int i = 0; i < AT_AHEAD; i++)
                if (!at_early(i)) ldsm4t(aq + (i & 1) * 16384 + (i >> 1) * 2048, at[i]);
            STAMPD(1, b[0][0]);
            #pragma unroll
            for (int i = 0; i < 4; i++) { for (int e = 0; e < 4; e++) acc[i >> 1][i & 1][e] = 0.f; }
            #pragma unroll
            for (int u = 0; u < 16; u++) {
                #pragma unroll
                for (int h = 0; h < 2; h++) {
                    const int j = 2 * u + h;
                    #pragma unroll
                    for (int m = 0; m < 2; m++) {
                        if ((j & 3) == 0) mma_a(acc[h][m], at[(j >> 2) * 2 + m], b[u & 1][2 * h], b[u & 1][2 * h + 1]);
                        else mma_a(acc[h][m], wr[reg_idx(j)][m], b[u & 1][2 * h], b[u & 1][2 * h + 1]);
                    }
                }
                if (u + 2 < 16) ldsm4t(mb + (u + 2) * 512, b[u & 1]);
                if (u + AT_AHEAD < 16 && !at_early(u + AT_AHEAD))
                    ldsm4t(aq + ((u + AT_AHEAD) & 1) * 16384 + ((u + AT_AHEAD) >> 1) * 2048, at[u + AT_AHEAD]);
            }
        }
        sts128(l16 + SM_RED + warp * 512, __float_as_uint(acc[0][1][0] + acc[1][1][0]), __float_as_uint(acc[0][1][1] + acc[1][1][1]),
               __float_as_uint(acc[0][1][2] + acc[1][1][2]), __float_as_uint(acc[0][1][3] + acc[1][1][3]));
        #pragma unroll
        for (int e = 0; e < 4; e++) acc[0][0][e] += acc[1][0][e];
        const uint32_t x16 = fresh(l16);
        const uint32_t sa = fresh((x16 & 0x70) * 8 + ((((x16 >> 3) & 0x30) ^ x16) & 0x70));
        const uint32_t sq = fresh(sa ^ ((((x16 >> 7) ^ (x16 >> 8)) & 1) * 0x30));
        const uint32_t x8 = (x16 & 0x1F0) >> 1;
        const uint32_t xra = fresh(x8 + __byte_perm(u_xa, u_bra, 0x7210)), xrb = fresh(x8 + __byte_perm(u_xa, u_brb, 0x7210));
        STAMP(2);
        named_bar_sync(1 + wq, 64);
        uint32_t p0, p1;
        {
            const uint4 v = lds128(l16 + SM_RED + (warp ^ 4) * 512);
            p0 = pack_bf16(acc[0][0][0] + __uint_as_float(v.x), acc[0][0][1] + __uint_as_float(v.y));
            p1 = pack_bf16(acc[0][0][2] + __uint_as_float(v.z), acc[0][0][3] + __uint_as_float(v.w));
        }
        auto send = [&](uint32_t y0, uint32_t y1) {
            st_async_v2(xra, y0, y1, u_bra);
            st_async_v2(xrb, y0, y1, u_brb);
            sts64(x8 + u_xa, y0, y1);
            warp_arrive(u_bx);
        };
        if (qk) {
            asm volatile("stmatrix.sync.aligned.m8n8.x2.trans.shared.b16 [%0], {%1,%2};" ::"r"(aq + u_st), "r"(p0), "r"(p1) : "memory");
            named_bar_sync(5, REC_THREADS);
            if (u_key != 0) {
                uint32_t qa[2][4], kf[2][4];
                ldsm4(sq + sb + SM_QK, qa[0]);
                ldsm4(sa + u_key, kf[0]);
                ldsm4((sq ^ 64) + sb + SM_QK, qa[1]);
                ldsm4((sa ^ 64) + u_key, kf[1]);
                float se[4] = {0.f, 0.f, 0.f, 0.f}, so[4] = {0.f, 0.f, 0.f, 0.f};
                #pragma unroll
                for (int u = 0; u < 2; u++) {
                    mma_a(se, qa[u], kf[u][0], kf[u][1]);
                    mma_a(so, qa[u], kf[u][2], kf[u][3]);
                }
                send(__float_as_uint(se[0] + so[2]), __float_as_uint(se[1] + so[3]));
            }
        } else {
            send(p0, p1);
        }
        STAMP(3);
        const uint32_t lane = (fresh(l16) >> 4) & 31;
        auto kv_stores = [&]() {
            if (u_kv != ~0u) {
                uint32_t* dst = reinterpret_cast<uint32_t*>(p.kv_mem) + (u_kv + s * (NH * 512) + lane);
                dst[0] = p0;
                dst[32] = p1;
            }
        };
        if (((s + 1) & 62) == 0) {
            if (s == NSEG - 1) { kv_stores(); break; }
            mbar_wait_bounded(bar + BAR_WO, 0);
            if (PDL_POS == 5) pdl_launch_dependents();
            PSTAMP(8);
        }
        const uint32_t slot = par * XCHG_SLOT;
        if (u_role & 2) {
            if (qk) mbar_wait_bounded(bar + BAR_V, par);
            uint32_t vt[2][4][4];
            auto v_load = [&](int i0, int i1) {
                #pragma unroll
                for (int i = i0; i < i1; i++) {
                    const uint4 v = lds128(l16 + SM_V + (warp & 1) * 1024 + (i & 3) * 2048 + (i >> 2) * 512);
                    vt[i >> 2][i & 3][0] = v.x; vt[i >> 2][i & 3][1] = v.y; vt[i >> 2][i & 3][2] = v.z; vt[i >> 2][i & 3][3] = v.w;
                }
            };
            v_load(0, V_EARLY);
            kv_stores();
            const uint32_t l8 = fresh(sb + lane * 8);
            mbar_wait_bounded(bar + BAR_X, par);
            STAMP(4);
            float sv[10];
            #pragma unroll
            for (int j = 0; j < 5; j++) {
                const uint2 a = lds64(l8 + SM_SP + j * 256), b = lds64(l8 + SM_SP + 1280 + j * 256);
                sv[2 * j] = __uint_as_float(a.x) + __uint_as_float(b.x);
                sv[2 * j + 1] = __uint_as_float(a.y) + __uint_as_float(b.y);
            }
            float mx = fmaxf(fmaxf(fmaxf(sv[0], sv[1]), fmaxf(sv[2], sv[3])), fmaxf(fmaxf(sv[4], sv[5]), fmaxf(sv[6], sv[7])));
            mx = fmaxf(mx, fmaxf(sv[8], sv[9]));
            const float m1 = __shfl_xor_sync(~0u, mx, 1), m2 = __shfl_xor_sync(~0u, mx, 2), m3 = __shfl_xor_sync(~0u, mx, 3);
            __syncwarp();
            v_load(V_EARLY, 8);
            const bool vm_ok = mbar_test_wait(bar + BAR_VM, par);
            mx = fmaxf(fmaxf(mx, m1), fmaxf(m2, m3));
            const float mo = mx * sl2;
            #pragma unroll
            for (int j = 0; j < 10; j++) sv[j] = ex2(fmaf(sv[j], sl2, -mo));
            const uint32_t e0 = pack_bf16(sv[0], sv[1]), e1 = pack_bf16(sv[2], sv[3]);
            const uint32_t e2 = pack_bf16(sv[4], sv[5]), e3 = pack_bf16(sv[6], sv[7]), em = pack_bf16(sv[8], sv[9]);
            float o[4][4];
            #pragma unroll
            for (int i = 0; i < 4; i++) {
                o[i][0] = o[i][1] = o[i][2] = o[i][3] = 0.f;
                mma_a(o[i], vt[0][i], e0, e1);
            }
            const float sum = (((sv[0] + sv[1]) + (sv[2] + sv[3])) + ((sv[4] + sv[5]) + (sv[6] + sv[7]))) + (sv[8] + sv[9]);
            if (!vm_ok) mbar_wait_bounded(bar + BAR_VM, par);
            uint2 vm[4];
            #pragma unroll
            for (int i = 0; i < 4; i++) {
                vm[i] = lds64(l8 + SM_VM + (warp & 1) * 1024 + i * 256);
                mma_a(o[i], vt[1][i], e2, e3);
            }
            #pragma unroll
            for (int i = 0; i < 4; i++) mma1688(o[i], vm[i].x, vm[i].y, em);
            {
                const float s1 = __shfl_xor_sync(~0u, sum, 1), s2 = __shfl_xor_sync(~0u, sum, 2), s3 = __shfl_xor_sync(~0u, sum, 3);
                sts32(sb + SM_SUM + (lane & 28), __float_as_uint((sum + s1) + (s2 + s3)));
            }
            #pragma unroll
            for (int i = 0; i < 4; i += 2)
                stsm_x4(l16 + SM_O + (warp & 1) * 1024 + i * 256, pack_bf16(o[i][0], o[i][1]), pack_bf16(o[i][2], o[i][3]),
                        pack_bf16(o[i + 1][0], o[i + 1][1]), pack_bf16(o[i + 1][2], o[i + 1][3]));
            STAMP(5);
            uint32_t st[16][4];
            #pragma unroll
            for (int n = 0; n < WO_PF0; n++) ldsm4t(wo_addr<2>(ao, 0, n), st[n]);
            named_bar_sync(6, REC_THREADS);
            wo_phase<2, WO_PF0>([&]() { if ((u_role & 16) && elect_one()) x_load(p, sb, s + 1, rank); }, st, ao, 0, l16, tbl, sb + SM_SUM, slot, xhi, 0, p.one[0] - 1, aq, bar + BAR_XG, par ^ 1, x0_ok);
        } else {
            const uint32_t a3 = fresh(ao) + (wg == 0 ? 10 : 6) * 8192;
            uint32_t st[24][4];
            #pragma unroll
            for (int n = 0; n < WO_PFA; n++) ldsm4t(wo_addr<3>(ao, a3, n), st[n]);
            if (KV_POS == 0) kv_stores();
            if (ST_POS == 0) tile_stores();
            if (RST_POS == 0) resets(1);
            if (warp == 1) {
                if (elect_one()) {
                    #pragma unroll
                    for (int g = 0; g < 4; g++) mbar_arrive_expect_tx(bar + BAR_XG + 8 * g, ((EXP >> g) & 1) ? 0 : 16384);
                }
                if (s + 2 < NSEG && cta < 4 && elect_one())
                    asm volatile("cp.async.bulk.prefetch.tensor.3d.L2.global [%0, {%1, %2, %3}];"
                                 ::"l"(&p.tmX), "r"(0), "r"((s + 2) * SEG), "r"(cta * 4) : "memory");
                if (X0_POS == 0 && rank == 0) {
                    mbar_wait_bounded(bar + BAR_F0, par);
                    if (elect_one()) x_load(p, sb, s + 1, 0);
                }
            }
            if (WO_PFA < WO_PF1 || (u_role & 16)) mbar_wait_bounded(bar + BAR_X, par);
            if (WO_PFA < WO_PF1) {
                spin_clks(WO_PFB_DELAY);
                #pragma unroll
                for (int n = WO_PFA; n < WO_PF1; n++) ldsm4t(wo_addr<3>(ao, a3, n), st[n]);
            }
            if (ST_POS == 1) tile_stores();
            if (RST_POS == 1) resets(1);
            if (KV_POS == 1) kv_stores();
            if (X0_POS == 1 && warp == 1 && rank == 0) {
                mbar_wait_bounded(bar + BAR_F0, par);
                if (elect_one()) x_load(p, sb, s + 1, 0);
            }
            if (XB_POS == 0 && (u_role & 16)) {
                spin_clks(XB_DELAY);
                mbar_wait_bounded(bar + BAR_VM, par);
                if (elect_one()) x_load(p, sb, s + 1, rank);
            }
            named_bar_sync(6, REC_THREADS);
            wo_phase<3, WO_PF1>([]() {}, st, ao, a3, l16, tbl, sb + SM_SUM, slot, xhi, u_role & 4, p.one[0] - 1, aq, bar + BAR_XG, par ^ 1, x0_ok);
        }
        STAMP(7);
        if (wg == 0) named_bar_sync(9, REC_THREADS); else named_bar_arrive(9, REC_THREADS);
    }
    if (threadIdx.x == 128) KMARK(8);
    if (warp == 4 && elect_one()) {
        bulk_wait_all();
        asm volatile("red.relaxed.gpu.global.add.u32 [%0], 1;" ::"l"(p.flags + F_LASTTOK) : "memory");
    }
    named_bar_sync(0, REC_THREADS);
    if (warp == 4) {
        if (elect_one()) {
            signal_flag(p.flags + F_PROGRESS + NSEG - 1);
            KMARK(9);
        }
    } else if (warp == 0) {
        mbar_wait(bar + BAR_X, 1);
        mbar_wait(bar + BAR_VM, 1);
        if (rank == 0) mbar_wait(bar + BAR_F0, 1);
    }
}

__global__ void __launch_bounds__(REC_THREADS, 1) rec_kernel(const __grid_constant__ RecParams p) {
    extern __shared__ __align__(1024) uint8_t smem_raw[];
    const uint32_t sb = smem_u32(smem_raw);
    const int tid = threadIdx.x, lane = tid & 31;
    const int warp = __shfl_sync(~0u, tid >> 5, 0);
    const int cta = blockIdx.x, head = cta / 3, rank = cta % 3;
    const int wg = warp >> 2, wq = warp & 3;
    const uint32_t bar = sb + SM_BAR;
    uint8_t* const xb = p.xchg;
    const uint32_t xlo = (uint32_t)(uint64_t)xb;
    if ((sb & 0x3FFFF) != SMEM_ORIGIN) __trap();
    KENTER(1);
    auto w_box = [&](int part, int g, int i, uint32_t dst, uint32_t mb) {
        const int m = i ^ g;
        const CUtensorMap* tm = &p.tmW[rank == 2 ? 2 : m];
        const int col = head * DH + (rank == 2 ? m : rank) * 64, row = ((part + 1) & 3) * 16;
        tma_load_3d(dst, tm, col, row, g * 8, mb);
    };
    if (tid == 0) {
        mbar_init(bar + BAR_V, 1);
        for (int i = 0; i < 4; i++) { mbar_init(bar + BAR_XG + 8 * i, 1); mbar_init(bar + BAR_M + 8 * i, 1); }
        mbar_init(bar + BAR_GO, 4);
        mbar_init(bar + BAR_PUB, 3);
        mbar_init(bar + BAR_PK, 4);
        mbar_init(bar + BAR_VM, rank < 2 ? 1 : 9);
        mbar_init(bar + BAR_F0, 3);
        mbar_init(bar + BAR_F3, 3);
        mbar_init(bar + BAR_VF, 3);
        sts64(bar + BAR_MIN, ~0u, ~0u);
        mbar_init(bar + BAR_X, rank < 2 ? 6 : 1);
        for (int i = 0; i < 3; i++) mbar_init(bar + BAR_P0 + 8 * i, 1);
        mbar_init(bar + BAR_WQ, 1);
        mbar_init(bar + BAR_WO, 1);
        sts32(bar + BAR_SELF, bar + BAR_SELF);
        asm volatile("fence.mbarrier_init.release.cluster;" ::: "memory");
    }
    auto build_tables = [&](uint32_t av) {
        for (uint32_t n = 0; !__all_sync(~0u, (av >> 24) == 24); n++) {
            av = ld_acquire_b32(p.arrivals + (lane & 3));
            if (n > SPIN_LIMIT) __trap();
        }
        uint32_t cm[3];
        #pragma unroll
        for (int i = 0; i < 3; i++) {
            const int o = i * 32 + lane;
            cm[i] = __ballot_sync(~0u, __popc((__shfl_sync(~0u, av, o / 24) >> (o % 24 / 3 * 3)) & 7) >= 2);
        }
        auto color_of = [&](int o) { return ((o < 32 ? cm[0] : o < 64 ? cm[1] : cm[2]) >> (o & 31)) & 1u; };
        auto inbox = [&](int o, int byte) {
            uint32_t c = color_of(o);
            int ones = 0;
            #pragma unroll
            for (int i = 0; i < 3; i++) ones += __popc(o >= i * 32 + 32 ? cm[i] : (o > i * 32 ? cm[i] & ((1u << (o - i * 32)) - 1) : 0u));
            int idx = c ? ones : o - ones;
            if (idx >= INBOX_MAX) { idx = 2 * INBOX_MAX - 1 - idx; c ^= 1; }
            const uint32_t lin = idx * 6144 + byte, q = XCHG_INBOX + (lin >> 12) * 8192;
            return q + class_off(xlo + q, c) + (lin & 4095);
        };
        uint32_t off = 0;
        const int grp = (warp + 3) & 3;
        if (lane < 12) {
            const int i = lane >> 2, lt0 = rank * 6;
            const int o = i < 2 ? rank * 32 + warp * 4 + (lane & 3) : (lt0 + ((warp + 4) & 7)) * 4 + (lane & 3);
            off = inbox(min(o, 95), i * 2048 + head * 64);
        } else if (lane == 12) {
            off = inbox(cta, (grp % 3) * 2048);
        } else if (lane == 13) {
            int T;
            if (grp < 2) {
                T = (cta >> 5) * 22 + 8 * grp + ((cta & 31) >> 2);
            } else {
                const int tl = (cta & 63) >> 2;
                T = (tl / 6) * 22 + 16 + tl % 6;
            }
            off = XCHG_PUB + (T >> 4) * 8192 + (T & 15) * 256 + (cta & 3) * 32;
        } else if (lane == 14) {
            const uint32_t q = XCHG_PUB + wq * 8192;
            off = q + class_off(xlo + q, color_of(cta));
        }
        if (lane < 16) asm volatile("st.shared.b32 [%0], %1;" ::"r"(sb + SM_TBL + warp * 64 + (lane & 3) * 16 + (lane >> 2) * 4), "r"(xlo + off) : "memory");
    };
    if (tid >= 32 && tid < 37) asm volatile("prefetch.tensormap [%0];" ::"l"(&p.tmW[0] + (tid - 32)) : "memory");
    if (cta == 0) for (int i = tid; i < F_COUNT; i += REC_THREADS) p.flags[i] = 0;
    __syncthreads();
    auto stage = [](int part) { return ((part + 2) % 3) * 65536; };
    auto load_part = [&](int part) {
        mbar_arrive_expect_tx(bar + BAR_P0 + 8 * part, 65536);
        for (int u = 0; u < 4; u++) w_box(part, u >> 1, u & 1, sb + stage(part) + u * 16384, bar + BAR_P0 + 8 * part);
    };
    asm volatile("barrier.cluster.arrive.relaxed.aligned;" ::: "memory");
    uint4 img = make_uint4(SENT, SENT, SENT, SENT);
    if (cta >= 92) {
        const unsigned short* m = reinterpret_cast<const unsigned short*>(p.mem0) + (cta - 92) * 256 + tid;
        uint32_t w[4];
        #pragma unroll
        for (int i = 0; i < 4; i++) w[i] = (uint32_t)__ldg(m + 2 * i * DM) | ((uint32_t)__ldg(m + (2 * i + 1) * DM) << 16);
        img = make_uint4(w[0], w[1], w[2], w[3]);
    }
    {
        constexpr int NPAIR = (XCHG_SLOT + PUB_BYTES) / 8192;
        uint8_t* pr = xb + (4 + cta) * 8192;
        const uint32_t c0 = class_off(xlo + (4 + cta) * 8192, 0);
        #pragma unroll
        for (int c = 0; c < 2; c++) {
            const bool timed = lane == 0 || (lane == 8 && c == (warp & 1));
            reinterpret_cast<uint4*>(pr + (c0 ^ (c << 12)))[tid] = make_uint4(timed ? 0u : SENT, SENT, SENT, SENT);
        }
        __syncwarp();
        if (lane == 0) {
            uint32_t x = 0;
            for (int k = 0; k < 3; k++) {
                if (k == PRO_EARLY && warp == 0) load_part(0);
                const uint32_t c = (k + warp) & 1, t0 = clock_after(x);
                x = atomicExch(reinterpret_cast<uint32_t*>(pr + (c0 ^ (c << 12)) + warp * 512 + (k >> 1) * 128 + x), SENT);
                const uint32_t lat = clock_after(x) - t0;
                asm volatile("red.shared.min.u32 [%0], %1;" ::"r"(bar + BAR_MIN + 4 * c), "r"(lat) : "memory");
            }
        }
        __syncwarp();
        if (cta >= 92 || 100 + cta < NPAIR) {
            if (cta >= 92) {
                if (img.x == SENT) img.x = 0x7FFF7FFFu;
                if (img.y == SENT) img.y = 0x7FFF7FFFu;
                if (img.z == SENT) img.z = 0x7FFF7FFFu;
                if (img.w == SENT) img.w = 0x7FFF7FFFu;
            }
            uint8_t* q = xb + (cta >= 92 ? cta - 92 : 100 + cta) * 8192;
            reinterpret_cast<uint4*>(q)[tid] = img;
            reinterpret_cast<uint4*>(q + 4096)[tid] = img;
        }
    }
    __syncthreads();
    PSTAMP(4);
    if (tid == 0) {
        for (int part = PRO_EARLY < 3 ? 1 : 0; part < 3; part++) load_part(part);
    }
    if (tid == 224) {
        const uint32_t c = lds32_volatile(bar + BAR_MIN) > lds32_volatile(bar + BAR_MIN + 4) ? 1 : 0;
        asm volatile("red.release.gpu.global.add.u32 [%0], %1;" ::"l"(p.arrivals + cta / 24), "r"((1u << 24) | (c << (cta % 24))) : "memory");
        if (PDL_POS == 0) pdl_launch_dependents();
    }
    uint32_t wr[NREG][2][4];
    uint32_t arrived = 0;
    {
        const int mi = lane >> 3, r8 = lane & 7;
        const uint32_t a0 = sb + wg * 32768 + ((mi >> 1) * 8 + r8) * 128 + (((wq * 2 + (mi & 1)) ^ r8) << 4);
        #pragma unroll
        for (int part = 0; part < 3; part++) {
            mbar_wait_bounded(bar + BAR_P0 + 8 * part, 0);
            if (part == 0) arrived = ld_relaxed_b32(p.arrivals + (lane & 3));
            #pragma unroll
            for (int j = 0; j < 8; j++) {
                #pragma unroll
                for (int i = 0; i < 2; i++) ldsm4t(a0 + stage(part) + i * 16384 + j * 2048, wr[part * 8 + j][i]);
            }
            asm volatile("fence.proxy.async.shared::cta;" ::: "memory");
            __syncthreads();
            PSTAMP(5 + part);
            if (tid == 224 && PDL_POS == part + 1) pdl_launch_dependents();
            if (tid == 0) {
                if (part == 0) {
                    for (int g = 0; g < 4; g++) {
                        mbar_arrive_expect_tx(bar + BAR_XG + 8 * g, 16384);
                        tma_load_3d(sb + SM_X + g * 16384, &p.tmX, 0, 0, g * 4, bar + BAR_XG + 8 * g);
                    }
                } else if (part == 1) {
                    mbar_arrive_expect_tx(bar + BAR_WQ, 65536);
                    for (int u = 0; u < 4; u++) w_box(3, u >> 1, u & 1, sb + SM_WQ + u * 16384, bar + BAR_WQ);
                } else {
                    mbar_arrive_expect_tx(bar + BAR_WO, 11 * 8192);
                    tma_load_3d(sb + SM_WO, &p.tmWo, 0, head * DH, rank * 11, bar + BAR_WO);
                    if (cta < 4)
                        asm volatile("cp.async.bulk.prefetch.tensor.3d.L2.global [%0, {%1, %2, %3}];"
                                     ::"l"(&p.tmX), "r"(0), "r"(SEG), "r"(cta * 4) : "memory");
                }
            }
        }
    }
    build_tables(arrived);
    if (tid == 64) {
        uint32_t smid;
        asm volatile("mov.u32 %0, %%smid;" : "=r"(smid));
        if (smid < 384) atomicOr(p.flags + F_RECSM + (smid >> 5), 1u << (smid & 31));
    }
    __syncwarp();
    PSTAMP(9);
    mbar_wait(bar + BAR_WQ, 0);
    if (PDL_POS == 4) pdl_launch_dependents();
    asm volatile("barrier.cluster.wait.aligned;" ::: "memory");

    rec_steps(p, wr, sb, warp, cta, head, rank);
    if (cta == 0 && tid < 4) p.arrivals[tid] = 0;
    if (tid == 128) KEXIT(1);
}

constexpr int ATT_SLOT = 28672;
constexpr int ATT_PAIRS = 8;
constexpr int ATT_BAR = ATT_PAIRS * ATT_SLOT;
constexpr int ATT_CNT = ATT_BAR + ATT_PAIRS * 16;
constexpr int ATT_SMEM = ATT_CNT + 96 * 4;
constexpr int ATT_THREADS = ATT_PAIRS * 64 + 32;
static_assert(F_OA == F_OB + 16, "one range of flags");
struct AttnParams {
    CUtensorMap tmOa;
    CUtensorMap tmQb, tmKb;
    CUtensorMap tmOb;
    const __nv_bfloat16* qkv_tok;
    const __nv_bfloat16* kv_mem;
    uint32_t* flags;
};

__device__ __forceinline__ void tok_attn_warp(uint32_t base, int mh, int lane) {
    const uint32_t sq = base, sk = base + 8192, sv = base + 16384, skm = base + 24576, svm = skm + 2048;
    const int g = lane >> 2, c = lane & 3, mi = lane >> 3, r8 = lane & 7;
    const int ntile = mh ? 5 : 3;
    float sc[5][4];
    #pragma unroll
    for (int j = 0; j < 5; j++) { sc[j][0] = sc[j][1] = sc[j][2] = sc[j][3] = 0.f; }
    #pragma unroll
    for (int t2 = 0; t2 < 4; t2++) {
        uint32_t a[2][4];
        #pragma unroll
        for (int h = 0; h < 2; h++) {
            const int row = mh * 16 + (mi & 1) * 8 + r8, ch16 = 4 * t2 + 2 * h + (mi >> 1);
            ldsm_x4(sq + (ch16 >> 3) * 4096 + row * 128 + (((ch16 & 7) ^ r8) << 4), a[h][0], a[h][1], a[h][2], a[h][3]);
        }
        const int ch16 = 4 * t2 + mi;
        uint32_t b[5][4];
        #pragma unroll
        for (int j = 0; j < 5; j++) {
            if (j < ntile) {
                if (j == 0) ldsm_x4_t(skm + t2 * 512 + lane * 16, b[j][0], b[j][1], b[j][2], b[j][3]);
                else ldsm_x4(sk + (ch16 >> 3) * 4096 + ((j - 1) * 8 + r8) * 128 + (((ch16 & 7) ^ r8) << 4), b[j][0], b[j][1], b[j][2], b[j][3]);
            }
        }
        #pragma unroll
        for (int h = 0; h < 2; h++) {
            #pragma unroll
            for (int j = 0; j < 5; j++)
                if (j < ntile) mma16816(sc[j], a[h][0], a[h][1], a[h][2], a[h][3], b[j][2 * h], b[j][2 * h + 1]);
        }
    }
    const float sl2 = 0.08838834764831845f * 1.4426950408889634f;
    uint32_t pf[2][5];
    float inv[2];
    #pragma unroll
    for (int q = 0; q < 2; q++) {
        const int tok = mh * 16 + q * 8 + g;
        float v[10];
        #pragma unroll
        for (int j = 0; j < 5; j++) {
            #pragma unroll
            for (int e = 0; e < 2; e++) {
                const int key = (j - 1) * 8 + 2 * c + e;
                v[2 * j + e] = (j == 0 || key <= tok) ? sc[j][2 * q + e] : -INFINITY;
            }
        }
        float mx = v[0];
        #pragma unroll
        for (int j = 1; j < 10; j++) mx = fmaxf(mx, v[j]);
        mx = fmaxf(mx, __shfl_xor_sync(~0u, mx, 1));
        mx = fmaxf(mx, __shfl_xor_sync(~0u, mx, 2));
        const float mo = mx * sl2;
        float sum = 0.f;
        #pragma unroll
        for (int j = 0; j < 10; j++) { v[j] = ex2(fmaf(v[j], sl2, -mo)); sum += v[j]; }
        sum += __shfl_xor_sync(~0u, sum, 1);
        sum += __shfl_xor_sync(~0u, sum, 2);
        inv[q] = rcp(sum);
        #pragma unroll
        for (int j = 0; j < 5; j++) pf[q][j] = pack_bf16(v[2 * j], v[2 * j + 1]);
    }
    auto load_v = [&](int n4, uint32_t (&vm)[4], uint32_t (&vt)[4][4]) {
        ldsm_x4(svm + n4 * 512 + lane * 16, vm[0], vm[1], vm[2], vm[3]);
        #pragma unroll
        for (int u = 0; u < 4; u++) {
            const int dt = 2 * n4 + (u >> 1), kh = u & 1;
            const uint4 v = lds128(sv + (dt & 3) * 2048 + (dt >> 2) * 1024 + kh * 512 + lane * 16);
            vt[u & 2][2 * kh] = v.x; vt[u & 2][2 * kh + 1] = v.z;
            vt[(u & 2) + 1][2 * kh] = v.y; vt[(u & 2) + 1][2 * kh + 1] = v.w;
        }
    };
    uint32_t vm[2][4], vt[2][4][4];
    load_v(0, vm[0], vt[0]);
    #pragma unroll
    for (int n4 = 0; n4 < 4; n4++) {
        const int cur = n4 & 1;
        if (n4 + 1 < 4) load_v(n4 + 1, vm[cur ^ 1], vt[cur ^ 1]);
        float o[4][4];
        #pragma unroll
        for (int u = 0; u < 4; u++) {
            o[u][0] = o[u][1] = o[u][2] = o[u][3] = 0.f;
            mma16816(o[u], pf[0][1], pf[1][1], pf[0][2], pf[1][2], vt[cur][u][0], vt[cur][u][1]);
        }
        if (mh) {
            #pragma unroll
            for (int u = 0; u < 4; u++) mma16816(o[u], pf[0][3], pf[1][3], pf[0][4], pf[1][4], vt[cur][u][2], vt[cur][u][3]);
        }
        #pragma unroll
        for (int u = 0; u < 4; u++) mma1688(o[u], pf[0][0], pf[1][0], vm[cur][u]);
        #pragma unroll
        for (int u = 0; u < 4; u += 2) {
            const int row = mh * 16 + (mi & 1) * 8 + r8, nt = 4 * n4 + u + (mi >> 1);
            stsm_x4(sq + (nt >> 3) * 4096 + row * 128 + (((nt & 7) ^ r8) << 4),
                    pack_bf16(o[u][0] * inv[0], o[u][1] * inv[0]), pack_bf16(o[u][2] * inv[1], o[u][3] * inv[1]),
                    pack_bf16(o[u + 1][0] * inv[0], o[u + 1][1] * inv[0]), pack_bf16(o[u + 1][2] * inv[1], o[u + 1][3] * inv[1]));
        }
    }
}

__device__ __forceinline__ void b_attn_warp(uint32_t base, int hl, int idx0, int lane) {
    const uint32_t sq = base, sk = base + 8192, sv = base + 8192 + 9216;
    const int g = lane >> 2, c = lane & 3;
    auto addr = [&](uint32_t t, int row, int ch) { return t + row * 128 + ((ch ^ (row & 7)) << 4); };
    const float sl2 = 0.17677669529663687f * 1.4426950408889634f;
    #pragma unroll 2
    for (int blk = 0; blk < 4; blk++) {
        const int r0 = blk * 16;
        float sc[3][4];
        #pragma unroll
        for (int j = 0; j < 3; j++) { sc[j][0] = sc[j][1] = sc[j][2] = sc[j][3] = 0.f; }
        #pragma unroll
        for (int t = 0; t < 2; t++) {
            uint32_t a0, a1, a2, a3, b0, b1, b2, b3, d0, d1, d2, d3;
            const int mi = lane >> 3, r = lane & 7;
            ldsm_x4(addr(sq, r0 + (mi & 1) * 8 + r, hl * 4 + 2 * t + (mi >> 1)), a0, a1, a2, a3);
            ldsm_x4(addr(sk, r0 + (mi >> 1) * 8 + r, hl * 4 + 2 * t + (mi & 1)), b0, b1, b2, b3);
            ldsm_x4(addr(sk, r0 + 16 + r, hl * 4 + 2 * t + (mi & 1)), d0, d1, d2, d3);
            mma16816(sc[0], a0, a1, a2, a3, b0, b1);
            mma16816(sc[1], a0, a1, a2, a3, b2, b3);
            mma16816(sc[2], a0, a1, a2, a3, d0, d1);
        }
        uint32_t pf[2][3];
        float inv[2];
        #pragma unroll
        for (int r = 0; r < 2; r++) {
            const int u = r * 8 + g;
            float v[6];
            #pragma unroll
            for (int j = 0; j < 3; j++) {
                #pragma unroll
                for (int e = 0; e < 2; e++) {
                    const int key = j * 8 + 2 * c + e;
                    const bool ok = key > u && key <= u + 8 && idx0 + r0 - 8 + key >= 0;
                    v[2 * j + e] = ok ? sc[j][2 * r + e] : -INFINITY;
                }
            }
            float mx = fmaxf(fmaxf(fmaxf(v[0], v[1]), fmaxf(v[2], v[3])), fmaxf(v[4], v[5]));
            mx = fmaxf(mx, __shfl_xor_sync(~0u, mx, 1));
            mx = fmaxf(mx, __shfl_xor_sync(~0u, mx, 2));
            const float mo = mx * sl2;
            float sum = 0.f;
            #pragma unroll
            for (int j = 0; j < 6; j++) { v[j] = ex2(fmaf(v[j], sl2, -mo)); sum += v[j]; }
            sum += __shfl_xor_sync(~0u, sum, 1);
            sum += __shfl_xor_sync(~0u, sum, 2);
            inv[r] = rcp(sum);
            #pragma unroll
            for (int j = 0; j < 3; j++) pf[r][j] = pack_bf16(v[2 * j], v[2 * j + 1]);
        }
        uint32_t ow[4][2];
        {
            const int mi = lane >> 3, r = lane & 7;
            uint32_t vv[4][4];
            #pragma unroll
            for (int nt = 0; nt < 4; nt++)
                ldsm_x4_t(addr(sv, r0 + min(mi, 2) * 8 + r, hl * 4 + nt), vv[nt][0], vv[nt][1], vv[nt][2], vv[nt][3]);
            float o[4][4];
            #pragma unroll
            for (int nt = 0; nt < 4; nt++) {
                o[nt][0] = o[nt][1] = o[nt][2] = o[nt][3] = 0.f;
                mma16816(o[nt], pf[0][0], pf[1][0], pf[0][1], pf[1][1], vv[nt][0], vv[nt][1]);
            }
            #pragma unroll
            for (int nt = 0; nt < 4; nt++) mma1688(o[nt], pf[0][2], pf[1][2], vv[nt][2]);
            #pragma unroll
            for (int nt = 0; nt < 4; nt++) {
                ow[nt][0] = pack_bf16(o[nt][0] * inv[0], o[nt][1] * inv[0]);
                ow[nt][1] = pack_bf16(o[nt][2] * inv[1], o[nt][3] * inv[1]);
            }
        }
        #pragma unroll
        for (int u = 0; u < 4; u += 2) {
            const int mi = lane >> 3, r = lane & 7;
            stsm_x4(addr(sq, r0 + (mi & 1) * 8 + r, hl * 4 + u + (mi >> 1)), ow[u][0], ow[u][1], ow[u + 1][0], ow[u + 1][1]);
        }
    }
}

constexpr uint32_t QKVB_TARGET = 12 * 8;
constexpr uint32_t PROGRESS_TARGET = 96;
constexpr uint32_t OA_TARGET = 64, OB_TARGET = 32;
#define ATT_RELAXED 1
#define LAST_EARLY 1
#define ATT_B0 8
#define ATT_BSTEP 2
constexpr int ATT_TASKS = (NSEG + 16) * 32;
static_assert(ATT_B0 + 16 * ATT_BSTEP <= NSEG, "order of the task groups");
__device__ __forceinline__ int att_group(int g, bool& isb) {
    constexpr int P = ATT_BSTEP + 1;
    const int q = g - ATT_B0;
    isb = q >= 0 && q < 16 * P && q % P == 0;
    return q < 0 ? g : q >= 16 * P ? g - 16 : isb ? q / P : g - q / P - 1;
}

__global__ void __launch_bounds__(ATT_THREADS, 1) attn_kernel(const __grid_constant__ AttnParams p) {
    extern __shared__ __align__(1024) uint8_t smem_raw[];
    const int tid = threadIdx.x, lane = tid & 31, warp = __shfl_sync(~0u, tid >> 5, 0);
    const int pair = warp >> 1, wi = warp & 1;
    const uint32_t base = smem_u32(smem_raw) + pair * ATT_SLOT, bar = smem_u32(smem_raw) + ATT_BAR + pair * 16;
    const bool leader = wi == 0 && lane == 0;
    if (tid == 0) pdl_launch_dependents();
    KENTER(3);
    const uint32_t cnt = smem_u32(smem_raw) + ATT_CNT;
    if (tid < 96) sts32(cnt + tid * 4, 0);
    __syncthreads();
    if (warp == 2 * ATT_PAIRS) {
        for (uint32_t n = 0; n < SPIN_LIMIT; n++) {
            const bool last = lds32_volatile(cnt + 320) == 2 * ATT_PAIRS;
            uint32_t v[3];
            #pragma unroll
            for (int i = 0; i < 3; i++) {
                v[i] = 0;
                if (i * 32 + lane < 80 && lds32_volatile(cnt + (i * 32 + lane) * 4) != 0)
                    asm volatile("atom.acquire.cta.shared.exch.b32 %0, [%1], 0;" : "=r"(v[i]) : "r"(cnt + (i * 32 + lane) * 4) : "memory");
            }
            if (v[0] | v[1] | v[2]) {
                if (!ATT_RELAXED) asm volatile("fence.acq_rel.gpu;" ::: "memory");
                #pragma unroll
                for (int i = 0; i < 3; i++)
                    if (v[i]) asm volatile("red.relaxed.gpu.global.add.u32 [%0], %1;" ::"l"(p.flags + F_OB + i * 32 + lane), "r"(v[i]) : "memory");
                if (v[2] && lane == 15) KMARK(14);
            }
            __syncwarp();
            if (last) break;
            __nanosleep(40);
        }
        if (lane == 0) KEXIT(3);
        return;
    }
    uint32_t phase = 0;
    if (leader) {
        mbar_init(bar, 1);
        asm volatile("fence.mbarrier_init.release.cluster;" ::: "memory");
    }
    uint32_t pending = 0;
    auto flush = [&]() {
        if (pending) {
            bulk_wait_all();
            if (pending == cnt + 79 * 4) KMARK(13);
            asm volatile("red.release.cta.shared.add.u32 [%0], 1;" ::"r"(pending) : "memory");
            pending = 0;
        }
    };
    int ready_a = -1, ready_b = -1;
    for (int task = pair * gridDim.x + blockIdx.x; task < ATT_TASKS; task += ATT_PAIRS * gridDim.x) {
        bool isb;
        const int grp = att_group(task >> 5, isb), i = task & 31;
        named_bar_sync(1 + pair, 64);
        if (leader) {
            {
                auto need = [&](const uint32_t* f, uint32_t target) {
                    if (ld_acquire_b32(f) < target) { flush(); wait_flag(f, target); }
                };
                if (isb) {
                    if (grp > ready_b) {
                        need(p.flags + F_QKVB + grp, QKVB_TARGET);
                        if (grp > 0) need(p.flags + F_QKVB + grp - 1, QKVB_TARGET);
                        asm volatile("fence.proxy.async.global;" ::: "memory");
                        ready_b = grp;
                    }
                    mbar_arrive_expect_tx(bar, 8192 + 2 * 9216);
                    tma_load_3d(base, &p.tmQb, (i >> 1) * 64, i & 1, grp * 64, bar);
                    tma_load_3d(base + 8192, &p.tmKb, DM + (i >> 1) * 64, i & 1, grp * 64 - 8, bar);
                    tma_load_3d(base + 8192 + 9216, &p.tmKb, 2 * DM + (i >> 1) * 64, i & 1, grp * 64 - 8, bar);
                } else {
                    if (grp > ready_a) {
                        need(p.flags + (LAST_EARLY && grp == NSEG - 1 ? F_LASTTOK : F_PROGRESS + grp), PROGRESS_TARGET);
                        asm volatile("fence.proxy.async.global;" ::: "memory");
                        ready_a = grp;
                    }
                    if (grp == 63) KMARK(10);
                    mbar_arrive_expect_tx(bar, ATT_SLOT);
                    #pragma unroll
                    for (int w = 0; w < 3; w++)
                        bulk_load(base + w * 8192, p.qkv_tok + (((size_t)w * NSEG + grp) * NH + i) * (SEG * DH), 8192, bar);
                    if (LAST_EARLY && grp == NSEG - 1) {
                        need(p.flags + F_PROGRESS + grp, PROGRESS_TARGET);
                        asm volatile("fence.proxy.async.global;" ::: "memory");
                    }
                    #pragma unroll
                    for (int w = 0; w < 2; w++)
                        bulk_load(base + 24576 + w * 2048, p.kv_mem + (((size_t)w * NSEG + grp) * NH + i) * (MROWS * DH), 2048, bar);
                }
            }
        }
        if (lane == 0) flush();
        __syncwarp();
        mbar_wait_sleep(bar, phase);
        phase ^= 1;
        if (isb) {
            b_attn_warp(base, wi, grp * 64, lane);
            asm volatile("fence.proxy.async.shared::cta;" ::: "memory");
            named_bar_sync(1 + pair, 64);
            if (wi == 1 && lane == 0) {
                asm volatile("cp.async.bulk.tensor.3d.global.shared::cta.bulk_group [%0, {%2, %3, %4}], [%1];"
                             ::"l"(&p.tmOb), "r"(base), "r"((i >> 1) * 64), "r"(i & 1), "r"(grp * 64) : "memory");
                pending = cnt + grp * 4;
            }
        } else {
            if (grp == 63 && lane == 0) KMARK(11);
            tok_attn_warp(base, wi, lane);
            if (grp == 63 && lane == 0) KMARK(12);
            asm volatile("fence.proxy.async.shared::cta;" ::: "memory");
            __syncwarp();
            if (lane == 0) {
                #pragma unroll
                for (int h = 0; h < 2; h++) tma_store_2d(&p.tmOa, base + h * 4096 + wi * 2048, i * DH + h * 64, grp * SEG + wi * 16);
                pending = cnt + (16 + grp) * 4;
            }
        }
        if (lane == 0) { bulk_commit(); bulk_wait_read_all(); }
        __syncwarp();
    }
    if (lane == 0) {
        flush();
        asm volatile("red.release.cta.shared.add.u32 [%0], 1;" ::"r"(cnt + 320) : "memory");
    }
}

typedef CUresult (*EncodeFn)(CUtensorMap*, CUtensorMapDataType, cuuint32_t, void*, const cuuint64_t*, const cuuint64_t*,
                             const cuuint32_t*, const cuuint32_t*, CUtensorMapInterleave, CUtensorMapSwizzle,
                             CUtensorMapL2promotion, CUtensorMapFloatOOBfill);

void make_map_2d(EncodeFn enc, CUtensorMap* m, const void* ptr, uint64_t rows, uint64_t cols, uint32_t box_rows) {
    cuuint64_t dims[2] = {cols, rows};
    cuuint64_t strides[1] = {cols * 2};
    cuuint32_t box[2] = {64, box_rows};
    cuuint32_t es[2] = {1, 1};
    enc(m, CU_TENSOR_MAP_DATA_TYPE_BFLOAT16, 2, const_cast<void*>(ptr), dims, strides, box, es,
        CU_TENSOR_MAP_INTERLEAVE_NONE, CU_TENSOR_MAP_SWIZZLE_128B, CU_TENSOR_MAP_L2_PROMOTION_L2_256B,
        CU_TENSOR_MAP_FLOAT_OOB_FILL_NONE);
}
void make_map_b(EncodeFn enc, CUtensorMap* m, const void* ptr, uint64_t k, uint64_t n, uint32_t nblk, uint32_t box_rows = 64,
                uint32_t bc = 64) {
    cuuint64_t dims[3] = {bc, k, n / bc};
    cuuint64_t strides[2] = {n * 2, bc * 2};
    cuuint32_t box[3] = {bc, box_rows, nblk};
    cuuint32_t es[3] = {1, 1, 1};
    enc(m, CU_TENSOR_MAP_DATA_TYPE_BFLOAT16, 3, const_cast<void*>(ptr), dims, strides, box, es,
        CU_TENSOR_MAP_INTERLEAVE_NONE, bc == 64 ? CU_TENSOR_MAP_SWIZZLE_128B : CU_TENSOR_MAP_SWIZZLE_64B, CU_TENSOR_MAP_L2_PROMOTION_L2_256B,
        CU_TENSOR_MAP_FLOAT_OOB_FILL_NONE);
}

void make_map_parity(EncodeFn enc, CUtensorMap* m, const void* ptr, uint64_t cols, uint32_t box_rows) {
    cuuint64_t dims[3] = {cols, 2, S_TOK / 2};
    cuuint64_t strides[2] = {cols * 2, cols * 4};
    cuuint32_t box[3] = {64, 1, box_rows};
    cuuint32_t es[3] = {1, 1, 1};
    enc(m, CU_TENSOR_MAP_DATA_TYPE_BFLOAT16, 3, const_cast<void*>(ptr), dims, strides, box, es,
        CU_TENSOR_MAP_INTERLEAVE_NONE, CU_TENSOR_MAP_SWIZZLE_128B, CU_TENSOR_MAP_L2_PROMOTION_L2_128B,
        CU_TENSOR_MAP_FLOAT_OOB_FILL_NONE);
}
void make_map_w(EncodeFn enc, CUtensorMap* m, const void* ptr) {
    cuuint64_t dims[3] = {HD, 64, DM / 64};
    cuuint64_t strides[2] = {HD * 2, 64 * HD * 2};
    cuuint32_t box[3] = {64, 16, 8};
    cuuint32_t es[3] = {1, 1, 1};
    enc(m, CU_TENSOR_MAP_DATA_TYPE_BFLOAT16, 3, const_cast<void*>(ptr), dims, strides, box, es,
        CU_TENSOR_MAP_INTERLEAVE_NONE, CU_TENSOR_MAP_SWIZZLE_128B, CU_TENSOR_MAP_L2_PROMOTION_L2_256B,
        CU_TENSOR_MAP_FLOAT_OOB_FILL_NONE);
}

#define OUTB_SIDE_BLOCKS 16
#define SIDE_ORDER 0
#define SERIAL_ATT_CTAS h.n_sm
#define N_TAIL_CTAS 28
#define N_SIDE_CTAS 28
#define N_ATT_CTAS 8
#define TAIL_BLOCK0 11

#define TAIL_SPARE 2
#define TAIL_KB2 30
#define TAIL_KB3 20
#define TAIL_BLOCK1 13
#define TAIL_BLOCK2 14

struct HostState {
    bool ready;
    bool overlap;
    int n_side, n_att, n_sm;
    SideParams seq_a, seq_b;
    const void* key[11];
    RecParams rec;
    SideParams side, tail, outb;
    FinalParams fin;
    AttnParams attn;
    __nv_bfloat16 *qkv_tok, *kv_mem, *o_tok, *qkv_b, *o_b;
    uint8_t* xchg;
};
HostState g_host;

void setup(void* const* d_in, void* d_out) {
    HostState& h = g_host;
    void* fn = nullptr;
    cudaDriverEntryPointQueryResult qr;
    cudaGetDriverEntryPoint("cuTensorMapEncodeTiled", &fn, cudaEnableDefault, &qr);
    EncodeFn enc = reinterpret_cast<EncodeFn>(fn);
    void* ptr;
    cudaGetSymbolAddress(&ptr, g_qkv_tok); h.qkv_tok = (__nv_bfloat16*)ptr;
    cudaGetSymbolAddress(&ptr, g_kv_mem);  h.kv_mem = (__nv_bfloat16*)ptr;
    cudaGetSymbolAddress(&ptr, g_o_tok);   h.o_tok = (__nv_bfloat16*)ptr;
    cudaGetSymbolAddress(&ptr, g_qkv_b);   h.qkv_b = (__nv_bfloat16*)ptr;
    cudaGetSymbolAddress(&ptr, g_o_b);     h.o_b = (__nv_bfloat16*)ptr;
    cudaGetSymbolAddress(&ptr, g_xchg);    h.xchg = (uint8_t*)(((uint64_t)ptr + XCHG_BYTES - 1) & ~(uint64_t)(XCHG_BYTES - 1));
    cudaGetSymbolAddress(&ptr, g_flags);   uint32_t* flags = (uint32_t*)ptr;
    cudaGetSymbolAddress(&ptr, g_arrivals); uint32_t* arrivals = (uint32_t*)ptr;

    const void *xa = d_in[0], *mem0 = d_in[1], *wq = d_in[2], *wk = d_in[3], *wv = d_in[4], *wo = d_in[5];
    const void *xb = d_in[7], *wqkv = d_in[8], *wob = d_in[9];

    RecParams& r = h.rec;
    make_map_w(enc, &r.tmW[0], wq);
    make_map_w(enc, &r.tmW[1], wk);
    make_map_w(enc, &r.tmW[2], wv);
    make_map_b(enc, &r.tmWo, wo, HD, DM, 11, 128, 32);
    r.mem0 = (const __nv_bfloat16*)mem0;
    r.qkv_tok = h.qkv_tok; r.kv_mem = h.kv_mem; r.xchg = h.xchg;
    r.flags = flags; r.arrivals = arrivals; r.one[0] = r.one[1] = 1;
    make_map_b(enc, &r.tmX, xa, S_TOK, DM, 4, SEG);

    SideParams& sd = h.side;
    SideProb& p0 = sd.prob[0];
    make_map_2d(enc, &p0.tmA, xb, S_TOK, DM, BM);
    make_map_b(enc, &p0.tmB, wqkv, DM, 3 * DM, 4);
    make_map_2d(enc, &p0.tmC, h.qkv_b, S_TOK, 3 * DM, 16);
    p0.n_tiles = 3 * DM / 256; p0.k_blocks = DM / BK; p0.c_col0 = 0; p0.dep = nullptr; p0.dep_target = 0; p0.dep_n = 1; p0.sig = flags + F_QKVB;
    SideProb& p1 = sd.prob[1];
    make_map_2d(enc, &p1.tmA, h.o_tok, S_TOK, HD, BM);
    make_map_b(enc, &p1.tmB, wo, HD, DM, 4);
    make_map_2d(enc, &p1.tmC, d_out, S_TOK, 2 * DM, 16);
    p1.n_tiles = DM / 256; p1.k_blocks = HD / BK; p1.c_col0 = 0; p1.dep = flags + F_OA; p1.dep_target = OA_TARGET; p1.dep_n = 4; p1.sig = nullptr;
    SideProb& p2 = sd.prob[2];
    make_map_2d(enc, &p2.tmA, h.o_b, S_TOK, DM, BM);
    make_map_b(enc, &p2.tmB, wob, DM, DM, 4);
    p2.tmC = p1.tmC;
    p2.n_tiles = DM / 256; p2.k_blocks = DM / BK; p2.c_col0 = DM; p2.dep = flags + F_OB; p2.dep_target = OB_TARGET; p2.dep_n = 1; p2.sig = nullptr;
    p0.n_split = p0.n_tiles; p1.n_split = p1.n_tiles; p2.n_split = p2.n_tiles;
    p0.part = p1.part = p2.part = nullptr;
    p0.k_total = p0.k_blocks; p1.k_total = p1.k_blocks; p2.k_total = p2.k_blocks;
    if (SIDE_ORDER == 0) { sd.seg[0] = {0, 0, 16}; sd.seg[1] = {1, 0, TAIL_BLOCK0}; }
    else { sd.seg[0] = {1, 0, TAIL_BLOCK0}; sd.seg[1] = {0, 0, 16}; }
    sd.seg[2] = {2, 0, OUTB_SIDE_BLOCKS};
    sd.nseg = 3; sd.queue = flags + F_SIDEQ; sd.spare_seg = 3; sd.flags = flags;
    h.outb = sd;
    h.outb.seg[0] = {2, OUTB_SIDE_BLOCKS, 16};
    h.outb.nseg = 1; h.outb.queue = flags + F_OUTBQ;

    SideParams& tl = h.tail;
    tl.prob[0] = p1;
    make_map_b(enc, &tl.prob[0].tmB, wo, HD, DM, 2);
    cudaGetSymbolAddress(&ptr, g_part);
    for (int i = 0; i < 3; i++) {
        SideProb& q = tl.prob[i];
        q = tl.prob[0];
        q.n_tiles = (i + 1) * DM / 128; q.n_split = DM / 128; q.k_blocks = i == 0 ? HD / BK : i == 1 ? TAIL_KB2 : TAIL_KB3;
        q.part = i ? (float*)ptr : nullptr; q.part_flag = flags + F_PART;
    }
    tl.seg[0] = {0, TAIL_BLOCK0, TAIL_BLOCK1};
    tl.seg[1] = {1, TAIL_BLOCK1, TAIL_BLOCK2};
    tl.seg[2] = {2, TAIL_BLOCK2, 15};
    tl.nseg = 3; tl.queue = flags + F_TAILQ; tl.spare_seg = TAIL_SPARE; tl.flags = flags;

    make_map_2d(enc, &h.fin.tmA, h.o_tok, S_TOK, HD, SEG);
    h.fin.tmB = tl.prob[0].tmB; h.fin.out = (__nv_bfloat16*)d_out;
    h.fin.dep = flags + F_OA + 60; h.fin.dep_target = OA_TARGET; h.fin.mt = 15;

    make_map_2d(enc, &h.attn.tmOa, h.o_tok, S_TOK, HD, 16);
    make_map_parity(enc, &h.attn.tmQb, h.qkv_b, 3 * DM, 64);
    make_map_parity(enc, &h.attn.tmKb, h.qkv_b, 3 * DM, 72);
    make_map_parity(enc, &h.attn.tmOb, h.o_b, DM, 64);
    h.attn.qkv_tok = h.qkv_tok; h.attn.kv_mem = h.kv_mem; h.attn.flags = flags;

    int dev = 0, nsm = 0;
    cudaGetDevice(&dev);
    cudaDeviceGetAttribute(&nsm, cudaDevAttrMultiProcessorCount, dev);
    h.n_sm = nsm;
    h.overlap = nsm - 96 >= N_SIDE_CTAS + N_ATT_CTAS;
    h.n_side = N_SIDE_CTAS; h.n_att = N_ATT_CTAS;
    h.seq_a = sd;
    h.seq_a.seg[0] = {0, 0, 16};
    h.seq_a.nseg = 1;
    h.seq_b = sd;
    h.seq_b.seg[0] = {1, 0, 16};
    h.seq_b.seg[1] = {2, 0, 16};
    h.seq_b.nseg = 2; h.seq_b.queue = flags + F_TAILQ;

    cudaFuncSetAttribute(side_gemm_kernel<256>, cudaFuncAttributeMaxDynamicSharedMemorySize, GemmCfg<256>::SMEM);
    cudaFuncSetAttribute(side_gemm_kernel<128>, cudaFuncAttributeMaxDynamicSharedMemorySize, GemmCfg<128>::SMEM);
    cudaFuncSetAttribute(final_gemm_kernel, cudaFuncAttributeMaxDynamicSharedMemorySize, FIN_SMEM);
    cudaFuncSetAttribute(rec_kernel, cudaFuncAttributeMaxDynamicSharedMemorySize, REC_SMEM);
    cudaFuncSetAttribute(attn_kernel, cudaFuncAttributeMaxDynamicSharedMemorySize, ATT_SMEM);
    for (int i = 0; i < 10; i++) h.key[i] = d_in[i];
    h.key[10] = d_out;
    h.ready = true;
}

template <typename K, typename P>
void launch(K kernel, int grid, int block, int smem, cudaStream_t st, const P& prm, int cluster, bool pdl) {
    cudaLaunchConfig_t cfg = {};
    cfg.gridDim = dim3(grid); cfg.blockDim = dim3(block); cfg.dynamicSmemBytes = smem; cfg.stream = st;
    cudaLaunchAttribute at[2];
    int n = 0;
    if (cluster > 1) {
        at[n].id = cudaLaunchAttributeClusterDimension;
        at[n].val.clusterDim.x = cluster; at[n].val.clusterDim.y = 1; at[n].val.clusterDim.z = 1;
        n++;
    }
    if (pdl) {
        at[n].id = cudaLaunchAttributeProgrammaticStreamSerialization;
        at[n].val.programmaticStreamSerializationAllowed = 1;
        n++;
    }
    cfg.attrs = at; cfg.numAttrs = n;
    cudaLaunchKernelEx(&cfg, kernel, prm);
}

}

extern "C" void kernel_launch(void* const* d_in, const int* in_sizes, int n_in, void* d_out, int out_size) {
    HostState& h = g_host;
    bool same = h.ready;
    for (int i = 0; same && i < 10; i++) same = h.key[i] == d_in[i];
    if (!same || h.key[10] != d_out) setup(d_in, d_out);
    cudaStream_t st = cudaStreamPerThread;

    launch(rec_kernel, 96, REC_THREADS, REC_SMEM, st, h.rec, 3, false);
    {
        if (!h.overlap) {
            launch(side_gemm_kernel<256>, h.n_sm, 384, GemmCfg<256>::SMEM, st, h.seq_a, 1, false);
            launch(attn_kernel, SERIAL_ATT_CTAS, ATT_THREADS, ATT_SMEM, st, h.attn, 1, false);
            launch(side_gemm_kernel<256>, h.n_sm, 384, GemmCfg<256>::SMEM, st, h.seq_b, 1, false);
            return;
        }
    }
    launch(side_gemm_kernel<256>, h.n_side, 384, GemmCfg<256>::SMEM, st, h.side, 1, true);
    launch(attn_kernel, h.n_att, ATT_THREADS, ATT_SMEM, st, h.attn, 1, true);
    launch(side_gemm_kernel<128>, N_TAIL_CTAS, 384, GemmCfg<128>::SMEM, st, h.tail, 1, true);
    launch(final_gemm_kernel, 8 * FIN_SPLIT, 384, FIN_SMEM, st, h.fin, FIN_SPLIT, true);
    if (OUTB_SIDE_BLOCKS < 16)
        launch(side_gemm_kernel<256>, (16 - OUTB_SIDE_BLOCKS) * 4, 384, GemmCfg<256>::SMEM, st, h.outb, 1, true);
}
```

```cpp
#include <cuda_runtime.h>
#include <cuda_bf16.h>
#include <cuda.h>
#include <stdint.h>

namespace {

constexpr int S_TOK = 2048;
constexpr int DM = 1024;
constexpr int NH = 32;
constexpr int DH = 128;
constexpr int HD = NH * DH;
constexpr int NSEG = 64;
constexpr int SEG = 32;
constexpr int MROWS = 8;
constexpr uint32_t SENT = 0xFFFFFFFFu;
constexpr uint32_t SPIN_LIMIT = 1u << 24;

__device__ __align__(1024) __nv_bfloat16 g_qkv_tok[3ull * NSEG * NH * SEG * DH];
__device__ __align__(1024) __nv_bfloat16 g_kv_mem[2ull * NSEG * NH * MROWS * DH];
__device__ __align__(1024) __nv_bfloat16 g_o_tok[(size_t)S_TOK * HD];
__device__ __align__(1024) __nv_bfloat16 g_qkv_b[(size_t)S_TOK * 3 * DM];
__device__ __align__(1024) __nv_bfloat16 g_o_b[(size_t)S_TOK * DM];
__device__ __align__(1024) float g_part[32 * 2 * 128 * 128];
constexpr int PUB_BYTES = 32768;
constexpr int XCHG_SLOT = 1 << 20;
constexpr int XCHG_PUB = 0, XCHG_INBOX = 2 * PUB_BYTES;
constexpr int INBOX_MAX = 80;
constexpr int XCHG_BYTES = 2 * XCHG_SLOT;
__device__ __align__(8192) uint8_t g_xchg[2 * XCHG_BYTES];
enum { F_LASTTOK = 0, F_RECSM = 4, F_PROGRESS = 16, F_QKVB = 80, F_OB = 96, F_OA = 112, F_PART = 176, F_SIDEQ = 208, F_TAILQ = 256, F_COUNT = 304 };
__device__ uint32_t g_flags[F_COUNT];
__device__ __align__(16) uint32_t g_arrivals[4];

#define STAMP(k) do {} while (0)
#define STAMPD(k, x) do {} while (0)
#define PSTAMP(k) do {} while (0)
#define KENTER(k) do {} while (0)
#define KEXIT(k) do {} while (0)
#define KMARK(k) do {} while (0)

__device__ __forceinline__ uint32_t class_off(uint64_t a, uint32_t c) {
    return ((__popc((uint32_t)a & 0xB3000u) ^ c) & 1u) << 12;
}
__device__ __forceinline__ uint32_t smem_u32(const void* p) { return (uint32_t)__cvta_generic_to_shared(p); }
__device__ __forceinline__ uint32_t pack_bf16(float lo, float hi) {
    uint32_t r;
    asm("cvt.rn.bf16x2.f32 %0, %1, %2;" : "=r"(r) : "f"(hi), "f"(lo));
    return r;
}
__device__ __forceinline__ float ex2(float x) {
    float y;
    asm("ex2.approx.ftz.f32 %0, %1;" : "=f"(y) : "f"(x));
    return y;
}
__device__ __forceinline__ float rcp(float x) {
    float y;
    asm("rcp.approx.ftz.f32 %0, %1;" : "=f"(y) : "f"(x));
    return y;
}
__device__ __forceinline__ uint32_t clock32() {
    uint32_t t;
    asm volatile("mov.u32 %0, %%clock;" : "=r"(t));
    return t;
}
__device__ __forceinline__ void spin_clks(uint32_t n) {
    if (n == 0) return;
    const uint32_t t0 = clock32();
    while (clock32() - t0 < n) {}
}
__device__ __forceinline__ void spin_until(uint32_t t) {
    while ((int)(clock32() - t) < 0) {}
}
__device__ __forceinline__ uint32_t clock_after(uint32_t x) {
    uint32_t t;
    asm volatile("{\n.reg .pred p;\nsetp.eq.u32 p, %1, 0x12345678;\n@p exit;\nmov.u32 %0, %%clock;\n}" : "=r"(t) : "r"(x) : "memory");
    return t;
}
__device__ __forceinline__ uint32_t opaque(uint32_t x) { return __shfl_sync(~0u, x, threadIdx.x & 31); }
__device__ __forceinline__ uint32_t uniform(uint32_t x) { return __shfl_sync(~0u, x + (threadIdx.x & 31), 0); }
__device__ __forceinline__ float bf16_lo(uint32_t w) { return __uint_as_float(w << 16); }
__device__ __forceinline__ float bf16_hi(uint32_t w) { return __uint_as_float(w & 0xFFFF0000u); }

__device__ __forceinline__ void mbar_init(uint32_t bar, uint32_t cnt) {
    asm volatile("mbarrier.init.shared::cta.b64 [%0], %1;" ::"r"(bar), "r"(cnt) : "memory");
}
__device__ __forceinline__ void mbar_arrive(uint32_t bar) {
    asm volatile("mbarrier.arrive.shared::cta.b64 _, [%0];" ::"r"(bar) : "memory");
}
__device__ __forceinline__ void mbar_arrive_expect_tx(uint32_t bar, uint32_t bytes) {
    asm volatile("mbarrier.arrive.expect_tx.shared::cta.b64 _, [%0], %1;" ::"r"(bar), "r"(bytes) : "memory");
}
__device__ __forceinline__ bool mbar_try_wait(uint32_t bar, uint32_t parity) {
    uint32_t ok;
    asm volatile(
        "{\n.reg .pred p;\n"
        "mbarrier.try_wait.parity.shared::cta.b64 p, [%1], %2;\n"
        "selp.u32 %0, 1, 0, p;\n}"
        : "=r"(ok) : "r"(bar), "r"(parity) : "memory");
    return ok != 0;
}
__device__ __forceinline__ bool mbar_test_wait(uint32_t bar, uint32_t parity) {
    uint32_t ok;
    asm volatile(
        "{\n.reg .pred p;\n"
        "mbarrier.test_wait.parity.shared::cta.b64 p, [%1], %2;\n"
        "selp.u32 %0, 1, 0, p;\n}"
        : "=r"(ok) : "r"(bar), "r"(parity) : "memory");
    return ok != 0;
}
__device__ __forceinline__ void mbar_wait(uint32_t bar, uint32_t parity) {
    uint32_t n = 0;
    while (!mbar_try_wait(bar, parity)) {
        if (++n > SPIN_LIMIT) __trap();
    }
}
__device__ __forceinline__ void mbar_wait_sleep(uint32_t bar, uint32_t parity) {
    uint32_t n = 0;
    while (!mbar_try_wait(bar, parity)) {
        __nanosleep(20);
        if (++n > SPIN_LIMIT) __trap();
    }
}
__device__ __forceinline__ void mbar_wait_bounded(uint32_t bar, uint32_t parity) {
    for (uint32_t n = 0; n < (1u << 20) && !mbar_try_wait(bar, parity); n++) {}
}
__device__ __forceinline__ bool elect_one() {
    uint32_t ok;
    asm volatile("{\n.reg .pred p;\nelect.sync _|p, 0xFFFFFFFF;\nselp.u32 %0, 1, 0, p;\n}" : "=r"(ok));
    return ok != 0;
}
__device__ __forceinline__ void named_bar_sync(int id, int nthreads) {
    asm volatile("bar.sync %0, %1;" ::"r"(id), "r"(nthreads) : "memory");
}
__device__ __forceinline__ void named_bar_arrive(int id, int nthreads) {
    asm volatile("bar.arrive %0, %1;" ::"r"(id), "r"(nthreads) : "memory");
}
__device__ __forceinline__ uint32_t mapa(uint32_t addr, uint32_t rank) {
    uint32_t r;
    asm volatile("mapa.shared::cluster.u32 %0, %1, %2;" : "=r"(r) : "r"(addr), "r"(rank));
    return r;
}

__device__ __forceinline__ void tma_load_2d(uint32_t dst, const CUtensorMap* tm, int c0, int c1, uint32_t bar) {
    asm volatile(
        "cp.async.bulk.tensor.2d.shared::cluster.global.mbarrier::complete_tx::bytes [%0], [%1, {%3, %4}], [%2];"
        ::"r"(dst), "l"(tm), "r"(bar), "r"(c0), "r"(c1) : "memory");
}
__device__ __forceinline__ void tma_load_3d(uint32_t dst, const CUtensorMap* tm, int c0, int c1, int c2, uint32_t bar) {
    asm volatile(
        "cp.async.bulk.tensor.3d.shared::cluster.global.mbarrier::complete_tx::bytes [%0], [%1, {%3, %4, %5}], [%2];"
        ::"r"(dst), "l"(tm), "r"(bar), "r"(c0), "r"(c1), "r"(c2) : "memory");
}
__device__ __forceinline__ void tma_load_3d_mc(uint32_t dst, const CUtensorMap* tm, int c0, int c1, int c2, uint32_t bar, uint16_t mask) {
    asm volatile(
        "cp.async.bulk.tensor.3d.shared::cluster.global.mbarrier::complete_tx::bytes.multicast::cluster [%0], [%1, {%3, %4, %5}], [%2], %6;"
        ::"r"(dst), "l"(tm), "r"(bar), "r"(c0), "r"(c1), "r"(c2), "h"(mask) : "memory");
}
__device__ __forceinline__ void tma_store_2d(const CUtensorMap* tm, uint32_t src, int c0, int c1) {
    asm volatile("cp.async.bulk.tensor.2d.global.shared::cta.bulk_group [%0, {%2, %3}], [%1];"
                 ::"l"(tm), "r"(src), "r"(c0), "r"(c1) : "memory");
}
__device__ __forceinline__ void bulk_store(void* dst, uint32_t src, uint32_t bytes) {
    asm volatile("cp.async.bulk.global.shared::cta.bulk_group [%0], [%1], %2;" ::"l"(dst), "r"(src), "r"(bytes) : "memory");
}
__device__ __forceinline__ void bulk_commit() { asm volatile("cp.async.bulk.commit_group;" ::: "memory"); }
__device__ __forceinline__ void bulk_wait_read_all() { asm volatile("cp.async.bulk.wait_group.read 0;" ::: "memory"); }
__device__ __forceinline__ void bulk_wait_all() { asm volatile("cp.async.bulk.wait_group 0;" ::: "memory"); }
__device__ __forceinline__ void bulk_load(uint32_t dst, const void* src, uint32_t bytes, uint32_t bar) {
    asm volatile("cp.async.bulk.shared::cluster.global.mbarrier::complete_tx::bytes [%0], [%1], %2, [%3];"
                 ::"r"(dst), "l"(src), "r"(bytes), "r"(bar) : "memory");
}

__device__ __forceinline__ void ldsm_x4(uint32_t addr, uint32_t& r0, uint32_t& r1, uint32_t& r2, uint32_t& r3) {
    asm volatile("ldmatrix.sync.aligned.m8n8.x4.shared.b16 {%0,%1,%2,%3}, [%4];"
                 : "=r"(r0), "=r"(r1), "=r"(r2), "=r"(r3) : "r"(addr) : "memory");
}
__device__ __forceinline__ void ldsm_x4_t(uint32_t addr, uint32_t& r0, uint32_t& r1, uint32_t& r2, uint32_t& r3) {
    asm volatile("ldmatrix.sync.aligned.m8n8.x4.trans.shared.b16 {%0,%1,%2,%3}, [%4];"
                 : "=r"(r0), "=r"(r1), "=r"(r2), "=r"(r3) : "r"(addr) : "memory");
}
__device__ __forceinline__ void stsm_x4(uint32_t addr, uint32_t r0, uint32_t r1, uint32_t r2, uint32_t r3) {
    asm volatile("stmatrix.sync.aligned.m8n8.x4.shared.b16 [%0], {%1,%2,%3,%4};"
                 ::"r"(addr), "r"(r0), "r"(r1), "r"(r2), "r"(r3) : "memory");
}
__device__ __forceinline__ void mma16816(float* d, uint32_t a0, uint32_t a1, uint32_t a2, uint32_t a3,
                                         uint32_t b0, uint32_t b1) {
    asm volatile(
        "mma.sync.aligned.m16n8k16.row.col.f32.bf16.bf16.f32 {%0,%1,%2,%3}, {%4,%5,%6,%7}, {%8,%9}, {%0,%1,%2,%3};"
        : "+f"(d[0]), "+f"(d[1]), "+f"(d[2]), "+f"(d[3])
        : "r"(a0), "r"(a1), "r"(a2), "r"(a3), "r"(b0), "r"(b1));
}
__device__ __forceinline__ void mma1688(float* d, uint32_t a0, uint32_t a1, uint32_t b0) {
    asm volatile("mma.sync.aligned.m16n8k8.row.col.f32.bf16.bf16.f32 {%0,%1,%2,%3}, {%4,%5}, {%6}, {%0,%1,%2,%3};"
                 : "+f"(d[0]), "+f"(d[1]), "+f"(d[2]), "+f"(d[3]) : "r"(a0), "r"(a1), "r"(b0));
}
__device__ __forceinline__ uint2 lds64(uint32_t addr) {
    uint2 v;
    asm volatile("ld.volatile.shared.v2.b32 {%0,%1}, [%2];" : "=r"(v.x), "=r"(v.y) : "r"(addr) : "memory");
    return v;
}
__device__ __forceinline__ uint4 lds128(uint32_t addr) {
    uint4 v;
    asm volatile("ld.volatile.shared.v4.b32 {%0,%1,%2,%3}, [%4];" : "=r"(v.x), "=r"(v.y), "=r"(v.z), "=r"(v.w) : "r"(addr) : "memory");
    return v;
}
__device__ __forceinline__ void sts32(uint32_t addr, uint32_t x) {
    asm volatile("st.volatile.shared.b32 [%0], %1;" ::"r"(addr), "r"(x) : "memory");
}
__device__ __forceinline__ void sts64(uint32_t addr, uint32_t x, uint32_t y) {
    asm volatile("st.volatile.shared.v2.b32 [%0], {%1,%2};" ::"r"(addr), "r"(x), "r"(y) : "memory");
}
__device__ __forceinline__ void sts128(uint32_t addr, uint32_t x, uint32_t y, uint32_t z, uint32_t w) {
    asm volatile("st.volatile.shared.v4.b32 [%0], {%1,%2,%3,%4};" ::"r"(addr), "r"(x), "r"(y), "r"(z), "r"(w) : "memory");
}
__device__ __forceinline__ void st_async_v2(uint32_t addr, uint32_t x, uint32_t y, uint32_t bar) {
    asm volatile("st.async.weak.shared::cluster.mbarrier::complete_tx::bytes.v2.b32 [%0], {%1,%2}, [%3];"
                 ::"r"(addr), "r"(x), "r"(y), "r"(bar) : "memory");
}
__device__ __forceinline__ void st_relaxed_v4(void* p, uint32_t x) {
    asm volatile("st.relaxed.gpu.global.v4.b32 [%0], {%1,%1,%1,%1};" ::"l"(p), "r"(x) : "memory");
}
__device__ __forceinline__ uint32_t ld_relaxed_b32(const void* p) {
    uint32_t v;
    asm volatile("ld.relaxed.gpu.global.b32 %0, [%1];" : "=r"(v) : "l"(p) : "memory");
    return v;
}
__device__ __forceinline__ uint32_t lds32_volatile(uint32_t addr) {
    uint32_t v;
    asm volatile("ld.volatile.shared.b32 %0, [%1];" : "=r"(v) : "r"(addr) : "memory");
    return v;
}
__device__ __forceinline__ void st_relaxed_b32(void* p, uint32_t x) {
    asm volatile("st.relaxed.gpu.global.b32 [%0], %1;" ::"l"(p), "r"(x) : "memory");
}

__device__ __forceinline__ uint32_t ld_acquire_b32(const void* p) {
    uint32_t v;
    asm volatile("ld.acquire.gpu.global.b32 %0, [%1];" : "=r"(v) : "l"(p) : "memory");
    return v;
}
__device__ __forceinline__ void wait_flag(const uint32_t* p, uint32_t target) {
    uint32_t n = 0;
    while (ld_acquire_b32(p) < target) {
        __nanosleep(64);
        if (++n > SPIN_LIMIT) __trap();
    }
}
__device__ __forceinline__ void signal_flag(uint32_t* p) {
    asm volatile("red.release.gpu.global.add.u32 [%0], 1;" ::"l"(p) : "memory");
}
__device__ __forceinline__ bool next_to_rec(const uint32_t* flags) {
    uint32_t smid;
    asm volatile("mov.u32 %0, %%smid;" : "=r"(smid));
    smid ^= 1;
    return smid < 384 && ((ld_relaxed_b32(flags + F_RECSM + (smid >> 5)) >> (smid & 31)) & 1);
}
__device__ __forceinline__ void pdl_launch_dependents() { asm volatile("griddepcontrol.launch_dependents;" ::: "memory"); }

constexpr int BM = 128, BK = 64;
constexpr int A_STAGE = BM * BK * 2;
template <int BN> struct GemmCfg {
    static constexpr int STAGES = BN == 256 ? 3 : 6;
    static constexpr int STAGE = A_STAGE + BK * BN * 2;
    static constexpr int EPI_WARP = 16 * BN * 2;
    static constexpr int SMEM = STAGES * STAGE + 8 * EPI_WARP + 1024 + 512;
};

struct SideProb {
    CUtensorMap tmA, tmB, tmC;
    int n_split;
    int n_tiles, k_blocks, k_total, c_col0;
    const uint32_t* dep;
    uint32_t dep_target;
    int dep_n;
    uint32_t* sig;
    float* part;
    uint32_t* part_flag;
};
struct SideSeg { int prob, m0, m1; };
constexpr int SIDE_MAX_SEG = 3;
struct SideParams {
    SideProb prob[3];
    SideSeg seg[SIDE_MAX_SEG];
    int nseg;
    int spare_seg;
    const uint32_t* flags;
    uint32_t* queue;
};
static_assert(sizeof(SideParams) <= 4096, "kernel parameter limit");

__device__ __forceinline__ uint64_t make_desc(uint32_t addr, uint32_t lbo, uint32_t sbo) {
    return (uint64_t)((addr & 0x3FFFF) >> 4) | ((uint64_t)(lbo >> 4) << 16) | ((uint64_t)(sbo >> 4) << 32) | (1ull << 62);
}

__device__ __forceinline__ void wgmma_m64n256k16(float (&d)[128], uint64_t da, uint64_t db, int scale_d) {
    asm volatile(
        "{\n.reg .pred p;\nsetp.ne.b32 p, %130, 0;\n"
        "wgmma.mma_async.sync.aligned.m64n256k16.f32.bf16.bf16 "
        "{%0,%1,%2,%3,%4,%5,%6,%7,%8,%9,%10,%11,%12,%13,%14,%15,"
        "%16,%17,%18,%19,%20,%21,%22,%23,%24,%25,%26,%27,%28,%29,%30,%31,"
        "%32,%33,%34,%35,%36,%37,%38,%39,%40,%41,%42,%43,%44,%45,%46,%47,"
        "%48,%49,%50,%51,%52,%53,%54,%55,%56,%57,%58,%59,%60,%61,%62,%63,"
        "%64,%65,%66,%67,%68,%69,%70,%71,%72,%73,%74,%75,%76,%77,%78,%79,"
        "%80,%81,%82,%83,%84,%85,%86,%87,%88,%89,%90,%91,%92,%93,%94,%95,"
        "%96,%97,%98,%99,%100,%101,%102,%103,%104,%105,%106,%107,%108,%109,%110,%111,"
        "%112,%113,%114,%115,%116,%117,%118,%119,%120,%121,%122,%123,%124,%125,%126,%127},"
        " %128, %129, p, 1, 1, 0, 1;\n}\n"
        : "+f"(d[0]), "+f"(d[1]), "+f"(d[2]), "+f"(d[3]), "+f"(d[4]), "+f"(d[5]), "+f"(d[6]), "+f"(d[7]),
          "+f"(d[8]), "+f"(d[9]), "+f"(d[10]), "+f"(d[11]), "+f"(d[12]), "+f"(d[13]), "+f"(d[14]), "+f"(d[15]),
          "+f"(d[16]), "+f"(d[17]), "+f"(d[18]), "+f"(d[19]), "+f"(d[20]), "+f"(d[21]), "+f"(d[22]), "+f"(d[23]),
          "+f"(d[24]), "+f"(d[25]), "+f"(d[26]), "+f"(d[27]), "+f"(d[28]), "+f"(d[29]), "+f"(d[30]), "+f"(d[31]),
          "+f"(d[32]), "+f"(d[33]), "+f"(d[34]), "+f"(d[35]), "+f"(d[36]), "+f"(d[37]), "+f"(d[38]), "+f"(d[39]),
          "+f"(d[40]), "+f"(d[41]), "+f"(d[42]), "+f"(d[43]), "+f"(d[44]), "+f"(d[45]), "+f"(d[46]), "+f"(d[47]),
          "+f"(d[48]), "+f"(d[49]), "+f"(d[50]), "+f"(d[51]), "+f"(d[52]), "+f"(d[53]), "+f"(d[54]), "+f"(d[55]),
          "+f"(d[56]), "+f"(d[57]), "+f"(d[58]), "+f"(d[59]), "+f"(d[60]), "+f"(d[61]), "+f"(d[62]), "+f"(d[63]),
          "+f"(d[64]), "+f"(d[65]), "+f"(d[66]), "+f"(d[67]), "+f"(d[68]), "+f"(d[69]), "+f"(d[70]), "+f"(d[71]),
          "+f"(d[72]), "+f"(d[73]), "+f"(d[74]), "+f"(d[75]), "+f"(d[76]), "+f"(d[77]), "+f"(d[78]), "+f"(d[79]),
          "+f"(d[80]), "+f"(d[81]), "+f"(d[82]), "+f"(d[83]), "+f"(d[84]), "+f"(d[85]), "+f"(d[86]), "+f"(d[87]),
          "+f"(d[88]), "+f"(d[89]), "+f"(d[90]), "+f"(d[91]), "+f"(d[92]), "+f"(d[93]), "+f"(d[94]), "+f"(d[95]),
          "+f"(d[96]), "+f"(d[97]), "+f"(d[98]), "+f"(d[99]), "+f"(d[100]), "+f"(d[101]), "+f"(d[102]), "+f"(d[103]),
          "+f"(d[104]), "+f"(d[105]), "+f"(d[106]), "+f"(d[107]), "+f"(d[108]), "+f"(d[109]), "+f"(d[110]), "+f"(d[111]),
          "+f"(d[112]), "+f"(d[113]), "+f"(d[114]), "+f"(d[115]), "+f"(d[116]), "+f"(d[117]), "+f"(d[118]), "+f"(d[119]),
          "+f"(d[120]), "+f"(d[121]), "+f"(d[122]), "+f"(d[123]), "+f"(d[124]), "+f"(d[125]), "+f"(d[126]), "+f"(d[127])
        : "l"(da), "l"(db), "r"(scale_d));
}

__device__ __forceinline__ void wgmma_m64n128k16(float (&d)[64], uint64_t da, uint64_t db, int scale_d) {
    asm volatile(
        "{\n.reg .pred p;\nsetp.ne.b32 p, %66, 0;\n"
        "wgmma.mma_async.sync.aligned.m64n128k16.f32.bf16.bf16 "
        "{%0,%1,%2,%3,%4,%5,%6,%7,%8,%9,%10,%11,%12,%13,%14,%15,"
        "%16,%17,%18,%19,%20,%21,%22,%23,%24,%25,%26,%27,%28,%29,%30,%31,"
        "%32,%33,%34,%35,%36,%37,%38,%39,%40,%41,%42,%43,%44,%45,%46,%47,"
        "%48,%49,%50,%51,%52,%53,%54,%55,%56,%57,%58,%59,%60,%61,%62,%63},"
        " %64, %65, p, 1, 1, 0, 1;\n}\n"
        : "+f"(d[0]), "+f"(d[1]), "+f"(d[2]), "+f"(d[3]), "+f"(d[4]), "+f"(d[5]), "+f"(d[6]), "+f"(d[7]),
          "+f"(d[8]), "+f"(d[9]), "+f"(d[10]), "+f"(d[11]), "+f"(d[12]), "+f"(d[13]), "+f"(d[14]), "+f"(d[15]),
          "+f"(d[16]), "+f"(d[17]), "+f"(d[18]), "+f"(d[19]), "+f"(d[20]), "+f"(d[21]), "+f"(d[22]), "+f"(d[23]),
          "+f"(d[24]), "+f"(d[25]), "+f"(d[26]), "+f"(d[27]), "+f"(d[28]), "+f"(d[29]), "+f"(d[30]), "+f"(d[31]),
          "+f"(d[32]), "+f"(d[33]), "+f"(d[34]), "+f"(d[35]), "+f"(d[36]), "+f"(d[37]), "+f"(d[38]), "+f"(d[39]),
          "+f"(d[40]), "+f"(d[41]), "+f"(d[42]), "+f"(d[43]), "+f"(d[44]), "+f"(d[45]), "+f"(d[46]), "+f"(d[47]),
          "+f"(d[48]), "+f"(d[49]), "+f"(d[50]), "+f"(d[51]), "+f"(d[52]), "+f"(d[53]), "+f"(d[54]), "+f"(d[55]),
          "+f"(d[56]), "+f"(d[57]), "+f"(d[58]), "+f"(d[59]), "+f"(d[60]), "+f"(d[61]), "+f"(d[62]), "+f"(d[63])
        : "l"(da), "l"(db), "r"(scale_d));
}
template <int BN> struct WgmmaOp;
template <> struct WgmmaOp<256> {
    static __device__ __forceinline__ void run(float (&d)[128], uint64_t a, uint64_t b, int sc) { wgmma_m64n256k16(d, a, b, sc); }
};
template <> struct WgmmaOp<128> {
    static __device__ __forceinline__ void run(float (&d)[64], uint64_t a, uint64_t b, int sc) { wgmma_m64n128k16(d, a, b, sc); }
};

struct StoreRec {
    uint64_t dst;
    uint64_t flag;
    int kind;
    int pad;
};
struct EpiCtx { uint32_t buf, rec, st_full, st_empty; uint32_t it; int lane; };
template <int N>
__device__ __forceinline__ void epi_hand_over(const float (&acc)[N], EpiCtx& e, uint64_t dst, uint64_t flag, int kind) {
    mbar_wait(e.st_empty, (e.it & 1) ^ 1);
    const int mi = e.lane >> 3, row = (mi & 1) * 8 + (e.lane & 7);
    #pragma unroll
    for (int j = 0; j < N / 4; j += 2) {
        const int chunk = (j & 7) + (mi >> 1);
        stsm_x4(e.buf + (j >> 3) * 2048 + row * 128 + ((chunk ^ (row & 7)) << 4),
                pack_bf16(acc[4 * j], acc[4 * j + 1]), pack_bf16(acc[4 * j + 2], acc[4 * j + 3]),
                pack_bf16(acc[4 * j + 4], acc[4 * j + 5]), pack_bf16(acc[4 * j + 6], acc[4 * j + 7]));
    }
    if (e.lane == 0) {
        asm volatile("st.shared.v2.b64 [%0], {%1, %2};" ::"r"(e.rec), "l"(dst), "l"(flag) : "memory");
        asm volatile("st.shared.b32 [%0], %1;" ::"r"(e.rec + 16), "r"(kind) : "memory");
    }
    asm volatile("fence.proxy.async.shared::cta;" ::: "memory");
    __syncwarp();
    if (e.lane == 0) mbar_arrive(e.st_full);
    e.it++;
}
__device__ __forceinline__ void epi_exit(EpiCtx& e) {
    mbar_wait(e.st_empty, (e.it & 1) ^ 1);
    if (e.lane == 0) {
        asm volatile("st.shared.b32 [%0], %1;" ::"r"(e.rec + 16), "r"(-1) : "memory");
        mbar_arrive(e.st_full);
    }
}
template <int BN>
__device__ __forceinline__ void gemm_mainloop(float (&acc)[BN / 2], int k_blocks, uint32_t sbase, uint32_t bar_base, int cw,
                                              bool elected, int& stage, uint32_t& phase) {
    using C = GemmCfg<BN>;
    auto release = [&](int st) { mbar_arrive(bar_base + 8 * (C::STAGES + st)); };
    int prev_stage = -1;
    for (int kb = 0; kb < k_blocks; kb++) {
        mbar_wait(bar_base + 8 * stage, phase);
        const uint32_t sa = sbase + stage * C::STAGE + cw * (64 * 128);
        const uint32_t sb = sbase + stage * C::STAGE + A_STAGE;
        asm volatile("wgmma.fence.sync.aligned;" ::: "memory");
        #pragma unroll
        for (int kk = 0; kk < BK / 16; kk++)
            WgmmaOp<BN>::run(acc, make_desc(sa + kk * 32, 16, 1024), make_desc(sb + kk * 2048, 8192, 1024), (kb | kk) != 0);
        asm volatile("wgmma.commit_group.sync.aligned;" ::: "memory");
        asm volatile("wgmma.wait_group.sync.aligned 1;" ::: "memory");
        if (prev_stage >= 0 && elected) release(prev_stage);
        prev_stage = stage;
        if (++stage == C::STAGES) { stage = 0; phase ^= 1; }
    }
    asm volatile("wgmma.wait_group.sync.aligned 0;" ::: "memory");
    if (elected) release(prev_stage);
}
template <int BN>
__device__ __forceinline__ void store_warp(uint32_t epi_base, uint32_t rec_base, uint32_t st_full, uint32_t st_empty, int lane,
                                           const uint8_t* tmaps, int tstride) {
    for (uint32_t it = 0;; it++) {
        mbar_wait(st_full, it & 1);
        uint64_t dst = 0, flag = 0;
        int kind = -1;
        if (lane < 8) {
            const uint32_t rec = rec_base + lane * 32;
            asm volatile("ld.volatile.shared.v2.b64 {%0, %1}, [%2];" : "=l"(dst), "=l"(flag) : "r"(rec) : "memory");
            kind = (int)lds32_volatile(rec + 16);
        }
        if (__shfl_sync(~0u, kind, 0) < 0) break;
        if (lane < 8) {
            const uint32_t buf = epi_base + lane * GemmCfg<BN>::EPI_WARP;
            #pragma unroll
            for (int q = 0; q < BN / 64; q++) {
                tma_store_2d(reinterpret_cast<const CUtensorMap*>(tmaps + (kind - 1) * tstride), buf + q * 2048,
                                  (int)(uint32_t)dst + q * 64, (int)(dst >> 32));
            }
            bulk_commit();
            bulk_wait_read_all();
            mbar_arrive(st_empty);
            if (flag) {
                bulk_wait_all();
                signal_flag(reinterpret_cast<uint32_t*>(flag));
            }
        }
        __syncwarp();
    }
    if (lane < 8) bulk_wait_all();
}

#define SCHED_AHEAD 4
template <int BN>
__global__ void __launch_bounds__(384, 1) side_gemm_kernel(const __grid_constant__ SideParams p) {
    using C = GemmCfg<BN>;
    extern __shared__ uint8_t smem_raw[];
    const uint32_t sbase = (smem_u32(smem_raw) + 1023) & ~1023u;
    const uint32_t epi_base = sbase + C::STAGES * C::STAGE;
    const uint32_t bar_base = epi_base + 8 * C::EPI_WARP;
    const uint32_t tfull = bar_base + 16 * C::STAGES, tempty = tfull + 16, tslot = tempty + 16, twant = tslot + 8;
    const uint32_t st_full = bar_base + 192, st_empty = st_full + 8, rec_base = bar_base + 256;
    const int tid = threadIdx.x, wg = tid >> 7;
    if (tid == 0) {
        for (int s = 0; s < C::STAGES; s++) { mbar_init(bar_base + 8 * s, 1); mbar_init(bar_base + 8 * (C::STAGES + s), 2); }
        for (int s = 0; s < 2; s++) { mbar_init(tfull + 8 * s, 1); mbar_init(tempty + 8 * s, 3); }
        mbar_init(twant, 1);
        mbar_init(st_full, 8);
        mbar_init(st_empty, 8);
        asm volatile("fence.mbarrier_init.release.cluster;" ::: "memory");
        pdl_launch_dependents();
    }
    __syncthreads();
    KENTER(BN == 256 ? 2 : 4);

    if (wg == 0) {
        asm volatile("setmaxnreg.dec.sync.aligned.u32 40;");
        if (tid == 0) {
            int stage = 0; uint32_t phase = 1;
            for (uint32_t it = 0;; it++) {
                mbar_wait(tfull + 8 * (it & 1), (it >> 1) & 1);
                const int code = (int)lds32_volatile(tslot + 4 * (it & 1));
                mbar_arrive(tempty + 8 * (it & 1));
                if (code < 0) break;
                const SideProb& q = p.prob[code >> 16];
                const int mt = (code >> 8) & 255, nt = code & 255;
                asm volatile("fence.proxy.async.global;" ::: "memory");
                const int kb0 = nt / q.n_split * q.k_blocks, nkb = nt + q.n_split < q.n_tiles ? q.k_blocks : q.k_total - kb0;
                for (int kb = 0; kb < nkb; kb++) {
                    if (kb == nkb - SCHED_AHEAD) mbar_arrive(twant);
                    mbar_wait(bar_base + 8 * (C::STAGES + stage), phase);
                    const uint32_t sa = sbase + stage * C::STAGE, fb = bar_base + 8 * stage;
                    mbar_arrive_expect_tx(fb, C::STAGE);
                    const int k0 = (kb0 + kb) * BK;
                    tma_load_2d(sa, &q.tmA, k0, mt * BM, fb);
                    tma_load_3d(sa + A_STAGE, &q.tmB, 0, k0, nt % q.n_split * (BN / 64), fb);
                    if (++stage == C::STAGES) { stage = 0; phase ^= 1; }
                }
            }
        } else if (tid >= 64 && tid < 96) {
            const int lane = tid & 31;
            const bool spare = p.spare_seg < 3 && next_to_rec(p.flags);
            uint32_t ntl[2], tgt[2], prb[2];
            const uint32_t* dp[2];
            #pragma unroll
            for (int u = 0; u < 2; u++) {
                const int g = u * 2 + (lane >> 4), mt = lane & 15;
                const bool on = g < p.nseg && mt >= p.seg[g < p.nseg ? g : 0].m0 && mt < p.seg[g < p.nseg ? g : 0].m1;
                prb[u] = p.seg[on ? g : 0].prob;
                const SideProb& q = p.prob[prb[u]];
                ntl[u] = on && !(g >= p.spare_seg && spare) ? q.n_tiles : 0;
                tgt[u] = on && q.dep ? q.dep_target : 0;
                dp[u] = tgt[u] ? q.dep + (mt + 1) * q.dep_n - 1 : p.queue;
            }
            for (uint32_t it = 0;; it++) {
                if (it > 0) mbar_wait_sleep(twant, (it - 1) & 1);
                int code = -1;
                for (uint32_t tries = 0; code < 0; tries++) {
                    const uint32_t c0 = ld_relaxed_b32(p.queue + lane), c1 = ld_relaxed_b32(p.queue + 32 + (lane & 15));
                    const uint32_t d0 = ld_relaxed_b32(dp[0]), d1 = ld_relaxed_b32(dp[1]);
                    const uint64_t left = __ballot_sync(~0u, c0 < ntl[0]) | (uint64_t)__ballot_sync(~0u, c1 < ntl[1]) << 32;
                    uint64_t ready = left & (__ballot_sync(~0u, d0 >= tgt[0]) | (uint64_t)__ballot_sync(~0u, d1 >= tgt[1]) << 32);
                    if (!left) break;
                    if (!ready && (BN == 128 || (left >> (((__ffsll(left) - 1) & ~15) + 16)) == 0)) ready = left;
                    if (!ready) __nanosleep(200);
                    while (ready) {
                        const int e = __ffsll(ready) - 1;
                        const uint32_t n = __shfl_sync(~0u, e < 32 ? ntl[0] : ntl[1], e & 31), pr = __shfl_sync(~0u, e < 32 ? prb[0] : prb[1], e & 31);
                        uint32_t idx = 0;
                        if (lane == 0) idx = atomicAdd(p.queue + e, 1u);
                        idx = __shfl_sync(~0u, idx, 0);
                        if (idx < n) { code = (pr << 16) | ((e & 15) << 8) | idx; break; }
                        for (uint32_t k = idx / n; k > 0; k--) ready &= ready - 1;
                    }
                    if (tries > SPIN_LIMIT) __trap();
                }
                if (code >= 0) {
                    const SideProb& q = p.prob[code >> 16];
                    if (q.dep && lane < q.dep_n) wait_flag(q.dep + ((code >> 8) & 255) * q.dep_n + lane, q.dep_target);
                    __syncwarp();
                }
                if (lane == 0) {
                    mbar_wait(tempty + 8 * (it & 1), ((it >> 1) & 1) ^ 1);
                    asm volatile("st.shared.b32 [%0], %1;" ::"r"(tslot + 4 * (it & 1)), "r"(code) : "memory");
                    mbar_arrive(tfull + 8 * (it & 1));
                }
                __syncwarp();
                if (code < 0) break;
            }
        } else if (tid >= 32 && tid < 64) {
            store_warp<BN>(epi_base, rec_base, st_full, st_empty, tid & 31, reinterpret_cast<const uint8_t*>(&p.prob[0].tmC),
                           (int)sizeof(SideProb));
        }
    } else {
        asm volatile("setmaxnreg.inc.sync.aligned.u32 232;");
        const int cw = wg - 1, lane = tid & 31, wi = (tid >> 5) & 3;
        const bool elected = (tid & 127) == 0;
        int stage = 0; uint32_t phase = 0;
        float acc[BN / 2];
        EpiCtx ectx = {epi_base + (cw * 4 + wi) * C::EPI_WARP, rec_base + (cw * 4 + wi) * 32, st_full, st_empty, 0, lane};
        for (uint32_t it = 0;; it++) {
            mbar_wait(tfull + 8 * (it & 1), (it >> 1) & 1);
            const int code = (int)lds32_volatile(tslot + 4 * (it & 1));
            named_bar_sync(1 + cw, 128);
            if (elected) mbar_arrive(tempty + 8 * (it & 1));
            if (code < 0) break;
            const SideProb& q = p.prob[code >> 16];
            const int mt = (code >> 8) & 255, nt = code & 255;
            gemm_mainloop<BN>(acc, nt + q.n_split < q.n_tiles ? q.k_blocks : q.k_total - nt / q.n_split * q.k_blocks, sbase, bar_base, cw, elected, stage, phase);
            const int row0 = mt * BM + cw * 64 + wi * 16, ntc = nt % q.n_split;
            if (BN == 128 && q.part) {
                const int idx = (mt & 3) * q.n_split + ntc, item = nt / q.n_split, nprev = q.n_tiles / q.n_split - 1;
                float4* part = reinterpret_cast<float4*>(q.part) + (size_t)idx * 2 * (BM * BN / 4) + (tid - 128);
                if (mt == 14 && elected) KMARK(21);
                if (item < nprev) {
                    #pragma unroll
                    for (int j = 0; j < BN / 8; j++)
                        __stcg(part + item * (BM * BN / 4) + j * 256, make_float4(acc[4 * j], acc[4 * j + 1], acc[4 * j + 2], acc[4 * j + 3]));
                    __syncwarp();
                    if (lane == 0) signal_flag(q.part_flag + idx);
                    continue;
                }
                if (lane == 0) wait_flag(q.part_flag + idx, 8 * nprev);
                __syncwarp();
                if (mt == 14 && elected) KMARK(22);
                for (int u = 0; u < nprev; u++) {
                    #pragma unroll
                    for (int j = 0; j < BN / 8; j++) {
                        const float4 v = __ldcg(part + u * (BM * BN / 4) + j * 256);
                        acc[4 * j] += v.x; acc[4 * j + 1] += v.y; acc[4 * j + 2] += v.z; acc[4 * j + 3] += v.w;
                    }
                }
            }
            if (BN == 128 && mt == 14 && elected) KMARK(23);
            epi_hand_over(acc, ectx, ((uint64_t)row0 << 32) | (uint32_t)(q.c_col0 + ntc * BN), q.sig ? (uint64_t)(q.sig + mt) : 0, 1 + (code >> 16));
        }
        epi_exit(ectx);
        if (elected) KEXIT(BN == 256 ? 2 : 4);
    }
}

constexpr int FIN_SPLIT = 8, FIN_KB = HD / BK / FIN_SPLIT;
constexpr int FIN_A1 = FIN_KB * 16384;
constexpr int FIN_A0 = FIN_A1 + FIN_KB * 8192;
constexpr int FIN_BAR = FIN_A0 + 4 * 8192, FIN_SMEM = FIN_BAR + 256;
enum { FB_B = 0, FB_A1 = 64, FB_A0 = 128, FB_E0 = 160, FB_RDY = 192, FB_RED = 208 };
struct FinalParams {
    CUtensorMap tmA, tmB;
    __nv_bfloat16* out;
    const uint32_t* dep;
    uint32_t dep_target;
    int mt;
};
__global__ void __launch_bounds__(384, 1) final_gemm_kernel(const __grid_constant__ FinalParams p) {
    extern __shared__ __align__(1024) uint8_t smem_raw[];
    const uint32_t sbase = smem_u32(smem_raw), bar = sbase + FIN_BAR;
    const int tid = threadIdx.x, wg = tid >> 7;
    const int rank = blockIdx.x % FIN_SPLIT, nt = blockIdx.x / FIN_SPLIT;
    KENTER(5);
    if (tid == 0) {
        for (int s = 0; s < FIN_KB; s++) { mbar_init(bar + FB_B + 8 * s, 1); mbar_init(bar + FB_A1 + 8 * s, 1); }
        for (int s = 0; s < 4; s++) { mbar_init(bar + FB_A0 + 8 * s, 1); mbar_init(bar + FB_E0 + 8 * s, 1); }
        for (int h = 0; h < 2; h++) { mbar_init(bar + FB_RDY + 8 * h, FIN_SPLIT); mbar_init(bar + FB_RED + 8 * h, 1); }
        asm volatile("fence.mbarrier_init.release.cluster;" ::: "memory");
        for (int h = 0; h < 2; h++) mbar_arrive_expect_tx(bar + FB_RED + 8 * h, (FIN_SPLIT - 1) * 4096);
        pdl_launch_dependents();
    }
    __syncthreads();
    asm volatile("barrier.cluster.arrive.relaxed.aligned;" ::: "memory");
    if (wg == 0) {
        auto need = [&](int i) {
            uint32_t n = 0;
            while (ld_acquire_b32(p.dep + i) < p.dep_target) { if (++n > SPIN_LIMIT) __trap(); }
            asm volatile("fence.proxy.async.global;" ::: "memory");
        };
        auto a_load = [&](uint32_t dst, int kb, int seg, uint32_t mb) { tma_load_2d(dst, &p.tmA, (rank * FIN_KB + kb) * BK, p.mt * BM + seg * SEG, mb); };
        if (tid == 0) {
            auto b_load = [&](int kb) {
                mbar_arrive_expect_tx(bar + FB_B + 8 * kb, 16384);
                tma_load_3d(sbase + kb * 16384, &p.tmB, 0, (rank * FIN_KB + kb) * BK, nt * 2, bar + FB_B + 8 * kb);
            };
            const uint32_t f0 = ld_relaxed_b32(p.dep);
            b_load(0);
            need(1);
            if (f0 < p.dep_target) need(0);
            for (int kb = 0; kb < FIN_KB; kb++) {
                if (kb >= 4) mbar_wait(bar + FB_E0 + 8 * (kb & 3), 0);
                mbar_arrive_expect_tx(bar + FB_A0 + 8 * (kb & 3), 8192);
                for (int u = 0; u < 2; u++) a_load(sbase + FIN_A0 + (kb & 3) * 8192 + u * 4096, kb, u, bar + FB_A0 + 8 * (kb & 3));
                if (kb < 3) b_load(kb + 1);
                if (kb == 3) { b_load(4); b_load(5); }
                if (kb == 4 || kb == 5) b_load(kb + 2);
            }
        } else if (tid == 96) {
            need(3);
            for (int kb = 1; kb < FIN_KB; kb += 2) a_load(sbase + FIN_A1 + kb * 8192 + 4096, kb, 3, bar + FB_A1 + 8 * kb);
        } else if (tid == 64) {
            mbar_wait(bar + FB_B + 8 * 3, 0);
            need(2);
            for (int kb = 0; kb < FIN_KB; kb++) {
                mbar_arrive_expect_tx(bar + FB_A1 + 8 * kb, 8192);
                a_load(sbase + FIN_A1 + kb * 8192, kb, 2, bar + FB_A1 + 8 * kb);
            }
            need(3);
            KMARK(15);
            for (int kb = 0; kb < FIN_KB; kb += 2) a_load(sbase + FIN_A1 + kb * 8192 + 4096, kb, 3, bar + FB_A1 + 8 * kb);
        }
        __syncwarp();
        asm volatile("barrier.cluster.wait.aligned;" ::: "memory");
    } else {
        const int h = wg - 1, lane = tid & 31, wi = (tid >> 5) & 3, t128 = tid & 127;
        asm volatile("barrier.cluster.wait.aligned;" ::: "memory");
        float acc[64];
        for (int kb = 0; kb < FIN_KB; kb++) {
            mbar_wait(bar + FB_B + 8 * kb, 0);
            if (h == 0) mbar_wait(bar + FB_A0 + 8 * (kb & 3), kb >> 2); else mbar_wait(bar + FB_A1 + 8 * kb, 0);
            const uint32_t sa = sbase + (h == 0 ? FIN_A0 + (kb & 3) * 8192 : FIN_A1 + kb * 8192), sb = sbase + kb * 16384;
            asm volatile("wgmma.fence.sync.aligned;" ::: "memory");
            #pragma unroll
            for (int kk = 0; kk < BK / 16; kk++)
                wgmma_m64n128k16(acc, make_desc(sa + kk * 32, 16, 1024), make_desc(sb + kk * 2048, 8192, 1024), (kb | kk) != 0);
            asm volatile("wgmma.commit_group.sync.aligned;" ::: "memory");
            asm volatile("wgmma.wait_group.sync.aligned 1;" ::: "memory");
            if (h == 0 && kb >= 1 && kb <= 4 && t128 == 0) mbar_arrive(bar + FB_E0 + 8 * (kb - 1));
        }
        asm volatile("wgmma.wait_group.sync.aligned 0;" ::: "memory");
        const uint32_t red = sbase + FIN_A0;
        auto ready = [&](int i) {
            named_bar_sync(1, 128);
            if (t128 < FIN_SPLIT)
                asm volatile("mbarrier.arrive.relaxed.cluster.shared::cluster.b64 _, [%0];" ::"r"(mapa(bar + FB_RDY + 8 * i, t128)) : "memory");
        };
        if (tid == 256) KMARK(16);
        if (tid == 128) KMARK(19);
        if (h == 0) ready(0);
        mbar_wait(bar + FB_RDY + 8 * h, 0);
        if (tid == 256) KMARK(17);
        #pragma unroll
        for (int q = 0; q < FIN_SPLIT; q++) {
            if (q != rank) {
                const uint32_t dst = mapa(red + (rank - (rank > q ? 1 : 0)) * 4096 + t128 * 16, q), rb = mapa(bar + FB_RED + 8 * h, q);
                #pragma unroll
                for (int j = 0; j < 2; j++)
                    asm volatile("st.async.weak.shared::cluster.mbarrier::complete_tx::bytes.v4.f32 [%0], {%1,%2,%3,%4}, [%5];"
                                 ::"r"(dst + j * 2048), "f"(acc[8 * q + 4 * j]), "f"(acc[8 * q + 4 * j + 1]),
                                   "f"(acc[8 * q + 4 * j + 2]), "f"(acc[8 * q + 4 * j + 3]), "r"(rb) : "memory");
            }
        }
        float o[8];
        #pragma unroll
        for (int q = 0; q < FIN_SPLIT; q++)
            if (q == rank) {
                #pragma unroll
                for (int e = 0; e < 8; e++) o[e] = acc[8 * q + e];
            }
        mbar_wait(bar + FB_RED + 8 * h, 0);
        if (tid == 256) KMARK(18);
        if (tid == 128) KMARK(20);
        #pragma unroll
        for (int sl = 0; sl < FIN_SPLIT - 1; sl++) {
            #pragma unroll
            for (int j = 0; j < 2; j++) {
                const uint4 v = lds128(red + sl * 4096 + j * 2048 + t128 * 16);
                o[4 * j] += __uint_as_float(v.x); o[4 * j + 1] += __uint_as_float(v.y);
                o[4 * j + 2] += __uint_as_float(v.z); o[4 * j + 3] += __uint_as_float(v.w);
            }
        }
        if (h == 0) ready(1);
        __nv_bfloat16* dst = p.out + (size_t)(p.mt * BM + h * 64 + wi * 16 + (lane >> 2)) * (2 * DM) + nt * 128 + rank * 16 + (lane & 3) * 2;
        #pragma unroll
        for (int j = 0; j < 2; j++) {
            *reinterpret_cast<uint32_t*>(dst + j * 8) = pack_bf16(o[4 * j], o[4 * j + 1]);
            *reinterpret_cast<uint32_t*>(dst + (size_t)8 * (2 * DM) + j * 8) = pack_bf16(o[4 * j + 2], o[4 * j + 3]);
        }
        if (t128 == 0) KEXIT(5);
    }
}

#define POLL_DELAY 2
#define FETCH_DELAY 360
#define AT_PF 7
#define AT_FIRST 4
#define WO_PF 11
#define WO_PFA 4
#define WO_PFB_DELAY 60
#define V_EARLY 6
constexpr int REC_THREADS = 256;
constexpr uint32_t POLL_LIMIT = 1u << 16;
constexpr int NREG = 24;
__host__ __device__ constexpr int reg_idx(int j) { return ((j & 3) - 1) * 8 + (j >> 2); }
constexpr int SM_WQ = 0;
constexpr int SM_WO = 65536;
constexpr int SM_X = SM_WO + 11 * 8192;
constexpr int SM_PARK0 = SM_X, SM_PARK1 = SM_X + 8192;
constexpr int SM_MEM = SM_X + 4 * 4096;
constexpr int SM_RED = SM_X + 8 * 4096;
constexpr int SM_V = SM_X + 12 * 4096;
constexpr int SM_K = SM_X + 14 * 4096;
constexpr int SM_QS = SM_X + 15 * 4096;
constexpr int SM_QK = SM_X + 65536;
constexpr int SM_SP = SM_QK + 2048;
constexpr int SM_VM = SM_SP + 2560;
constexpr int SM_O = SM_VM + 2048;
constexpr int SM_SUM = SM_O + 2048;
constexpr int SM_TBL = SM_SUM + 128;
constexpr int SM_BAR = SM_TBL + 512;
constexpr int SM_STAMP = SM_BAR + 192;
constexpr int REC_SMEM = SM_STAMP;
static_assert(REC_SMEM <= 232448, "shared memory");
enum { BAR_V = 0, BAR_X = 8, BAR_P0 = 16, BAR_WQ = 40, BAR_WO = 48, BAR_XG = 56, BAR_F0 = 88, BAR_F3 = 96, BAR_VF = 104,
       BAR_M = 112, BAR_GO = 144, BAR_PK = 152, BAR_VM = 160, BAR_SELF = 168, BAR_TPUB = 176, BAR_MIN = 176 };

template <int V> struct IntC { static constexpr int value = V; };
template <int I, int N, typename F> __device__ __forceinline__ void sfor(F&& f) {
    if constexpr (I < N) { f(IntC<I>{}); sfor<I + 1, N>(f); }
}

struct RecParams {
    CUtensorMap tmW[3];
    CUtensorMap tmWo;
    CUtensorMap tmX;
    const __nv_bfloat16* mem0;
    __nv_bfloat16* qkv_tok;
    __nv_bfloat16* kv_mem;
    uint8_t* xchg;
    uint32_t* flags;
    uint32_t one[2];
    uint32_t* arrivals;
};

__device__ __forceinline__ void mma_a(float* d, const uint32_t* a, uint32_t b0, uint32_t b1) {
    mma16816(d, a[0], a[1], a[2], a[3], b0, b1);
}
__device__ __forceinline__ void ldsm4(uint32_t addr, uint32_t* r) { ldsm_x4(addr, r[0], r[1], r[2], r[3]); }
__device__ __forceinline__ void ldsm4t(uint32_t addr, uint32_t* r) { ldsm_x4_t(addr, r[0], r[1], r[2], r[3]); }
template <int OFF> __device__ __forceinline__ void repoll_v2(uint2& v, const uint8_t* p) {
    asm volatile("{\n.reg .pred q;\nsetp.eq.u32 q, %1, 0xFFFFFFFF;\n@q ld.relaxed.gpu.global.v2.b32 {%0,%1}, [%2+%3];\n}"
                 : "+r"(v.x), "+r"(v.y) : "l"(p), "n"(OFF) : "memory");
}
__device__ __forceinline__ uint32_t max3(uint32_t a, uint32_t b, uint32_t c) { return max(max(a, b), c); }
__device__ __forceinline__ uint32_t pub_slot(int s) { return (s & 1) * XCHG_SLOT + ((s >> 1) & 1) * PUB_BYTES; }

__device__ __forceinline__ uint8_t* xaddr(uint32_t lo, uint32_t hi) {
    uint64_t a;
    asm("mov.b64 %0, {%1, %2};" : "=l"(a) : "r"(lo), "r"(hi));
    return reinterpret_cast<uint8_t*>(a);
}
template <int N> __device__ __forceinline__ uint32_t delay_zero(uint32_t a) {
    uint32_t x = a;
    #pragma unroll
    for (int i = 0; i < N; i++) x = lds32_volatile(x);
    return x - a;
}
__device__ __forceinline__ uint32_t fresh(uint32_t x) { asm volatile("" : "+r"(x)); return x; }

template <int NT> __device__ __forceinline__ uint32_t wo_addr(uint32_t ao, uint32_t a3, int n) {
    return (n % NT == 2 ? a3 : ao + (n % NT) * 32768) + (n / NT) * 1024;
}
template <int NT, int PF>
__device__ __forceinline__ void wo_phase(uint32_t (&st)[8 * NT][4], uint32_t ao, uint32_t a3, uint32_t l16, uint32_t tbl, uint32_t sums,
                                         uint32_t slot, uint32_t xhi, uint32_t third, uint32_t xbar, uint32_t xpar, bool& x_ok) {
    constexpr int AHEAD = PF > 0 ? PF - NT : 10;
    uint32_t of[4][4];
    uint2 sm;
    uint4 t;
    ldsm4t(l16 + SM_O, of[0]);
    #pragma unroll
    for (int n = PF; n < AHEAD; n++) {
        ldsm4t(wo_addr<NT>(ao, a3, n), st[n]);
        if (n == 2 * NT - 1) ldsm4t(l16 + SM_O + 512, of[1]);
    }
    if (PF >= 2 * NT) ldsm4t(l16 + SM_O + 512, of[1]);
    float acc[NT][4];
    #pragma unroll
    for (int i = 0; i < NT; i++) { acc[i][0] = acc[i][1] = acc[i][2] = acc[i][3] = 0.f; }
    #pragma unroll
    for (int kk = 0; kk < 8; kk++) {
        #pragma unroll
        for (int i = 0; i < NT; i++) {
            const int n = kk * NT + i;
            mma_a(acc[i], st[n], of[kk >> 1][(kk & 1) * 2], of[kk >> 1][(kk & 1) * 2 + 1]);
            if (n + AHEAD >= PF && n + AHEAD < 8 * NT) ldsm4t(wo_addr<NT>(ao, a3, n + AHEAD), st[n + AHEAD]);
        }
        if (kk == 1 || kk == 3) ldsm4t(l16 + SM_O + ((kk >> 1) + 2) * 512, of[(kk >> 1) + 2]);
        if (kk == (NT == 3 ? 5 : 4)) {
            const uint32_t x = fresh(l16);
            sm = lds64(sums + ((x >> 1) & 0x18));
            t = lds128(tbl + ((x >> 3) & 0x30));
            x_ok = mbar_test_wait(xbar, xpar);
        }
    }
    const float i0 = rcp(__uint_as_float(sm.x)), i1 = rcp(__uint_as_float(sm.y));
    const uint32_t d = slot + ((fresh(l16) >> 1) & 0x38);
    const uint32_t pl[3] = {t.x + d, t.y + d, t.z + d};
    #pragma unroll
    for (int i = 0; i < NT; i++)
        asm volatile("{\n.reg .pred p;\nsetp.ne.u32 p, %3, 0;\n@p st.relaxed.gpu.global.v2.b32 [%0], {%1,%2};\n}"
                     ::"l"(xaddr(pl[i], xhi)), "r"(pack_bf16(acc[i][0] * i0, acc[i][1] * i1)), "r"(pack_bf16(acc[i][2] * i0, acc[i][3] * i1)),
                       "r"(i < 2 ? 1u : third) : "memory");
}

constexpr uint32_t SMEM_ORIGIN = 1024;
constexpr uint64_t DESC_BASE = (1ull << 16) | (0x40000040ull << 32);
template <int OFFB, int SCALE_D>
__device__ __forceinline__ void wgmma_n32_rs(float (&d)[16], const uint32_t* a, uint32_t one) {
    asm volatile(
        "{\n.reg .b64 db;\nmad.wide.u32 db, %20, %21, %22;\n"
        "wgmma.mma_async.sync.aligned.m64n32k16.f32.bf16.bf16 {%0,%1,%2,%3,%4,%5,%6,%7,%8,%9,%10,%11,%12,%13,%14,%15}, "
        "{%16,%17,%18,%19}, db, %23, 1, 1, 0;\n}"
        : "+f"(d[0]), "+f"(d[1]), "+f"(d[2]), "+f"(d[3]), "+f"(d[4]), "+f"(d[5]), "+f"(d[6]), "+f"(d[7]),
          "+f"(d[8]), "+f"(d[9]), "+f"(d[10]), "+f"(d[11]), "+f"(d[12]), "+f"(d[13]), "+f"(d[14]), "+f"(d[15])
        : "r"(a[0]), "r"(a[1]), "r"(a[2]), "r"(a[3]), "r"(one), "n"((SMEM_ORIGIN + OFFB) >> 4), "l"(DESC_BASE), "n"(SCALE_D));
}
template <int OFFA, int OFFB, int SCALE_D>
__device__ __forceinline__ void wgmma_n32_ss(float (&d)[16], uint32_t one) {
    asm volatile(
        "{\n.reg .b64 da, db;\nmad.wide.u32 da, %16, %17, %19;\nmad.wide.u32 db, %16, %18, %19;\n"
        "wgmma.mma_async.sync.aligned.m64n32k16.f32.bf16.bf16 {%0,%1,%2,%3,%4,%5,%6,%7,%8,%9,%10,%11,%12,%13,%14,%15}, "
        "da, db, %20, 1, 1, 1, 0;\n}"
        : "+f"(d[0]), "+f"(d[1]), "+f"(d[2]), "+f"(d[3]), "+f"(d[4]), "+f"(d[5]), "+f"(d[6]), "+f"(d[7]),
          "+f"(d[8]), "+f"(d[9]), "+f"(d[10]), "+f"(d[11]), "+f"(d[12]), "+f"(d[13]), "+f"(d[14]), "+f"(d[15])
        : "r"(one), "n"((SMEM_ORIGIN + OFFA) >> 4), "n"((SMEM_ORIGIN + OFFB) >> 4), "l"(DESC_BASE), "n"(SCALE_D));
}
template <int WG, int J0, int J1, int I, bool ACC, bool FENCE = true>
__device__ __forceinline__ void token_mma(float (&ta)[2][16], const uint32_t (&wr)[NREG][2][4], uint32_t one) {
    if (FENCE) asm volatile("wgmma.fence.sync.aligned;" ::: "memory");
    sfor<J0, J1>([&](auto J) {
        constexpr int j = J.value, c = j >> 2, offb = SM_X + WG * 32768 + c * 4096 + (j & 3) * 32, sc = (ACC || j != J0) ? 1 : 0;
        if constexpr ((j & 3) != 0) wgmma_n32_rs<offb, sc>(ta[I], wr[reg_idx(j)][I], one);
        else if constexpr (WG == 0 || (I == 1 && c >= 4)) wgmma_n32_ss<SM_WQ + WG * 32768 + I * 16384 + c * 2048, offb, sc>(ta[I], one);
        constexpr int m = I ? c : c - 4;
        if constexpr (WG == 0 && (j & 3) == 1 && m >= 0)
            wgmma_n32_ss<SM_WQ + 32768 + (1 - I) * 16384 + m * 2048, SM_X + 32768 + m * 4096, 1>(ta[I], one);
    });
    asm volatile("wgmma.commit_group.sync.aligned;" ::: "memory");
}
__device__ __forceinline__ void warp_arrive(uint32_t bar) {
    __syncwarp();
    if (elect_one()) mbar_arrive(bar);
}
__device__ __forceinline__ void remote_arrive(uint32_t bar, uint32_t rank) {
    asm volatile("mbarrier.arrive.relaxed.cluster.shared::cluster.b64 _, [%0];" ::"r"(mapa(bar, rank)) : "memory");
}
__device__ __forceinline__ void x_load(const RecParams& p, uint32_t sb, int sg, int g) {
    tma_load_3d_mc(sb + SM_X + g * 16384, &p.tmX, 0, sg * SEG, g * 4, sb + SM_BAR + BAR_XG + 8 * g, (uint16_t)7);
}

__device__ __forceinline__ void rec_steps(const RecParams& p, const uint32_t (&wr)[NREG][2][4], const uint32_t sb, const int warp,
                                          const int cta, const int head, const int rank) {
    const int wq = warp & 3, wg = warp >> 2;
    const uint32_t bar = sb + SM_BAR;
    const uint32_t xhi = (uint32_t)((uint64_t)p.xchg >> 32);
    const float sl2 = 0.08838834764831845f * 1.4426950408889634f;
    const bool has_unit = warp >= 5 && (warp < 7 || cta < 64);
    const bool qk = rank < 2;
    const uint32_t pa = rank == 2 ? 0 : rank + 1, pb = rank == 0 ? 2 : rank - 1;
    const uint32_t tbl = sb + SM_TBL + warp * 64;
    const bool att = (warp & 6) == 2;
    const int stile = warp < 5 ? warp : warp - 3;

    const uint32_t u_st = uniform(SM_QK - SM_WQ - wg * (32768 - 1024));
    const uint32_t u_xa = uniform(sb + (qk ? SM_SP + rank * 1280 + stile * 256 : SM_VM + warp * 256));
    const uint32_t u_key = uniform(!qk || att || warp == 7 ? 0 : sb + (warp == 4 ? SM_QK + 1024 : SM_K + stile * 1024));
    const uint32_t u_bx = uniform(bar + (qk ? BAR_X : BAR_VM)), u_bra = uniform(mapa(u_bx, pa)), u_brb = uniform(mapa(u_bx, pb));
    const uint32_t u_src = uniform(lds32_volatile(tbl + 44));
    const uint32_t u_kv = uniform(qk && wg == 0 ? ~0u : (((rank >> 1) * NSEG * NH + head) * 8 + (qk ? rank * 4 + wq : warp)) * 64);
    const uint32_t u_free = uniform(mapa(bar + (warp == 5 ? BAR_VF : BAR_F0), warp == 5 ? 2 : 0));
    const uint32_t u_role = uniform((has_unit ? 1 : 0) | (att ? 2 : 0) | (wg == 1 || qk ? 4 : 0) | (!qk && warp == 0 ? 8 : 0) | (rank != 0 && warp == 1 ? 16 : 0) |
                                    (warp == 5 || warp == 6 ? 32 : 0));
    uint32_t l16, aq, ao;
    {
        const int lane = threadIdx.x & 31, mi = lane >> 3, r8 = lane & 7, r16 = (mi >> 1) * 8 + r8;
        l16 = opaque(sb + lane * 16);
        aq = opaque(sb + SM_WQ + wg * 32768 + r16 * 128 + (((wq * 2 + (mi & 1)) ^ r8) << 4));
        ao = opaque(sb + SM_WO + (warp >> 1) * 8192 + r16 * 64 + ((((warp & 1) * 2 + (mi & 1)) ^ ((r8 >> 1) & 3)) << 4));
    }

    uint32_t mphase = 0;
    bool x0_ok = false;
    #pragma unroll 1
    for (int s = 0;; s++) {
        const uint32_t par = s & 1;
        uint32_t at[16][4];
        auto at_early = [](int i) { return i < 2 || ((i & 1) == 1 && (i >> 1) <= AT_PF - 2); };
        auto at_prefetch = [&](bool first) {
            #pragma unroll
            for (int i = 0; i < 16; i++)
                if (at_early(i) && first == ((i & 1) == 1 && (i >> 1) < AT_FIRST)) ldsm4t(aq + (i & 1) * 16384 + (i >> 1) * 2048, at[i]);
        };
        auto tile_stores = [&]() {
            if (warp == 4) {
                asm volatile("fence.proxy.async.shared::cta;" ::: "memory");
                if (elect_one()) {
                    __nv_bfloat16* dst = p.qkv_tok + ((size_t)s * NH + head) * (SEG * DH);
                    constexpr size_t MAT = (size_t)NSEG * NH * SEG * DH;
                    bulk_store(dst + (qk ? rank * (SEG * 64) : 2 * MAT), sb + (qk ? SM_QS : SM_V), 4096);
                    bulk_store(dst + (qk ? MAT + rank * (SEG * 64) : 2 * MAT + SEG * 64), sb + (qk ? SM_K : SM_V + 4096), 4096);
                    bulk_commit();
                }
            }
        };
        if (wg == 0) {
            float ta[2][16];
            if (!x0_ok) mbar_wait_bounded(bar + BAR_XG, par);
            STAMP(6);
            auto park = [&](int i, uint32_t dst) {
                #pragma unroll
                for (int e = 0; e < 16; e++) asm volatile("" : "+f"(ta[i][e]));
                #pragma unroll
                for (int j = 0; j < 4; j++)
                    sts128(l16 + dst + j * 2048 + wq * 512, __float_as_uint(ta[i][4 * j]), __float_as_uint(ta[i][4 * j + 1]),
                           __float_as_uint(ta[i][4 * j + 2]), __float_as_uint(ta[i][4 * j + 3]));
            };
            token_mma<0, 0, 16, 0, false>(ta, wr, 1);
            mbar_wait_bounded(bar + BAR_XG + 8, par);
            mbar_wait_bounded(bar + BAR_XG + 16, par);
            at_prefetch(true);
            token_mma<0, 16, 32, 0, true>(ta, wr, p.one[1]);
            token_mma<0, 0, 16, 1, false, false>(ta, wr, p.one[0]);
            mbar_wait_bounded(bar + BAR_XG + 24, par);
            token_mma<0, 16, 32, 1, true>(ta, wr, 1);
            asm volatile("wgmma.wait_group.sync.aligned 1;" ::: "memory");
            park(0, SM_PARK0);
            warp_arrive(bar + BAR_GO);
            asm volatile("wgmma.wait_group.sync.aligned 0;" ::: "memory");
            park(1, SM_PARK1);
            warp_arrive(bar + BAR_PK);
            const uint8_t* src = xaddr(u_src + pub_slot(s), xhi);
            auto fetch = [&]() {
                if (elect_one()) {
                    mbar_arrive_expect_tx(bar + BAR_M + 8 * wq, 4096);
                    bulk_load(sb + SM_MEM + wq * 4096, src, 4096, bar + BAR_M + 8 * wq);
                }
            };
            named_bar_sync(7, REC_THREADS - 32);
            {
                const uint4 t = lds128(bar + BAR_TPUB);
                const uint32_t now = clock32();
                spin_until(now + FETCH_DELAY - min(min(min(now - t.y, now - t.z), now - t.w), (uint32_t)FETCH_DELAY));
            }
            fetch();
            STAMP(12);
            if (warp == 0 && elect_one()) {
                if (qk) mbar_arrive_expect_tx(bar + BAR_V, 8192);
                mbar_arrive_expect_tx(bar + BAR_X, qk ? 1280 : 2560);
                mbar_arrive_expect_tx(bar + BAR_VM, qk ? 2048 : 0);
            }
            at_prefetch(false);
            const uint32_t x = fresh(l16) - sb;
            const uint32_t ca = sb + SM_MEM + wq * 4096 + x * 2 + ((x >> 4) & 0x1C);
            #pragma unroll 1
            for (uint32_t n = 0; n < POLL_LIMIT; n++) {
                mbar_wait_bounded(bar + BAR_M + 8 * wq, mphase);
                mphase ^= 1;
                const uint32_t c0 = lds32_volatile(ca), c1 = lds32_volatile(ca + 1024), c2 = lds32_volatile(ca + 2048), c3 = lds32_volatile(ca + 3072);
                if (!__any_sync(~0u, max(max3(c0, c1, c2), c3) == SENT)) break;
                fetch();
            }
            STAMP(0);
            named_bar_sync(0, REC_THREADS);
            if (warp == 0 && rank == 0 && s + 1 < NSEG) {
                mbar_wait_bounded(bar + BAR_F0, par);
                if (elect_one()) x_load(p, sb, s + 1, 0);
            }
            if (u_role & 8) {
                asm volatile("fence.proxy.async.shared::cta;" ::: "memory");
                mbar_wait_bounded(bar + BAR_VF, par);
                if (s < NSEG - 1 && elect_one()) {
                    #pragma unroll
                    for (int r = 0; r < 2; r++)
                        asm volatile("cp.async.bulk.shared::cluster.shared::cta.mbarrier::complete_tx::bytes [%0], [%1], %2, [%3];"
                                     ::"r"(mapa(sb + SM_V, r)), "r"(sb + SM_V), "r"(8192), "r"(mapa(bar + BAR_V, r)) : "memory");
                }
            }
        } else {
            at_prefetch(true);
            if (s > 0) {
                if (u_role & 1) {
                    const uint32_t ln = (fresh(l16) >> 4) & 31;
                    const uint32_t ibl = lds32_volatile(tbl + 12) + (par ^ 1) * XCHG_SLOT + ln * 8;
                    const uint32_t publ = lds32_volatile(tbl + 28) + pub_slot(s) + (ln & 16) * 256 + (ln & 8) * 16 + (ln & 7) * 4;
                    const bool odd = ln & 8;
                    const uint8_t* ib = xaddr(ibl + delay_zero<POLL_DELAY>(bar + BAR_SELF), xhi);
                    STAMP(8);
                    uint2 v[8];
                    #pragma unroll
                    for (int i = 0; i < 8; i++) v[i] = make_uint2(SENT, SENT);
                    #pragma unroll 1
                    for (uint32_t n = 0; n < POLL_LIMIT; n++) {
                        sfor<0, 8>([&](auto I) { repoll_v2<I.value * 256>(v[I.value], ib); });
                        const uint32_t mx = max(max3(v[0].y, v[1].y, v[2].y), max3(max3(v[3].y, v[4].y, v[5].y), v[6].y, v[7].y));
                        if (!__any_sync(~0u, mx == SENT)) break;
                    }
                    STAMP(9);
                    const float a0 = ((bf16_lo(v[0].x) + bf16_lo(v[1].x)) + (bf16_lo(v[2].x) + bf16_lo(v[3].x))) +
                                     ((bf16_lo(v[4].x) + bf16_lo(v[5].x)) + (bf16_lo(v[6].x) + bf16_lo(v[7].x)));
                    const float a1 = ((bf16_hi(v[0].x) + bf16_hi(v[1].x)) + (bf16_hi(v[2].x) + bf16_hi(v[3].x))) +
                                     ((bf16_hi(v[4].x) + bf16_hi(v[5].x)) + (bf16_hi(v[6].x) + bf16_hi(v[7].x)));
                    const float a2 = ((bf16_lo(v[0].y) + bf16_lo(v[1].y)) + (bf16_lo(v[2].y) + bf16_lo(v[3].y))) +
                                     ((bf16_lo(v[4].y) + bf16_lo(v[5].y)) + (bf16_lo(v[6].y) + bf16_lo(v[7].y)));
                    const float a3 = ((bf16_hi(v[0].y) + bf16_hi(v[1].y)) + (bf16_hi(v[2].y) + bf16_hi(v[3].y))) +
                                     ((bf16_hi(v[4].y) + bf16_hi(v[5].y)) + (bf16_hi(v[6].y) + bf16_hi(v[7].y)));
                    float k0 = odd ? a2 : a0, k1 = odd ? a3 : a1;
                    k0 += __shfl_xor_sync(~0u, odd ? a0 : a2, 8);
                    k1 += __shfl_xor_sync(~0u, odd ? a1 : a3, 8);
                    k0 += __shfl_xor_sync(~0u, k0, 16);
                    k1 += __shfl_xor_sync(~0u, k1, 16);
                    st_relaxed_b32(xaddr(publ, xhi), pack_bf16(k0, k1));
                    STAMP(11);
                } else if (warp == 4) {
                    bulk_wait_read_all();
                    if (elect_one()) remote_arrive(bar + BAR_F3, 2);
                    if (!qk) {
                        mbar_wait_bounded(bar + BAR_F3, par ^ 1);
                        if (elect_one()) x_load(p, sb, s, 3);
                    }
                    if (elect_one()) {
                        bulk_wait_all();
                        signal_flag(p.flags + F_PROGRESS + s - 1);
                    }
                    __syncwarp();
                    STAMP(10);
                }
            }
            float ta[2][16];
            uint32_t w[8];
            auto unpark = [&](int i, uint32_t src) {
                mbar_wait_bounded(bar + (i ? BAR_GO : BAR_PK), par);
                #pragma unroll
                for (int j = 0; j < 4; j++) {
                    const uint4 v = lds128(l16 + src + j * 2048 + wq * 512);
                    ta[i][4 * j] = __uint_as_float(v.x); ta[i][4 * j + 1] = __uint_as_float(v.y);
                    ta[i][4 * j + 2] = __uint_as_float(v.z); ta[i][4 * j + 3] = __uint_as_float(v.w);
                }
            };
            sts32(bar + BAR_TPUB + 4 * wq, clock32());
            if (warp != 4) named_bar_arrive(7, REC_THREADS - 32);
            unpark(1, SM_PARK0);
            STAMP(6);
            token_mma<1, 0, 16, 1, true>(ta, wr, 1);
            unpark(0, SM_PARK1);
            token_mma<1, 16, 32, 1, true>(ta, wr, 1);
            token_mma<1, 16, 32, 0, true>(ta, wr, 1);
            token_mma<1, 0, 16, 0, true, false>(ta, wr, 1);
            auto put_tile = [&](int m, const uint32_t (&q)[8]) {
                #pragma unroll
                for (int h = 0; h < 2; h++) {
                    if (qk) asm volatile("stmatrix.sync.aligned.m8n8.x4.trans.shared.b16 [%0], {%1,%2,%3,%4};"
                                         ::"r"(aq - (SM_WQ + 32768) + (m ? SM_K : SM_QS) + h * 2048), "r"(q[4 * h]), "r"(q[4 * h + 1]),
                                           "r"(q[4 * h + 2]), "r"(q[4 * h + 3]) : "memory");
                    else sts128(l16 + SM_V + wq * 2048 + m * 1024 + h * 512, q[4 * h], q[4 * h + 1], q[4 * h + 2], q[4 * h + 3]);
                }
            };
            auto pack_tile = [&](int i) {
                #pragma unroll
                for (int e = 0; e < 16; e++) asm volatile("" : "+f"(ta[i][e]));
                #pragma unroll
                for (int j = 0; j < 8; j++) w[j] = pack_bf16(ta[i][2 * j], ta[i][2 * j + 1]);
            };
            asm volatile("wgmma.wait_group.sync.aligned 2;" ::: "memory");
            pack_tile(1);
            at_prefetch(false);
            asm volatile("wgmma.wait_group.sync.aligned 1;" ::: "memory");
            if ((u_role & 32) && elect_one())
                asm volatile("mbarrier.arrive.relaxed.cluster.shared::cluster.b64 _, [%0];" ::"r"(u_free) : "memory");
            put_tile(0, w);
            asm volatile("wgmma.wait_group.sync.aligned 0;" ::: "memory");
            pack_tile(0);
            put_tile(1, w);
            STAMP(0);
            named_bar_sync(0, REC_THREADS);
            if (s == NSEG - 1) tile_stores();
            STAMP(14);
        }
        const uint32_t mb = l16 + SM_MEM + wg * 8192;
        float acc[2][2][4];
        {
            uint32_t b[2][4];
            ldsm4t(mb, b[0]);
            ldsm4t(mb + 512, b[1]);
            #pragma unroll
            for (int i = 0; i < 4; i++)
                if (!at_early(i)) ldsm4t(aq + (i & 1) * 16384 + (i >> 1) * 2048, at[i]);
            STAMPD(1, b[0][0]);
            #pragma unroll
            for (int i = 0; i < 4; i++) { for (int e = 0; e < 4; e++) acc[i >> 1][i & 1][e] = 0.f; }
            #pragma unroll
            for (int u = 0; u < 16; u++) {
                #pragma unroll
                for (int h = 0; h < 2; h++) {
                    const int j = 2 * u + h;
                    #pragma unroll
                    for (int m = 0; m < 2; m++) {
                        if ((j & 3) == 0) mma_a(acc[h][m], at[(j >> 2) * 2 + m], b[u & 1][2 * h], b[u & 1][2 * h + 1]);
                        else mma_a(acc[h][m], wr[reg_idx(j)][m], b[u & 1][2 * h], b[u & 1][2 * h + 1]);
                    }
                }
                if (u + 2 < 16) ldsm4t(mb + (u + 2) * 512, b[u & 1]);
                if (u + 4 < 16 && !at_early(u + 4))
                    ldsm4t(aq + ((u + 4) & 1) * 16384 + ((u + 4) >> 1) * 2048, at[u + 4]);
            }
        }
        sts128(l16 + SM_RED + warp * 512, __float_as_uint(acc[0][1][0] + acc[1][1][0]), __float_as_uint(acc[0][1][1] + acc[1][1][1]),
               __float_as_uint(acc[0][1][2] + acc[1][1][2]), __float_as_uint(acc[0][1][3] + acc[1][1][3]));
        #pragma unroll
        for (int e = 0; e < 4; e++) acc[0][0][e] += acc[1][0][e];
        const uint32_t x16 = fresh(l16);
        const uint32_t sa = fresh((x16 & 0x70) * 8 + ((((x16 >> 3) & 0x30) ^ x16) & 0x70));
        const uint32_t sq = fresh(sa ^ ((((x16 >> 7) ^ (x16 >> 8)) & 1) * 0x30));
        const uint32_t x8 = (x16 & 0x1F0) >> 1;
        const uint32_t xra = fresh(x8 + __byte_perm(u_xa, u_bra, 0x7210)), xrb = fresh(x8 + __byte_perm(u_xa, u_brb, 0x7210));
        STAMP(2);
        named_bar_sync(1 + wq, 64);
        uint32_t p0, p1;
        {
            const uint4 v = lds128(l16 + SM_RED + (warp ^ 4) * 512);
            p0 = pack_bf16(acc[0][0][0] + __uint_as_float(v.x), acc[0][0][1] + __uint_as_float(v.y));
            p1 = pack_bf16(acc[0][0][2] + __uint_as_float(v.z), acc[0][0][3] + __uint_as_float(v.w));
        }
        auto send = [&](uint32_t y0, uint32_t y1) {
            st_async_v2(xra, y0, y1, u_bra);
            st_async_v2(xrb, y0, y1, u_brb);
            sts64(x8 + u_xa, y0, y1);
            warp_arrive(u_bx);
        };
        if (qk) {
            asm volatile("stmatrix.sync.aligned.m8n8.x2.trans.shared.b16 [%0], {%1,%2};" ::"r"(aq + u_st), "r"(p0), "r"(p1) : "memory");
            named_bar_sync(5, REC_THREADS);
            if (u_key != 0) {
                uint32_t qa[2][4], kf[2][4];
                ldsm4(sq + sb + SM_QK, qa[0]);
                ldsm4(sa + u_key, kf[0]);
                ldsm4((sq ^ 64) + sb + SM_QK, qa[1]);
                ldsm4((sa ^ 64) + u_key, kf[1]);
                float se[4] = {0.f, 0.f, 0.f, 0.f}, so[4] = {0.f, 0.f, 0.f, 0.f};
                #pragma unroll
                for (int u = 0; u < 2; u++) {
                    mma_a(se, qa[u], kf[u][0], kf[u][1]);
                    mma_a(so, qa[u], kf[u][2], kf[u][3]);
                }
                send(__float_as_uint(se[0] + so[2]), __float_as_uint(se[1] + so[3]));
            }
        } else {
            send(p0, p1);
        }
        STAMP(3);
        const uint32_t lane = (fresh(l16) >> 4) & 31;
        auto kv_stores = [&]() {
            if (u_kv != ~0u) {
                uint32_t* dst = reinterpret_cast<uint32_t*>(p.kv_mem) + (u_kv + s * (NH * 512) + lane);
                dst[0] = p0;
                dst[32] = p1;
            }
        };
        if (((s + 1) & 62) == 0) {
            if (s == NSEG - 1) { kv_stores(); break; }
            mbar_wait_bounded(bar + BAR_WO, 0);
            pdl_launch_dependents();
            PSTAMP(8);
        }
        const uint32_t slot = par * XCHG_SLOT;
        if (u_role & 2) {
            if (qk) mbar_wait_bounded(bar + BAR_V, par);
            uint32_t vt[2][4][4];
            auto v_load = [&](int i0, int i1) {
                #pragma unroll
                for (int i = i0; i < i1; i++) {
                    const uint4 v = lds128(l16 + SM_V + (warp & 1) * 1024 + (i & 3) * 2048 + (i >> 2) * 512);
                    vt[i >> 2][i & 3][0] = v.x; vt[i >> 2][i & 3][1] = v.y; vt[i >> 2][i & 3][2] = v.z; vt[i >> 2][i & 3][3] = v.w;
                }
            };
            v_load(0, V_EARLY);
            kv_stores();
            const uint32_t l8 = fresh(sb + lane * 8);
            mbar_wait_bounded(bar + BAR_X, par);
            STAMP(4);
            float sv[10];
            #pragma unroll
            for (int j = 0; j < 5; j++) {
                const uint2 a = lds64(l8 + SM_SP + j * 256), b = lds64(l8 + SM_SP + 1280 + j * 256);
                sv[2 * j] = __uint_as_float(a.x) + __uint_as_float(b.x);
                sv[2 * j + 1] = __uint_as_float(a.y) + __uint_as_float(b.y);
            }
            float mx = fmaxf(fmaxf(fmaxf(sv[0], sv[1]), fmaxf(sv[2], sv[3])), fmaxf(fmaxf(sv[4], sv[5]), fmaxf(sv[6], sv[7])));
            mx = fmaxf(mx, fmaxf(sv[8], sv[9]));
            const float m1 = __shfl_xor_sync(~0u, mx, 1), m2 = __shfl_xor_sync(~0u, mx, 2), m3 = __shfl_xor_sync(~0u, mx, 3);
            __syncwarp();
            v_load(V_EARLY, 8);
            const bool vm_ok = mbar_test_wait(bar + BAR_VM, par);
            mx = fmaxf(fmaxf(mx, m1), fmaxf(m2, m3));
            const float mo = mx * sl2;
            #pragma unroll
            for (int j = 0; j < 10; j++) sv[j] = ex2(fmaf(sv[j], sl2, -mo));
            const uint32_t e0 = pack_bf16(sv[0], sv[1]), e1 = pack_bf16(sv[2], sv[3]);
            const uint32_t e2 = pack_bf16(sv[4], sv[5]), e3 = pack_bf16(sv[6], sv[7]), em = pack_bf16(sv[8], sv[9]);
            float o[4][4];
            #pragma unroll
            for (int i = 0; i < 4; i++) {
                o[i][0] = o[i][1] = o[i][2] = o[i][3] = 0.f;
                mma_a(o[i], vt[0][i], e0, e1);
            }
            const float sum = (((sv[0] + sv[1]) + (sv[2] + sv[3])) + ((sv[4] + sv[5]) + (sv[6] + sv[7]))) + (sv[8] + sv[9]);
            if (!vm_ok) mbar_wait_bounded(bar + BAR_VM, par);
            uint2 vm[4];
            #pragma unroll
            for (int i = 0; i < 4; i++) {
                vm[i] = lds64(l8 + SM_VM + (warp & 1) * 1024 + i * 256);
                mma_a(o[i], vt[1][i], e2, e3);
            }
            #pragma unroll
            for (int i = 0; i < 4; i++) mma1688(o[i], vm[i].x, vm[i].y, em);
            {
                const float s1 = __shfl_xor_sync(~0u, sum, 1), s2 = __shfl_xor_sync(~0u, sum, 2), s3 = __shfl_xor_sync(~0u, sum, 3);
                sts32(sb + SM_SUM + (lane & 28), __float_as_uint((sum + s1) + (s2 + s3)));
            }
            #pragma unroll
            for (int i = 0; i < 4; i += 2)
                stsm_x4(l16 + SM_O + (warp & 1) * 1024 + i * 256, pack_bf16(o[i][0], o[i][1]), pack_bf16(o[i][2], o[i][3]),
                        pack_bf16(o[i + 1][0], o[i + 1][1]), pack_bf16(o[i + 1][2], o[i + 1][3]));
            STAMP(5);
            uint32_t st[16][4];
            named_bar_sync(6, REC_THREADS);
            wo_phase<2, 0>(st, ao, 0, l16, tbl, sb + SM_SUM, slot, xhi, 0, bar + BAR_XG, par ^ 1, x0_ok);
        } else {
            const uint32_t a3 = fresh(ao) + (wg == 0 ? 10 : 6) * 8192;
            uint32_t st[24][4];
            #pragma unroll
            for (int n = 0; n < WO_PFA; n++) ldsm4t(wo_addr<3>(ao, a3, n), st[n]);
            if (u_role & 1) {
                const uint32_t ln = (fresh(l16) >> 4) & 31;
                uint8_t* ib = xaddr(lds32_volatile(tbl + 12) + (par ^ 1) * XCHG_SLOT + ln * 16, xhi);
                #pragma unroll
                for (int i = 0; i < 4; i++) st_relaxed_v4(ib + i * 512, SENT);
                st_relaxed_b32(xaddr(lds32_volatile(tbl + 28) + pub_slot(s + 3) + (ln & 16) * 256 + (ln & 8) * 16 + (ln & 7) * 4, xhi), SENT);
            }
            if (warp == 1) {
                if (elect_one()) {
                    #pragma unroll
                    for (int g = 0; g < 4; g++) mbar_arrive_expect_tx(bar + BAR_XG + 8 * g, 16384);
                }
                if (s + 2 < NSEG && cta < 4 && elect_one())
                    asm volatile("cp.async.bulk.prefetch.tensor.3d.L2.global [%0, {%1, %2, %3}];"
                                 ::"l"(&p.tmX), "r"(0), "r"((s + 2) * SEG), "r"(cta * 4) : "memory");
            }
            mbar_wait_bounded(bar + BAR_X, par);
            spin_clks(WO_PFB_DELAY);
            #pragma unroll
            for (int n = WO_PFA; n < WO_PF; n++) ldsm4t(wo_addr<3>(ao, a3, n), st[n]);
            tile_stores();
            kv_stores();
            if (u_role & 16) {
                mbar_wait_bounded(bar + BAR_VM, par);
                if (elect_one()) x_load(p, sb, s + 1, rank);
            }
            named_bar_sync(6, REC_THREADS);
            wo_phase<3, WO_PF>(st, ao, a3, l16, tbl, sb + SM_SUM, slot, xhi, u_role & 4, bar + BAR_XG, par ^ 1, x0_ok);
        }
        STAMP(7);
        if (wg == 0) named_bar_sync(9, REC_THREADS); else named_bar_arrive(9, REC_THREADS);
    }
    if (threadIdx.x == 128) KMARK(8);
    if (warp == 4 && elect_one()) {
        bulk_wait_all();
        asm volatile("red.relaxed.gpu.global.add.u32 [%0], 1;" ::"l"(p.flags + F_LASTTOK) : "memory");
    }
    named_bar_sync(0, REC_THREADS);
    if (warp == 4) {
        if (elect_one()) {
            signal_flag(p.flags + F_PROGRESS + NSEG - 1);
            KMARK(9);
        }
    } else if (warp == 0) {
        mbar_wait(bar + BAR_X, 1);
        mbar_wait(bar + BAR_VM, 1);
        if (rank == 0) mbar_wait(bar + BAR_F0, 1);
    }
}

__global__ void __launch_bounds__(REC_THREADS, 1) rec_kernel(const __grid_constant__ RecParams p) {
    extern __shared__ __align__(1024) uint8_t smem_raw[];
    const uint32_t sb = smem_u32(smem_raw);
    const int tid = threadIdx.x, lane = tid & 31;
    const int warp = __shfl_sync(~0u, tid >> 5, 0);
    const int cta = blockIdx.x, head = cta / 3, rank = cta % 3;
    const int wg = warp >> 2, wq = warp & 3;
    const uint32_t bar = sb + SM_BAR;
    uint8_t* const xb = p.xchg;
    const uint32_t xlo = (uint32_t)(uint64_t)xb;
    if ((sb & 0x3FFFF) != SMEM_ORIGIN) __trap();
    KENTER(1);
    auto w_box = [&](int part, int g, int i, uint32_t dst, uint32_t mb) {
        const int m = i ^ g;
        const CUtensorMap* tm = &p.tmW[rank == 2 ? 2 : m];
        const int col = head * DH + (rank == 2 ? m : rank) * 64, row = ((part + 1) & 3) * 16;
        tma_load_3d(dst, tm, col, row, g * 8, mb);
    };
    if (tid == 0) {
        mbar_init(bar + BAR_V, 1);
        for (int i = 0; i < 4; i++) { mbar_init(bar + BAR_XG + 8 * i, 1); mbar_init(bar + BAR_M + 8 * i, 1); }
        mbar_init(bar + BAR_GO, 4);
        mbar_init(bar + BAR_PK, 4);
        mbar_init(bar + BAR_VM, rank < 2 ? 1 : 9);
        mbar_init(bar + BAR_F0, 3);
        mbar_init(bar + BAR_F3, 3);
        mbar_init(bar + BAR_VF, 3);
        sts64(bar + BAR_MIN, ~0u, ~0u);
        mbar_init(bar + BAR_X, rank < 2 ? 6 : 1);
        for (int i = 0; i < 3; i++) mbar_init(bar + BAR_P0 + 8 * i, 1);
        mbar_init(bar + BAR_WQ, 1);
        mbar_init(bar + BAR_WO, 1);
        sts32(bar + BAR_SELF, bar + BAR_SELF);
        asm volatile("fence.mbarrier_init.release.cluster;" ::: "memory");
    }
    auto build_tables = [&](uint32_t av) {
        for (uint32_t n = 0; !__all_sync(~0u, (av >> 24) == 24); n++) {
            av = ld_acquire_b32(p.arrivals + (lane & 3));
            if (n > SPIN_LIMIT) __trap();
        }
        uint32_t cm[3];
        #pragma unroll
        for (int i = 0; i < 3; i++) {
            const int o = i * 32 + lane;
            cm[i] = __ballot_sync(~0u, __popc((__shfl_sync(~0u, av, o / 24) >> (o % 24 / 3 * 3)) & 7) >= 2);
        }
        auto color_of = [&](int o) { return ((o < 32 ? cm[0] : o < 64 ? cm[1] : cm[2]) >> (o & 31)) & 1u; };
        auto inbox = [&](int o, int byte) {
            uint32_t c = color_of(o);
            int ones = 0;
            #pragma unroll
            for (int i = 0; i < 3; i++) ones += __popc(o >= i * 32 + 32 ? cm[i] : (o > i * 32 ? cm[i] & ((1u << (o - i * 32)) - 1) : 0u));
            int idx = c ? ones : o - ones;
            if (idx >= INBOX_MAX) { idx = 2 * INBOX_MAX - 1 - idx; c ^= 1; }
            const uint32_t lin = idx * 6144 + byte, q = XCHG_INBOX + (lin >> 12) * 8192;
            return q + class_off(xlo + q, c) + (lin & 4095);
        };
        uint32_t off = 0;
        const int grp = (warp + 3) & 3;
        if (lane < 12) {
            const int i = lane >> 2, lt0 = rank * 6;
            const int o = i < 2 ? rank * 32 + warp * 4 + (lane & 3) : (lt0 + ((warp + 4) & 7)) * 4 + (lane & 3);
            off = inbox(min(o, 95), i * 2048 + head * 64);
        } else if (lane == 12) {
            off = inbox(cta, (grp % 3) * 2048);
        } else if (lane == 13) {
            int T;
            if (grp < 2) {
                T = (cta >> 5) * 22 + 8 * grp + ((cta & 31) >> 2);
            } else {
                const int tl = (cta & 63) >> 2;
                T = (tl / 6) * 22 + 16 + tl % 6;
            }
            off = XCHG_PUB + (T >> 4) * 8192 + (T & 15) * 256 + (cta & 3) * 32;
        } else if (lane == 14) {
            const uint32_t q = XCHG_PUB + wq * 8192;
            off = q + class_off(xlo + q, color_of(cta));
        }
        if (lane < 16) asm volatile("st.shared.b32 [%0], %1;" ::"r"(sb + SM_TBL + warp * 64 + (lane & 3) * 16 + (lane >> 2) * 4), "r"(xlo + off) : "memory");
    };
    if (tid >= 32 && tid < 37) asm volatile("prefetch.tensormap [%0];" ::"l"(&p.tmW[0] + (tid - 32)) : "memory");
    if (cta == 0) for (int i = tid; i < F_COUNT; i += REC_THREADS) p.flags[i] = 0;
    __syncthreads();
    auto stage = [](int part) { return ((part + 2) % 3) * 65536; };
    auto load_part = [&](int part) {
        mbar_arrive_expect_tx(bar + BAR_P0 + 8 * part, 65536);
        for (int u = 0; u < 4; u++) w_box(part, u >> 1, u & 1, sb + stage(part) + u * 16384, bar + BAR_P0 + 8 * part);
    };
    asm volatile("barrier.cluster.arrive.relaxed.aligned;" ::: "memory");
    uint4 img = make_uint4(SENT, SENT, SENT, SENT);
    if (cta >= 92) {
        const unsigned short* m = reinterpret_cast<const unsigned short*>(p.mem0) + (cta - 92) * 256 + tid;
        uint32_t w[4];
        #pragma unroll
        for (int i = 0; i < 4; i++) w[i] = (uint32_t)__ldg(m + 2 * i * DM) | ((uint32_t)__ldg(m + (2 * i + 1) * DM) << 16);
        img = make_uint4(w[0], w[1], w[2], w[3]);
    }
    {
        constexpr int NPAIR = (XCHG_SLOT + PUB_BYTES) / 8192;
        uint8_t* pr = xb + (4 + cta) * 8192;
        const uint32_t c0 = class_off(xlo + (4 + cta) * 8192, 0);
        #pragma unroll
        for (int c = 0; c < 2; c++) {
            const bool timed = lane == 0 || (lane == 8 && c == (warp & 1));
            reinterpret_cast<uint4*>(pr + (c0 ^ (c << 12)))[tid] = make_uint4(timed ? 0u : SENT, SENT, SENT, SENT);
        }
        __syncwarp();
        if (lane == 0) {
            uint32_t x = 0;
            for (int k = 0; k < 3; k++) {
                if (k == 0 && warp == 0) load_part(0);
                const uint32_t c = (k + warp) & 1, t0 = clock_after(x);
                x = atomicExch(reinterpret_cast<uint32_t*>(pr + (c0 ^ (c << 12)) + warp * 512 + (k >> 1) * 128 + x), SENT);
                const uint32_t lat = clock_after(x) - t0;
                asm volatile("red.shared.min.u32 [%0], %1;" ::"r"(bar + BAR_MIN + 4 * c), "r"(lat) : "memory");
            }
        }
        __syncwarp();
        if (cta >= 92 || 100 + cta < NPAIR) {
            if (cta >= 92) {
                if (img.x == SENT) img.x = 0x7FFF7FFFu;
                if (img.y == SENT) img.y = 0x7FFF7FFFu;
                if (img.z == SENT) img.z = 0x7FFF7FFFu;
                if (img.w == SENT) img.w = 0x7FFF7FFFu;
            }
            uint8_t* q = xb + (cta >= 92 ? cta - 92 : 100 + cta) * 8192;
            reinterpret_cast<uint4*>(q)[tid] = img;
            reinterpret_cast<uint4*>(q + 4096)[tid] = img;
        }
    }
    __syncthreads();
    PSTAMP(4);
    if (tid == 0) {
        for (int part = 1; part < 3; part++) load_part(part);
    }
    if (tid == 224) {
        const uint32_t c = lds32_volatile(bar + BAR_MIN) > lds32_volatile(bar + BAR_MIN + 4) ? 1 : 0;
        asm volatile("red.release.gpu.global.add.u32 [%0], %1;" ::"l"(p.arrivals + cta / 24), "r"((1u << 24) | (c << (cta % 24))) : "memory");
    }
    uint32_t wr[NREG][2][4];
    uint32_t arrived = 0;
    {
        const int mi = lane >> 3, r8 = lane & 7;
        const uint32_t a0 = sb + wg * 32768 + ((mi >> 1) * 8 + r8) * 128 + (((wq * 2 + (mi & 1)) ^ r8) << 4);
        #pragma unroll
        for (int part = 0; part < 3; part++) {
            mbar_wait_bounded(bar + BAR_P0 + 8 * part, 0);
            if (part == 0) arrived = ld_relaxed_b32(p.arrivals + (lane & 3));
            #pragma unroll
            for (int j = 0; j < 8; j++) {
                #pragma unroll
                for (int i = 0; i < 2; i++) ldsm4t(a0 + stage(part) + i * 16384 + j * 2048, wr[part * 8 + j][i]);
            }
            asm volatile("fence.proxy.async.shared::cta;" ::: "memory");
            __syncthreads();
            PSTAMP(5 + part);
            if (tid == 0) {
                if (part == 0) {
                    for (int g = 0; g < 4; g++) {
                        mbar_arrive_expect_tx(bar + BAR_XG + 8 * g, 16384);
                        tma_load_3d(sb + SM_X + g * 16384, &p.tmX, 0, 0, g * 4, bar + BAR_XG + 8 * g);
                    }
                } else if (part == 1) {
                    mbar_arrive_expect_tx(bar + BAR_WQ, 65536);
                    for (int u = 0; u < 4; u++) w_box(3, u >> 1, u & 1, sb + SM_WQ + u * 16384, bar + BAR_WQ);
                } else {
                    mbar_arrive_expect_tx(bar + BAR_WO, 11 * 8192);
                    tma_load_3d(sb + SM_WO, &p.tmWo, 0, head * DH, rank * 11, bar + BAR_WO);
                    if (cta < 4)
                        asm volatile("cp.async.bulk.prefetch.tensor.3d.L2.global [%0, {%1, %2, %3}];"
                                     ::"l"(&p.tmX), "r"(0), "r"(SEG), "r"(cta * 4) : "memory");
                }
            }
        }
    }
    build_tables(arrived);
    if (tid == 64) {
        uint32_t smid;
        asm volatile("mov.u32 %0, %%smid;" : "=r"(smid));
        if (smid < 384) atomicOr(p.flags + F_RECSM + (smid >> 5), 1u << (smid & 31));
    }
    __syncwarp();
    PSTAMP(9);
    mbar_wait(bar + BAR_WQ, 0);
    asm volatile("barrier.cluster.wait.aligned;" ::: "memory");

    rec_steps(p, wr, sb, warp, cta, head, rank);
    if (cta == 0 && tid < 4) p.arrivals[tid] = 0;
    if (tid == 128) KEXIT(1);
}

constexpr int ATT_SLOT = 28672;
constexpr int ATT_PAIRS = 8;
constexpr int ATT_BAR = ATT_PAIRS * ATT_SLOT;
constexpr int ATT_SMEM = ATT_BAR + ATT_PAIRS * 16;
constexpr int ATT_THREADS = ATT_PAIRS * 64;
struct AttnParams {
    CUtensorMap tmOa;
    CUtensorMap tmQb, tmKb;
    CUtensorMap tmOb;
    const __nv_bfloat16* qkv_tok;
    const __nv_bfloat16* kv_mem;
    uint32_t* flags;
};

__device__ __forceinline__ void tok_attn_warp(uint32_t base, int mh, int lane) {
    const uint32_t sq = base, sk = base + 8192, sv = base + 16384, skm = base + 24576, svm = skm + 2048;
    const int g = lane >> 2, c = lane & 3, mi = lane >> 3, r8 = lane & 7;
    const int ntile = mh ? 5 : 3;
    float sc[5][4];
    #pragma unroll
    for (int j = 0; j < 5; j++) { sc[j][0] = sc[j][1] = sc[j][2] = sc[j][3] = 0.f; }
    #pragma unroll
    for (int t2 = 0; t2 < 4; t2++) {
        uint32_t a[2][4];
        #pragma unroll
        for (int h = 0; h < 2; h++) {
            const int row = mh * 16 + (mi & 1) * 8 + r8, ch16 = 4 * t2 + 2 * h + (mi >> 1);
            ldsm_x4(sq + (ch16 >> 3) * 4096 + row * 128 + (((ch16 & 7) ^ r8) << 4), a[h][0], a[h][1], a[h][2], a[h][3]);
        }
        const int ch16 = 4 * t2 + mi;
        uint32_t b[5][4];
        #pragma unroll
        for (int j = 0; j < 5; j++) {
            if (j < ntile) {
                if (j == 0) ldsm_x4_t(skm + t2 * 512 + lane * 16, b[j][0], b[j][1], b[j][2], b[j][3]);
                else ldsm_x4(sk + (ch16 >> 3) * 4096 + ((j - 1) * 8 + r8) * 128 + (((ch16 & 7) ^ r8) << 4), b[j][0], b[j][1], b[j][2], b[j][3]);
            }
        }
        #pragma unroll
        for (int h = 0; h < 2; h++) {
            #pragma unroll
            for (int j = 0; j < 5; j++)
                if (j < ntile) mma16816(sc[j], a[h][0], a[h][1], a[h][2], a[h][3], b[j][2 * h], b[j][2 * h + 1]);
        }
    }
    const float sl2 = 0.08838834764831845f * 1.4426950408889634f;
    uint32_t pf[2][5];
    float inv[2];
    #pragma unroll
    for (int q = 0; q < 2; q++) {
        const int tok = mh * 16 + q * 8 + g;
        float v[10];
        #pragma unroll
        for (int j = 0; j < 5; j++) {
            #pragma unroll
            for (int e = 0; e < 2; e++) {
                const int key = (j - 1) * 8 + 2 * c + e;
                v[2 * j + e] = (j == 0 || key <= tok) ? sc[j][2 * q + e] : -INFINITY;
            }
        }
        float mx = v[0];
        #pragma unroll
        for (int j = 1; j < 10; j++) mx = fmaxf(mx, v[j]);
        mx = fmaxf(mx, __shfl_xor_sync(~0u, mx, 1));
        mx = fmaxf(mx, __shfl_xor_sync(~0u, mx, 2));
        const float mo = mx * sl2;
        float sum = 0.f;
        #pragma unroll
        for (int j = 0; j < 10; j++) { v[j] = ex2(fmaf(v[j], sl2, -mo)); sum += v[j]; }
        sum += __shfl_xor_sync(~0u, sum, 1);
        sum += __shfl_xor_sync(~0u, sum, 2);
        inv[q] = rcp(sum);
        #pragma unroll
        for (int j = 0; j < 5; j++) pf[q][j] = pack_bf16(v[2 * j], v[2 * j + 1]);
    }
    auto load_v = [&](int n4, uint32_t (&vm)[4], uint32_t (&vt)[4][4]) {
        ldsm_x4(svm + n4 * 512 + lane * 16, vm[0], vm[1], vm[2], vm[3]);
        #pragma unroll
        for (int u = 0; u < 4; u++) {
            const int dt = 2 * n4 + (u >> 1), kh = u & 1;
            const uint4 v = lds128(sv + (dt & 3) * 2048 + (dt >> 2) * 1024 + kh * 512 + lane * 16);
            vt[u & 2][2 * kh] = v.x; vt[u & 2][2 * kh + 1] = v.z;
            vt[(u & 2) + 1][2 * kh] = v.y; vt[(u & 2) + 1][2 * kh + 1] = v.w;
        }
    };
    uint32_t vm[2][4], vt[2][4][4];
    load_v(0, vm[0], vt[0]);
    #pragma unroll
    for (int n4 = 0; n4 < 4; n4++) {
        const int cur = n4 & 1;
        if (n4 + 1 < 4) load_v(n4 + 1, vm[cur ^ 1], vt[cur ^ 1]);
        float o[4][4];
        #pragma unroll
        for (int u = 0; u < 4; u++) {
            o[u][0] = o[u][1] = o[u][2] = o[u][3] = 0.f;
            mma16816(o[u], pf[0][1], pf[1][1], pf[0][2], pf[1][2], vt[cur][u][0], vt[cur][u][1]);
        }
        if (mh) {
            #pragma unroll
            for (int u = 0; u < 4; u++) mma16816(o[u], pf[0][3], pf[1][3], pf[0][4], pf[1][4], vt[cur][u][2], vt[cur][u][3]);
        }
        #pragma unroll
        for (int u = 0; u < 4; u++) mma1688(o[u], pf[0][0], pf[1][0], vm[cur][u]);
        #pragma unroll
        for (int u = 0; u < 4; u += 2) {
            const int row = mh * 16 + (mi & 1) * 8 + r8, nt = 4 * n4 + u + (mi >> 1);
            stsm_x4(sq + (nt >> 3) * 4096 + row * 128 + (((nt & 7) ^ r8) << 4),
                    pack_bf16(o[u][0] * inv[0], o[u][1] * inv[0]), pack_bf16(o[u][2] * inv[1], o[u][3] * inv[1]),
                    pack_bf16(o[u + 1][0] * inv[0], o[u + 1][1] * inv[0]), pack_bf16(o[u + 1][2] * inv[1], o[u + 1][3] * inv[1]));
        }
    }
}

__device__ __forceinline__ void b_attn_warp(uint32_t base, int hl, int idx0, int lane) {
    const uint32_t sq = base, sk = base + 8192, sv = base + 8192 + 9216;
    const int g = lane >> 2, c = lane & 3;
    auto addr = [&](uint32_t t, int row, int ch) { return t + row * 128 + ((ch ^ (row & 7)) << 4); };
    const float sl2 = 0.17677669529663687f * 1.4426950408889634f;
    #pragma unroll 2
    for (int blk = 0; blk < 4; blk++) {
        const int r0 = blk * 16;
        float sc[3][4];
        #pragma unroll
        for (int j = 0; j < 3; j++) { sc[j][0] = sc[j][1] = sc[j][2] = sc[j][3] = 0.f; }
        #pragma unroll
        for (int t = 0; t < 2; t++) {
            uint32_t a0, a1, a2, a3, b0, b1, b2, b3, d0, d1, d2, d3;
            const int mi = lane >> 3, r = lane & 7;
            ldsm_x4(addr(sq, r0 + (mi & 1) * 8 + r, hl * 4 + 2 * t + (mi >> 1)), a0, a1, a2, a3);
            ldsm_x4(addr(sk, r0 + (mi >> 1) * 8 + r, hl * 4 + 2 * t + (mi & 1)), b0, b1, b2, b3);
            ldsm_x4(addr(sk, r0 + 16 + r, hl * 4 + 2 * t + (mi & 1)), d0, d1, d2, d3);
            mma16816(sc[0], a0, a1, a2, a3, b0, b1);
            mma16816(sc[1], a0, a1, a2, a3, b2, b3);
            mma16816(sc[2], a0, a1, a2, a3, d0, d1);
        }
        uint32_t pf[2][3];
        float inv[2];
        #pragma unroll
        for (int r = 0; r < 2; r++) {
            const int u = r * 8 + g;
            float v[6];
            #pragma unroll
            for (int j = 0; j < 3; j++) {
                #pragma unroll
                for (int e = 0; e < 2; e++) {
                    const int key = j * 8 + 2 * c + e;
                    const bool ok = key > u && key <= u + 8 && idx0 + r0 - 8 + key >= 0;
                    v[2 * j + e] = ok ? sc[j][2 * r + e] : -INFINITY;
                }
            }
            float mx = fmaxf(fmaxf(fmaxf(v[0], v[1]), fmaxf(v[2], v[3])), fmaxf(v[4], v[5]));
            mx = fmaxf(mx, __shfl_xor_sync(~0u, mx, 1));
            mx = fmaxf(mx, __shfl_xor_sync(~0u, mx, 2));
            const float mo = mx * sl2;
            float sum = 0.f;
            #pragma unroll
            for (int j = 0; j < 6; j++) { v[j] = ex2(fmaf(v[j], sl2, -mo)); sum += v[j]; }
            sum += __shfl_xor_sync(~0u, sum, 1);
            sum += __shfl_xor_sync(~0u, sum, 2);
            inv[r] = rcp(sum);
            #pragma unroll
            for (int j = 0; j < 3; j++) pf[r][j] = pack_bf16(v[2 * j], v[2 * j + 1]);
        }
        uint32_t ow[4][2];
        {
            const int mi = lane >> 3, r = lane & 7;
            uint32_t vv[4][4];
            #pragma unroll
            for (int nt = 0; nt < 4; nt++)
                ldsm_x4_t(addr(sv, r0 + min(mi, 2) * 8 + r, hl * 4 + nt), vv[nt][0], vv[nt][1], vv[nt][2], vv[nt][3]);
            float o[4][4];
            #pragma unroll
            for (int nt = 0; nt < 4; nt++) {
                o[nt][0] = o[nt][1] = o[nt][2] = o[nt][3] = 0.f;
                mma16816(o[nt], pf[0][0], pf[1][0], pf[0][1], pf[1][1], vv[nt][0], vv[nt][1]);
            }
            #pragma unroll
            for (int nt = 0; nt < 4; nt++) mma1688(o[nt], pf[0][2], pf[1][2], vv[nt][2]);
            #pragma unroll
            for (int nt = 0; nt < 4; nt++) {
                ow[nt][0] = pack_bf16(o[nt][0] * inv[0], o[nt][1] * inv[0]);
                ow[nt][1] = pack_bf16(o[nt][2] * inv[1], o[nt][3] * inv[1]);
            }
        }
        #pragma unroll
        for (int u = 0; u < 4; u += 2) {
            const int mi = lane >> 3, r = lane & 7;
            stsm_x4(addr(sq, r0 + (mi & 1) * 8 + r, hl * 4 + u + (mi >> 1)), ow[u][0], ow[u][1], ow[u + 1][0], ow[u + 1][1]);
        }
    }
}

constexpr uint32_t QKVB_TARGET = 12 * 8;
constexpr uint32_t PROGRESS_TARGET = 96;
constexpr uint32_t OA_TARGET = 64, OB_TARGET = 32;
#define ATT_B0 8
#define ATT_BSTEP 2
constexpr int ATT_TASKS = (NSEG + 16) * 32;
static_assert(ATT_B0 + 16 * ATT_BSTEP <= NSEG, "order of the task groups");
__device__ __forceinline__ int att_group(int g, bool& isb) {
    constexpr int P = ATT_BSTEP + 1;
    const int q = g - ATT_B0;
    isb = q >= 0 && q < 16 * P && q % P == 0;
    return q < 0 ? g : q >= 16 * P ? g - 16 : isb ? q / P : g - q / P - 1;
}

__global__ void __launch_bounds__(ATT_THREADS, 1) attn_kernel(const __grid_constant__ AttnParams p) {
    extern __shared__ __align__(1024) uint8_t smem_raw[];
    const int tid = threadIdx.x, lane = tid & 31, warp = __shfl_sync(~0u, tid >> 5, 0);
    const int pair = warp >> 1, wi = warp & 1;
    const uint32_t base = smem_u32(smem_raw) + pair * ATT_SLOT, bar = smem_u32(smem_raw) + ATT_BAR + pair * 16;
    const bool leader = wi == 0 && lane == 0;
    if (tid == 0) pdl_launch_dependents();
    KENTER(3);
    uint32_t phase = 0;
    if (leader) {
        mbar_init(bar, 1);
        asm volatile("fence.mbarrier_init.release.cluster;" ::: "memory");
    }
    uint32_t* pending = nullptr;
    auto flush = [&]() {
        if (pending) {
            bulk_wait_all();
            asm volatile("red.relaxed.gpu.global.add.u32 [%0], 1;" ::"l"(pending) : "memory");
            if (pending == p.flags + F_OA + NSEG - 1) KMARK(14);
            pending = nullptr;
        }
    };
    int ready_a = -1, ready_b = -1;
    for (int task = pair * gridDim.x + blockIdx.x; task < ATT_TASKS; task += ATT_PAIRS * gridDim.x) {
        bool isb;
        const int grp = att_group(task >> 5, isb), i = task & 31;
        named_bar_sync(1 + pair, 64);
        if (leader) {
            {
                auto need = [&](const uint32_t* f, uint32_t target) {
                    if (ld_acquire_b32(f) < target) { flush(); wait_flag(f, target); }
                };
                if (isb) {
                    if (grp > ready_b) {
                        need(p.flags + F_QKVB + grp, QKVB_TARGET);
                        if (grp > 0) need(p.flags + F_QKVB + grp - 1, QKVB_TARGET);
                        asm volatile("fence.proxy.async.global;" ::: "memory");
                        ready_b = grp;
                    }
                    mbar_arrive_expect_tx(bar, 8192 + 2 * 9216);
                    tma_load_3d(base, &p.tmQb, (i >> 1) * 64, i & 1, grp * 64, bar);
                    tma_load_3d(base + 8192, &p.tmKb, DM + (i >> 1) * 64, i & 1, grp * 64 - 8, bar);
                    tma_load_3d(base + 8192 + 9216, &p.tmKb, 2 * DM + (i >> 1) * 64, i & 1, grp * 64 - 8, bar);
                } else {
                    if (grp > ready_a) {
                        need(p.flags + (grp == NSEG - 1 ? F_LASTTOK : F_PROGRESS + grp), PROGRESS_TARGET);
                        asm volatile("fence.proxy.async.global;" ::: "memory");
                        ready_a = grp;
                    }
                    if (grp == 63) KMARK(10);
                    mbar_arrive_expect_tx(bar, ATT_SLOT);
                    #pragma unroll
                    for (int w = 0; w < 3; w++)
                        bulk_load(base + w * 8192, p.qkv_tok + (((size_t)w * NSEG + grp) * NH + i) * (SEG * DH), 8192, bar);
                    if (grp == NSEG - 1) {
                        need(p.flags + F_PROGRESS + grp, PROGRESS_TARGET);
                        asm volatile("fence.proxy.async.global;" ::: "memory");
                    }
                    #pragma unroll
                    for (int w = 0; w < 2; w++)
                        bulk_load(base + 24576 + w * 2048, p.kv_mem + (((size_t)w * NSEG + grp) * NH + i) * (MROWS * DH), 2048, bar);
                }
            }
        }
        if (lane == 0) flush();
        __syncwarp();
        mbar_wait_sleep(bar, phase);
        phase ^= 1;
        if (isb) {
            b_attn_warp(base, wi, grp * 64, lane);
            asm volatile("fence.proxy.async.shared::cta;" ::: "memory");
            named_bar_sync(1 + pair, 64);
            if (wi == 1 && lane == 0) {
                asm volatile("cp.async.bulk.tensor.3d.global.shared::cta.bulk_group [%0, {%2, %3, %4}], [%1];"
                             ::"l"(&p.tmOb), "r"(base), "r"((i >> 1) * 64), "r"(i & 1), "r"(grp * 64) : "memory");
                pending = p.flags + F_OB + grp;
            }
        } else {
            if (grp == 63 && lane == 0) KMARK(11);
            tok_attn_warp(base, wi, lane);
            if (grp == 63 && lane == 0) KMARK(12);
            asm volatile("fence.proxy.async.shared::cta;" ::: "memory");
            __syncwarp();
            if (lane == 0) {
                #pragma unroll
                for (int h = 0; h < 2; h++) tma_store_2d(&p.tmOa, base + h * 4096 + wi * 2048, i * DH + h * 64, grp * SEG + wi * 16);
                pending = p.flags + F_OA + grp;
            }
        }
        if (lane == 0) { bulk_commit(); bulk_wait_read_all(); }
        __syncwarp();
    }
    if (lane == 0) { flush(); KEXIT(3); }
}

typedef CUresult (*EncodeFn)(CUtensorMap*, CUtensorMapDataType, cuuint32_t, void*, const cuuint64_t*, const cuuint64_t*,
                             const cuuint32_t*, const cuuint32_t*, CUtensorMapInterleave, CUtensorMapSwizzle,
                             CUtensorMapL2promotion, CUtensorMapFloatOOBfill);

void make_map_2d(EncodeFn enc, CUtensorMap* m, const void* ptr, uint64_t rows, uint64_t cols, uint32_t box_rows) {
    cuuint64_t dims[2] = {cols, rows};
    cuuint64_t strides[1] = {cols * 2};
    cuuint32_t box[2] = {64, box_rows};
    cuuint32_t es[2] = {1, 1};
    enc(m, CU_TENSOR_MAP_DATA_TYPE_BFLOAT16, 2, const_cast<void*>(ptr), dims, strides, box, es,
        CU_TENSOR_MAP_INTERLEAVE_NONE, CU_TENSOR_MAP_SWIZZLE_128B, CU_TENSOR_MAP_L2_PROMOTION_L2_256B,
        CU_TENSOR_MAP_FLOAT_OOB_FILL_NONE);
}
void make_map_b(EncodeFn enc, CUtensorMap* m, const void* ptr, uint64_t k, uint64_t n, uint32_t nblk, uint32_t box_rows = 64,
                uint32_t bc = 64) {
    cuuint64_t dims[3] = {bc, k, n / bc};
    cuuint64_t strides[2] = {n * 2, bc * 2};
    cuuint32_t box[3] = {bc, box_rows, nblk};
    cuuint32_t es[3] = {1, 1, 1};
    enc(m, CU_TENSOR_MAP_DATA_TYPE_BFLOAT16, 3, const_cast<void*>(ptr), dims, strides, box, es,
        CU_TENSOR_MAP_INTERLEAVE_NONE, bc == 64 ? CU_TENSOR_MAP_SWIZZLE_128B : CU_TENSOR_MAP_SWIZZLE_64B, CU_TENSOR_MAP_L2_PROMOTION_L2_256B,
        CU_TENSOR_MAP_FLOAT_OOB_FILL_NONE);
}

void make_map_parity(EncodeFn enc, CUtensorMap* m, const void* ptr, uint64_t cols, uint32_t box_rows) {
    cuuint64_t dims[3] = {cols, 2, S_TOK / 2};
    cuuint64_t strides[2] = {cols * 2, cols * 4};
    cuuint32_t box[3] = {64, 1, box_rows};
    cuuint32_t es[3] = {1, 1, 1};
    enc(m, CU_TENSOR_MAP_DATA_TYPE_BFLOAT16, 3, const_cast<void*>(ptr), dims, strides, box, es,
        CU_TENSOR_MAP_INTERLEAVE_NONE, CU_TENSOR_MAP_SWIZZLE_128B, CU_TENSOR_MAP_L2_PROMOTION_L2_128B,
        CU_TENSOR_MAP_FLOAT_OOB_FILL_NONE);
}
void make_map_w(EncodeFn enc, CUtensorMap* m, const void* ptr) {
    cuuint64_t dims[3] = {HD, 64, DM / 64};
    cuuint64_t strides[2] = {HD * 2, 64 * HD * 2};
    cuuint32_t box[3] = {64, 16, 8};
    cuuint32_t es[3] = {1, 1, 1};
    enc(m, CU_TENSOR_MAP_DATA_TYPE_BFLOAT16, 3, const_cast<void*>(ptr), dims, strides, box, es,
        CU_TENSOR_MAP_INTERLEAVE_NONE, CU_TENSOR_MAP_SWIZZLE_128B, CU_TENSOR_MAP_L2_PROMOTION_L2_256B,
        CU_TENSOR_MAP_FLOAT_OOB_FILL_NONE);
}

#define SIDE_ORDER 0
#define SERIAL_ATT_CTAS h.n_sm
#define N_TAIL_CTAS 28
#define N_SIDE_CTAS 28
#define N_ATT_CTAS 8
#define TAIL_BLOCK0 11

#define TAIL_SPARE 2
#define TAIL_KB2 30
#define TAIL_KB3 20
#define TAIL_BLOCK1 13
#define TAIL_BLOCK2 14

struct HostState {
    bool ready;
    bool overlap;
    int n_side, n_att, n_sm;
    SideParams seq_a, seq_b;
    const void* key[11];
    RecParams rec;
    SideParams side, tail;
    FinalParams fin;
    AttnParams attn;
    __nv_bfloat16 *qkv_tok, *kv_mem, *o_tok, *qkv_b, *o_b;
    uint8_t* xchg;
};
HostState g_host;

void setup(void* const* d_in, void* d_out) {
    HostState& h = g_host;
    void* fn = nullptr;
    cudaDriverEntryPointQueryResult qr;
    cudaGetDriverEntryPoint("cuTensorMapEncodeTiled", &fn, cudaEnableDefault, &qr);
    EncodeFn enc = reinterpret_cast<EncodeFn>(fn);
    void* ptr;
    cudaGetSymbolAddress(&ptr, g_qkv_tok); h.qkv_tok = (__nv_bfloat16*)ptr;
    cudaGetSymbolAddress(&ptr, g_kv_mem);  h.kv_mem = (__nv_bfloat16*)ptr;
    cudaGetSymbolAddress(&ptr, g_o_tok);   h.o_tok = (__nv_bfloat16*)ptr;
    cudaGetSymbolAddress(&ptr, g_qkv_b);   h.qkv_b = (__nv_bfloat16*)ptr;
    cudaGetSymbolAddress(&ptr, g_o_b);     h.o_b = (__nv_bfloat16*)ptr;
    cudaGetSymbolAddress(&ptr, g_xchg);    h.xchg = (uint8_t*)(((uint64_t)ptr + XCHG_BYTES - 1) & ~(uint64_t)(XCHG_BYTES - 1));
    cudaGetSymbolAddress(&ptr, g_flags);   uint32_t* flags = (uint32_t*)ptr;
    cudaGetSymbolAddress(&ptr, g_arrivals); uint32_t* arrivals = (uint32_t*)ptr;

    const void *xa = d_in[0], *mem0 = d_in[1], *wq = d_in[2], *wk = d_in[3], *wv = d_in[4], *wo = d_in[5];
    const void *xb = d_in[7], *wqkv = d_in[8], *wob = d_in[9];

    RecParams& r = h.rec;
    make_map_w(enc, &r.tmW[0], wq);
    make_map_w(enc, &r.tmW[1], wk);
    make_map_w(enc, &r.tmW[2], wv);
    make_map_b(enc, &r.tmWo, wo, HD, DM, 11, 128, 32);
    r.mem0 = (const __nv_bfloat16*)mem0;
    r.qkv_tok = h.qkv_tok; r.kv_mem = h.kv_mem; r.xchg = h.xchg;
    r.flags = flags; r.arrivals = arrivals; r.one[0] = r.one[1] = 1;
    make_map_b(enc, &r.tmX, xa, S_TOK, DM, 4, SEG);

    SideParams& sd = h.side;
    SideProb& p0 = sd.prob[0];
    make_map_2d(enc, &p0.tmA, xb, S_TOK, DM, BM);
    make_map_b(enc, &p0.tmB, wqkv, DM, 3 * DM, 4);
    make_map_2d(enc, &p0.tmC, h.qkv_b, S_TOK, 3 * DM, 16);
    p0.n_tiles = 3 * DM / 256; p0.k_blocks = DM / BK; p0.c_col0 = 0; p0.dep = nullptr; p0.dep_target = 0; p0.dep_n = 1; p0.sig = flags + F_QKVB;
    SideProb& p1 = sd.prob[1];
    make_map_2d(enc, &p1.tmA, h.o_tok, S_TOK, HD, BM);
    make_map_b(enc, &p1.tmB, wo, HD, DM, 4);
    make_map_2d(enc, &p1.tmC, d_out, S_TOK, 2 * DM, 16);
    p1.n_tiles = DM / 256; p1.k_blocks = HD / BK; p1.c_col0 = 0; p1.dep = flags + F_OA; p1.dep_target = OA_TARGET; p1.dep_n = 4; p1.sig = nullptr;
    SideProb& p2 = sd.prob[2];
    make_map_2d(enc, &p2.tmA, h.o_b, S_TOK, DM, BM);
    make_map_b(enc, &p2.tmB, wob, DM, DM, 4);
    p2.tmC = p1.tmC;
    p2.n_tiles = DM / 256; p2.k_blocks = DM / BK; p2.c_col0 = DM; p2.dep = flags + F_OB; p2.dep_target = OB_TARGET; p2.dep_n = 1; p2.sig = nullptr;
    p0.n_split = p0.n_tiles; p1.n_split = p1.n_tiles; p2.n_split = p2.n_tiles;
    p0.part = p1.part = p2.part = nullptr;
    p0.k_total = p0.k_blocks; p1.k_total = p1.k_blocks; p2.k_total = p2.k_blocks;
    if (SIDE_ORDER == 0) { sd.seg[0] = {0, 0, 16}; sd.seg[1] = {1, 0, TAIL_BLOCK0}; }
    else { sd.seg[0] = {1, 0, TAIL_BLOCK0}; sd.seg[1] = {0, 0, 16}; }
    sd.seg[2] = {2, 0, 16};
    sd.nseg = 3; sd.queue = flags + F_SIDEQ; sd.spare_seg = 3; sd.flags = flags;

    SideParams& tl = h.tail;
    tl.prob[0] = p1;
    make_map_b(enc, &tl.prob[0].tmB, wo, HD, DM, 2);
    cudaGetSymbolAddress(&ptr, g_part);
    for (int i = 0; i < 3; i++) {
        SideProb& q = tl.prob[i];
        q = tl.prob[0];
        q.n_tiles = (i + 1) * DM / 128; q.n_split = DM / 128; q.k_blocks = i == 0 ? HD / BK : i == 1 ? TAIL_KB2 : TAIL_KB3;
        q.part = i ? (float*)ptr : nullptr; q.part_flag = flags + F_PART;
    }
    tl.seg[0] = {0, TAIL_BLOCK0, TAIL_BLOCK1};
    tl.seg[1] = {1, TAIL_BLOCK1, TAIL_BLOCK2};
    tl.seg[2] = {2, TAIL_BLOCK2, 15};
    tl.nseg = 3; tl.queue = flags + F_TAILQ; tl.spare_seg = TAIL_SPARE; tl.flags = flags;

    make_map_2d(enc, &h.fin.tmA, h.o_tok, S_TOK, HD, SEG);
    h.fin.tmB = tl.prob[0].tmB; h.fin.out = (__nv_bfloat16*)d_out;
    h.fin.dep = flags + F_OA + 60; h.fin.dep_target = OA_TARGET; h.fin.mt = 15;

    make_map_2d(enc, &h.attn.tmOa, h.o_tok, S_TOK, HD, 16);
    make_map_parity(enc, &h.attn.tmQb, h.qkv_b, 3 * DM, 64);
    make_map_parity(enc, &h.attn.tmKb, h.qkv_b, 3 * DM, 72);
    make_map_parity(enc, &h.attn.tmOb, h.o_b, DM, 64);
    h.attn.qkv_tok = h.qkv_tok; h.attn.kv_mem = h.kv_mem; h.attn.flags = flags;

    int dev = 0, nsm = 0;
    cudaGetDevice(&dev);
    cudaDeviceGetAttribute(&nsm, cudaDevAttrMultiProcessorCount, dev);
    h.n_sm = nsm;
    h.overlap = nsm - 96 >= N_SIDE_CTAS + N_ATT_CTAS;
    h.n_side = N_SIDE_CTAS; h.n_att = N_ATT_CTAS;
    h.seq_a = sd;
    h.seq_a.seg[0] = {0, 0, 16};
    h.seq_a.nseg = 1;
    h.seq_b = sd;
    h.seq_b.seg[0] = {1, 0, 16};
    h.seq_b.seg[1] = {2, 0, 16};
    h.seq_b.nseg = 2; h.seq_b.queue = flags + F_TAILQ;

    cudaFuncSetAttribute(side_gemm_kernel<256>, cudaFuncAttributeMaxDynamicSharedMemorySize, GemmCfg<256>::SMEM);
    cudaFuncSetAttribute(side_gemm_kernel<128>, cudaFuncAttributeMaxDynamicSharedMemorySize, GemmCfg<128>::SMEM);
    cudaFuncSetAttribute(final_gemm_kernel, cudaFuncAttributeMaxDynamicSharedMemorySize, FIN_SMEM);
    cudaFuncSetAttribute(rec_kernel, cudaFuncAttributeMaxDynamicSharedMemorySize, REC_SMEM);
    cudaFuncSetAttribute(attn_kernel, cudaFuncAttributeMaxDynamicSharedMemorySize, ATT_SMEM);
    for (int i = 0; i < 10; i++) h.key[i] = d_in[i];
    h.key[10] = d_out;
    h.ready = true;
}

template <typename K, typename P>
void launch(K kernel, int grid, int block, int smem, cudaStream_t st, const P& prm, int cluster, bool pdl) {
    cudaLaunchConfig_t cfg = {};
    cfg.gridDim = dim3(grid); cfg.blockDim = dim3(block); cfg.dynamicSmemBytes = smem; cfg.stream = st;
    cudaLaunchAttribute at[2];
    int n = 0;
    if (cluster > 1) {
        at[n].id = cudaLaunchAttributeClusterDimension;
        at[n].val.clusterDim.x = cluster; at[n].val.clusterDim.y = 1; at[n].val.clusterDim.z = 1;
        n++;
    }
    if (pdl) {
        at[n].id = cudaLaunchAttributeProgrammaticStreamSerialization;
        at[n].val.programmaticStreamSerializationAllowed = 1;
        n++;
    }
    cfg.attrs = at; cfg.numAttrs = n;
    cudaLaunchKernelEx(&cfg, kernel, prm);
}

}

extern "C" void kernel_launch(void* const* d_in, const int* in_sizes, int n_in, void* d_out, int out_size) {
    HostState& h = g_host;
    bool same = h.ready;
    for (int i = 0; same && i < 10; i++) same = h.key[i] == d_in[i];
    if (!same || h.key[10] != d_out) setup(d_in, d_out);
    cudaStream_t st = cudaStreamPerThread;

    launch(rec_kernel, 96, REC_THREADS, REC_SMEM, st, h.rec, 3, false);
    {
        if (!h.overlap) {
            launch(side_gemm_kernel<256>, h.n_sm, 384, GemmCfg<256>::SMEM, st, h.seq_a, 1, false);
            launch(attn_kernel, SERIAL_ATT_CTAS, ATT_THREADS, ATT_SMEM, st, h.attn, 1, false);
            launch(side_gemm_kernel<256>, h.n_sm, 384, GemmCfg<256>::SMEM, st, h.seq_b, 1, false);
            return;
        }
    }
    launch(side_gemm_kernel<256>, h.n_side, 384, GemmCfg<256>::SMEM, st, h.side, 1, true);
    launch(attn_kernel, h.n_att, ATT_THREADS, ATT_SMEM, st, h.attn, 1, true);
    launch(side_gemm_kernel<128>, N_TAIL_CTAS, 384, GemmCfg<128>::SMEM, st, h.tail, 1, true);
    launch(final_gemm_kernel, 8 * FIN_SPLIT, 384, FIN_SMEM, st, h.fin, FIN_SPLIT, true);
}
```

```cpp
#include <cuda_runtime.h>
#include <cuda_bf16.h>
#include <cuda.h>
#include <stdint.h>

namespace {

constexpr int S_TOK = 2048;
constexpr int DM = 1024;
constexpr int NH = 32;
constexpr int DH = 128;
constexpr int HD = NH * DH;
constexpr int NSEG = 64;
constexpr int SEG = 32;
constexpr int MROWS = 8;
constexpr uint32_t SENT = 0xFFFFFFFFu;
constexpr uint32_t SPIN_LIMIT = 1u << 24;

__device__ __align__(1024) __nv_bfloat16 g_qkv_tok[3ull * NSEG * NH * SEG * DH];
__device__ __align__(1024) __nv_bfloat16 g_kv_mem[2ull * NSEG * NH * MROWS * DH];
__device__ __align__(1024) __nv_bfloat16 g_o_tok[(size_t)S_TOK * HD];
__device__ __align__(1024) __nv_bfloat16 g_qkv_b[(size_t)S_TOK * 3 * DM];
__device__ __align__(1024) __nv_bfloat16 g_o_b[(size_t)S_TOK * DM];
__device__ __align__(1024) float g_part[32 * 2 * 128 * 128];
constexpr int PUB_BYTES = 32768;
constexpr int XCHG_SLOT = 1 << 20;
constexpr int XCHG_PUB = 0, XCHG_INBOX = 2 * PUB_BYTES;
constexpr int INBOX_MAX = 80;
constexpr int XCHG_BYTES = 2 * XCHG_SLOT;
__device__ __align__(8192) uint8_t g_xchg[2 * XCHG_BYTES];
enum { F_LASTTOK = 0, F_RECSM = 4, F_PROGRESS = 16, F_QKVB = 80, F_OB = 96, F_OA = 112, F_PART = 176, F_SIDEQ = 208, F_TAILQ = 256, F_COUNT = 304 };
__device__ uint32_t g_flags[F_COUNT];
__device__ __align__(16) uint32_t g_arrivals[4];

#define STAMP(k) do {} while (0)
#define STAMPD(k, x) do {} while (0)
#define PSTAMP(k) do {} while (0)
#define KENTER(k) do {} while (0)
#define KEXIT(k) do {} while (0)
#define KMARK(k) do {} while (0)

__device__ __forceinline__ uint32_t class_off(uint64_t a, uint32_t c) {
    return ((__popc((uint32_t)a & 0xB3000u) ^ c) & 1u) << 12;
}
__device__ __forceinline__ uint32_t smem_u32(const void* p) { return (uint32_t)__cvta_generic_to_shared(p); }
__device__ __forceinline__ uint32_t pack_bf16(float lo, float hi) {
    uint32_t r;
    asm("cvt.rn.bf16x2.f32 %0, %1, %2;" : "=r"(r) : "f"(hi), "f"(lo));
    return r;
}
__device__ __forceinline__ float ex2(float x) {
    float y;
    asm("ex2.approx.ftz.f32 %0, %1;" : "=f"(y) : "f"(x));
    return y;
}
__device__ __forceinline__ float rcp(float x) {
    float y;
    asm("rcp.approx.ftz.f32 %0, %1;" : "=f"(y) : "f"(x));
    return y;
}
__device__ __forceinline__ uint32_t clock32() {
    uint32_t t;
    asm volatile("mov.u32 %0, %%clock;" : "=r"(t));
    return t;
}
__device__ __forceinline__ void spin_clks(uint32_t n) {
    if (n == 0) return;
    const uint32_t t0 = clock32();
    while (clock32() - t0 < n) {}
}
__device__ __forceinline__ void spin_until(uint32_t t) {
    while ((int)(clock32() - t) < 0) {}
}
__device__ __forceinline__ uint32_t clock_after(uint32_t x) {
    uint32_t t;
    asm volatile("{\n.reg .pred p;\nsetp.eq.u32 p, %1, 0x12345678;\n@p exit;\nmov.u32 %0, %%clock;\n}" : "=r"(t) : "r"(x) : "memory");
    return t;
}
__device__ __forceinline__ uint32_t opaque(uint32_t x) { return __shfl_sync(~0u, x, threadIdx.x & 31); }
__device__ __forceinline__ uint32_t uniform(uint32_t x) { return __shfl_sync(~0u, x + (threadIdx.x & 31), 0); }
__device__ __forceinline__ float bf16_lo(uint32_t w) { return __uint_as_float(w << 16); }
__device__ __forceinline__ float bf16_hi(uint32_t w) { return __uint_as_float(w & 0xFFFF0000u); }

__device__ __forceinline__ void mbar_init(uint32_t bar, uint32_t cnt) {
    asm volatile("mbarrier.init.shared::cta.b64 [%0], %1;" ::"r"(bar), "r"(cnt) : "memory");
}
__device__ __forceinline__ void mbar_arrive(uint32_t bar) {
    asm volatile("mbarrier.arrive.shared::cta.b64 _, [%0];" ::"r"(bar) : "memory");
}
__device__ __forceinline__ void mbar_arrive_expect_tx(uint32_t bar, uint32_t bytes) {
    asm volatile("mbarrier.arrive.expect_tx.shared::cta.b64 _, [%0], %1;" ::"r"(bar), "r"(bytes) : "memory");
}
__device__ __forceinline__ bool mbar_try_wait(uint32_t bar, uint32_t parity) {
    uint32_t ok;
    asm volatile(
        "{\n.reg .pred p;\n"
        "mbarrier.try_wait.parity.shared::cta.b64 p, [%1], %2;\n"
        "selp.u32 %0, 1, 0, p;\n}"
        : "=r"(ok) : "r"(bar), "r"(parity) : "memory");
    return ok != 0;
}
__device__ __forceinline__ bool mbar_test_wait(uint32_t bar, uint32_t parity) {
    uint32_t ok;
    asm volatile(
        "{\n.reg .pred p;\n"
        "mbarrier.test_wait.parity.shared::cta.b64 p, [%1], %2;\n"
        "selp.u32 %0, 1, 0, p;\n}"
        : "=r"(ok) : "r"(bar), "r"(parity) : "memory");
    return ok != 0;
}
__device__ __forceinline__ void mbar_wait(uint32_t bar, uint32_t parity) {
    uint32_t n = 0;
    while (!mbar_try_wait(bar, parity)) {
        if (++n > SPIN_LIMIT) __trap();
    }
}
__device__ __forceinline__ void mbar_wait_sleep(uint32_t bar, uint32_t parity) {
    uint32_t n = 0;
    while (!mbar_try_wait(bar, parity)) {
        __nanosleep(20);
        if (++n > SPIN_LIMIT) __trap();
    }
}
__device__ __forceinline__ void mbar_wait_bounded(uint32_t bar, uint32_t parity) {
    for (uint32_t n = 0; n < (1u << 20) && !mbar_try_wait(bar, parity); n++) {}
}
__device__ __forceinline__ bool elect_one() {
    uint32_t ok;
    asm volatile("{\n.reg .pred p;\nelect.sync _|p, 0xFFFFFFFF;\nselp.u32 %0, 1, 0, p;\n}" : "=r"(ok));
    return ok != 0;
}
__device__ __forceinline__ void named_bar_sync(int id, int nthreads) {
    asm volatile("bar.sync %0, %1;" ::"r"(id), "r"(nthreads) : "memory");
}
__device__ __forceinline__ void named_bar_arrive(int id, int nthreads) {
    asm volatile("bar.arrive %0, %1;" ::"r"(id), "r"(nthreads) : "memory");
}
__device__ __forceinline__ uint32_t mapa(uint32_t addr, uint32_t rank) {
    uint32_t r;
    asm volatile("mapa.shared::cluster.u32 %0, %1, %2;" : "=r"(r) : "r"(addr), "r"(rank));
    return r;
}

__device__ __forceinline__ void tma_load_2d(uint32_t dst, const CUtensorMap* tm, int c0, int c1, uint32_t bar) {
    asm volatile(
        "cp.async.bulk.tensor.2d.shared::cluster.global.mbarrier::complete_tx::bytes [%0], [%1, {%3, %4}], [%2];"
        ::"r"(dst), "l"(tm), "r"(bar), "r"(c0), "r"(c1) : "memory");
}
__device__ __forceinline__ void tma_load_3d(uint32_t dst, const CUtensorMap* tm, int c0, int c1, int c2, uint32_t bar) {
    asm volatile(
        "cp.async.bulk.tensor.3d.shared::cluster.global.mbarrier::complete_tx::bytes [%0], [%1, {%3, %4, %5}], [%2];"
        ::"r"(dst), "l"(tm), "r"(bar), "r"(c0), "r"(c1), "r"(c2) : "memory");
}
__device__ __forceinline__ void tma_load_3d_mc(uint32_t dst, const CUtensorMap* tm, int c0, int c1, int c2, uint32_t bar, uint16_t mask) {
    asm volatile(
        "cp.async.bulk.tensor.3d.shared::cluster.global.mbarrier::complete_tx::bytes.multicast::cluster [%0], [%1, {%3, %4, %5}], [%2], %6;"
        ::"r"(dst), "l"(tm), "r"(bar), "r"(c0), "r"(c1), "r"(c2), "h"(mask) : "memory");
}
__device__ __forceinline__ void tma_store_2d(const CUtensorMap* tm, uint32_t src, int c0, int c1) {
    asm volatile("cp.async.bulk.tensor.2d.global.shared::cta.bulk_group [%0, {%2, %3}], [%1];"
                 ::"l"(tm), "r"(src), "r"(c0), "r"(c1) : "memory");
}
__device__ __forceinline__ void bulk_store(void* dst, uint32_t src, uint32_t bytes) {
    asm volatile("cp.async.bulk.global.shared::cta.bulk_group [%0], [%1], %2;" ::"l"(dst), "r"(src), "r"(bytes) : "memory");
}
__device__ __forceinline__ void bulk_commit() { asm volatile("cp.async.bulk.commit_group;" ::: "memory"); }
__device__ __forceinline__ void bulk_wait_read_all() { asm volatile("cp.async.bulk.wait_group.read 0;" ::: "memory"); }
__device__ __forceinline__ void bulk_wait_all() { asm volatile("cp.async.bulk.wait_group 0;" ::: "memory"); }
__device__ __forceinline__ void bulk_load(uint32_t dst, const void* src, uint32_t bytes, uint32_t bar) {
    asm volatile("cp.async.bulk.shared::cluster.global.mbarrier::complete_tx::bytes [%0], [%1], %2, [%3];"
                 ::"r"(dst), "l"(src), "r"(bytes), "r"(bar) : "memory");
}

__device__ __forceinline__ void ldsm_x4(uint32_t addr, uint32_t& r0, uint32_t& r1, uint32_t& r2, uint32_t& r3) {
    asm volatile("ldmatrix.sync.aligned.m8n8.x4.shared.b16 {%0,%1,%2,%3}, [%4];"
                 : "=r"(r0), "=r"(r1), "=r"(r2), "=r"(r3) : "r"(addr) : "memory");
}
__device__ __forceinline__ void ldsm_x4_t(uint32_t addr, uint32_t& r0, uint32_t& r1, uint32_t& r2, uint32_t& r3) {
    asm volatile("ldmatrix.sync.aligned.m8n8.x4.trans.shared.b16 {%0,%1,%2,%3}, [%4];"
                 : "=r"(r0), "=r"(r1), "=r"(r2), "=r"(r3) : "r"(addr) : "memory");
}
__device__ __forceinline__ void stsm_x4(uint32_t addr, uint32_t r0, uint32_t r1, uint32_t r2, uint32_t r3) {
    asm volatile("stmatrix.sync.aligned.m8n8.x4.shared.b16 [%0], {%1,%2,%3,%4};"
                 ::"r"(addr), "r"(r0), "r"(r1), "r"(r2), "r"(r3) : "memory");
}
__device__ __forceinline__ void mma16816(float* d, uint32_t a0, uint32_t a1, uint32_t a2, uint32_t a3,
                                         uint32_t b0, uint32_t b1) {
    asm volatile(
        "mma.sync.aligned.m16n8k16.row.col.f32.bf16.bf16.f32 {%0,%1,%2,%3}, {%4,%5,%6,%7}, {%8,%9}, {%0,%1,%2,%3};"
        : "+f"(d[0]), "+f"(d[1]), "+f"(d[2]), "+f"(d[3])
        : "r"(a0), "r"(a1), "r"(a2), "r"(a3), "r"(b0), "r"(b1));
}
__device__ __forceinline__ void mma1688(float* d, uint32_t a0, uint32_t a1, uint32_t b0) {
    asm volatile("mma.sync.aligned.m16n8k8.row.col.f32.bf16.bf16.f32 {%0,%1,%2,%3}, {%4,%5}, {%6}, {%0,%1,%2,%3};"
                 : "+f"(d[0]), "+f"(d[1]), "+f"(d[2]), "+f"(d[3]) : "r"(a0), "r"(a1), "r"(b0));
}
__device__ __forceinline__ uint2 lds64(uint32_t addr) {
    uint2 v;
    asm volatile("ld.volatile.shared.v2.b32 {%0,%1}, [%2];" : "=r"(v.x), "=r"(v.y) : "r"(addr) : "memory");
    return v;
}
__device__ __forceinline__ uint4 lds128(uint32_t addr) {
    uint4 v;
    asm volatile("ld.volatile.shared.v4.b32 {%0,%1,%2,%3}, [%4];" : "=r"(v.x), "=r"(v.y), "=r"(v.z), "=r"(v.w) : "r"(addr) : "memory");
    return v;
}
__device__ __forceinline__ void sts32(uint32_t addr, uint32_t x) {
    asm volatile("st.volatile.shared.b32 [%0], %1;" ::"r"(addr), "r"(x) : "memory");
}
__device__ __forceinline__ void sts64(uint32_t addr, uint32_t x, uint32_t y) {
    asm volatile("st.volatile.shared.v2.b32 [%0], {%1,%2};" ::"r"(addr), "r"(x), "r"(y) : "memory");
}
__device__ __forceinline__ void sts128(uint32_t addr, uint32_t x, uint32_t y, uint32_t z, uint32_t w) {
    asm volatile("st.volatile.shared.v4.b32 [%0], {%1,%2,%3,%4};" ::"r"(addr), "r"(x), "r"(y), "r"(z), "r"(w) : "memory");
}
__device__ __forceinline__ void st_async_v2(uint32_t addr, uint32_t x, uint32_t y, uint32_t bar) {
    asm volatile("st.async.weak.shared::cluster.mbarrier::complete_tx::bytes.v2.b32 [%0], {%1,%2}, [%3];"
                 ::"r"(addr), "r"(x), "r"(y), "r"(bar) : "memory");
}
__device__ __forceinline__ void st_relaxed_v4(void* p, uint32_t x) {
    asm volatile("st.relaxed.gpu.global.v4.b32 [%0], {%1,%1,%1,%1};" ::"l"(p), "r"(x) : "memory");
}
__device__ __forceinline__ uint32_t ld_relaxed_b32(const void* p) {
    uint32_t v;
    asm volatile("ld.relaxed.gpu.global.b32 %0, [%1];" : "=r"(v) : "l"(p) : "memory");
    return v;
}
__device__ __forceinline__ uint32_t lds32_volatile(uint32_t addr) {
    uint32_t v;
    asm volatile("ld.volatile.shared.b32 %0, [%1];" : "=r"(v) : "r"(addr) : "memory");
    return v;
}
__device__ __forceinline__ void st_relaxed_b32(void* p, uint32_t x) {
    asm volatile("st.relaxed.gpu.global.b32 [%0], %1;" ::"l"(p), "r"(x) : "memory");
}

__device__ __forceinline__ uint32_t ld_acquire_b32(const void* p) {
    uint32_t v;
    asm volatile("ld.acquire.gpu.global.b32 %0, [%1];" : "=r"(v) : "l"(p) : "memory");
    return v;
}
__device__ __forceinline__ void wait_flag(const uint32_t* p, uint32_t target) {
    uint32_t n = 0;
    while (ld_acquire_b32(p) < target) {
        __nanosleep(64);
        if (++n > SPIN_LIMIT) __trap();
    }
}
__device__ __forceinline__ void signal_flag(uint32_t* p) {
    asm volatile("red.release.gpu.global.add.u32 [%0], 1;" ::"l"(p) : "memory");
}
__device__ __forceinline__ void signal_bulk(uint32_t* p) {
    asm volatile("red.relaxed.gpu.global.add.u32 [%0], 1;" ::"l"(p) : "memory");
}
__device__ __forceinline__ bool next_to_rec(const uint32_t* flags) {
    uint32_t smid;
    asm volatile("mov.u32 %0, %%smid;" : "=r"(smid));
    smid ^= 1;
    return smid < 384 && ((ld_relaxed_b32(flags + F_RECSM + (smid >> 5)) >> (smid & 31)) & 1);
}
__device__ __forceinline__ void pdl_launch_dependents() { asm volatile("griddepcontrol.launch_dependents;" ::: "memory"); }

constexpr int BM = 128, BK = 64;
constexpr int A_STAGE = BM * BK * 2;
template <int BN> struct GemmCfg {
    static constexpr int STAGES = BN == 256 ? 3 : 6;
    static constexpr int STAGE = A_STAGE + BK * BN * 2;
    static constexpr int EPI_WARP = 16 * BN * 2;
    static constexpr int SMEM = STAGES * STAGE + 8 * EPI_WARP + 1024 + 512;
};

struct SideProb {
    CUtensorMap tmA, tmB, tmC;
    int n_split;
    int n_tiles, k_blocks, k_total, c_col0;
    const uint32_t* dep;
    uint32_t dep_target;
    int dep_n;
    uint32_t* sig;
    float* part;
    uint32_t* part_flag;
};
struct SideSeg { int prob, m0, m1; };
constexpr int SIDE_MAX_SEG = 3;
struct SideParams {
    SideProb prob[3];
    SideSeg seg[SIDE_MAX_SEG];
    int nseg;
    int spare_seg;
    const uint32_t* flags;
    uint32_t* queue;
};
static_assert(sizeof(SideParams) <= 4096, "kernel parameter limit");

__device__ __forceinline__ uint64_t make_desc(uint32_t addr, uint32_t lbo, uint32_t sbo) {
    return (uint64_t)((addr & 0x3FFFF) >> 4) | ((uint64_t)(lbo >> 4) << 16) | ((uint64_t)(sbo >> 4) << 32) | (1ull << 62);
}

__device__ __forceinline__ void wgmma_m64n256k16(float (&d)[128], uint64_t da, uint64_t db, int scale_d) {
    asm volatile(
        "{\n.reg .pred p;\nsetp.ne.b32 p, %130, 0;\n"
        "wgmma.mma_async.sync.aligned.m64n256k16.f32.bf16.bf16 "
        "{%0,%1,%2,%3,%4,%5,%6,%7,%8,%9,%10,%11,%12,%13,%14,%15,"
        "%16,%17,%18,%19,%20,%21,%22,%23,%24,%25,%26,%27,%28,%29,%30,%31,"
        "%32,%33,%34,%35,%36,%37,%38,%39,%40,%41,%42,%43,%44,%45,%46,%47,"
        "%48,%49,%50,%51,%52,%53,%54,%55,%56,%57,%58,%59,%60,%61,%62,%63,"
        "%64,%65,%66,%67,%68,%69,%70,%71,%72,%73,%74,%75,%76,%77,%78,%79,"
        "%80,%81,%82,%83,%84,%85,%86,%87,%88,%89,%90,%91,%92,%93,%94,%95,"
        "%96,%97,%98,%99,%100,%101,%102,%103,%104,%105,%106,%107,%108,%109,%110,%111,"
        "%112,%113,%114,%115,%116,%117,%118,%119,%120,%121,%122,%123,%124,%125,%126,%127},"
        " %128, %129, p, 1, 1, 0, 1;\n}\n"
        : "+f"(d[0]), "+f"(d[1]), "+f"(d[2]), "+f"(d[3]), "+f"(d[4]), "+f"(d[5]), "+f"(d[6]), "+f"(d[7]),
          "+f"(d[8]), "+f"(d[9]), "+f"(d[10]), "+f"(d[11]), "+f"(d[12]), "+f"(d[13]), "+f"(d[14]), "+f"(d[15]),
          "+f"(d[16]), "+f"(d[17]), "+f"(d[18]), "+f"(d[19]), "+f"(d[20]), "+f"(d[21]), "+f"(d[22]), "+f"(d[23]),
          "+f"(d[24]), "+f"(d[25]), "+f"(d[26]), "+f"(d[27]), "+f"(d[28]), "+f"(d[29]), "+f"(d[30]), "+f"(d[31]),
          "+f"(d[32]), "+f"(d[33]), "+f"(d[34]), "+f"(d[35]), "+f"(d[36]), "+f"(d[37]), "+f"(d[38]), "+f"(d[39]),
          "+f"(d[40]), "+f"(d[41]), "+f"(d[42]), "+f"(d[43]), "+f"(d[44]), "+f"(d[45]), "+f"(d[46]), "+f"(d[47]),
          "+f"(d[48]), "+f"(d[49]), "+f"(d[50]), "+f"(d[51]), "+f"(d[52]), "+f"(d[53]), "+f"(d[54]), "+f"(d[55]),
          "+f"(d[56]), "+f"(d[57]), "+f"(d[58]), "+f"(d[59]), "+f"(d[60]), "+f"(d[61]), "+f"(d[62]), "+f"(d[63]),
          "+f"(d[64]), "+f"(d[65]), "+f"(d[66]), "+f"(d[67]), "+f"(d[68]), "+f"(d[69]), "+f"(d[70]), "+f"(d[71]),
          "+f"(d[72]), "+f"(d[73]), "+f"(d[74]), "+f"(d[75]), "+f"(d[76]), "+f"(d[77]), "+f"(d[78]), "+f"(d[79]),
          "+f"(d[80]), "+f"(d[81]), "+f"(d[82]), "+f"(d[83]), "+f"(d[84]), "+f"(d[85]), "+f"(d[86]), "+f"(d[87]),
          "+f"(d[88]), "+f"(d[89]), "+f"(d[90]), "+f"(d[91]), "+f"(d[92]), "+f"(d[93]), "+f"(d[94]), "+f"(d[95]),
          "+f"(d[96]), "+f"(d[97]), "+f"(d[98]), "+f"(d[99]), "+f"(d[100]), "+f"(d[101]), "+f"(d[102]), "+f"(d[103]),
          "+f"(d[104]), "+f"(d[105]), "+f"(d[106]), "+f"(d[107]), "+f"(d[108]), "+f"(d[109]), "+f"(d[110]), "+f"(d[111]),
          "+f"(d[112]), "+f"(d[113]), "+f"(d[114]), "+f"(d[115]), "+f"(d[116]), "+f"(d[117]), "+f"(d[118]), "+f"(d[119]),
          "+f"(d[120]), "+f"(d[121]), "+f"(d[122]), "+f"(d[123]), "+f"(d[124]), "+f"(d[125]), "+f"(d[126]), "+f"(d[127])
        : "l"(da), "l"(db), "r"(scale_d));
}

__device__ __forceinline__ void wgmma_m64n128k16(float (&d)[64], uint64_t da, uint64_t db, int scale_d) {
    asm volatile(
        "{\n.reg .pred p;\nsetp.ne.b32 p, %66, 0;\n"
        "wgmma.mma_async.sync.aligned.m64n128k16.f32.bf16.bf16 "
        "{%0,%1,%2,%3,%4,%5,%6,%7,%8,%9,%10,%11,%12,%13,%14,%15,"
        "%16,%17,%18,%19,%20,%21,%22,%23,%24,%25,%26,%27,%28,%29,%30,%31,"
        "%32,%33,%34,%35,%36,%37,%38,%39,%40,%41,%42,%43,%44,%45,%46,%47,"
        "%48,%49,%50,%51,%52,%53,%54,%55,%56,%57,%58,%59,%60,%61,%62,%63},"
        " %64, %65, p, 1, 1, 0, 1;\n}\n"
        : "+f"(d[0]), "+f"(d[1]), "+f"(d[2]), "+f"(d[3]), "+f"(d[4]), "+f"(d[5]), "+f"(d[6]), "+f"(d[7]),
          "+f"(d[8]), "+f"(d[9]), "+f"(d[10]), "+f"(d[11]), "+f"(d[12]), "+f"(d[13]), "+f"(d[14]), "+f"(d[15]),
          "+f"(d[16]), "+f"(d[17]), "+f"(d[18]), "+f"(d[19]), "+f"(d[20]), "+f"(d[21]), "+f"(d[22]), "+f"(d[23]),
          "+f"(d[24]), "+f"(d[25]), "+f"(d[26]), "+f"(d[27]), "+f"(d[28]), "+f"(d[29]), "+f"(d[30]), "+f"(d[31]),
          "+f"(d[32]), "+f"(d[33]), "+f"(d[34]), "+f"(d[35]), "+f"(d[36]), "+f"(d[37]), "+f"(d[38]), "+f"(d[39]),
          "+f"(d[40]), "+f"(d[41]), "+f"(d[42]), "+f"(d[43]), "+f"(d[44]), "+f"(d[45]), "+f"(d[46]), "+f"(d[47]),
          "+f"(d[48]), "+f"(d[49]), "+f"(d[50]), "+f"(d[51]), "+f"(d[52]), "+f"(d[53]), "+f"(d[54]), "+f"(d[55]),
          "+f"(d[56]), "+f"(d[57]), "+f"(d[58]), "+f"(d[59]), "+f"(d[60]), "+f"(d[61]), "+f"(d[62]), "+f"(d[63])
        : "l"(da), "l"(db), "r"(scale_d));
}
template <int BN> struct WgmmaOp;
template <> struct WgmmaOp<256> {
    static __device__ __forceinline__ void run(float (&d)[128], uint64_t a, uint64_t b, int sc) { wgmma_m64n256k16(d, a, b, sc); }
};
template <> struct WgmmaOp<128> {
    static __device__ __forceinline__ void run(float (&d)[64], uint64_t a, uint64_t b, int sc) { wgmma_m64n128k16(d, a, b, sc); }
};

struct StoreRec {
    uint64_t dst;
    uint64_t flag;
    int kind;
    int pad;
};
struct EpiCtx { uint32_t buf, rec, st_full, st_empty; uint32_t it; int lane; };
template <int N>
__device__ __forceinline__ void epi_hand_over(const float (&acc)[N], EpiCtx& e, uint64_t dst, uint64_t flag, int kind) {
    mbar_wait(e.st_empty, (e.it & 1) ^ 1);
    const int mi = e.lane >> 3, row = (mi & 1) * 8 + (e.lane & 7);
    #pragma unroll
    for (int j = 0; j < N / 4; j += 2) {
        const int chunk = (j & 7) + (mi >> 1);
        stsm_x4(e.buf + (j >> 3) * 2048 + row * 128 + ((chunk ^ (row & 7)) << 4),
                pack_bf16(acc[4 * j], acc[4 * j + 1]), pack_bf16(acc[4 * j + 2], acc[4 * j + 3]),
                pack_bf16(acc[4 * j + 4], acc[4 * j + 5]), pack_bf16(acc[4 * j + 6], acc[4 * j + 7]));
    }
    if (e.lane == 0) {
        asm volatile("st.shared.v2.b64 [%0], {%1, %2};" ::"r"(e.rec), "l"(dst), "l"(flag) : "memory");
        asm volatile("st.shared.b32 [%0], %1;" ::"r"(e.rec + 16), "r"(kind) : "memory");
    }
    asm volatile("fence.proxy.async.shared::cta;" ::: "memory");
    __syncwarp();
    if (e.lane == 0) mbar_arrive(e.st_full);
    e.it++;
}
__device__ __forceinline__ void epi_exit(EpiCtx& e) {
    mbar_wait(e.st_empty, (e.it & 1) ^ 1);
    if (e.lane == 0) {
        asm volatile("st.shared.b32 [%0], %1;" ::"r"(e.rec + 16), "r"(-1) : "memory");
        mbar_arrive(e.st_full);
    }
}
template <int BN>
__device__ __forceinline__ void gemm_mainloop(float (&acc)[BN / 2], int k_blocks, uint32_t sbase, uint32_t bar_base, int cw,
                                              bool elected, int& stage, uint32_t& phase) {
    using C = GemmCfg<BN>;
    auto release = [&](int st) { mbar_arrive(bar_base + 8 * (C::STAGES + st)); };
    int prev_stage = -1;
    for (int kb = 0; kb < k_blocks; kb++) {
        mbar_wait(bar_base + 8 * stage, phase);
        const uint32_t sa = sbase + stage * C::STAGE + cw * (64 * 128);
        const uint32_t sb = sbase + stage * C::STAGE + A_STAGE;
        asm volatile("wgmma.fence.sync.aligned;" ::: "memory");
        #pragma unroll
        for (int kk = 0; kk < BK / 16; kk++)
            WgmmaOp<BN>::run(acc, make_desc(sa + kk * 32, 16, 1024), make_desc(sb + kk * 2048, 8192, 1024), (kb | kk) != 0);
        asm volatile("wgmma.commit_group.sync.aligned;" ::: "memory");
        asm volatile("wgmma.wait_group.sync.aligned 1;" ::: "memory");
        if (prev_stage >= 0 && elected) release(prev_stage);
        prev_stage = stage;
        if (++stage == C::STAGES) { stage = 0; phase ^= 1; }
    }
    asm volatile("wgmma.wait_group.sync.aligned 0;" ::: "memory");
    if (elected) release(prev_stage);
}
template <int BN>
__device__ __forceinline__ void store_warp(uint32_t epi_base, uint32_t rec_base, uint32_t st_full, uint32_t st_empty, int lane,
                                           const uint8_t* tmaps, int tstride) {
    for (uint32_t it = 0;; it++) {
        mbar_wait(st_full, it & 1);
        uint64_t dst = 0, flag = 0;
        int kind = -1;
        if (lane < 8) {
            const uint32_t rec = rec_base + lane * 32;
            asm volatile("ld.volatile.shared.v2.b64 {%0, %1}, [%2];" : "=l"(dst), "=l"(flag) : "r"(rec) : "memory");
            kind = (int)lds32_volatile(rec + 16);
        }
        if (__shfl_sync(~0u, kind, 0) < 0) break;
        if (lane < 8) {
            const uint32_t buf = epi_base + lane * GemmCfg<BN>::EPI_WARP;
            #pragma unroll
            for (int q = 0; q < BN / 64; q++) {
                tma_store_2d(reinterpret_cast<const CUtensorMap*>(tmaps + (kind - 1) * tstride), buf + q * 2048,
                                  (int)(uint32_t)dst + q * 64, (int)(dst >> 32));
            }
            bulk_commit();
            bulk_wait_read_all();
            mbar_arrive(st_empty);
            if (flag) {
                bulk_wait_all();
                signal_bulk(reinterpret_cast<uint32_t*>(flag));
            }
        }
        __syncwarp();
    }
    if (lane < 8) bulk_wait_all();
}

#define SCHED_AHEAD 4
template <int BN>
__global__ void __launch_bounds__(384, 1) side_gemm_kernel(const __grid_constant__ SideParams p) {
    using C = GemmCfg<BN>;
    extern __shared__ uint8_t smem_raw[];
    const uint32_t sbase = (smem_u32(smem_raw) + 1023) & ~1023u;
    const uint32_t epi_base = sbase + C::STAGES * C::STAGE;
    const uint32_t bar_base = epi_base + 8 * C::EPI_WARP;
    const uint32_t tfull = bar_base + 16 * C::STAGES, tempty = tfull + 16, tslot = tempty + 16, twant = tslot + 8;
    const uint32_t st_full = bar_base + 192, st_empty = st_full + 8, rec_base = bar_base + 256;
    const int tid = threadIdx.x, wg = tid >> 7;
    if (tid == 0) {
        for (int s = 0; s < C::STAGES; s++) { mbar_init(bar_base + 8 * s, 1); mbar_init(bar_base + 8 * (C::STAGES + s), 2); }
        for (int s = 0; s < 2; s++) { mbar_init(tfull + 8 * s, 1); mbar_init(tempty + 8 * s, 3); }
        mbar_init(twant, 1);
        mbar_init(st_full, 8);
        mbar_init(st_empty, 8);
        asm volatile("fence.mbarrier_init.release.cluster;" ::: "memory");
        pdl_launch_dependents();
    }
    __syncthreads();
    KENTER(BN == 256 ? 2 : 4);

    if (wg == 0) {
        asm volatile("setmaxnreg.dec.sync.aligned.u32 40;");
        if (tid == 0) {
            int stage = 0; uint32_t phase = 1;
            for (uint32_t it = 0;; it++) {
                mbar_wait(tfull + 8 * (it & 1), (it >> 1) & 1);
                const int code = (int)lds32_volatile(tslot + 4 * (it & 1));
                mbar_arrive(tempty + 8 * (it & 1));
                if (code < 0) break;
                const SideProb& q = p.prob[code >> 16];
                const int mt = (code >> 8) & 255, nt = code & 255;
                asm volatile("fence.proxy.async.global;" ::: "memory");
                const int kb0 = nt / q.n_split * q.k_blocks, nkb = nt + q.n_split < q.n_tiles ? q.k_blocks : q.k_total - kb0;
                for (int kb = 0; kb < nkb; kb++) {
                    if (kb == nkb - SCHED_AHEAD) mbar_arrive(twant);
                    mbar_wait(bar_base + 8 * (C::STAGES + stage), phase);
                    const uint32_t sa = sbase + stage * C::STAGE, fb = bar_base + 8 * stage;
                    mbar_arrive_expect_tx(fb, C::STAGE);
                    const int k0 = (kb0 + kb) * BK;
                    tma_load_2d(sa, &q.tmA, k0, mt * BM, fb);
                    tma_load_3d(sa + A_STAGE, &q.tmB, 0, k0, nt % q.n_split * (BN / 64), fb);
                    if (++stage == C::STAGES) { stage = 0; phase ^= 1; }
                }
            }
        } else if (tid >= 64 && tid < 96) {
            const int lane = tid & 31;
            const bool spare = p.spare_seg < 3 && next_to_rec(p.flags);
            uint32_t ntl[2], tgt[2], prb[2];
            const uint32_t* dp[2];
            #pragma unroll
            for (int u = 0; u < 2; u++) {
                const int g = u * 2 + (lane >> 4), mt = lane & 15;
                const bool on = g < p.nseg && mt >= p.seg[g < p.nseg ? g : 0].m0 && mt < p.seg[g < p.nseg ? g : 0].m1;
                prb[u] = p.seg[on ? g : 0].prob;
                const SideProb& q = p.prob[prb[u]];
                ntl[u] = on && !(g >= p.spare_seg && spare) ? q.n_tiles : 0;
                tgt[u] = on && q.dep ? q.dep_target : 0;
                dp[u] = tgt[u] ? q.dep + (mt + 1) * q.dep_n - 1 : p.queue;
            }
            for (uint32_t it = 0;; it++) {
                if (it > 0) mbar_wait_sleep(twant, (it - 1) & 1);
                int code = -1;
                for (uint32_t tries = 0; code < 0; tries++) {
                    const uint32_t c0 = ld_relaxed_b32(p.queue + lane), c1 = ld_relaxed_b32(p.queue + 32 + (lane & 15));
                    const uint32_t d0 = ld_relaxed_b32(dp[0]), d1 = ld_relaxed_b32(dp[1]);
                    const uint64_t left = __ballot_sync(~0u, c0 < ntl[0]) | (uint64_t)__ballot_sync(~0u, c1 < ntl[1]) << 32;
                    uint64_t ready = left & (__ballot_sync(~0u, d0 >= tgt[0]) | (uint64_t)__ballot_sync(~0u, d1 >= tgt[1]) << 32);
                    if (!left) break;
                    if (!ready && (BN == 128 || (left >> (((__ffsll(left) - 1) & ~15) + 16)) == 0)) ready = left;
                    if (!ready) __nanosleep(200);
                    while (ready) {
                        const int e = __ffsll(ready) - 1;
                        const uint32_t n = __shfl_sync(~0u, e < 32 ? ntl[0] : ntl[1], e & 31), pr = __shfl_sync(~0u, e < 32 ? prb[0] : prb[1], e & 31);
                        uint32_t idx = 0;
                        if (lane == 0) idx = atomicAdd(p.queue + e, 1u);
                        idx = __shfl_sync(~0u, idx, 0);
                        if (idx < n) { code = (pr << 16) | ((e & 15) << 8) | idx; break; }
                        for (uint32_t k = idx / n; k > 0; k--) ready &= ready - 1;
                    }
                    if (tries > SPIN_LIMIT) __trap();
                }
                if (code >= 0) {
                    const SideProb& q = p.prob[code >> 16];
                    if (q.dep && lane < q.dep_n) wait_flag(q.dep + ((code >> 8) & 255) * q.dep_n + lane, q.dep_target);
                    __syncwarp();
                }
                if (lane == 0) {
                    mbar_wait(tempty + 8 * (it & 1), ((it >> 1) & 1) ^ 1);
                    asm volatile("st.shared.b32 [%0], %1;" ::"r"(tslot + 4 * (it & 1)), "r"(code) : "memory");
                    mbar_arrive(tfull + 8 * (it & 1));
                }
                __syncwarp();
                if (code < 0) break;
            }
        } else if (tid >= 32 && tid < 64) {
            store_warp<BN>(epi_base, rec_base, st_full, st_empty, tid & 31, reinterpret_cast<const uint8_t*>(&p.prob[0].tmC),
                           (int)sizeof(SideProb));
        }
    } else {
        asm volatile("setmaxnreg.inc.sync.aligned.u32 232;");
        const int cw = wg - 1, lane = tid & 31, wi = (tid >> 5) & 3;
        const bool elected = (tid & 127) == 0;
        int stage = 0; uint32_t phase = 0;
        float acc[BN / 2];
        EpiCtx ectx = {epi_base + (cw * 4 + wi) * C::EPI_WARP, rec_base + (cw * 4 + wi) * 32, st_full, st_empty, 0, lane};
        for (uint32_t it = 0;; it++) {
            mbar_wait(tfull + 8 * (it & 1), (it >> 1) & 1);
            const int code = (int)lds32_volatile(tslot + 4 * (it & 1));
            named_bar_sync(1 + cw, 128);
            if (elected) mbar_arrive(tempty + 8 * (it & 1));
            if (code < 0) break;
            const SideProb& q = p.prob[code >> 16];
            const int mt = (code >> 8) & 255, nt = code & 255;
            gemm_mainloop<BN>(acc, nt + q.n_split < q.n_tiles ? q.k_blocks : q.k_total - nt / q.n_split * q.k_blocks, sbase, bar_base, cw, elected, stage, phase);
            const int row0 = mt * BM + cw * 64 + wi * 16, ntc = nt % q.n_split;
            if (BN == 128 && q.part) {
                const int idx = (mt & 3) * q.n_split + ntc, item = nt / q.n_split, nprev = q.n_tiles / q.n_split - 1;
                float4* part = reinterpret_cast<float4*>(q.part) + (size_t)idx * 2 * (BM * BN / 4) + (tid - 128);
                if (mt == 14 && elected) KMARK(21);
                if (item < nprev) {
                    #pragma unroll
                    for (int j = 0; j < BN / 8; j++)
                        __stcg(part + item * (BM * BN / 4) + j * 256, make_float4(acc[4 * j], acc[4 * j + 1], acc[4 * j + 2], acc[4 * j + 3]));
                    __syncwarp();
                    if (lane == 0) signal_flag(q.part_flag + idx);
                    continue;
                }
                if (lane == 0) wait_flag(q.part_flag + idx, 8 * nprev);
                __syncwarp();
                if (mt == 14 && elected) KMARK(22);
                for (int u = 0; u < nprev; u++) {
                    #pragma unroll
                    for (int j = 0; j < BN / 8; j++) {
                        const float4 v = __ldcg(part + u * (BM * BN / 4) + j * 256);
                        acc[4 * j] += v.x; acc[4 * j + 1] += v.y; acc[4 * j + 2] += v.z; acc[4 * j + 3] += v.w;
                    }
                }
            }
            if (BN == 128 && mt == 14 && elected) KMARK(23);
            epi_hand_over(acc, ectx, ((uint64_t)row0 << 32) | (uint32_t)(q.c_col0 + ntc * BN), q.sig ? (uint64_t)(q.sig + mt) : 0, 1 + (code >> 16));
        }
        epi_exit(ectx);
        if (elected) KEXIT(BN == 256 ? 2 : 4);
    }
}

constexpr int FIN_SPLIT = 8, FIN_KB = HD / BK / FIN_SPLIT;
constexpr int FIN_A1 = FIN_KB * 16384;
constexpr int FIN_A0 = FIN_A1 + FIN_KB * 8192;
constexpr int FIN_BAR = FIN_A0 + 4 * 8192, FIN_SMEM = FIN_BAR + 256;
enum { FB_B = 0, FB_A1 = 64, FB_A0 = 128, FB_E0 = 160, FB_RDY = 192, FB_RED = 208 };
struct FinalParams {
    CUtensorMap tmA, tmB;
    __nv_bfloat16* out;
    const uint32_t* dep;
    uint32_t dep_target;
    int mt;
};
__global__ void __launch_bounds__(384, 1) final_gemm_kernel(const __grid_constant__ FinalParams p) {
    extern __shared__ __align__(1024) uint8_t smem_raw[];
    const uint32_t sbase = smem_u32(smem_raw), bar = sbase + FIN_BAR;
    const int tid = threadIdx.x, wg = tid >> 7;
    const int rank = blockIdx.x % FIN_SPLIT, nt = blockIdx.x / FIN_SPLIT;
    KENTER(5);
    if (tid == 0) {
        for (int s = 0; s < FIN_KB; s++) { mbar_init(bar + FB_B + 8 * s, 1); mbar_init(bar + FB_A1 + 8 * s, 1); }
        for (int s = 0; s < 4; s++) { mbar_init(bar + FB_A0 + 8 * s, 1); mbar_init(bar + FB_E0 + 8 * s, 1); }
        for (int h = 0; h < 2; h++) { mbar_init(bar + FB_RDY + 8 * h, FIN_SPLIT); mbar_init(bar + FB_RED + 8 * h, 1); }
        asm volatile("fence.mbarrier_init.release.cluster;" ::: "memory");
        for (int h = 0; h < 2; h++) mbar_arrive_expect_tx(bar + FB_RED + 8 * h, (FIN_SPLIT - 1) * 4096);
        pdl_launch_dependents();
    }
    __syncthreads();
    asm volatile("barrier.cluster.arrive.relaxed.aligned;" ::: "memory");
    if (wg == 0) {
        auto need = [&](int i) {
            uint32_t n = 0;
            while (ld_acquire_b32(p.dep + i) < p.dep_target) { if (++n > SPIN_LIMIT) __trap(); }
            asm volatile("fence.proxy.async.global;" ::: "memory");
        };
        auto a_load = [&](uint32_t dst, int kb, int seg, uint32_t mb) { tma_load_2d(dst, &p.tmA, (rank * FIN_KB + kb) * BK, p.mt * BM + seg * SEG, mb); };
        if (tid == 0) {
            auto b_load = [&](int kb) {
                mbar_arrive_expect_tx(bar + FB_B + 8 * kb, 16384);
                tma_load_3d(sbase + kb * 16384, &p.tmB, 0, (rank * FIN_KB + kb) * BK, nt * 2, bar + FB_B + 8 * kb);
            };
            const uint32_t f0 = ld_relaxed_b32(p.dep);
            b_load(0);
            need(1);
            if (f0 < p.dep_target) need(0);
            for (int kb = 0; kb < FIN_KB; kb++) {
                if (kb >= 4) mbar_wait(bar + FB_E0 + 8 * (kb & 3), 0);
                mbar_arrive_expect_tx(bar + FB_A0 + 8 * (kb & 3), 8192);
                for (int u = 0; u < 2; u++) a_load(sbase + FIN_A0 + (kb & 3) * 8192 + u * 4096, kb, u, bar + FB_A0 + 8 * (kb & 3));
                if (kb < 3) b_load(kb + 1);
                if (kb == 3) { b_load(4); b_load(5); }
                if (kb == 4 || kb == 5) b_load(kb + 2);
            }
        } else if (tid == 96) {
            need(3);
            for (int kb = 1; kb < FIN_KB; kb += 2) a_load(sbase + FIN_A1 + kb * 8192 + 4096, kb, 3, bar + FB_A1 + 8 * kb);
        } else if (tid == 64) {
            mbar_wait(bar + FB_B + 8 * 3, 0);
            need(2);
            for (int kb = 0; kb < FIN_KB; kb++) {
                mbar_arrive_expect_tx(bar + FB_A1 + 8 * kb, 8192);
                a_load(sbase + FIN_A1 + kb * 8192, kb, 2, bar + FB_A1 + 8 * kb);
            }
            need(3);
            KMARK(15);
            for (int kb = 0; kb < FIN_KB; kb += 2) a_load(sbase + FIN_A1 + kb * 8192 + 4096, kb, 3, bar + FB_A1 + 8 * kb);
        }
        __syncwarp();
        asm volatile("barrier.cluster.wait.aligned;" ::: "memory");
    } else {
        const int h = wg - 1, lane = tid & 31, wi = (tid >> 5) & 3, t128 = tid & 127;
        asm volatile("barrier.cluster.wait.aligned;" ::: "memory");
        float acc[64];
        for (int kb = 0; kb < FIN_KB; kb++) {
            mbar_wait(bar + FB_B + 8 * kb, 0);
            if (h == 0) mbar_wait(bar + FB_A0 + 8 * (kb & 3), kb >> 2); else mbar_wait(bar + FB_A1 + 8 * kb, 0);
            const uint32_t sa = sbase + (h == 0 ? FIN_A0 + (kb & 3) * 8192 : FIN_A1 + kb * 8192), sb = sbase + kb * 16384;
            asm volatile("wgmma.fence.sync.aligned;" ::: "memory");
            #pragma unroll
            for (int kk = 0; kk < BK / 16; kk++)
                wgmma_m64n128k16(acc, make_desc(sa + kk * 32, 16, 1024), make_desc(sb + kk * 2048, 8192, 1024), (kb | kk) != 0);
            asm volatile("wgmma.commit_group.sync.aligned;" ::: "memory");
            asm volatile("wgmma.wait_group.sync.aligned 1;" ::: "memory");
            if (h == 0 && kb >= 1 && kb <= 4 && t128 == 0) mbar_arrive(bar + FB_E0 + 8 * (kb - 1));
        }
        asm volatile("wgmma.wait_group.sync.aligned 0;" ::: "memory");
        const uint32_t red = sbase + FIN_A0;
        auto ready = [&](int i) {
            named_bar_sync(1, 128);
            if (t128 < FIN_SPLIT)
                asm volatile("mbarrier.arrive.relaxed.cluster.shared::cluster.b64 _, [%0];" ::"r"(mapa(bar + FB_RDY + 8 * i, t128)) : "memory");
        };
        if (tid == 256) KMARK(16);
        if (tid == 128) KMARK(19);
        if (h == 0) ready(0);
        mbar_wait(bar + FB_RDY + 8 * h, 0);
        if (tid == 256) KMARK(17);
        #pragma unroll
        for (int q = 0; q < FIN_SPLIT; q++) {
            if (q != rank) {
                const uint32_t dst = mapa(red + (rank - (rank > q ? 1 : 0)) * 4096 + t128 * 16, q), rb = mapa(bar + FB_RED + 8 * h, q);
                #pragma unroll
                for (int j = 0; j < 2; j++)
                    asm volatile("st.async.weak.shared::cluster.mbarrier::complete_tx::bytes.v4.f32 [%0], {%1,%2,%3,%4}, [%5];"
                                 ::"r"(dst + j * 2048), "f"(acc[8 * q + 4 * j]), "f"(acc[8 * q + 4 * j + 1]),
                                   "f"(acc[8 * q + 4 * j + 2]), "f"(acc[8 * q + 4 * j + 3]), "r"(rb) : "memory");
            }
        }
        float o[8];
        #pragma unroll
        for (int q = 0; q < FIN_SPLIT; q++)
            if (q == rank) {
                #pragma unroll
                for (int e = 0; e < 8; e++) o[e] = acc[8 * q + e];
            }
        mbar_wait(bar + FB_RED + 8 * h, 0);
        if (tid == 256) KMARK(18);
        if (tid == 128) KMARK(20);
        #pragma unroll
        for (int sl = 0; sl < FIN_SPLIT - 1; sl++) {
            #pragma unroll
            for (int j = 0; j < 2; j++) {
                const uint4 v = lds128(red + sl * 4096 + j * 2048 + t128 * 16);
                o[4 * j] += __uint_as_float(v.x); o[4 * j + 1] += __uint_as_float(v.y);
                o[4 * j + 2] += __uint_as_float(v.z); o[4 * j + 3] += __uint_as_float(v.w);
            }
        }
        if (h == 0) ready(1);
        __nv_bfloat16* dst = p.out + (size_t)(p.mt * BM + h * 64 + wi * 16 + (lane >> 2)) * (2 * DM) + nt * 128 + rank * 16 + (lane & 3) * 2;
        #pragma unroll
        for (int j = 0; j < 2; j++) {
            *reinterpret_cast<uint32_t*>(dst + j * 8) = pack_bf16(o[4 * j], o[4 * j + 1]);
            *reinterpret_cast<uint32_t*>(dst + (size_t)8 * (2 * DM) + j * 8) = pack_bf16(o[4 * j + 2], o[4 * j + 3]);
        }
        if (t128 == 0) KEXIT(5);
    }
}

#define POLL_DELAY 2
#define FETCH_DELAY 330
#define AT_PF 7
#define AT_FIRST 4
#define WO_PF 12
#define WO_PFA 6
#define WO_PFB_DELAY 60
#define V_EARLY 6
constexpr int REC_THREADS = 256;
constexpr uint32_t POLL_LIMIT = 1u << 16;
constexpr int NREG = 24;
__host__ __device__ constexpr int reg_idx(int j) { return ((j & 3) - 1) * 8 + (j >> 2); }
constexpr int SM_WQ = 0;
constexpr int SM_WO = 65536;
constexpr int SM_X = SM_WO + 11 * 8192;
constexpr int SM_PARK0 = SM_X, SM_PARK1 = SM_X + 8192;
constexpr int SM_MEM = SM_X + 4 * 4096;
constexpr int SM_RED = SM_X + 8 * 4096;
constexpr int SM_V = SM_X + 12 * 4096;
constexpr int SM_K = SM_X + 14 * 4096;
constexpr int SM_QS = SM_X + 15 * 4096;
constexpr int SM_QK = SM_X + 65536;
constexpr int SM_SP = SM_QK + 2048;
constexpr int SM_VM = SM_SP + 2560;
constexpr int SM_O = SM_VM + 2048;
constexpr int SM_SUM = SM_O + 2048;
constexpr int SM_TBL = SM_SUM + 128;
constexpr int SM_BAR = SM_TBL + 512;
constexpr int SM_STAMP = SM_BAR + 192;
constexpr int REC_SMEM = SM_STAMP;
static_assert(REC_SMEM <= 232448, "shared memory");
enum { BAR_V = 0, BAR_X = 8, BAR_P0 = 16, BAR_WQ = 40, BAR_WO = 48, BAR_XG = 56, BAR_F0 = 88, BAR_F3 = 96, BAR_VF = 104,
       BAR_M = 112, BAR_GO = 144, BAR_PK = 152, BAR_VM = 160, BAR_SELF = 168, BAR_TPUB = 176, BAR_MIN = 176 };

template <int V> struct IntC { static constexpr int value = V; };
template <int I, int N, typename F> __device__ __forceinline__ void sfor(F&& f) {
    if constexpr (I < N) { f(IntC<I>{}); sfor<I + 1, N>(f); }
}

struct RecParams {
    CUtensorMap tmW[3];
    CUtensorMap tmWo;
    CUtensorMap tmX;
    const __nv_bfloat16* mem0;
    __nv_bfloat16* qkv_tok;
    __nv_bfloat16* kv_mem;
    uint8_t* xchg;
    uint32_t* flags;
    uint32_t one[2];
    uint32_t* arrivals;
};

__device__ __forceinline__ void mma_a(float* d, const uint32_t* a, uint32_t b0, uint32_t b1) {
    mma16816(d, a[0], a[1], a[2], a[3], b0, b1);
}
__device__ __forceinline__ void ldsm4(uint32_t addr, uint32_t* r) { ldsm_x4(addr, r[0], r[1], r[2], r[3]); }
__device__ __forceinline__ void ldsm4t(uint32_t addr, uint32_t* r) { ldsm_x4_t(addr, r[0], r[1], r[2], r[3]); }
template <int OFF> __device__ __forceinline__ void repoll_v2(uint2& v, const uint8_t* p) {
    asm volatile("{\n.reg .pred q;\nsetp.eq.u32 q, %1, 0xFFFFFFFF;\n@q ld.relaxed.gpu.global.v2.b32 {%0,%1}, [%2+%3];\n}"
                 : "+r"(v.x), "+r"(v.y) : "l"(p), "n"(OFF) : "memory");
}
__device__ __forceinline__ uint32_t max3(uint32_t a, uint32_t b, uint32_t c) { return max(max(a, b), c); }
__device__ __forceinline__ uint32_t pub_slot(int s) { return (s & 1) * XCHG_SLOT + ((s >> 1) & 1) * PUB_BYTES; }

__device__ __forceinline__ uint8_t* xaddr(uint32_t lo, uint32_t hi) {
    uint64_t a;
    asm("mov.b64 %0, {%1, %2};" : "=l"(a) : "r"(lo), "r"(hi));
    return reinterpret_cast<uint8_t*>(a);
}
template <int N> __device__ __forceinline__ uint32_t delay_zero(uint32_t a) {
    uint32_t x = a;
    #pragma unroll
    for (int i = 0; i < N; i++) x = lds32_volatile(x);
    return x - a;
}
__device__ __forceinline__ uint32_t fresh(uint32_t x) { asm volatile("" : "+r"(x)); return x; }

template <int NT> __device__ __forceinline__ uint32_t wo_addr(uint32_t ao, uint32_t a3, int n) {
    return (n % NT == 2 ? a3 : ao + (n % NT) * 32768) + (n / NT) * 1024;
}
template <int NT, int PF>
__device__ __forceinline__ void wo_phase(uint32_t (&st)[8 * NT][4], uint32_t ao, uint32_t a3, uint32_t l16, uint32_t tbl, uint32_t sums,
                                         uint32_t slot, uint32_t xhi, uint32_t third, uint32_t xbar, uint32_t xpar, bool& x_ok) {
    constexpr int AHEAD = PF > 0 ? PF - NT : 10;
    uint32_t of[4][4];
    uint2 sm;
    uint4 t;
    ldsm4t(l16 + SM_O, of[0]);
    #pragma unroll
    for (int n = PF; n < AHEAD; n++) {
        ldsm4t(wo_addr<NT>(ao, a3, n), st[n]);
        if (n == 2 * NT - 1) ldsm4t(l16 + SM_O + 512, of[1]);
    }
    if (PF >= 2 * NT) ldsm4t(l16 + SM_O + 512, of[1]);
    float acc[NT][4];
    #pragma unroll
    for (int i = 0; i < NT; i++) { acc[i][0] = acc[i][1] = acc[i][2] = acc[i][3] = 0.f; }
    #pragma unroll
    for (int kk = 0; kk < 8; kk++) {
        #pragma unroll
        for (int i = 0; i < NT; i++) {
            const int n = kk * NT + i;
            mma_a(acc[i], st[n], of[kk >> 1][(kk & 1) * 2], of[kk >> 1][(kk & 1) * 2 + 1]);
            if (n + AHEAD >= PF && n + AHEAD < 8 * NT) ldsm4t(wo_addr<NT>(ao, a3, n + AHEAD), st[n + AHEAD]);
        }
        if (kk == 1 || kk == 3) ldsm4t(l16 + SM_O + ((kk >> 1) + 2) * 512, of[(kk >> 1) + 2]);
        if (kk == (NT == 3 ? 5 : 4)) {
            const uint32_t x = fresh(l16);
            sm = lds64(sums + ((x >> 1) & 0x18));
            t = lds128(tbl + ((x >> 3) & 0x30));
            x_ok = mbar_test_wait(xbar, xpar);
        }
    }
    const float i0 = rcp(__uint_as_float(sm.x)), i1 = rcp(__uint_as_float(sm.y));
    const uint32_t d = slot + ((fresh(l16) >> 1) & 0x38);
    const uint32_t pl[3] = {t.x + d, t.y + d, t.z + d};
    #pragma unroll
    for (int i = 0; i < NT; i++)
        asm volatile("{\n.reg .pred p;\nsetp.ne.u32 p, %3, 0;\n@p st.relaxed.gpu.global.v2.b32 [%0], {%1,%2};\n}"
                     ::"l"(xaddr(pl[i], xhi)), "r"(pack_bf16(acc[i][0] * i0, acc[i][1] * i1)), "r"(pack_bf16(acc[i][2] * i0, acc[i][3] * i1)),
                       "r"(i < 2 ? 1u : third) : "memory");
}

constexpr uint32_t SMEM_ORIGIN = 1024;
constexpr uint64_t DESC_BASE = (1ull << 16) | (0x40000040ull << 32);
template <int OFFB, int SCALE_D>
__device__ __forceinline__ void wgmma_n32_rs(float (&d)[16], const uint32_t* a, uint32_t one) {
    asm volatile(
        "{\n.reg .b64 db;\nmad.wide.u32 db, %20, %21, %22;\n"
        "wgmma.mma_async.sync.aligned.m64n32k16.f32.bf16.bf16 {%0,%1,%2,%3,%4,%5,%6,%7,%8,%9,%10,%11,%12,%13,%14,%15}, "
        "{%16,%17,%18,%19}, db, %23, 1, 1, 0;\n}"
        : "+f"(d[0]), "+f"(d[1]), "+f"(d[2]), "+f"(d[3]), "+f"(d[4]), "+f"(d[5]), "+f"(d[6]), "+f"(d[7]),
          "+f"(d[8]), "+f"(d[9]), "+f"(d[10]), "+f"(d[11]), "+f"(d[12]), "+f"(d[13]), "+f"(d[14]), "+f"(d[15])
        : "r"(a[0]), "r"(a[1]), "r"(a[2]), "r"(a[3]), "r"(one), "n"((SMEM_ORIGIN + OFFB) >> 4), "l"(DESC_BASE), "n"(SCALE_D));
}
template <int OFFA, int OFFB, int SCALE_D>
__device__ __forceinline__ void wgmma_n32_ss(float (&d)[16], uint32_t one) {
    asm volatile(
        "{\n.reg .b64 da, db;\nmad.wide.u32 da, %16, %17, %19;\nmad.wide.u32 db, %16, %18, %19;\n"
        "wgmma.mma_async.sync.aligned.m64n32k16.f32.bf16.bf16 {%0,%1,%2,%3,%4,%5,%6,%7,%8,%9,%10,%11,%12,%13,%14,%15}, "
        "da, db, %20, 1, 1, 1, 0;\n}"
        : "+f"(d[0]), "+f"(d[1]), "+f"(d[2]), "+f"(d[3]), "+f"(d[4]), "+f"(d[5]), "+f"(d[6]), "+f"(d[7]),
          "+f"(d[8]), "+f"(d[9]), "+f"(d[10]), "+f"(d[11]), "+f"(d[12]), "+f"(d[13]), "+f"(d[14]), "+f"(d[15])
        : "r"(one), "n"((SMEM_ORIGIN + OFFA) >> 4), "n"((SMEM_ORIGIN + OFFB) >> 4), "l"(DESC_BASE), "n"(SCALE_D));
}
template <int WG, int J0, int J1, int I, bool ACC, bool FENCE = true>
__device__ __forceinline__ void token_mma(float (&ta)[2][16], const uint32_t (&wr)[NREG][2][4], uint32_t one) {
    if (FENCE) asm volatile("wgmma.fence.sync.aligned;" ::: "memory");
    sfor<J0, J1>([&](auto J) {
        constexpr int j = J.value, c = j >> 2, offb = SM_X + WG * 32768 + c * 4096 + (j & 3) * 32, sc = (ACC || j != J0) ? 1 : 0;
        if constexpr ((j & 3) != 0) wgmma_n32_rs<offb, sc>(ta[I], wr[reg_idx(j)][I], one);
        else if constexpr (WG == 0 || (I == 1 && c >= 4)) wgmma_n32_ss<SM_WQ + WG * 32768 + I * 16384 + c * 2048, offb, sc>(ta[I], one);
        constexpr int m = I ? c : c - 4;
        if constexpr (WG == 0 && (j & 3) == 1 && m >= 0)
            wgmma_n32_ss<SM_WQ + 32768 + (1 - I) * 16384 + m * 2048, SM_X + 32768 + m * 4096, 1>(ta[I], one);
    });
    asm volatile("wgmma.commit_group.sync.aligned;" ::: "memory");
}
__device__ __forceinline__ void warp_arrive(uint32_t bar) {
    __syncwarp();
    if (elect_one()) mbar_arrive(bar);
}
__device__ __forceinline__ void remote_arrive(uint32_t bar, uint32_t rank) {
    asm volatile("mbarrier.arrive.relaxed.cluster.shared::cluster.b64 _, [%0];" ::"r"(mapa(bar, rank)) : "memory");
}
__device__ __forceinline__ void x_load(const RecParams& p, uint32_t sb, int sg, int g) {
    tma_load_3d_mc(sb + SM_X + g * 16384, &p.tmX, 0, sg * SEG, g * 4, sb + SM_BAR + BAR_XG + 8 * g, (uint16_t)7);
}

__device__ __forceinline__ void rec_steps(const RecParams& p, const uint32_t (&wr)[NREG][2][4], const uint32_t sb, const int warp,
                                          const int cta, const int head, const int rank) {
    const int wq = warp & 3, wg = warp >> 2;
    const uint32_t bar = sb + SM_BAR;
    const uint32_t xhi = (uint32_t)((uint64_t)p.xchg >> 32);
    const float sl2 = 0.08838834764831845f * 1.4426950408889634f;
    const bool has_unit = warp >= 5 && (warp < 7 || cta < 64);
    const bool qk = rank < 2;
    const uint32_t pa = rank == 2 ? 0 : rank + 1, pb = rank == 0 ? 2 : rank - 1;
    const uint32_t tbl = sb + SM_TBL + warp * 64;
    const bool att = (warp & 6) == 2;
    const int stile = warp < 5 ? warp : warp - 3;

    const uint32_t u_st = uniform(SM_QK - SM_WQ - wg * (32768 - 1024));
    const uint32_t u_xa = uniform(sb + (qk ? SM_SP + rank * 1280 + stile * 256 : SM_VM + warp * 256));
    const uint32_t u_key = uniform(!qk || att || warp == 7 ? 0 : sb + (warp == 4 ? SM_QK + 1024 : SM_K + stile * 1024));
    const uint32_t u_bx = uniform(bar + (qk ? BAR_X : BAR_VM)), u_bra = uniform(mapa(u_bx, pa)), u_brb = uniform(mapa(u_bx, pb));
    const uint32_t u_src = uniform(lds32_volatile(tbl + 44));
    const uint32_t u_free = uniform(mapa(bar + (warp == 5 ? BAR_VF : BAR_F0), warp == 5 ? 2 : 0));
    const uint32_t u_role = uniform((has_unit ? 1 : 0) | (att ? 2 : 0) | (wg == 1 || qk ? 4 : 0) | (!qk && warp == 0 ? 8 : 0) | (rank != 0 && warp == 1 ? 16 : 0) |
                                    (warp == 5 || warp == 6 ? 32 : 0));
    uint32_t l16, aq, ao;
    {
        const int lane = threadIdx.x & 31, mi = lane >> 3, r8 = lane & 7, r16 = (mi >> 1) * 8 + r8;
        l16 = opaque(sb + lane * 16);
        aq = opaque(sb + SM_WQ + wg * 32768 + r16 * 128 + (((wq * 2 + (mi & 1)) ^ r8) << 4));
        ao = opaque(sb + SM_WO + (warp >> 1) * 8192 + r16 * 64 + ((((warp & 1) * 2 + (mi & 1)) ^ ((r8 >> 1) & 3)) << 4));
    }

    uint32_t mphase = 0;
    bool x0_ok = false;
    #pragma unroll 1
    for (int s = 0;; s++) {
        const uint32_t par = s & 1;
        uint32_t at[16][4];
        auto at_early = [](int i) { return i < 2 || ((i & 1) == 1 && (i >> 1) <= AT_PF - 2); };
        auto at_prefetch = [&](bool first) {
            #pragma unroll
            for (int i = 0; i < 16; i++)
                if (at_early(i) && first == ((i & 1) == 1 && (i >> 1) < AT_FIRST)) ldsm4t(aq + (i & 1) * 16384 + (i >> 1) * 2048, at[i]);
        };
        auto att_stores = [&](bool tiles, bool rows) {
            if (warp == 4) {
                if (rows && !qk) mbar_wait_bounded(bar + BAR_VM, par);
                asm volatile("fence.proxy.async.shared::cta;" ::: "memory");
                if (elect_one()) {
                    if (tiles) {
                        __nv_bfloat16* dst = p.qkv_tok + ((size_t)s * NH + head) * (SEG * DH);
                        constexpr size_t MAT = (size_t)NSEG * NH * SEG * DH;
                        bulk_store(dst + (qk ? rank * (SEG * 64) : 2 * MAT), sb + (qk ? SM_QS : SM_V), 4096);
                        bulk_store(dst + (qk ? MAT + rank * (SEG * 64) : 2 * MAT + SEG * 64), sb + (qk ? SM_K : SM_V + 4096), 4096);
                    }
                    if (rows)
                        bulk_store(p.kv_mem + ((size_t)s * NH + head) * (MROWS * DH) + (qk ? rank * (MROWS * 64) : NSEG * NH * MROWS * DH),
                                   sb + (qk ? SM_QK + 1024 : SM_VM), qk ? 1024 : 2048);
                    bulk_commit();
                }
            }
        };
        if (wg == 0) {
            float ta[2][16];
            if (!x0_ok) mbar_wait_bounded(bar + BAR_XG, par);
            STAMP(6);
            auto park = [&](int i, uint32_t dst) {
                #pragma unroll
                for (int e = 0; e < 16; e++) asm volatile("" : "+f"(ta[i][e]));
                #pragma unroll
                for (int j = 0; j < 4; j++)
                    sts128(l16 + dst + j * 2048 + wq * 512, __float_as_uint(ta[i][4 * j]), __float_as_uint(ta[i][4 * j + 1]),
                           __float_as_uint(ta[i][4 * j + 2]), __float_as_uint(ta[i][4 * j + 3]));
            };
            token_mma<0, 0, 16, 0, false>(ta, wr, 1);
            mbar_wait_bounded(bar + BAR_XG + 8, par);
            mbar_wait_bounded(bar + BAR_XG + 16, par);
            at_prefetch(true);
            token_mma<0, 16, 32, 0, true>(ta, wr, p.one[1]);
            token_mma<0, 0, 16, 1, false, false>(ta, wr, p.one[0]);
            mbar_wait_bounded(bar + BAR_XG + 24, par);
            token_mma<0, 16, 32, 1, true>(ta, wr, 1);
            asm volatile("wgmma.wait_group.sync.aligned 1;" ::: "memory");
            park(0, SM_PARK0);
            warp_arrive(bar + BAR_GO);
            asm volatile("wgmma.wait_group.sync.aligned 0;" ::: "memory");
            park(1, SM_PARK1);
            warp_arrive(bar + BAR_PK);
            const uint8_t* src = xaddr(u_src + pub_slot(s), xhi);
            auto fetch = [&]() {
                if (elect_one()) {
                    mbar_arrive_expect_tx(bar + BAR_M + 8 * wq, 4096);
                    bulk_load(sb + SM_MEM + wq * 4096, src, 4096, bar + BAR_M + 8 * wq);
                }
            };
            named_bar_sync(7, REC_THREADS - 32);
            {
                const uint4 t = lds128(bar + BAR_TPUB);
                const uint32_t now = clock32();
                spin_until(now + FETCH_DELAY - min(min(min(now - t.y, now - t.z), now - t.w), (uint32_t)FETCH_DELAY));
            }
            fetch();
            STAMP(12);
            if (warp == 0 && elect_one()) {
                if (qk) mbar_arrive_expect_tx(bar + BAR_V, 8192);
                mbar_arrive_expect_tx(bar + BAR_X, qk ? 1280 : 2560);
                mbar_arrive_expect_tx(bar + BAR_VM, qk ? 2048 : 0);
            }
            at_prefetch(false);
            const uint32_t x = fresh(l16) - sb;
            const uint32_t ca = sb + SM_MEM + wq * 4096 + x * 2 + ((x >> 4) & 0x1C);
            #pragma unroll 1
            for (uint32_t n = 0; n < POLL_LIMIT; n++) {
                mbar_wait_bounded(bar + BAR_M + 8 * wq, mphase);
                mphase ^= 1;
                const uint32_t c0 = lds32_volatile(ca), c1 = lds32_volatile(ca + 1024), c2 = lds32_volatile(ca + 2048), c3 = lds32_volatile(ca + 3072);
                if (!__any_sync(~0u, max(max3(c0, c1, c2), c3) == SENT)) break;
                fetch();
            }
            STAMP(0);
            named_bar_sync(0, REC_THREADS);
            if (warp == 0 && rank == 0 && s + 1 < NSEG) {
                mbar_wait_bounded(bar + BAR_F0, par);
                if (elect_one()) x_load(p, sb, s + 1, 0);
            }
            if (u_role & 8) {
                asm volatile("fence.proxy.async.shared::cta;" ::: "memory");
                mbar_wait_bounded(bar + BAR_VF, par);
                if (s < NSEG - 1 && elect_one()) {
                    #pragma unroll
                    for (int r = 0; r < 2; r++)
                        asm volatile("cp.async.bulk.shared::cluster.shared::cta.mbarrier::complete_tx::bytes [%0], [%1], %2, [%3];"
                                     ::"r"(mapa(sb + SM_V, r)), "r"(sb + SM_V), "r"(8192), "r"(mapa(bar + BAR_V, r)) : "memory");
                }
            }
        } else {
            at_prefetch(true);
            if (s > 0) {
                if (u_role & 1) {
                    const uint32_t ln = (fresh(l16) >> 4) & 31;
                    const uint32_t ibl = lds32_volatile(tbl + 12) + (par ^ 1) * XCHG_SLOT + ln * 8;
                    const uint32_t publ = lds32_volatile(tbl + 28) + pub_slot(s) + (ln & 16) * 256 + (ln & 8) * 16 + (ln & 7) * 4;
                    const bool odd = ln & 8;
                    const uint8_t* ib = xaddr(ibl + delay_zero<POLL_DELAY>(bar + BAR_SELF), xhi);
                    STAMP(8);
                    uint2 v[8];
                    #pragma unroll
                    for (int i = 0; i < 8; i++) v[i] = make_uint2(SENT, SENT);
                    #pragma unroll 1
                    for (uint32_t n = 0; n < POLL_LIMIT; n++) {
                        sfor<0, 8>([&](auto I) { repoll_v2<I.value * 256>(v[I.value], ib); });
                        const uint32_t mx = max(max3(v[0].y, v[1].y, v[2].y), max3(max3(v[3].y, v[4].y, v[5].y), v[6].y, v[7].y));
                        if (!__any_sync(~0u, mx == SENT)) break;
                    }
                    STAMP(9);
                    const float a0 = ((bf16_lo(v[0].x) + bf16_lo(v[1].x)) + (bf16_lo(v[2].x) + bf16_lo(v[3].x))) +
                                     ((bf16_lo(v[4].x) + bf16_lo(v[5].x)) + (bf16_lo(v[6].x) + bf16_lo(v[7].x)));
                    const float a1 = ((bf16_hi(v[0].x) + bf16_hi(v[1].x)) + (bf16_hi(v[2].x) + bf16_hi(v[3].x))) +
                                     ((bf16_hi(v[4].x) + bf16_hi(v[5].x)) + (bf16_hi(v[6].x) + bf16_hi(v[7].x)));
                    const float a2 = ((bf16_lo(v[0].y) + bf16_lo(v[1].y)) + (bf16_lo(v[2].y) + bf16_lo(v[3].y))) +
                                     ((bf16_lo(v[4].y) + bf16_lo(v[5].y)) + (bf16_lo(v[6].y) + bf16_lo(v[7].y)));
                    const float a3 = ((bf16_hi(v[0].y) + bf16_hi(v[1].y)) + (bf16_hi(v[2].y) + bf16_hi(v[3].y))) +
                                     ((bf16_hi(v[4].y) + bf16_hi(v[5].y)) + (bf16_hi(v[6].y) + bf16_hi(v[7].y)));
                    float k0 = odd ? a2 : a0, k1 = odd ? a3 : a1;
                    k0 += __shfl_xor_sync(~0u, odd ? a0 : a2, 8);
                    k1 += __shfl_xor_sync(~0u, odd ? a1 : a3, 8);
                    k0 += __shfl_xor_sync(~0u, k0, 16);
                    k1 += __shfl_xor_sync(~0u, k1, 16);
                    st_relaxed_b32(xaddr(publ, xhi), pack_bf16(k0, k1));
                    STAMP(11);
                } else if (warp == 4) {
                    bulk_wait_read_all();
                    if (elect_one()) remote_arrive(bar + BAR_F3, 2);
                    if (!qk) {
                        mbar_wait_bounded(bar + BAR_F3, par ^ 1);
                        if (elect_one()) x_load(p, sb, s, 3);
                    }
                    if (elect_one()) {
                        bulk_wait_all();
                        signal_bulk(p.flags + F_PROGRESS + s - 1);
                    }
                    __syncwarp();
                    STAMP(10);
                }
            }
            float ta[2][16];
            uint32_t w[8];
            auto unpark = [&](int i, uint32_t src) {
                mbar_wait_bounded(bar + (i ? BAR_GO : BAR_PK), par);
                #pragma unroll
                for (int j = 0; j < 4; j++) {
                    const uint4 v = lds128(l16 + src + j * 2048 + wq * 512);
                    ta[i][4 * j] = __uint_as_float(v.x); ta[i][4 * j + 1] = __uint_as_float(v.y);
                    ta[i][4 * j + 2] = __uint_as_float(v.z); ta[i][4 * j + 3] = __uint_as_float(v.w);
                }
            };
            sts32(bar + BAR_TPUB + 4 * wq, clock32());
            if (warp != 4) named_bar_arrive(7, REC_THREADS - 32);
            unpark(1, SM_PARK0);
            STAMP(6);
            token_mma<1, 0, 16, 1, true>(ta, wr, 1);
            unpark(0, SM_PARK1);
            token_mma<1, 16, 32, 1, true>(ta, wr, 1);
            token_mma<1, 16, 32, 0, true>(ta, wr, 1);
            token_mma<1, 0, 16, 0, true, false>(ta, wr, 1);
            auto put_tile = [&](int m, const uint32_t (&q)[8]) {
                #pragma unroll
                for (int h = 0; h < 2; h++) {
                    if (qk) asm volatile("stmatrix.sync.aligned.m8n8.x4.trans.shared.b16 [%0], {%1,%2,%3,%4};"
                                         ::"r"(aq - (SM_WQ + 32768) + (m ? SM_K : SM_QS) + h * 2048), "r"(q[4 * h]), "r"(q[4 * h + 1]),
                                           "r"(q[4 * h + 2]), "r"(q[4 * h + 3]) : "memory");
                    else sts128(l16 + SM_V + wq * 2048 + m * 1024 + h * 512, q[4 * h], q[4 * h + 1], q[4 * h + 2], q[4 * h + 3]);
                }
            };
            auto pack_tile = [&](int i) {
                #pragma unroll
                for (int e = 0; e < 16; e++) asm volatile("" : "+f"(ta[i][e]));
                #pragma unroll
                for (int j = 0; j < 8; j++) w[j] = pack_bf16(ta[i][2 * j], ta[i][2 * j + 1]);
            };
            asm volatile("wgmma.wait_group.sync.aligned 2;" ::: "memory");
            pack_tile(1);
            at_prefetch(false);
            asm volatile("wgmma.wait_group.sync.aligned 1;" ::: "memory");
            if ((u_role & 32) && elect_one())
                asm volatile("mbarrier.arrive.relaxed.cluster.shared::cluster.b64 _, [%0];" ::"r"(u_free) : "memory");
            put_tile(0, w);
            asm volatile("wgmma.wait_group.sync.aligned 0;" ::: "memory");
            pack_tile(0);
            put_tile(1, w);
            STAMP(0);
            named_bar_sync(0, REC_THREADS);
            if (s == NSEG - 1) att_stores(true, false);
            STAMP(14);
        }
        const uint32_t mb = l16 + SM_MEM + wg * 8192;
        float acc[2][2][4];
        {
            uint32_t b[2][4];
            ldsm4t(mb, b[0]);
            ldsm4t(mb + 512, b[1]);
            #pragma unroll
            for (int i = 0; i < 4; i++)
                if (!at_early(i)) ldsm4t(aq + (i & 1) * 16384 + (i >> 1) * 2048, at[i]);
            STAMPD(1, b[0][0]);
            #pragma unroll
            for (int i = 0; i < 4; i++) { for (int e = 0; e < 4; e++) acc[i >> 1][i & 1][e] = 0.f; }
            #pragma unroll
            for (int u = 0; u < 16; u++) {
                #pragma unroll
                for (int h = 0; h < 2; h++) {
                    const int j = 2 * u + h;
                    #pragma unroll
                    for (int m = 0; m < 2; m++) {
                        if ((j & 3) == 0) mma_a(acc[h][m], at[(j >> 2) * 2 + m], b[u & 1][2 * h], b[u & 1][2 * h + 1]);
                        else mma_a(acc[h][m], wr[reg_idx(j)][m], b[u & 1][2 * h], b[u & 1][2 * h + 1]);
                    }
                }
                if (u + 2 < 16) ldsm4t(mb + (u + 2) * 512, b[u & 1]);
                if (u + 4 < 16 && !at_early(u + 4))
                    ldsm4t(aq + ((u + 4) & 1) * 16384 + ((u + 4) >> 1) * 2048, at[u + 4]);
            }
        }
        sts128(l16 + SM_RED + warp * 512, __float_as_uint(acc[0][1][0] + acc[1][1][0]), __float_as_uint(acc[0][1][1] + acc[1][1][1]),
               __float_as_uint(acc[0][1][2] + acc[1][1][2]), __float_as_uint(acc[0][1][3] + acc[1][1][3]));
        #pragma unroll
        for (int e = 0; e < 4; e++) acc[0][0][e] += acc[1][0][e];
        const uint32_t x16 = fresh(l16);
        const uint32_t sa = fresh((x16 & 0x70) * 8 + ((((x16 >> 3) & 0x30) ^ x16) & 0x70));
        const uint32_t sq = fresh(sa ^ ((((x16 >> 7) ^ (x16 >> 8)) & 1) * 0x30));
        const uint32_t x8 = (x16 & 0x1F0) >> 1;
        const uint32_t xra = fresh(x8 + __byte_perm(u_xa, u_bra, 0x7210)), xrb = fresh(x8 + __byte_perm(u_xa, u_brb, 0x7210));
        STAMP(2);
        named_bar_sync(1 + wq, 64);
        uint32_t p0, p1;
        {
            const uint4 v = lds128(l16 + SM_RED + (warp ^ 4) * 512);
            p0 = pack_bf16(acc[0][0][0] + __uint_as_float(v.x), acc[0][0][1] + __uint_as_float(v.y));
            p1 = pack_bf16(acc[0][0][2] + __uint_as_float(v.z), acc[0][0][3] + __uint_as_float(v.w));
        }
        auto send = [&](uint32_t y0, uint32_t y1) {
            st_async_v2(xra, y0, y1, u_bra);
            st_async_v2(xrb, y0, y1, u_brb);
            sts64(x8 + u_xa, y0, y1);
            warp_arrive(u_bx);
        };
        if (qk) {
            asm volatile("stmatrix.sync.aligned.m8n8.x2.trans.shared.b16 [%0], {%1,%2};" ::"r"(aq + u_st), "r"(p0), "r"(p1) : "memory");
            named_bar_sync(5, REC_THREADS);
            if (u_key != 0) {
                uint32_t qa[2][4], kf[2][4];
                ldsm4(sq + sb + SM_QK, qa[0]);
                ldsm4(sa + u_key, kf[0]);
                ldsm4((sq ^ 64) + sb + SM_QK, qa[1]);
                ldsm4((sa ^ 64) + u_key, kf[1]);
                float se[4] = {0.f, 0.f, 0.f, 0.f}, so[4] = {0.f, 0.f, 0.f, 0.f};
                #pragma unroll
                for (int u = 0; u < 2; u++) {
                    mma_a(se, qa[u], kf[u][0], kf[u][1]);
                    mma_a(so, qa[u], kf[u][2], kf[u][3]);
                }
                send(__float_as_uint(se[0] + so[2]), __float_as_uint(se[1] + so[3]));
            }
        } else {
            send(p0, p1);
        }
        STAMP(3);
        const uint32_t lane = (fresh(l16) >> 4) & 31;
        if (((s + 1) & 62) == 0) {
            if (s == NSEG - 1) { att_stores(false, true); break; }
            mbar_wait_bounded(bar + BAR_WO, 0);
            pdl_launch_dependents();
            PSTAMP(8);
        }
        const uint32_t slot = par * XCHG_SLOT;
        if (u_role & 2) {
            if (qk) mbar_wait_bounded(bar + BAR_V, par);
            uint32_t vt[2][4][4];
            auto v_load = [&](int i0, int i1) {
                #pragma unroll
                for (int i = i0; i < i1; i++) {
                    const uint4 v = lds128(l16 + SM_V + (warp & 1) * 1024 + (i & 3) * 2048 + (i >> 2) * 512);
                    vt[i >> 2][i & 3][0] = v.x; vt[i >> 2][i & 3][1] = v.y; vt[i >> 2][i & 3][2] = v.z; vt[i >> 2][i & 3][3] = v.w;
                }
            };
            v_load(0, V_EARLY);
            const uint32_t l8 = fresh(sb + lane * 8);
            mbar_wait_bounded(bar + BAR_X, par);
            STAMP(4);
            float sv[10];
            #pragma unroll
            for (int j = 0; j < 5; j++) {
                const uint2 a = lds64(l8 + SM_SP + j * 256), b = lds64(l8 + SM_SP + 1280 + j * 256);
                sv[2 * j] = __uint_as_float(a.x) + __uint_as_float(b.x);
                sv[2 * j + 1] = __uint_as_float(a.y) + __uint_as_float(b.y);
            }
            float mx = fmaxf(fmaxf(fmaxf(sv[0], sv[1]), fmaxf(sv[2], sv[3])), fmaxf(fmaxf(sv[4], sv[5]), fmaxf(sv[6], sv[7])));
            mx = fmaxf(mx, fmaxf(sv[8], sv[9]));
            const float m1 = __shfl_xor_sync(~0u, mx, 1), m2 = __shfl_xor_sync(~0u, mx, 2), m3 = __shfl_xor_sync(~0u, mx, 3);
            __syncwarp();
            v_load(V_EARLY, 8);
            const bool vm_ok = mbar_test_wait(bar + BAR_VM, par);
            mx = fmaxf(fmaxf(mx, m1), fmaxf(m2, m3));
            const float mo = mx * sl2;
            #pragma unroll
            for (int j = 0; j < 10; j++) sv[j] = ex2(fmaf(sv[j], sl2, -mo));
            const uint32_t e0 = pack_bf16(sv[0], sv[1]), e1 = pack_bf16(sv[2], sv[3]);
            const uint32_t e2 = pack_bf16(sv[4], sv[5]), e3 = pack_bf16(sv[6], sv[7]), em = pack_bf16(sv[8], sv[9]);
            float o[4][4];
            #pragma unroll
            for (int i = 0; i < 4; i++) {
                o[i][0] = o[i][1] = o[i][2] = o[i][3] = 0.f;
                mma_a(o[i], vt[0][i], e0, e1);
            }
            const float sum = (((sv[0] + sv[1]) + (sv[2] + sv[3])) + ((sv[4] + sv[5]) + (sv[6] + sv[7]))) + (sv[8] + sv[9]);
            if (!vm_ok) mbar_wait_bounded(bar + BAR_VM, par);
            uint2 vm[4];
            #pragma unroll
            for (int i = 0; i < 4; i++) {
                vm[i] = lds64(l8 + SM_VM + (warp & 1) * 1024 + i * 256);
                mma_a(o[i], vt[1][i], e2, e3);
            }
            #pragma unroll
            for (int i = 0; i < 4; i++) mma1688(o[i], vm[i].x, vm[i].y, em);
            {
                const float s1 = __shfl_xor_sync(~0u, sum, 1), s2 = __shfl_xor_sync(~0u, sum, 2), s3 = __shfl_xor_sync(~0u, sum, 3);
                sts32(sb + SM_SUM + (lane & 28), __float_as_uint((sum + s1) + (s2 + s3)));
            }
            #pragma unroll
            for (int i = 0; i < 4; i += 2)
                stsm_x4(l16 + SM_O + (warp & 1) * 1024 + i * 256, pack_bf16(o[i][0], o[i][1]), pack_bf16(o[i][2], o[i][3]),
                        pack_bf16(o[i + 1][0], o[i + 1][1]), pack_bf16(o[i + 1][2], o[i + 1][3]));
            STAMP(5);
            uint32_t st[16][4];
            named_bar_sync(6, REC_THREADS);
            wo_phase<2, 0>(st, ao, 0, l16, tbl, sb + SM_SUM, slot, xhi, 0, bar + BAR_XG, par ^ 1, x0_ok);
        } else {
            const uint32_t a3 = fresh(ao) + (wg == 0 ? 10 : 6) * 8192;
            uint32_t st[24][4];
            #pragma unroll
            for (int n = 0; n < WO_PFA; n++) ldsm4t(wo_addr<3>(ao, a3, n), st[n]);
            if (u_role & 1) {
                const uint32_t ln = (fresh(l16) >> 4) & 31;
                uint8_t* ib = xaddr(lds32_volatile(tbl + 12) + (par ^ 1) * XCHG_SLOT + ln * 16, xhi);
                #pragma unroll
                for (int i = 0; i < 4; i++) st_relaxed_v4(ib + i * 512, SENT);
                st_relaxed_b32(xaddr(lds32_volatile(tbl + 28) + pub_slot(s + 3) + (ln & 16) * 256 + (ln & 8) * 16 + (ln & 7) * 4, xhi), SENT);
            }
            if (warp == 1) {
                if (elect_one()) {
                    #pragma unroll
                    for (int g = 0; g < 4; g++) mbar_arrive_expect_tx(bar + BAR_XG + 8 * g, 16384);
                }
                if (s + 2 < NSEG && cta < 4 && elect_one())
                    asm volatile("cp.async.bulk.prefetch.tensor.3d.L2.global [%0, {%1, %2, %3}];"
                                 ::"l"(&p.tmX), "r"(0), "r"((s + 2) * SEG), "r"(cta * 4) : "memory");
            }
            mbar_wait_bounded(bar + BAR_X, par);
            spin_clks(WO_PFB_DELAY);
            #pragma unroll
            for (int n = WO_PFA; n < WO_PF; n++) ldsm4t(wo_addr<3>(ao, a3, n), st[n]);
            att_stores(true, true);
            if (u_role & 16) {
                mbar_wait_bounded(bar + BAR_VM, par);
                if (elect_one()) x_load(p, sb, s + 1, rank);
            }
            named_bar_sync(6, REC_THREADS);
            wo_phase<3, WO_PF>(st, ao, a3, l16, tbl, sb + SM_SUM, slot, xhi, u_role & 4, bar + BAR_XG, par ^ 1, x0_ok);
        }
        STAMP(7);
        if (wg == 0) named_bar_sync(9, REC_THREADS); else named_bar_arrive(9, REC_THREADS);
    }
    if (threadIdx.x == 128) KMARK(8);
    if (warp == 4) {
        if (elect_one()) {
            asm volatile("cp.async.bulk.wait_group 1;" ::: "memory");
            signal_bulk(p.flags + F_LASTTOK);
            bulk_wait_all();
            signal_bulk(p.flags + F_PROGRESS + NSEG - 1);
            KMARK(9);
        }
    } else if (warp == 0) {
        mbar_wait(bar + BAR_X, 1);
        mbar_wait(bar + BAR_VM, 1);
        if (rank == 0) mbar_wait(bar + BAR_F0, 1);
    }
}

__global__ void __launch_bounds__(REC_THREADS, 1) rec_kernel(const __grid_constant__ RecParams p) {
    extern __shared__ __align__(1024) uint8_t smem_raw[];
    const uint32_t sb = smem_u32(smem_raw);
    const int tid = threadIdx.x, lane = tid & 31;
    const int warp = __shfl_sync(~0u, tid >> 5, 0);
    const int cta = blockIdx.x, head = cta / 3, rank = cta % 3;
    const int wg = warp >> 2, wq = warp & 3;
    const uint32_t bar = sb + SM_BAR;
    uint8_t* const xb = p.xchg;
    const uint32_t xlo = (uint32_t)(uint64_t)xb;
    if ((sb & 0x3FFFF) != SMEM_ORIGIN) __trap();
    KENTER(1);
    auto w_box = [&](int part, int g, int i, uint32_t dst, uint32_t mb) {
        const int m = i ^ g;
        const CUtensorMap* tm = &p.tmW[rank == 2 ? 2 : m];
        const int col = head * DH + (rank == 2 ? m : rank) * 64, row = ((part + 1) & 3) * 16;
        tma_load_3d(dst, tm, col, row, g * 8, mb);
    };
    if (tid == 0) {
        mbar_init(bar + BAR_V, 1);
        for (int i = 0; i < 4; i++) { mbar_init(bar + BAR_XG + 8 * i, 1); mbar_init(bar + BAR_M + 8 * i, 1); }
        mbar_init(bar + BAR_GO, 4);
        mbar_init(bar + BAR_PK, 4);
        mbar_init(bar + BAR_VM, rank < 2 ? 1 : 9);
        mbar_init(bar + BAR_F0, 3);
        mbar_init(bar + BAR_F3, 3);
        mbar_init(bar + BAR_VF, 3);
        sts64(bar + BAR_MIN, ~0u, ~0u);
        mbar_init(bar + BAR_X, rank < 2 ? 6 : 1);
        for (int i = 0; i < 3; i++) mbar_init(bar + BAR_P0 + 8 * i, 1);
        mbar_init(bar + BAR_WQ, 1);
        mbar_init(bar + BAR_WO, 1);
        sts32(bar + BAR_SELF, bar + BAR_SELF);
        asm volatile("fence.mbarrier_init.release.cluster;" ::: "memory");
    }
    auto build_tables = [&](uint32_t av) {
        for (uint32_t n = 0; !__all_sync(~0u, (av >> 24) == 24); n++) {
            av = ld_acquire_b32(p.arrivals + (lane & 3));
            if (n > SPIN_LIMIT) __trap();
        }
        uint32_t cm[3];
        #pragma unroll
        for (int i = 0; i < 3; i++) {
            const int o = i * 32 + lane;
            cm[i] = __ballot_sync(~0u, __popc((__shfl_sync(~0u, av, o / 24) >> (o % 24 / 3 * 3)) & 7) >= 2);
        }
        auto color_of = [&](int o) { return ((o < 32 ? cm[0] : o < 64 ? cm[1] : cm[2]) >> (o & 31)) & 1u; };
        auto inbox = [&](int o, int byte) {
            uint32_t c = color_of(o);
            int ones = 0;
            #pragma unroll
            for (int i = 0; i < 3; i++) ones += __popc(o >= i * 32 + 32 ? cm[i] : (o > i * 32 ? cm[i] & ((1u << (o - i * 32)) - 1) : 0u));
            int idx = c ? ones : o - ones;
            if (idx >= INBOX_MAX) { idx = 2 * INBOX_MAX - 1 - idx; c ^= 1; }
            const uint32_t lin = idx * 6144 + byte, q = XCHG_INBOX + (lin >> 12) * 8192;
            return q + class_off(xlo + q, c) + (lin & 4095);
        };
        uint32_t off = 0;
        const int grp = (warp + 3) & 3;
        if (lane < 12) {
            const int i = lane >> 2, lt0 = rank * 6;
            const int o = i < 2 ? rank * 32 + warp * 4 + (lane & 3) : (lt0 + ((warp + 4) & 7)) * 4 + (lane & 3);
            off = inbox(min(o, 95), i * 2048 + head * 64);
        } else if (lane == 12) {
            off = inbox(cta, (grp % 3) * 2048);
        } else if (lane == 13) {
            int T;
            if (grp < 2) {
                T = (cta >> 5) * 22 + 8 * grp + ((cta & 31) >> 2);
            } else {
                const int tl = (cta & 63) >> 2;
                T = (tl / 6) * 22 + 16 + tl % 6;
            }
            off = XCHG_PUB + (T >> 4) * 8192 + (T & 15) * 256 + (cta & 3) * 32;
        } else if (lane == 14) {
            const uint32_t q = XCHG_PUB + wq * 8192;
            off = q + class_off(xlo + q, color_of(cta));
        }
        if (lane < 16) asm volatile("st.shared.b32 [%0], %1;" ::"r"(sb + SM_TBL + warp * 64 + (lane & 3) * 16 + (lane >> 2) * 4), "r"(xlo + off) : "memory");
    };
    if (tid >= 32 && tid < 37) asm volatile("prefetch.tensormap [%0];" ::"l"(&p.tmW[0] + (tid - 32)) : "memory");
    if (cta == 0) for (int i = tid; i < F_COUNT; i += REC_THREADS) p.flags[i] = 0;
    __syncthreads();
    auto stage = [](int part) { return ((part + 2) % 3) * 65536; };
    auto load_part = [&](int part) {
        mbar_arrive_expect_tx(bar + BAR_P0 + 8 * part, 65536);
        for (int u = 0; u < 4; u++) w_box(part, u >> 1, u & 1, sb + stage(part) + u * 16384, bar + BAR_P0 + 8 * part);
    };
    asm volatile("barrier.cluster.arrive.relaxed.aligned;" ::: "memory");
    uint4 img = make_uint4(SENT, SENT, SENT, SENT);
    if (cta >= 92) {
        const unsigned short* m = reinterpret_cast<const unsigned short*>(p.mem0) + (cta - 92) * 256 + tid;
        uint32_t w[4];
        #pragma unroll
        for (int i = 0; i < 4; i++) w[i] = (uint32_t)__ldg(m + 2 * i * DM) | ((uint32_t)__ldg(m + (2 * i + 1) * DM) << 16);
        img = make_uint4(w[0], w[1], w[2], w[3]);
    }
    {
        constexpr int NPAIR = (XCHG_SLOT + PUB_BYTES) / 8192;
        uint8_t* pr = xb + (4 + cta) * 8192;
        const uint32_t c0 = class_off(xlo + (4 + cta) * 8192, 0);
        #pragma unroll
        for (int c = 0; c < 2; c++) {
            const bool timed = lane == 0 || (lane == 8 && c == (warp & 1));
            reinterpret_cast<uint4*>(pr + (c0 ^ (c << 12)))[tid] = make_uint4(timed ? 0u : SENT, SENT, SENT, SENT);
        }
        __syncwarp();
        if (lane == 0) {
            uint32_t x = 0;
            for (int k = 0; k < 3; k++) {
                if (k == 0 && warp == 0) load_part(0);
                const uint32_t c = (k + warp) & 1, t0 = clock_after(x);
                x = atomicExch(reinterpret_cast<uint32_t*>(pr + (c0 ^ (c << 12)) + warp * 512 + (k >> 1) * 128 + x), SENT);
                const uint32_t lat = clock_after(x) - t0;
                asm volatile("red.shared.min.u32 [%0], %1;" ::"r"(bar + BAR_MIN + 4 * c), "r"(lat) : "memory");
            }
        }
        __syncwarp();
        if (cta >= 92 || 100 + cta < NPAIR) {
            if (cta >= 92) {
                if (img.x == SENT) img.x = 0x7FFF7FFFu;
                if (img.y == SENT) img.y = 0x7FFF7FFFu;
                if (img.z == SENT) img.z = 0x7FFF7FFFu;
                if (img.w == SENT) img.w = 0x7FFF7FFFu;
            }
            uint8_t* q = xb + (cta >= 92 ? cta - 92 : 100 + cta) * 8192;
            reinterpret_cast<uint4*>(q)[tid] = img;
            reinterpret_cast<uint4*>(q + 4096)[tid] = img;
        }
    }
    __syncthreads();
    PSTAMP(4);
    if (tid == 0) {
        for (int part = 1; part < 3; part++) load_part(part);
    }
    if (tid == 224) {
        const uint32_t c = lds32_volatile(bar + BAR_MIN) > lds32_volatile(bar + BAR_MIN + 4) ? 1 : 0;
        asm volatile("red.release.gpu.global.add.u32 [%0], %1;" ::"l"(p.arrivals + cta / 24), "r"((1u << 24) | (c << (cta % 24))) : "memory");
    }
    uint32_t wr[NREG][2][4];
    uint32_t arrived = 0;
    {
        const int mi = lane >> 3, r8 = lane & 7;
        const uint32_t a0 = sb + wg * 32768 + ((mi >> 1) * 8 + r8) * 128 + (((wq * 2 + (mi & 1)) ^ r8) << 4);
        #pragma unroll
        for (int part = 0; part < 3; part++) {
            mbar_wait_bounded(bar + BAR_P0 + 8 * part, 0);
            if (part == 0) arrived = ld_relaxed_b32(p.arrivals + (lane & 3));
            #pragma unroll
            for (int j = 0; j < 8; j++) {
                #pragma unroll
                for (int i = 0; i < 2; i++) ldsm4t(a0 + stage(part) + i * 16384 + j * 2048, wr[part * 8 + j][i]);
            }
            asm volatile("fence.proxy.async.shared::cta;" ::: "memory");
            __syncthreads();
            PSTAMP(5 + part);
            if (tid == 0) {
                if (part == 0) {
                    for (int g = 0; g < 4; g++) {
                        mbar_arrive_expect_tx(bar + BAR_XG + 8 * g, 16384);
                        tma_load_3d(sb + SM_X + g * 16384, &p.tmX, 0, 0, g * 4, bar + BAR_XG + 8 * g);
                    }
                } else if (part == 1) {
                    mbar_arrive_expect_tx(bar + BAR_WQ, 65536);
                    for (int u = 0; u < 4; u++) w_box(3, u >> 1, u & 1, sb + SM_WQ + u * 16384, bar + BAR_WQ);
                } else {
                    mbar_arrive_expect_tx(bar + BAR_WO, 11 * 8192);
                    tma_load_3d(sb + SM_WO, &p.tmWo, 0, head * DH, rank * 11, bar + BAR_WO);
                    if (cta < 4)
                        asm volatile("cp.async.bulk.prefetch.tensor.3d.L2.global [%0, {%1, %2, %3}];"
                                     ::"l"(&p.tmX), "r"(0), "r"(SEG), "r"(cta * 4) : "memory");
                }
            }
        }
    }
    build_tables(arrived);
    if (tid == 64) {
        uint32_t smid;
        asm volatile("mov.u32 %0, %%smid;" : "=r"(smid));
        if (smid < 384) atomicOr(p.flags + F_RECSM + (smid >> 5), 1u << (smid & 31));
    }
    __syncwarp();
    PSTAMP(9);
    mbar_wait(bar + BAR_WQ, 0);
    asm volatile("barrier.cluster.wait.aligned;" ::: "memory");

    rec_steps(p, wr, sb, warp, cta, head, rank);
    if (cta == 0 && tid < 4) p.arrivals[tid] = 0;
    if (tid == 128) KEXIT(1);
}

constexpr int ATT_SLOT = 28672;
constexpr int ATT_PAIRS = 8;
constexpr int ATT_BAR = ATT_PAIRS * ATT_SLOT;
constexpr int ATT_SMEM = ATT_BAR + ATT_PAIRS * 16;
constexpr int ATT_THREADS = ATT_PAIRS * 64;
struct AttnParams {
    CUtensorMap tmOa;
    CUtensorMap tmQb, tmKb;
    CUtensorMap tmOb;
    const __nv_bfloat16* qkv_tok;
    const __nv_bfloat16* kv_mem;
    uint32_t* flags;
};

__device__ __forceinline__ void tok_attn_warp(uint32_t base, int mh, int lane) {
    const uint32_t sq = base, sk = base + 8192, sv = base + 16384, skm = base + 24576, svm = skm + 2048;
    const int g = lane >> 2, c = lane & 3, mi = lane >> 3, r8 = lane & 7;
    const int ntile = mh ? 5 : 3;
    float sc[5][4];
    #pragma unroll
    for (int j = 0; j < 5; j++) { sc[j][0] = sc[j][1] = sc[j][2] = sc[j][3] = 0.f; }
    #pragma unroll
    for (int t2 = 0; t2 < 4; t2++) {
        uint32_t a[2][4];
        #pragma unroll
        for (int h = 0; h < 2; h++) {
            const int row = mh * 16 + (mi & 1) * 8 + r8, ch16 = 4 * t2 + 2 * h + (mi >> 1);
            ldsm_x4(sq + (ch16 >> 3) * 4096 + row * 128 + (((ch16 & 7) ^ r8) << 4), a[h][0], a[h][1], a[h][2], a[h][3]);
        }
        const int ch16 = 4 * t2 + mi;
        uint32_t b[5][4];
        #pragma unroll
        for (int j = 0; j < 5; j++) {
            if (j < ntile) {
                if (j == 0) ldsm_x4(skm + (ch16 >> 3) * 1024 + r8 * 128 + (((ch16 & 7) ^ r8) << 4), b[j][0], b[j][1], b[j][2], b[j][3]);
                else ldsm_x4(sk + (ch16 >> 3) * 4096 + ((j - 1) * 8 + r8) * 128 + (((ch16 & 7) ^ r8) << 4), b[j][0], b[j][1], b[j][2], b[j][3]);
            }
        }
        #pragma unroll
        for (int h = 0; h < 2; h++) {
            #pragma unroll
            for (int j = 0; j < 5; j++)
                if (j < ntile) mma16816(sc[j], a[h][0], a[h][1], a[h][2], a[h][3], b[j][2 * h], b[j][2 * h + 1]);
        }
    }
    const float sl2 = 0.08838834764831845f * 1.4426950408889634f;
    uint32_t pf[2][5];
    float inv[2];
    #pragma unroll
    for (int q = 0; q < 2; q++) {
        const int tok = mh * 16 + q * 8 + g;
        float v[10];
        #pragma unroll
        for (int j = 0; j < 5; j++) {
            #pragma unroll
            for (int e = 0; e < 2; e++) {
                const int key = (j - 1) * 8 + 2 * c + e;
                v[2 * j + e] = (j == 0 || key <= tok) ? sc[j][2 * q + e] : -INFINITY;
            }
        }
        float mx = v[0];
        #pragma unroll
        for (int j = 1; j < 10; j++) mx = fmaxf(mx, v[j]);
        mx = fmaxf(mx, __shfl_xor_sync(~0u, mx, 1));
        mx = fmaxf(mx, __shfl_xor_sync(~0u, mx, 2));
        const float mo = mx * sl2;
        float sum = 0.f;
        #pragma unroll
        for (int j = 0; j < 10; j++) { v[j] = ex2(fmaf(v[j], sl2, -mo)); sum += v[j]; }
        sum += __shfl_xor_sync(~0u, sum, 1);
        sum += __shfl_xor_sync(~0u, sum, 2);
        inv[q] = rcp(sum);
        #pragma unroll
        for (int j = 0; j < 5; j++) pf[q][j] = pack_bf16(v[2 * j], v[2 * j + 1]);
    }
    auto load_v = [&](int n4, uint32_t (&vm)[4], uint32_t (&vt)[4][4]) {
        const uint2 va = lds64(svm + n4 * 512 + lane * 8), vb = lds64(svm + n4 * 512 + 256 + lane * 8);
        vm[0] = va.x; vm[1] = va.y; vm[2] = vb.x; vm[3] = vb.y;
        #pragma unroll
        for (int u = 0; u < 4; u++) {
            const int dt = 2 * n4 + (u >> 1), kh = u & 1;
            const uint4 v = lds128(sv + (dt & 3) * 2048 + (dt >> 2) * 1024 + kh * 512 + lane * 16);
            vt[u & 2][2 * kh] = v.x; vt[u & 2][2 * kh + 1] = v.z;
            vt[(u & 2) + 1][2 * kh] = v.y; vt[(u & 2) + 1][2 * kh + 1] = v.w;
        }
    };
    uint32_t vm[2][4], vt[2][4][4];
    load_v(0, vm[0], vt[0]);
    #pragma unroll
    for (int n4 = 0; n4 < 4; n4++) {
        const int cur = n4 & 1;
        if (n4 + 1 < 4) load_v(n4 + 1, vm[cur ^ 1], vt[cur ^ 1]);
        float o[4][4];
        #pragma unroll
        for (int u = 0; u < 4; u++) {
            o[u][0] = o[u][1] = o[u][2] = o[u][3] = 0.f;
            mma16816(o[u], pf[0][1], pf[1][1], pf[0][2], pf[1][2], vt[cur][u][0], vt[cur][u][1]);
        }
        if (mh) {
            #pragma unroll
            for (int u = 0; u < 4; u++) mma16816(o[u], pf[0][3], pf[1][3], pf[0][4], pf[1][4], vt[cur][u][2], vt[cur][u][3]);
        }
        #pragma unroll
        for (int u = 0; u < 4; u++) mma1688(o[u], pf[0][0], pf[1][0], vm[cur][u]);
        #pragma unroll
        for (int u = 0; u < 4; u += 2) {
            const int row = mh * 16 + (mi & 1) * 8 + r8, nt = 4 * n4 + u + (mi >> 1);
            stsm_x4(sq + (nt >> 3) * 4096 + row * 128 + (((nt & 7) ^ r8) << 4),
                    pack_bf16(o[u][0] * inv[0], o[u][1] * inv[0]), pack_bf16(o[u][2] * inv[1], o[u][3] * inv[1]),
                    pack_bf16(o[u + 1][0] * inv[0], o[u + 1][1] * inv[0]), pack_bf16(o[u + 1][2] * inv[1], o[u + 1][3] * inv[1]));
        }
    }
}

__device__ __forceinline__ void b_attn_warp(uint32_t base, int hl, int idx0, int lane) {
    const uint32_t sq = base, sk = base + 8192, sv = base + 8192 + 9216;
    const int g = lane >> 2, c = lane & 3;
    auto addr = [&](uint32_t t, int row, int ch) { return t + row * 128 + ((ch ^ (row & 7)) << 4); };
    const float sl2 = 0.17677669529663687f * 1.4426950408889634f;
    #pragma unroll 2
    for (int blk = 0; blk < 4; blk++) {
        const int r0 = blk * 16;
        float sc[3][4];
        #pragma unroll
        for (int j = 0; j < 3; j++) { sc[j][0] = sc[j][1] = sc[j][2] = sc[j][3] = 0.f; }
        #pragma unroll
        for (int t = 0; t < 2; t++) {
            uint32_t a0, a1, a2, a3, b0, b1, b2, b3, d0, d1, d2, d3;
            const int mi = lane >> 3, r = lane & 7;
            ldsm_x4(addr(sq, r0 + (mi & 1) * 8 + r, hl * 4 + 2 * t + (mi >> 1)), a0, a1, a2, a3);
            ldsm_x4(addr(sk, r0 + (mi >> 1) * 8 + r, hl * 4 + 2 * t + (mi & 1)), b0, b1, b2, b3);
            ldsm_x4(addr(sk, r0 + 16 + r, hl * 4 + 2 * t + (mi & 1)), d0, d1, d2, d3);
            mma16816(sc[0], a0, a1, a2, a3, b0, b1);
            mma16816(sc[1], a0, a1, a2, a3, b2, b3);
            mma16816(sc[2], a0, a1, a2, a3, d0, d1);
        }
        uint32_t pf[2][3];
        float inv[2];
        #pragma unroll
        for (int r = 0; r < 2; r++) {
            const int u = r * 8 + g;
            float v[6];
            #pragma unroll
            for (int j = 0; j < 3; j++) {
                #pragma unroll
                for (int e = 0; e < 2; e++) {
                    const int key = j * 8 + 2 * c + e;
                    const bool ok = key > u && key <= u + 8 && idx0 + r0 - 8 + key >= 0;
                    v[2 * j + e] = ok ? sc[j][2 * r + e] : -INFINITY;
                }
            }
            float mx = fmaxf(fmaxf(fmaxf(v[0], v[1]), fmaxf(v[2], v[3])), fmaxf(v[4], v[5]));
            mx = fmaxf(mx, __shfl_xor_sync(~0u, mx, 1));
            mx = fmaxf(mx, __shfl_xor_sync(~0u, mx, 2));
            const float mo = mx * sl2;
            float sum = 0.f;
            #pragma unroll
            for (int j = 0; j < 6; j++) { v[j] = ex2(fmaf(v[j], sl2, -mo)); sum += v[j]; }
            sum += __shfl_xor_sync(~0u, sum, 1);
            sum += __shfl_xor_sync(~0u, sum, 2);
            inv[r] = rcp(sum);
            #pragma unroll
            for (int j = 0; j < 3; j++) pf[r][j] = pack_bf16(v[2 * j], v[2 * j + 1]);
        }
        uint32_t ow[4][2];
        {
            const int mi = lane >> 3, r = lane & 7;
            uint32_t vv[4][4];
            #pragma unroll
            for (int nt = 0; nt < 4; nt++)
                ldsm_x4_t(addr(sv, r0 + min(mi, 2) * 8 + r, hl * 4 + nt), vv[nt][0], vv[nt][1], vv[nt][2], vv[nt][3]);
            float o[4][4];
            #pragma unroll
            for (int nt = 0; nt < 4; nt++) {
                o[nt][0] = o[nt][1] = o[nt][2] = o[nt][3] = 0.f;
                mma16816(o[nt], pf[0][0], pf[1][0], pf[0][1], pf[1][1], vv[nt][0], vv[nt][1]);
            }
            #pragma unroll
            for (int nt = 0; nt < 4; nt++) mma1688(o[nt], pf[0][2], pf[1][2], vv[nt][2]);
            #pragma unroll
            for (int nt = 0; nt < 4; nt++) {
                ow[nt][0] = pack_bf16(o[nt][0] * inv[0], o[nt][1] * inv[0]);
                ow[nt][1] = pack_bf16(o[nt][2] * inv[1], o[nt][3] * inv[1]);
            }
        }
        #pragma unroll
        for (int u = 0; u < 4; u += 2) {
            const int mi = lane >> 3, r = lane & 7;
            stsm_x4(addr(sq, r0 + (mi & 1) * 8 + r, hl * 4 + u + (mi >> 1)), ow[u][0], ow[u][1], ow[u + 1][0], ow[u + 1][1]);
        }
    }
}

constexpr uint32_t QKVB_TARGET = 12 * 8;
constexpr uint32_t PROGRESS_TARGET = 96;
constexpr uint32_t OA_TARGET = 64, OB_TARGET = 32;
#define ATT_B0 8
#define ATT_BSTEP 2
constexpr int ATT_TASKS = (NSEG + 16) * 32;
static_assert(ATT_B0 + 16 * ATT_BSTEP <= NSEG, "order of the task groups");
__device__ __forceinline__ int att_group(int g, bool& isb) {
    constexpr int P = ATT_BSTEP + 1;
    const int q = g - ATT_B0;
    isb = q >= 0 && q < 16 * P && q % P == 0;
    return q < 0 ? g : q >= 16 * P ? g - 16 : isb ? q / P : g - q / P - 1;
}

__global__ void __launch_bounds__(ATT_THREADS, 1) attn_kernel(const __grid_constant__ AttnParams p) {
    extern __shared__ __align__(1024) uint8_t smem_raw[];
    const int tid = threadIdx.x, lane = tid & 31, warp = __shfl_sync(~0u, tid >> 5, 0);
    const int pair = warp >> 1, wi = warp & 1;
    const uint32_t base = smem_u32(smem_raw) + pair * ATT_SLOT, bar = smem_u32(smem_raw) + ATT_BAR + pair * 16;
    const bool leader = wi == 0 && lane == 0;
    if (tid == 0) pdl_launch_dependents();
    KENTER(3);
    uint32_t phase = 0;
    if (leader) {
        mbar_init(bar, 1);
        asm volatile("fence.mbarrier_init.release.cluster;" ::: "memory");
    }
    uint32_t* pending = nullptr;
    auto flush = [&]() {
        if (pending) {
            bulk_wait_all();
            signal_bulk(pending);
            if (pending == p.flags + F_OA + NSEG - 1) KMARK(14);
            pending = nullptr;
        }
    };
    int ready_a = -1, ready_b = -1;
    for (int task = pair * gridDim.x + blockIdx.x; task < ATT_TASKS; task += ATT_PAIRS * gridDim.x) {
        bool isb;
        const int grp = att_group(task >> 5, isb), i = task & 31;
        named_bar_sync(1 + pair, 64);
        if (leader) {
            {
                auto need = [&](const uint32_t* f, uint32_t target) {
                    if (ld_acquire_b32(f) < target) { flush(); wait_flag(f, target); }
                };
                if (isb) {
                    if (grp > ready_b) {
                        need(p.flags + F_QKVB + grp, QKVB_TARGET);
                        if (grp > 0) need(p.flags + F_QKVB + grp - 1, QKVB_TARGET);
                        asm volatile("fence.proxy.async.global;" ::: "memory");
                        ready_b = grp;
                    }
                    mbar_arrive_expect_tx(bar, 8192 + 2 * 9216);
                    tma_load_3d(base, &p.tmQb, (i >> 1) * 64, i & 1, grp * 64, bar);
                    tma_load_3d(base + 8192, &p.tmKb, DM + (i >> 1) * 64, i & 1, grp * 64 - 8, bar);
                    tma_load_3d(base + 8192 + 9216, &p.tmKb, 2 * DM + (i >> 1) * 64, i & 1, grp * 64 - 8, bar);
                } else {
                    if (grp > ready_a) {
                        need(p.flags + (grp == NSEG - 1 ? F_LASTTOK : F_PROGRESS + grp), PROGRESS_TARGET);
                        asm volatile("fence.proxy.async.global;" ::: "memory");
                        ready_a = grp;
                    }
                    if (grp == 63) KMARK(10);
                    mbar_arrive_expect_tx(bar, ATT_SLOT);
                    #pragma unroll
                    for (int w = 0; w < 3; w++)
                        bulk_load(base + w * 8192, p.qkv_tok + (((size_t)w * NSEG + grp) * NH + i) * (SEG * DH), 8192, bar);
                    if (grp == NSEG - 1) {
                        need(p.flags + F_PROGRESS + grp, PROGRESS_TARGET);
                        asm volatile("fence.proxy.async.global;" ::: "memory");
                    }
                    #pragma unroll
                    for (int w = 0; w < 2; w++)
                        bulk_load(base + 24576 + w * 2048, p.kv_mem + (((size_t)w * NSEG + grp) * NH + i) * (MROWS * DH), 2048, bar);
                }
            }
        }
        if (lane == 0) flush();
        __syncwarp();
        mbar_wait_sleep(bar, phase);
        phase ^= 1;
        if (isb) {
            b_attn_warp(base, wi, grp * 64, lane);
            asm volatile("fence.proxy.async.shared::cta;" ::: "memory");
            named_bar_sync(1 + pair, 64);
            if (wi == 1 && lane == 0) {
                asm volatile("cp.async.bulk.tensor.3d.global.shared::cta.bulk_group [%0, {%2, %3, %4}], [%1];"
                             ::"l"(&p.tmOb), "r"(base), "r"((i >> 1) * 64), "r"(i & 1), "r"(grp * 64) : "memory");
                pending = p.flags + F_OB + grp;
            }
        } else {
            if (grp == 63 && lane == 0) KMARK(11);
            tok_attn_warp(base, wi, lane);
            if (grp == 63 && lane == 0) KMARK(12);
            asm volatile("fence.proxy.async.shared::cta;" ::: "memory");
            __syncwarp();
            if (lane == 0) {
                #pragma unroll
                for (int h = 0; h < 2; h++) tma_store_2d(&p.tmOa, base + h * 4096 + wi * 2048, i * DH + h * 64, grp * SEG + wi * 16);
                pending = p.flags + F_OA + grp;
            }
        }
        if (lane == 0) { bulk_commit(); bulk_wait_read_all(); }
        __syncwarp();
    }
    if (lane == 0) { flush(); KEXIT(3); }
}

typedef CUresult (*EncodeFn)(CUtensorMap*, CUtensorMapDataType, cuuint32_t, void*, const cuuint64_t*, const cuuint64_t*,
                             const cuuint32_t*, const cuuint32_t*, CUtensorMapInterleave, CUtensorMapSwizzle,
                             CUtensorMapL2promotion, CUtensorMapFloatOOBfill);

void make_map_2d(EncodeFn enc, CUtensorMap* m, const void* ptr, uint64_t rows, uint64_t cols, uint32_t box_rows) {
    cuuint64_t dims[2] = {cols, rows};
    cuuint64_t strides[1] = {cols * 2};
    cuuint32_t box[2] = {64, box_rows};
    cuuint32_t es[2] = {1, 1};
    enc(m, CU_TENSOR_MAP_DATA_TYPE_BFLOAT16, 2, const_cast<void*>(ptr), dims, strides, box, es,
        CU_TENSOR_MAP_INTERLEAVE_NONE, CU_TENSOR_MAP_SWIZZLE_128B, CU_TENSOR_MAP_L2_PROMOTION_L2_256B,
        CU_TENSOR_MAP_FLOAT_OOB_FILL_NONE);
}
void make_map_b(EncodeFn enc, CUtensorMap* m, const void* ptr, uint64_t k, uint64_t n, uint32_t nblk, uint32_t box_rows = 64,
                uint32_t bc = 64) {
    cuuint64_t dims[3] = {bc, k, n / bc};
    cuuint64_t strides[2] = {n * 2, bc * 2};
    cuuint32_t box[3] = {bc, box_rows, nblk};
    cuuint32_t es[3] = {1, 1, 1};
    enc(m, CU_TENSOR_MAP_DATA_TYPE_BFLOAT16, 3, const_cast<void*>(ptr), dims, strides, box, es,
        CU_TENSOR_MAP_INTERLEAVE_NONE, bc == 64 ? CU_TENSOR_MAP_SWIZZLE_128B : CU_TENSOR_MAP_SWIZZLE_64B, CU_TENSOR_MAP_L2_PROMOTION_L2_256B,
        CU_TENSOR_MAP_FLOAT_OOB_FILL_NONE);
}

void make_map_parity(EncodeFn enc, CUtensorMap* m, const void* ptr, uint64_t cols, uint32_t box_rows) {
    cuuint64_t dims[3] = {cols, 2, S_TOK / 2};
    cuuint64_t strides[2] = {cols * 2, cols * 4};
    cuuint32_t box[3] = {64, 1, box_rows};
    cuuint32_t es[3] = {1, 1, 1};
    enc(m, CU_TENSOR_MAP_DATA_TYPE_BFLOAT16, 3, const_cast<void*>(ptr), dims, strides, box, es,
        CU_TENSOR_MAP_INTERLEAVE_NONE, CU_TENSOR_MAP_SWIZZLE_128B, CU_TENSOR_MAP_L2_PROMOTION_L2_128B,
        CU_TENSOR_MAP_FLOAT_OOB_FILL_NONE);
}
void make_map_w(EncodeFn enc, CUtensorMap* m, const void* ptr) {
    cuuint64_t dims[3] = {HD, 64, DM / 64};
    cuuint64_t strides[2] = {HD * 2, 64 * HD * 2};
    cuuint32_t box[3] = {64, 16, 8};
    cuuint32_t es[3] = {1, 1, 1};
    enc(m, CU_TENSOR_MAP_DATA_TYPE_BFLOAT16, 3, const_cast<void*>(ptr), dims, strides, box, es,
        CU_TENSOR_MAP_INTERLEAVE_NONE, CU_TENSOR_MAP_SWIZZLE_128B, CU_TENSOR_MAP_L2_PROMOTION_L2_256B,
        CU_TENSOR_MAP_FLOAT_OOB_FILL_NONE);
}

#define SIDE_ORDER 0
#define SERIAL_ATT_CTAS h.n_sm
#define N_TAIL_CTAS 28
#define N_SIDE_CTAS 28
#define N_ATT_CTAS 8
#define TAIL_BLOCK0 11

#define TAIL_SPARE 2
#define TAIL_KB2 30
#define TAIL_KB3 20
#define TAIL_BLOCK1 13
#define TAIL_BLOCK2 14

struct HostState {
    bool ready;
    bool overlap;
    int n_side, n_att, n_sm;
    SideParams seq_a, seq_b;
    const void* key[11];
    RecParams rec;
    SideParams side, tail;
    FinalParams fin;
    AttnParams attn;
    __nv_bfloat16 *qkv_tok, *kv_mem, *o_tok, *qkv_b, *o_b;
    uint8_t* xchg;
};
HostState g_host;

void setup(void* const* d_in, void* d_out) {
    HostState& h = g_host;
    void* fn = nullptr;
    cudaDriverEntryPointQueryResult qr;
    cudaGetDriverEntryPoint("cuTensorMapEncodeTiled", &fn, cudaEnableDefault, &qr);
    EncodeFn enc = reinterpret_cast<EncodeFn>(fn);
    void* ptr;
    cudaGetSymbolAddress(&ptr, g_qkv_tok); h.qkv_tok = (__nv_bfloat16*)ptr;
    cudaGetSymbolAddress(&ptr, g_kv_mem);  h.kv_mem = (__nv_bfloat16*)ptr;
    cudaGetSymbolAddress(&ptr, g_o_tok);   h.o_tok = (__nv_bfloat16*)ptr;
    cudaGetSymbolAddress(&ptr, g_qkv_b);   h.qkv_b = (__nv_bfloat16*)ptr;
    cudaGetSymbolAddress(&ptr, g_o_b);     h.o_b = (__nv_bfloat16*)ptr;
    cudaGetSymbolAddress(&ptr, g_xchg);    h.xchg = (uint8_t*)(((uint64_t)ptr + XCHG_BYTES - 1) & ~(uint64_t)(XCHG_BYTES - 1));
    cudaGetSymbolAddress(&ptr, g_flags);   uint32_t* flags = (uint32_t*)ptr;
    cudaGetSymbolAddress(&ptr, g_arrivals); uint32_t* arrivals = (uint32_t*)ptr;

    const void *xa = d_in[0], *mem0 = d_in[1], *wq = d_in[2], *wk = d_in[3], *wv = d_in[4], *wo = d_in[5];
    const void *xb = d_in[7], *wqkv = d_in[8], *wob = d_in[9];

    RecParams& r = h.rec;
    make_map_w(enc, &r.tmW[0], wq);
    make_map_w(enc, &r.tmW[1], wk);
    make_map_w(enc, &r.tmW[2], wv);
    make_map_b(enc, &r.tmWo, wo, HD, DM, 11, 128, 32);
    r.mem0 = (const __nv_bfloat16*)mem0;
    r.qkv_tok = h.qkv_tok; r.kv_mem = h.kv_mem; r.xchg = h.xchg;
    r.flags = flags; r.arrivals = arrivals; r.one[0] = r.one[1] = 1;
    make_map_b(enc, &r.tmX, xa, S_TOK, DM, 4, SEG);

    SideParams& sd = h.side;
    SideProb& p0 = sd.prob[0];
    make_map_2d(enc, &p0.tmA, xb, S_TOK, DM, BM);
    make_map_b(enc, &p0.tmB, wqkv, DM, 3 * DM, 4);
    make_map_2d(enc, &p0.tmC, h.qkv_b, S_TOK, 3 * DM, 16);
    p0.n_tiles = 3 * DM / 256; p0.k_blocks = DM / BK; p0.c_col0 = 0; p0.dep = nullptr; p0.dep_target = 0; p0.dep_n = 1; p0.sig = flags + F_QKVB;
    SideProb& p1 = sd.prob[1];
    make_map_2d(enc, &p1.tmA, h.o_tok, S_TOK, HD, BM);
    make_map_b(enc, &p1.tmB, wo, HD, DM, 4);
    make_map_2d(enc, &p1.tmC, d_out, S_TOK, 2 * DM, 16);
    p1.n_tiles = DM / 256; p1.k_blocks = HD / BK; p1.c_col0 = 0; p1.dep = flags + F_OA; p1.dep_target = OA_TARGET; p1.dep_n = 4; p1.sig = nullptr;
    SideProb& p2 = sd.prob[2];
    make_map_2d(enc, &p2.tmA, h.o_b, S_TOK, DM, BM);
    make_map_b(enc, &p2.tmB, wob, DM, DM, 4);
    p2.tmC = p1.tmC;
    p2.n_tiles = DM / 256; p2.k_blocks = DM / BK; p2.c_col0 = DM; p2.dep = flags + F_OB; p2.dep_target = OB_TARGET; p2.dep_n = 1; p2.sig = nullptr;
    p0.n_split = p0.n_tiles; p1.n_split = p1.n_tiles; p2.n_split = p2.n_tiles;
    p0.part = p1.part = p2.part = nullptr;
    p0.k_total = p0.k_blocks; p1.k_total = p1.k_blocks; p2.k_total = p2.k_blocks;
    if (SIDE_ORDER == 0) { sd.seg[0] = {0, 0, 16}; sd.seg[1] = {1, 0, TAIL_BLOCK0}; }
    else { sd.seg[0] = {1, 0, TAIL_BLOCK0}; sd.seg[1] = {0, 0, 16}; }
    sd.seg[2] = {2, 0, 16};
    sd.nseg = 3; sd.queue = flags + F_SIDEQ; sd.spare_seg = 3; sd.flags = flags;

    SideParams& tl = h.tail;
    tl.prob[0] = p1;
    make_map_b(enc, &tl.prob[0].tmB, wo, HD, DM, 2);
    cudaGetSymbolAddress(&ptr, g_part);
    for (int i = 0; i < 3; i++) {
        SideProb& q = tl.prob[i];
        q = tl.prob[0];
        q.n_tiles = (i + 1) * DM / 128; q.n_split = DM / 128; q.k_blocks = i == 0 ? HD / BK : i == 1 ? TAIL_KB2 : TAIL_KB3;
        q.part = i ? (float*)ptr : nullptr; q.part_flag = flags + F_PART;
    }
    tl.seg[0] = {0, TAIL_BLOCK0, TAIL_BLOCK1};
    tl.seg[1] = {1, TAIL_BLOCK1, TAIL_BLOCK2};
    tl.seg[2] = {2, TAIL_BLOCK2, 15};
    tl.nseg = 3; tl.queue = flags + F_TAILQ; tl.spare_seg = TAIL_SPARE; tl.flags = flags;

    make_map_2d(enc, &h.fin.tmA, h.o_tok, S_TOK, HD, SEG);
    h.fin.tmB = tl.prob[0].tmB; h.fin.out = (__nv_bfloat16*)d_out;
    h.fin.dep = flags + F_OA + 60; h.fin.dep_target = OA_TARGET; h.fin.mt = 15;

    make_map_2d(enc, &h.attn.tmOa, h.o_tok, S_TOK, HD, 16);
    make_map_parity(enc, &h.attn.tmQb, h.qkv_b, 3 * DM, 64);
    make_map_parity(enc, &h.attn.tmKb, h.qkv_b, 3 * DM, 72);
    make_map_parity(enc, &h.attn.tmOb, h.o_b, DM, 64);
    h.attn.qkv_tok = h.qkv_tok; h.attn.kv_mem = h.kv_mem; h.attn.flags = flags;

    int dev = 0, nsm = 0;
    cudaGetDevice(&dev);
    cudaDeviceGetAttribute(&nsm, cudaDevAttrMultiProcessorCount, dev);
    h.n_sm = nsm;
    h.overlap = nsm - 96 >= N_SIDE_CTAS + N_ATT_CTAS;
    h.n_side = N_SIDE_CTAS; h.n_att = N_ATT_CTAS;
    h.seq_a = sd;
    h.seq_a.seg[0] = {0, 0, 16};
    h.seq_a.nseg = 1;
    h.seq_b = sd;
    h.seq_b.seg[0] = {1, 0, 16};
    h.seq_b.seg[1] = {2, 0, 16};
    h.seq_b.nseg = 2; h.seq_b.queue = flags + F_TAILQ;

    cudaFuncSetAttribute(side_gemm_kernel<256>, cudaFuncAttributeMaxDynamicSharedMemorySize, GemmCfg<256>::SMEM);
    cudaFuncSetAttribute(side_gemm_kernel<128>, cudaFuncAttributeMaxDynamicSharedMemorySize, GemmCfg<128>::SMEM);
    cudaFuncSetAttribute(final_gemm_kernel, cudaFuncAttributeMaxDynamicSharedMemorySize, FIN_SMEM);
    cudaFuncSetAttribute(rec_kernel, cudaFuncAttributeMaxDynamicSharedMemorySize, REC_SMEM);
    cudaFuncSetAttribute(attn_kernel, cudaFuncAttributeMaxDynamicSharedMemorySize, ATT_SMEM);
    for (int i = 0; i < 10; i++) h.key[i] = d_in[i];
    h.key[10] = d_out;
    h.ready = true;
}

template <typename K, typename P>
void launch(K kernel, int grid, int block, int smem, cudaStream_t st, const P& prm, int cluster, bool pdl) {
    cudaLaunchConfig_t cfg = {};
    cfg.gridDim = dim3(grid); cfg.blockDim = dim3(block); cfg.dynamicSmemBytes = smem; cfg.stream = st;
    cudaLaunchAttribute at[2];
    int n = 0;
    if (cluster > 1) {
        at[n].id = cudaLaunchAttributeClusterDimension;
        at[n].val.clusterDim.x = cluster; at[n].val.clusterDim.y = 1; at[n].val.clusterDim.z = 1;
        n++;
    }
    if (pdl) {
        at[n].id = cudaLaunchAttributeProgrammaticStreamSerialization;
        at[n].val.programmaticStreamSerializationAllowed = 1;
        n++;
    }
    cfg.attrs = at; cfg.numAttrs = n;
    cudaLaunchKernelEx(&cfg, kernel, prm);
}

}

extern "C" void kernel_launch(void* const* d_in, const int* in_sizes, int n_in, void* d_out, int out_size) {
    HostState& h = g_host;
    bool same = h.ready;
    for (int i = 0; same && i < 10; i++) same = h.key[i] == d_in[i];
    if (!same || h.key[10] != d_out) setup(d_in, d_out);
    cudaStream_t st = cudaStreamPerThread;

    launch(rec_kernel, 96, REC_THREADS, REC_SMEM, st, h.rec, 3, false);
    {
        if (!h.overlap) {
            launch(side_gemm_kernel<256>, h.n_sm, 384, GemmCfg<256>::SMEM, st, h.seq_a, 1, false);
            launch(attn_kernel, SERIAL_ATT_CTAS, ATT_THREADS, ATT_SMEM, st, h.attn, 1, false);
            launch(side_gemm_kernel<256>, h.n_sm, 384, GemmCfg<256>::SMEM, st, h.seq_b, 1, false);
            return;
        }
    }
    launch(side_gemm_kernel<256>, h.n_side, 384, GemmCfg<256>::SMEM, st, h.side, 1, true);
    launch(attn_kernel, h.n_att, ATT_THREADS, ATT_SMEM, st, h.attn, 1, true);
    launch(side_gemm_kernel<128>, N_TAIL_CTAS, 384, GemmCfg<128>::SMEM, st, h.tail, 1, true);
    launch(final_gemm_kernel, 8 * FIN_SPLIT, 384, FIN_SMEM, st, h.fin, FIN_SPLIT, true);
}
```

```cpp
#include <cuda_runtime.h>
#include <cuda_bf16.h>
#include <cuda.h>
#include <stdint.h>

namespace {

constexpr int S_TOK = 2048;
constexpr int DM = 1024;
constexpr int NH = 32;
constexpr int DH = 128;
constexpr int HD = NH * DH;
constexpr int NSEG = 64;
constexpr int SEG = 32;
constexpr int MROWS = 8;
constexpr uint32_t SENT = 0xFFFFFFFFu;
constexpr uint32_t SPIN_LIMIT = 1u << 24;

__device__ __align__(1024) __nv_bfloat16 g_qkv_tok[3ull * NSEG * NH * SEG * DH];
__device__ __align__(1024) __nv_bfloat16 g_kv_mem[2ull * NSEG * NH * MROWS * DH];
__device__ __align__(1024) __nv_bfloat16 g_o_tok[(size_t)S_TOK * HD];
__device__ __align__(1024) __nv_bfloat16 g_qkv_b[(size_t)S_TOK * 3 * DM];
__device__ __align__(1024) __nv_bfloat16 g_o_b[(size_t)S_TOK * DM];
__device__ __align__(1024) float g_part[32 * 2 * 128 * 128];
constexpr int PUB_BYTES = 32768;
constexpr int XCHG_SLOT = 1 << 20;
constexpr int XCHG_PUB = 0, XCHG_INBOX = 2 * PUB_BYTES;
constexpr int INBOX_MAX = 80;
constexpr int XCHG_BYTES = 2 * XCHG_SLOT;
__device__ __align__(8192) uint8_t g_xchg[2 * XCHG_BYTES];
enum { F_LASTTOK = 0, F_RECSM = 4, F_PROGRESS = 16, F_QKVB = 80, F_OB = 96, F_OA = 112, F_PART = 176, F_SIDEQ = 208, F_TAILQ = 256, F_COUNT = 304 };
__device__ uint32_t g_flags[F_COUNT];
__device__ __align__(16) uint32_t g_arrivals[4];

#define STAMP(k) do {} while (0)
#define STAMPD(k, x) do {} while (0)
#define PSTAMP(k) do {} while (0)
#define KENTER(k) do {} while (0)
#define KEXIT(k) do {} while (0)
#define KMARK(k) do {} while (0)

__device__ __forceinline__ uint32_t class_off(uint64_t a, uint32_t c) {
    return ((__popc((uint32_t)a & 0xB3000u) ^ c) & 1u) << 12;
}
__device__ __forceinline__ uint32_t smem_u32(const void* p) { return (uint32_t)__cvta_generic_to_shared(p); }
__device__ __forceinline__ uint32_t pack_bf16(float lo, float hi) {
    uint32_t r;
    asm("cvt.rn.bf16x2.f32 %0, %1, %2;" : "=r"(r) : "f"(hi), "f"(lo));
    return r;
}
__device__ __forceinline__ float ex2(float x) {
    float y;
    asm("ex2.approx.ftz.f32 %0, %1;" : "=f"(y) : "f"(x));
    return y;
}
__device__ __forceinline__ float rcp(float x) {
    float y;
    asm("rcp.approx.ftz.f32 %0, %1;" : "=f"(y) : "f"(x));
    return y;
}
__device__ __forceinline__ uint32_t clock32() {
    uint32_t t;
    asm volatile("mov.u32 %0, %%clock;" : "=r"(t));
    return t;
}
__device__ __forceinline__ uint32_t clock_lo() {
    unsigned long long t;
    asm volatile("mov.u64 %0, %%clock64;" : "=l"(t));
    return (uint32_t)t;
}
__device__ __forceinline__ uint32_t clock_after(uint32_t x) {
    uint32_t t;
    asm volatile("{\n.reg .pred p;\nsetp.eq.u32 p, %1, 0x12345678;\n@p exit;\nmov.u32 %0, %%clock;\n}" : "=r"(t) : "r"(x) : "memory");
    return t;
}
__device__ __forceinline__ uint32_t opaque(uint32_t x) { return __shfl_sync(~0u, x, threadIdx.x & 31); }
__device__ __forceinline__ uint32_t uniform(uint32_t x) { return __shfl_sync(~0u, x + (threadIdx.x & 31), 0); }
__device__ __forceinline__ float bf16_lo(uint32_t w) { return __uint_as_float(w << 16); }
__device__ __forceinline__ float bf16_hi(uint32_t w) { return __uint_as_float(w & 0xFFFF0000u); }

__device__ __forceinline__ void mbar_init(uint32_t bar, uint32_t cnt) {
    asm volatile("mbarrier.init.shared::cta.b64 [%0], %1;" ::"r"(bar), "r"(cnt) : "memory");
}
__device__ __forceinline__ void mbar_arrive(uint32_t bar) {
    asm volatile("mbarrier.arrive.shared::cta.b64 _, [%0];" ::"r"(bar) : "memory");
}
__device__ __forceinline__ void mbar_arrive_expect_tx(uint32_t bar, uint32_t bytes) {
    asm volatile("mbarrier.arrive.expect_tx.shared::cta.b64 _, [%0], %1;" ::"r"(bar), "r"(bytes) : "memory");
}
__device__ __forceinline__ bool mbar_try_wait(uint32_t bar, uint32_t parity) {
    uint32_t ok;
    asm volatile(
        "{\n.reg .pred p;\n"
        "mbarrier.try_wait.parity.shared::cta.b64 p, [%1], %2;\n"
        "selp.u32 %0, 1, 0, p;\n}"
        : "=r"(ok) : "r"(bar), "r"(parity) : "memory");
    return ok != 0;
}
__device__ __forceinline__ bool mbar_test_wait(uint32_t bar, uint32_t parity) {
    uint32_t ok;
    asm volatile(
        "{\n.reg .pred p;\n"
        "mbarrier.test_wait.parity.shared::cta.b64 p, [%1], %2;\n"
        "selp.u32 %0, 1, 0, p;\n}"
        : "=r"(ok) : "r"(bar), "r"(parity) : "memory");
    return ok != 0;
}
__device__ __forceinline__ void mbar_wait(uint32_t bar, uint32_t parity) {
    uint32_t n = 0;
    while (!mbar_try_wait(bar, parity)) {
        if (++n > SPIN_LIMIT) __trap();
    }
}
__device__ __forceinline__ void mbar_wait_sleep(uint32_t bar, uint32_t parity) {
    uint32_t n = 0;
    while (!mbar_try_wait(bar, parity)) {
        __nanosleep(20);
        if (++n > SPIN_LIMIT) __trap();
    }
}
__device__ __forceinline__ void mbar_wait_bounded(uint32_t bar, uint32_t parity) {
    for (uint32_t n = 0; n < (1u << 20) && !mbar_try_wait(bar, parity); n++) {}
}
__device__ __forceinline__ bool elect_one() {
    uint32_t ok;
    asm volatile("{\n.reg .pred p;\nelect.sync _|p, 0xFFFFFFFF;\nselp.u32 %0, 1, 0, p;\n}" : "=r"(ok));
    return ok != 0;
}
__device__ __forceinline__ void named_bar_sync(int id, int nthreads) {
    asm volatile("bar.sync %0, %1;" ::"r"(id), "r"(nthreads) : "memory");
}
__device__ __forceinline__ void named_bar_arrive(int id, int nthreads) {
    asm volatile("bar.arrive %0, %1;" ::"r"(id), "r"(nthreads) : "memory");
}
__device__ __forceinline__ uint32_t mapa(uint32_t addr, uint32_t rank) {
    uint32_t r;
    asm volatile("mapa.shared::cluster.u32 %0, %1, %2;" : "=r"(r) : "r"(addr), "r"(rank));
    return r;
}

__device__ __forceinline__ void tma_load_2d(uint32_t dst, const CUtensorMap* tm, int c0, int c1, uint32_t bar) {
    asm volatile(
        "cp.async.bulk.tensor.2d.shared::cluster.global.mbarrier::complete_tx::bytes [%0], [%1, {%3, %4}], [%2];"
        ::"r"(dst), "l"(tm), "r"(bar), "r"(c0), "r"(c1) : "memory");
}
__device__ __forceinline__ void tma_load_3d(uint32_t dst, const CUtensorMap* tm, int c0, int c1, int c2, uint32_t bar) {
    asm volatile(
        "cp.async.bulk.tensor.3d.shared::cluster.global.mbarrier::complete_tx::bytes [%0], [%1, {%3, %4, %5}], [%2];"
        ::"r"(dst), "l"(tm), "r"(bar), "r"(c0), "r"(c1), "r"(c2) : "memory");
}
__device__ __forceinline__ void tma_load_3d_mc(uint32_t dst, const CUtensorMap* tm, int c0, int c1, int c2, uint32_t bar, uint16_t mask) {
    asm volatile(
        "cp.async.bulk.tensor.3d.shared::cluster.global.mbarrier::complete_tx::bytes.multicast::cluster [%0], [%1, {%3, %4, %5}], [%2], %6;"
        ::"r"(dst), "l"(tm), "r"(bar), "r"(c0), "r"(c1), "r"(c2), "h"(mask) : "memory");
}
__device__ __forceinline__ void tma_store_2d(const CUtensorMap* tm, uint32_t src, int c0, int c1) {
    asm volatile("cp.async.bulk.tensor.2d.global.shared::cta.bulk_group [%0, {%2, %3}], [%1];"
                 ::"l"(tm), "r"(src), "r"(c0), "r"(c1) : "memory");
}
__device__ __forceinline__ void bulk_store(void* dst, uint32_t src, uint32_t bytes) {
    asm volatile("cp.async.bulk.global.shared::cta.bulk_group [%0], [%1], %2;" ::"l"(dst), "r"(src), "r"(bytes) : "memory");
}
__device__ __forceinline__ void bulk_commit() { asm volatile("cp.async.bulk.commit_group;" ::: "memory"); }
__device__ __forceinline__ void bulk_wait_read_all() { asm volatile("cp.async.bulk.wait_group.read 0;" ::: "memory"); }
__device__ __forceinline__ void bulk_wait_all() { asm volatile("cp.async.bulk.wait_group 0;" ::: "memory"); }
__device__ __forceinline__ void bulk_load(uint32_t dst, const void* src, uint32_t bytes, uint32_t bar) {
    asm volatile("cp.async.bulk.shared::cluster.global.mbarrier::complete_tx::bytes [%0], [%1], %2, [%3];"
                 ::"r"(dst), "l"(src), "r"(bytes), "r"(bar) : "memory");
}

__device__ __forceinline__ void ldsm_x4(uint32_t addr, uint32_t& r0, uint32_t& r1, uint32_t& r2, uint32_t& r3) {
    asm volatile("ldmatrix.sync.aligned.m8n8.x4.shared.b16 {%0,%1,%2,%3}, [%4];"
                 : "=r"(r0), "=r"(r1), "=r"(r2), "=r"(r3) : "r"(addr) : "memory");
}
__device__ __forceinline__ void ldsm_x4_t(uint32_t addr, uint32_t& r0, uint32_t& r1, uint32_t& r2, uint32_t& r3) {
    asm volatile("ldmatrix.sync.aligned.m8n8.x4.trans.shared.b16 {%0,%1,%2,%3}, [%4];"
                 : "=r"(r0), "=r"(r1), "=r"(r2), "=r"(r3) : "r"(addr) : "memory");
}
__device__ __forceinline__ void stsm_x4(uint32_t addr, uint32_t r0, uint32_t r1, uint32_t r2, uint32_t r3) {
    asm volatile("stmatrix.sync.aligned.m8n8.x4.shared.b16 [%0], {%1,%2,%3,%4};"
                 ::"r"(addr), "r"(r0), "r"(r1), "r"(r2), "r"(r3) : "memory");
}
__device__ __forceinline__ void mma16816(float* d, uint32_t a0, uint32_t a1, uint32_t a2, uint32_t a3,
                                         uint32_t b0, uint32_t b1) {
    asm volatile(
        "mma.sync.aligned.m16n8k16.row.col.f32.bf16.bf16.f32 {%0,%1,%2,%3}, {%4,%5,%6,%7}, {%8,%9}, {%0,%1,%2,%3};"
        : "+f"(d[0]), "+f"(d[1]), "+f"(d[2]), "+f"(d[3])
        : "r"(a0), "r"(a1), "r"(a2), "r"(a3), "r"(b0), "r"(b1));
}
__device__ __forceinline__ void mma1688(float* d, uint32_t a0, uint32_t a1, uint32_t b0) {
    asm volatile("mma.sync.aligned.m16n8k8.row.col.f32.bf16.bf16.f32 {%0,%1,%2,%3}, {%4,%5}, {%6}, {%0,%1,%2,%3};"
                 : "+f"(d[0]), "+f"(d[1]), "+f"(d[2]), "+f"(d[3]) : "r"(a0), "r"(a1), "r"(b0));
}
__device__ __forceinline__ uint2 lds64(uint32_t addr) {
    uint2 v;
    asm volatile("ld.volatile.shared.v2.b32 {%0,%1}, [%2];" : "=r"(v.x), "=r"(v.y) : "r"(addr) : "memory");
    return v;
}
__device__ __forceinline__ uint4 lds128(uint32_t addr) {
    uint4 v;
    asm volatile("ld.volatile.shared.v4.b32 {%0,%1,%2,%3}, [%4];" : "=r"(v.x), "=r"(v.y), "=r"(v.z), "=r"(v.w) : "r"(addr) : "memory");
    return v;
}
__device__ __forceinline__ void sts32(uint32_t addr, uint32_t x) {
    asm volatile("st.volatile.shared.b32 [%0], %1;" ::"r"(addr), "r"(x) : "memory");
}
__device__ __forceinline__ void sts64(uint32_t addr, uint32_t x, uint32_t y) {
    asm volatile("st.volatile.shared.v2.b32 [%0], {%1,%2};" ::"r"(addr), "r"(x), "r"(y) : "memory");
}
__device__ __forceinline__ void sts128(uint32_t addr, uint32_t x, uint32_t y, uint32_t z, uint32_t w) {
    asm volatile("st.volatile.shared.v4.b32 [%0], {%1,%2,%3,%4};" ::"r"(addr), "r"(x), "r"(y), "r"(z), "r"(w) : "memory");
}
__device__ __forceinline__ void st_async_v2(uint32_t addr, uint32_t x, uint32_t y, uint32_t bar) {
    asm volatile("st.async.weak.shared::cluster.mbarrier::complete_tx::bytes.v2.b32 [%0], {%1,%2}, [%3];"
                 ::"r"(addr), "r"(x), "r"(y), "r"(bar) : "memory");
}
__device__ __forceinline__ void st_relaxed_v4(void* p, uint32_t x) {
    asm volatile("st.relaxed.gpu.global.v4.b32 [%0], {%1,%1,%1,%1};" ::"l"(p), "r"(x) : "memory");
}
__device__ __forceinline__ uint32_t ld_relaxed_b32(const void* p) {
    uint32_t v;
    asm volatile("ld.relaxed.gpu.global.b32 %0, [%1];" : "=r"(v) : "l"(p) : "memory");
    return v;
}
__device__ __forceinline__ uint32_t lds32_volatile(uint32_t addr) {
    uint32_t v;
    asm volatile("ld.volatile.shared.b32 %0, [%1];" : "=r"(v) : "r"(addr) : "memory");
    return v;
}
__device__ __forceinline__ void st_relaxed_b32(void* p, uint32_t x) {
    asm volatile("st.relaxed.gpu.global.b32 [%0], %1;" ::"l"(p), "r"(x) : "memory");
}

__device__ __forceinline__ uint32_t ld_acquire_b32(const void* p) {
    uint32_t v;
    asm volatile("ld.acquire.gpu.global.b32 %0, [%1];" : "=r"(v) : "l"(p) : "memory");
    return v;
}
__device__ __forceinline__ void wait_flag(const uint32_t* p, uint32_t target) {
    uint32_t n = 0;
    while (ld_acquire_b32(p) < target) {
        __nanosleep(64);
        if (++n > SPIN_LIMIT) __trap();
    }
}
__device__ __forceinline__ void signal_flag(uint32_t* p) {
    asm volatile("red.release.gpu.global.add.u32 [%0], 1;" ::"l"(p) : "memory");
}
__device__ __forceinline__ void signal_bulk(uint32_t* p) {
    asm volatile("red.relaxed.gpu.global.add.u32 [%0], 1;" ::"l"(p) : "memory");
}
__device__ __forceinline__ bool next_to_rec(const uint32_t* flags) {
    uint32_t smid;
    asm volatile("mov.u32 %0, %%smid;" : "=r"(smid));
    smid ^= 1;
    return smid < 384 && ((ld_relaxed_b32(flags + F_RECSM + (smid >> 5)) >> (smid & 31)) & 1);
}
__device__ __forceinline__ void pdl_launch_dependents() { asm volatile("griddepcontrol.launch_dependents;" ::: "memory"); }

constexpr int BM = 128, BK = 64;
constexpr int A_STAGE = BM * BK * 2;
template <int BN> struct GemmCfg {
    static constexpr int STAGES = BN == 256 ? 3 : 6;
    static constexpr int STAGE = A_STAGE + BK * BN * 2;
    static constexpr int EPI_WARP = 16 * BN * 2;
    static constexpr int SMEM = STAGES * STAGE + 8 * EPI_WARP + 1024 + 512;
};

struct SideProb {
    CUtensorMap tmA, tmB, tmC;
    int n_split;
    int n_tiles, k_blocks, k_total, c_col0;
    const uint32_t* dep;
    uint32_t dep_target;
    int dep_n;
    uint32_t* sig;
    float* part;
    uint32_t* part_flag;
};
struct SideSeg { int prob, m0, m1; };
constexpr int SIDE_MAX_SEG = 3;
struct SideParams {
    SideProb prob[3];
    SideSeg seg[SIDE_MAX_SEG];
    int nseg;
    int spare_seg;
    const uint32_t* flags;
    uint32_t* queue;
};
static_assert(sizeof(SideParams) <= 4096, "kernel parameter limit");

__device__ __forceinline__ uint64_t make_desc(uint32_t addr, uint32_t lbo, uint32_t sbo) {
    return (uint64_t)((addr & 0x3FFFF) >> 4) | ((uint64_t)(lbo >> 4) << 16) | ((uint64_t)(sbo >> 4) << 32) | (1ull << 62);
}

__device__ __forceinline__ void wgmma_m64n256k16(float (&d)[128], uint64_t da, uint64_t db, int scale_d) {
    asm volatile(
        "{\n.reg .pred p;\nsetp.ne.b32 p, %130, 0;\n"
        "wgmma.mma_async.sync.aligned.m64n256k16.f32.bf16.bf16 "
        "{%0,%1,%2,%3,%4,%5,%6,%7,%8,%9,%10,%11,%12,%13,%14,%15,"
        "%16,%17,%18,%19,%20,%21,%22,%23,%24,%25,%26,%27,%28,%29,%30,%31,"
        "%32,%33,%34,%35,%36,%37,%38,%39,%40,%41,%42,%43,%44,%45,%46,%47,"
        "%48,%49,%50,%51,%52,%53,%54,%55,%56,%57,%58,%59,%60,%61,%62,%63,"
        "%64,%65,%66,%67,%68,%69,%70,%71,%72,%73,%74,%75,%76,%77,%78,%79,"
        "%80,%81,%82,%83,%84,%85,%86,%87,%88,%89,%90,%91,%92,%93,%94,%95,"
        "%96,%97,%98,%99,%100,%101,%102,%103,%104,%105,%106,%107,%108,%109,%110,%111,"
        "%112,%113,%114,%115,%116,%117,%118,%119,%120,%121,%122,%123,%124,%125,%126,%127},"
        " %128, %129, p, 1, 1, 0, 1;\n}\n"
        : "+f"(d[0]), "+f"(d[1]), "+f"(d[2]), "+f"(d[3]), "+f"(d[4]), "+f"(d[5]), "+f"(d[6]), "+f"(d[7]),
          "+f"(d[8]), "+f"(d[9]), "+f"(d[10]), "+f"(d[11]), "+f"(d[12]), "+f"(d[13]), "+f"(d[14]), "+f"(d[15]),
          "+f"(d[16]), "+f"(d[17]), "+f"(d[18]), "+f"(d[19]), "+f"(d[20]), "+f"(d[21]), "+f"(d[22]), "+f"(d[23]),
          "+f"(d[24]), "+f"(d[25]), "+f"(d[26]), "+f"(d[27]), "+f"(d[28]), "+f"(d[29]), "+f"(d[30]), "+f"(d[31]),
          "+f"(d[32]), "+f"(d[33]), "+f"(d[34]), "+f"(d[35]), "+f"(d[36]), "+f"(d[37]), "+f"(d[38]), "+f"(d[39]),
          "+f"(d[40]), "+f"(d[41]), "+f"(d[42]), "+f"(d[43]), "+f"(d[44]), "+f"(d[45]), "+f"(d[46]), "+f"(d[47]),
          "+f"(d[48]), "+f"(d[49]), "+f"(d[50]), "+f"(d[51]), "+f"(d[52]), "+f"(d[53]), "+f"(d[54]), "+f"(d[55]),
          "+f"(d[56]), "+f"(d[57]), "+f"(d[58]), "+f"(d[59]), "+f"(d[60]), "+f"(d[61]), "+f"(d[62]), "+f"(d[63]),
          "+f"(d[64]), "+f"(d[65]), "+f"(d[66]), "+f"(d[67]), "+f"(d[68]), "+f"(d[69]), "+f"(d[70]), "+f"(d[71]),
          "+f"(d[72]), "+f"(d[73]), "+f"(d[74]), "+f"(d[75]), "+f"(d[76]), "+f"(d[77]), "+f"(d[78]), "+f"(d[79]),
          "+f"(d[80]), "+f"(d[81]), "+f"(d[82]), "+f"(d[83]), "+f"(d[84]), "+f"(d[85]), "+f"(d[86]), "+f"(d[87]),
          "+f"(d[88]), "+f"(d[89]), "+f"(d[90]), "+f"(d[91]), "+f"(d[92]), "+f"(d[93]), "+f"(d[94]), "+f"(d[95]),
          "+f"(d[96]), "+f"(d[97]), "+f"(d[98]), "+f"(d[99]), "+f"(d[100]), "+f"(d[101]), "+f"(d[102]), "+f"(d[103]),
          "+f"(d[104]), "+f"(d[105]), "+f"(d[106]), "+f"(d[107]), "+f"(d[108]), "+f"(d[109]), "+f"(d[110]), "+f"(d[111]),
          "+f"(d[112]), "+f"(d[113]), "+f"(d[114]), "+f"(d[115]), "+f"(d[116]), "+f"(d[117]), "+f"(d[118]), "+f"(d[119]),
          "+f"(d[120]), "+f"(d[121]), "+f"(d[122]), "+f"(d[123]), "+f"(d[124]), "+f"(d[125]), "+f"(d[126]), "+f"(d[127])
        : "l"(da), "l"(db), "r"(scale_d));
}

__device__ __forceinline__ void wgmma_m64n128k16(float (&d)[64], uint64_t da, uint64_t db, int scale_d) {
    asm volatile(
        "{\n.reg .pred p;\nsetp.ne.b32 p, %66, 0;\n"
        "wgmma.mma_async.sync.aligned.m64n128k16.f32.bf16.bf16 "
        "{%0,%1,%2,%3,%4,%5,%6,%7,%8,%9,%10,%11,%12,%13,%14,%15,"
        "%16,%17,%18,%19,%20,%21,%22,%23,%24,%25,%26,%27,%28,%29,%30,%31,"
        "%32,%33,%34,%35,%36,%37,%38,%39,%40,%41,%42,%43,%44,%45,%46,%47,"
        "%48,%49,%50,%51,%52,%53,%54,%55,%56,%57,%58,%59,%60,%61,%62,%63},"
        " %64, %65, p, 1, 1, 0, 1;\n}\n"
        : "+f"(d[0]), "+f"(d[1]), "+f"(d[2]), "+f"(d[3]), "+f"(d[4]), "+f"(d[5]), "+f"(d[6]), "+f"(d[7]),
          "+f"(d[8]), "+f"(d[9]), "+f"(d[10]), "+f"(d[11]), "+f"(d[12]), "+f"(d[13]), "+f"(d[14]), "+f"(d[15]),
          "+f"(d[16]), "+f"(d[17]), "+f"(d[18]), "+f"(d[19]), "+f"(d[20]), "+f"(d[21]), "+f"(d[22]), "+f"(d[23]),
          "+f"(d[24]), "+f"(d[25]), "+f"(d[26]), "+f"(d[27]), "+f"(d[28]), "+f"(d[29]), "+f"(d[30]), "+f"(d[31]),
          "+f"(d[32]), "+f"(d[33]), "+f"(d[34]), "+f"(d[35]), "+f"(d[36]), "+f"(d[37]), "+f"(d[38]), "+f"(d[39]),
          "+f"(d[40]), "+f"(d[41]), "+f"(d[42]), "+f"(d[43]), "+f"(d[44]), "+f"(d[45]), "+f"(d[46]), "+f"(d[47]),
          "+f"(d[48]), "+f"(d[49]), "+f"(d[50]), "+f"(d[51]), "+f"(d[52]), "+f"(d[53]), "+f"(d[54]), "+f"(d[55]),
          "+f"(d[56]), "+f"(d[57]), "+f"(d[58]), "+f"(d[59]), "+f"(d[60]), "+f"(d[61]), "+f"(d[62]), "+f"(d[63])
        : "l"(da), "l"(db), "r"(scale_d));
}
template <int BN> struct WgmmaOp;
template <> struct WgmmaOp<256> {
    static __device__ __forceinline__ void run(float (&d)[128], uint64_t a, uint64_t b, int sc) { wgmma_m64n256k16(d, a, b, sc); }
};
template <> struct WgmmaOp<128> {
    static __device__ __forceinline__ void run(float (&d)[64], uint64_t a, uint64_t b, int sc) { wgmma_m64n128k16(d, a, b, sc); }
};

struct StoreRec {
    uint64_t dst;
    uint64_t flag;
    int kind;
    int pad;
};
struct EpiCtx { uint32_t buf, rec, st_full, st_empty; uint32_t it; int lane; };
template <int N>
__device__ __forceinline__ void epi_hand_over(const float (&acc)[N], EpiCtx& e, uint64_t dst, uint64_t flag, int kind) {
    mbar_wait(e.st_empty, (e.it & 1) ^ 1);
    const int mi = e.lane >> 3, row = (mi & 1) * 8 + (e.lane & 7);
    #pragma unroll
    for (int j = 0; j < N / 4; j += 2) {
        const int chunk = (j & 7) + (mi >> 1);
        stsm_x4(e.buf + (j >> 3) * 2048 + row * 128 + ((chunk ^ (row & 7)) << 4),
                pack_bf16(acc[4 * j], acc[4 * j + 1]), pack_bf16(acc[4 * j + 2], acc[4 * j + 3]),
                pack_bf16(acc[4 * j + 4], acc[4 * j + 5]), pack_bf16(acc[4 * j + 6], acc[4 * j + 7]));
    }
    if (e.lane == 0) {
        asm volatile("st.shared.v2.b64 [%0], {%1, %2};" ::"r"(e.rec), "l"(dst), "l"(flag) : "memory");
        asm volatile("st.shared.b32 [%0], %1;" ::"r"(e.rec + 16), "r"(kind) : "memory");
    }
    asm volatile("fence.proxy.async.shared::cta;" ::: "memory");
    __syncwarp();
    if (e.lane == 0) mbar_arrive(e.st_full);
    e.it++;
}
__device__ __forceinline__ void epi_exit(EpiCtx& e) {
    mbar_wait(e.st_empty, (e.it & 1) ^ 1);
    if (e.lane == 0) {
        asm volatile("st.shared.b32 [%0], %1;" ::"r"(e.rec + 16), "r"(-1) : "memory");
        mbar_arrive(e.st_full);
    }
}
template <int BN>
__device__ __forceinline__ void gemm_mainloop(float (&acc)[BN / 2], int k_blocks, uint32_t sbase, uint32_t bar_base, int cw,
                                              bool elected, int& stage, uint32_t& phase) {
    using C = GemmCfg<BN>;
    auto release = [&](int st) { mbar_arrive(bar_base + 8 * (C::STAGES + st)); };
    int prev_stage = -1;
    for (int kb = 0; kb < k_blocks; kb++) {
        mbar_wait(bar_base + 8 * stage, phase);
        const uint32_t sa = sbase + stage * C::STAGE + cw * (64 * 128);
        const uint32_t sb = sbase + stage * C::STAGE + A_STAGE;
        asm volatile("wgmma.fence.sync.aligned;" ::: "memory");
        #pragma unroll
        for (int kk = 0; kk < BK / 16; kk++)
            WgmmaOp<BN>::run(acc, make_desc(sa + kk * 32, 16, 1024), make_desc(sb + kk * 2048, 8192, 1024), (kb | kk) != 0);
        asm volatile("wgmma.commit_group.sync.aligned;" ::: "memory");
        asm volatile("wgmma.wait_group.sync.aligned 1;" ::: "memory");
        if (prev_stage >= 0 && elected) release(prev_stage);
        prev_stage = stage;
        if (++stage == C::STAGES) { stage = 0; phase ^= 1; }
    }
    asm volatile("wgmma.wait_group.sync.aligned 0;" ::: "memory");
    if (elected) release(prev_stage);
}
template <int BN>
__device__ __forceinline__ void store_warp(uint32_t epi_base, uint32_t rec_base, uint32_t st_full, uint32_t st_empty, int lane,
                                           const uint8_t* tmaps, int tstride) {
    for (uint32_t it = 0;; it++) {
        mbar_wait(st_full, it & 1);
        uint64_t dst = 0, flag = 0;
        int kind = -1;
        if (lane < 8) {
            const uint32_t rec = rec_base + lane * 32;
            asm volatile("ld.volatile.shared.v2.b64 {%0, %1}, [%2];" : "=l"(dst), "=l"(flag) : "r"(rec) : "memory");
            kind = (int)lds32_volatile(rec + 16);
        }
        if (__shfl_sync(~0u, kind, 0) < 0) break;
        if (lane < 8) {
            const uint32_t buf = epi_base + lane * GemmCfg<BN>::EPI_WARP;
            #pragma unroll
            for (int q = 0; q < BN / 64; q++) {
                tma_store_2d(reinterpret_cast<const CUtensorMap*>(tmaps + (kind - 1) * tstride), buf + q * 2048,
                                  (int)(uint32_t)dst + q * 64, (int)(dst >> 32));
            }
            bulk_commit();
            bulk_wait_read_all();
            mbar_arrive(st_empty);
            if (flag) {
                bulk_wait_all();
                signal_bulk(reinterpret_cast<uint32_t*>(flag));
            }
        }
        __syncwarp();
    }
    if (lane < 8) bulk_wait_all();
}

#define SCHED_AHEAD 4
template <int BN>
__global__ void __launch_bounds__(384, 1) side_gemm_kernel(const __grid_constant__ SideParams p) {
    using C = GemmCfg<BN>;
    extern __shared__ uint8_t smem_raw[];
    const uint32_t sbase = (smem_u32(smem_raw) + 1023) & ~1023u;
    const uint32_t epi_base = sbase + C::STAGES * C::STAGE;
    const uint32_t bar_base = epi_base + 8 * C::EPI_WARP;
    const uint32_t tfull = bar_base + 16 * C::STAGES, tempty = tfull + 16, tslot = tempty + 16, twant = tslot + 8;
    const uint32_t st_full = bar_base + 192, st_empty = st_full + 8, rec_base = bar_base + 256;
    const int tid = threadIdx.x, wg = tid >> 7;
    if (tid == 0) {
        for (int s = 0; s < C::STAGES; s++) { mbar_init(bar_base + 8 * s, 1); mbar_init(bar_base + 8 * (C::STAGES + s), 2); }
        for (int s = 0; s < 2; s++) { mbar_init(tfull + 8 * s, 1); mbar_init(tempty + 8 * s, 3); }
        mbar_init(twant, 1);
        mbar_init(st_full, 8);
        mbar_init(st_empty, 8);
        asm volatile("fence.mbarrier_init.release.cluster;" ::: "memory");
        pdl_launch_dependents();
    }
    __syncthreads();
    KENTER(BN == 256 ? 2 : 4);

    if (wg == 0) {
        asm volatile("setmaxnreg.dec.sync.aligned.u32 40;");
        if (tid == 0) {
            int stage = 0; uint32_t phase = 1;
            for (uint32_t it = 0;; it++) {
                mbar_wait(tfull + 8 * (it & 1), (it >> 1) & 1);
                const int code = (int)lds32_volatile(tslot + 4 * (it & 1));
                mbar_arrive(tempty + 8 * (it & 1));
                if (code < 0) break;
                const SideProb& q = p.prob[code >> 16];
                const int mt = (code >> 8) & 255, nt = code & 255;
                asm volatile("fence.proxy.async.global;" ::: "memory");
                const int kb0 = nt / q.n_split * q.k_blocks, nkb = nt + q.n_split < q.n_tiles ? q.k_blocks : q.k_total - kb0;
                for (int kb = 0; kb < nkb; kb++) {
                    if (kb == nkb - SCHED_AHEAD) mbar_arrive(twant);
                    mbar_wait(bar_base + 8 * (C::STAGES + stage), phase);
                    const uint32_t sa = sbase + stage * C::STAGE, fb = bar_base + 8 * stage;
                    mbar_arrive_expect_tx(fb, C::STAGE);
                    const int k0 = (kb0 + kb) * BK;
                    tma_load_2d(sa, &q.tmA, k0, mt * BM, fb);
                    tma_load_3d(sa + A_STAGE, &q.tmB, 0, k0, nt % q.n_split * (BN / 64), fb);
                    if (++stage == C::STAGES) { stage = 0; phase ^= 1; }
                }
            }
        } else if (tid >= 64 && tid < 96) {
            const int lane = tid & 31;
            const bool spare = p.spare_seg < 3 && next_to_rec(p.flags);
            uint32_t ntl[2], tgt[2], prb[2];
            const uint32_t* dp[2];
            #pragma unroll
            for (int u = 0; u < 2; u++) {
                const int g = u * 2 + (lane >> 4), mt = lane & 15;
                const bool on = g < p.nseg && mt >= p.seg[g < p.nseg ? g : 0].m0 && mt < p.seg[g < p.nseg ? g : 0].m1;
                prb[u] = p.seg[on ? g : 0].prob;
                const SideProb& q = p.prob[prb[u]];
                ntl[u] = on && !(g >= p.spare_seg && spare) ? q.n_tiles : 0;
                tgt[u] = on && q.dep ? q.dep_target : 0;
                dp[u] = tgt[u] ? q.dep + (mt + 1) * q.dep_n - 1 : p.queue;
            }
            for (uint32_t it = 0;; it++) {
                if (it > 0) mbar_wait_sleep(twant, (it - 1) & 1);
                int code = -1;
                for (uint32_t tries = 0; code < 0; tries++) {
                    const uint32_t c0 = ld_relaxed_b32(p.queue + lane), c1 = ld_relaxed_b32(p.queue + 32 + (lane & 15));
                    const uint32_t d0 = ld_relaxed_b32(dp[0]), d1 = ld_relaxed_b32(dp[1]);
                    const uint64_t left = __ballot_sync(~0u, c0 < ntl[0]) | (uint64_t)__ballot_sync(~0u, c1 < ntl[1]) << 32;
                    uint64_t ready = left & (__ballot_sync(~0u, d0 >= tgt[0]) | (uint64_t)__ballot_sync(~0u, d1 >= tgt[1]) << 32);
                    if (!left) break;
                    if (!ready && (BN == 128 || (left >> (((__ffsll(left) - 1) & ~15) + 16)) == 0)) ready = left;
                    if (!ready) __nanosleep(200);
                    while (ready) {
                        const int e = __ffsll(ready) - 1;
                        const uint32_t n = __shfl_sync(~0u, e < 32 ? ntl[0] : ntl[1], e & 31), pr = __shfl_sync(~0u, e < 32 ? prb[0] : prb[1], e & 31);
                        uint32_t idx = 0;
                        if (lane == 0) idx = atomicAdd(p.queue + e, 1u);
                        idx = __shfl_sync(~0u, idx, 0);
                        if (idx < n) { code = (pr << 16) | ((e & 15) << 8) | idx; break; }
                        for (uint32_t k = idx / n; k > 0; k--) ready &= ready - 1;
                    }
                    if (tries > SPIN_LIMIT) __trap();
                }
                if (code >= 0) {
                    const SideProb& q = p.prob[code >> 16];
                    if (q.dep && lane < q.dep_n) wait_flag(q.dep + ((code >> 8) & 255) * q.dep_n + lane, q.dep_target);
                    __syncwarp();
                }
                if (lane == 0) {
                    mbar_wait(tempty + 8 * (it & 1), ((it >> 1) & 1) ^ 1);
                    asm volatile("st.shared.b32 [%0], %1;" ::"r"(tslot + 4 * (it & 1)), "r"(code) : "memory");
                    mbar_arrive(tfull + 8 * (it & 1));
                }
                __syncwarp();
                if (code < 0) break;
            }
        } else if (tid >= 32 && tid < 64) {
            store_warp<BN>(epi_base, rec_base, st_full, st_empty, tid & 31, reinterpret_cast<const uint8_t*>(&p.prob[0].tmC),
                           (int)sizeof(SideProb));
        }
    } else {
        asm volatile("setmaxnreg.inc.sync.aligned.u32 232;");
        const int cw = wg - 1, lane = tid & 31, wi = (tid >> 5) & 3;
        const bool elected = (tid & 127) == 0;
        int stage = 0; uint32_t phase = 0;
        float acc[BN / 2];
        EpiCtx ectx = {epi_base + (cw * 4 + wi) * C::EPI_WARP, rec_base + (cw * 4 + wi) * 32, st_full, st_empty, 0, lane};
        for (uint32_t it = 0;; it++) {
            mbar_wait(tfull + 8 * (it & 1), (it >> 1) & 1);
            const int code = (int)lds32_volatile(tslot + 4 * (it & 1));
            named_bar_sync(1 + cw, 128);
            if (elected) mbar_arrive(tempty + 8 * (it & 1));
            if (code < 0) break;
            const SideProb& q = p.prob[code >> 16];
            const int mt = (code >> 8) & 255, nt = code & 255;
            gemm_mainloop<BN>(acc, nt + q.n_split < q.n_tiles ? q.k_blocks : q.k_total - nt / q.n_split * q.k_blocks, sbase, bar_base, cw, elected, stage, phase);
            const int row0 = mt * BM + cw * 64 + wi * 16, ntc = nt % q.n_split;
            if (BN == 128 && q.part) {
                const int idx = (mt & 3) * q.n_split + ntc, item = nt / q.n_split, nprev = q.n_tiles / q.n_split - 1;
                float4* part = reinterpret_cast<float4*>(q.part) + (size_t)idx * 2 * (BM * BN / 4) + (tid - 128);
                if (mt == 14 && elected) KMARK(21);
                if (item < nprev) {
                    #pragma unroll
                    for (int j = 0; j < BN / 8; j++)
                        __stcg(part + item * (BM * BN / 4) + j * 256, make_float4(acc[4 * j], acc[4 * j + 1], acc[4 * j + 2], acc[4 * j + 3]));
                    __syncwarp();
                    if (lane == 0) signal_flag(q.part_flag + idx);
                    continue;
                }
                if (lane == 0) wait_flag(q.part_flag + idx, 8 * nprev);
                __syncwarp();
                if (mt == 14 && elected) KMARK(22);
                for (int u = 0; u < nprev; u++) {
                    #pragma unroll
                    for (int j = 0; j < BN / 8; j++) {
                        const float4 v = __ldcg(part + u * (BM * BN / 4) + j * 256);
                        acc[4 * j] += v.x; acc[4 * j + 1] += v.y; acc[4 * j + 2] += v.z; acc[4 * j + 3] += v.w;
                    }
                }
            }
            if (BN == 128 && mt == 14 && elected) KMARK(23);
            epi_hand_over(acc, ectx, ((uint64_t)row0 << 32) | (uint32_t)(q.c_col0 + ntc * BN), q.sig ? (uint64_t)(q.sig + mt) : 0, 1 + (code >> 16));
        }
        epi_exit(ectx);
        if (elected) KEXIT(BN == 256 ? 2 : 4);
    }
}

constexpr int FIN_SPLIT = 8, FIN_KB = HD / BK / FIN_SPLIT;
constexpr int FIN_A1 = FIN_KB * 16384;
constexpr int FIN_A0 = FIN_A1 + FIN_KB * 8192;
constexpr int FIN_BAR = FIN_A0 + 4 * 8192, FIN_SMEM = FIN_BAR + 256;
enum { FB_B = 0, FB_A1 = 64, FB_A0 = 128, FB_E0 = 160, FB_RDY = 192, FB_RED = 208 };
struct FinalParams {
    CUtensorMap tmA, tmB;
    __nv_bfloat16* out;
    const uint32_t* dep;
    uint32_t dep_target;
    int mt;
};
__global__ void __launch_bounds__(384, 1) final_gemm_kernel(const __grid_constant__ FinalParams p) {
    extern __shared__ __align__(1024) uint8_t smem_raw[];
    const uint32_t sbase = smem_u32(smem_raw), bar = sbase + FIN_BAR;
    const int tid = threadIdx.x, wg = tid >> 7;
    const int rank = blockIdx.x % FIN_SPLIT, nt = blockIdx.x / FIN_SPLIT;
    KENTER(5);
    if (tid == 0) {
        for (int s = 0; s < FIN_KB; s++) { mbar_init(bar + FB_B + 8 * s, 1); mbar_init(bar + FB_A1 + 8 * s, 1); }
        for (int s = 0; s < 4; s++) { mbar_init(bar + FB_A0 + 8 * s, 1); mbar_init(bar + FB_E0 + 8 * s, 1); }
        for (int h = 0; h < 2; h++) { mbar_init(bar + FB_RDY + 8 * h, FIN_SPLIT); mbar_init(bar + FB_RED + 8 * h, 1); }
        asm volatile("fence.mbarrier_init.release.cluster;" ::: "memory");
        for (int h = 0; h < 2; h++) mbar_arrive_expect_tx(bar + FB_RED + 8 * h, (FIN_SPLIT - 1) * 4096);
        pdl_launch_dependents();
    }
    __syncthreads();
    asm volatile("barrier.cluster.arrive.relaxed.aligned;" ::: "memory");
    if (wg == 0) {
        auto need = [&](int i) {
            uint32_t n = 0;
            while (ld_acquire_b32(p.dep + i) < p.dep_target) { if (++n > SPIN_LIMIT) __trap(); }
            asm volatile("fence.proxy.async.global;" ::: "memory");
        };
        auto a_load = [&](uint32_t dst, int kb, int seg, uint32_t mb) { tma_load_2d(dst, &p.tmA, (rank * FIN_KB + kb) * BK, p.mt * BM + seg * SEG, mb); };
        if (tid == 0) {
            auto b_load = [&](int kb) {
                mbar_arrive_expect_tx(bar + FB_B + 8 * kb, 16384);
                tma_load_3d(sbase + kb * 16384, &p.tmB, 0, (rank * FIN_KB + kb) * BK, nt * 2, bar + FB_B + 8 * kb);
            };
            const uint32_t f0 = ld_relaxed_b32(p.dep);
            b_load(0);
            need(1);
            if (f0 < p.dep_target) need(0);
            for (int kb = 0; kb < FIN_KB; kb++) {
                if (kb >= 4) mbar_wait(bar + FB_E0 + 8 * (kb & 3), 0);
                mbar_arrive_expect_tx(bar + FB_A0 + 8 * (kb & 3), 8192);
                for (int u = 0; u < 2; u++) a_load(sbase + FIN_A0 + (kb & 3) * 8192 + u * 4096, kb, u, bar + FB_A0 + 8 * (kb & 3));
                if (kb < 3) b_load(kb + 1);
                if (kb == 3) { b_load(4); b_load(5); }
                if (kb == 4 || kb == 5) b_load(kb + 2);
            }
        } else if (tid == 96) {
            need(3);
            for (int kb = 1; kb < FIN_KB; kb += 2) a_load(sbase + FIN_A1 + kb * 8192 + 4096, kb, 3, bar + FB_A1 + 8 * kb);
        } else if (tid == 64) {
            mbar_wait(bar + FB_B + 8 * 3, 0);
            need(2);
            for (int kb = 0; kb < FIN_KB; kb++) {
                mbar_arrive_expect_tx(bar + FB_A1 + 8 * kb, 8192);
                a_load(sbase + FIN_A1 + kb * 8192, kb, 2, bar + FB_A1 + 8 * kb);
            }
            need(3);
            KMARK(15);
            for (int kb = 0; kb < FIN_KB; kb += 2) a_load(sbase + FIN_A1 + kb * 8192 + 4096, kb, 3, bar + FB_A1 + 8 * kb);
        }
        __syncwarp();
        asm volatile("barrier.cluster.wait.aligned;" ::: "memory");
    } else {
        const int h = wg - 1, lane = tid & 31, wi = (tid >> 5) & 3, t128 = tid & 127;
        asm volatile("barrier.cluster.wait.aligned;" ::: "memory");
        float acc[64];
        for (int kb = 0; kb < FIN_KB; kb++) {
            mbar_wait(bar + FB_B + 8 * kb, 0);
            if (h == 0) mbar_wait(bar + FB_A0 + 8 * (kb & 3), kb >> 2); else mbar_wait(bar + FB_A1 + 8 * kb, 0);
            const uint32_t sa = sbase + (h == 0 ? FIN_A0 + (kb & 3) * 8192 : FIN_A1 + kb * 8192), sb = sbase + kb * 16384;
            asm volatile("wgmma.fence.sync.aligned;" ::: "memory");
            #pragma unroll
            for (int kk = 0; kk < BK / 16; kk++)
                wgmma_m64n128k16(acc, make_desc(sa + kk * 32, 16, 1024), make_desc(sb + kk * 2048, 8192, 1024), (kb | kk) != 0);
            asm volatile("wgmma.commit_group.sync.aligned;" ::: "memory");
            asm volatile("wgmma.wait_group.sync.aligned 1;" ::: "memory");
            if (h == 0 && kb >= 1 && kb <= 4 && t128 == 0) mbar_arrive(bar + FB_E0 + 8 * (kb - 1));
        }
        asm volatile("wgmma.wait_group.sync.aligned 0;" ::: "memory");
        const uint32_t red = sbase + FIN_A0;
        auto ready = [&](int i) {
            named_bar_sync(1, 128);
            if (t128 < FIN_SPLIT)
                asm volatile("mbarrier.arrive.relaxed.cluster.shared::cluster.b64 _, [%0];" ::"r"(mapa(bar + FB_RDY + 8 * i, t128)) : "memory");
        };
        if (tid == 256) KMARK(16);
        if (tid == 128) KMARK(19);
        if (h == 0) ready(0);
        mbar_wait(bar + FB_RDY + 8 * h, 0);
        if (tid == 256) KMARK(17);
        #pragma unroll
        for (int q = 0; q < FIN_SPLIT; q++) {
            if (q != rank) {
                const uint32_t dst = mapa(red + (rank - (rank > q ? 1 : 0)) * 4096 + t128 * 16, q), rb = mapa(bar + FB_RED + 8 * h, q);
                #pragma unroll
                for (int j = 0; j < 2; j++)
                    asm volatile("st.async.weak.shared::cluster.mbarrier::complete_tx::bytes.v4.f32 [%0], {%1,%2,%3,%4}, [%5];"
                                 ::"r"(dst + j * 2048), "f"(acc[8 * q + 4 * j]), "f"(acc[8 * q + 4 * j + 1]),
                                   "f"(acc[8 * q + 4 * j + 2]), "f"(acc[8 * q + 4 * j + 3]), "r"(rb) : "memory");
            }
        }
        float o[8];
        #pragma unroll
        for (int q = 0; q < FIN_SPLIT; q++)
            if (q == rank) {
                #pragma unroll
                for (int e = 0; e < 8; e++) o[e] = acc[8 * q + e];
            }
        mbar_wait(bar + FB_RED + 8 * h, 0);
        if (tid == 256) KMARK(18);
        if (tid == 128) KMARK(20);
        #pragma unroll
        for (int sl = 0; sl < FIN_SPLIT - 1; sl++) {
            #pragma unroll
            for (int j = 0; j < 2; j++) {
                const uint4 v = lds128(red + sl * 4096 + j * 2048 + t128 * 16);
                o[4 * j] += __uint_as_float(v.x); o[4 * j + 1] += __uint_as_float(v.y);
                o[4 * j + 2] += __uint_as_float(v.z); o[4 * j + 3] += __uint_as_float(v.w);
            }
        }
        if (h == 0) ready(1);
        __nv_bfloat16* dst = p.out + (size_t)(p.mt * BM + h * 64 + wi * 16 + (lane >> 2)) * (2 * DM) + nt * 128 + rank * 16 + (lane & 3) * 2;
        #pragma unroll
        for (int j = 0; j < 2; j++) {
            *reinterpret_cast<uint32_t*>(dst + j * 8) = pack_bf16(o[4 * j], o[4 * j + 1]);
            *reinterpret_cast<uint32_t*>(dst + (size_t)8 * (2 * DM) + j * 8) = pack_bf16(o[4 * j + 2], o[4 * j + 3]);
        }
        if (t128 == 0) KEXIT(5);
    }
}

#define POLL_DELAY 2
#define FETCH_DELAY 450
#define AT_PF 7
#define AT_FIRST 4
#define WO_PF 12
#define WO_PFA 6
#define WO_PFB_DELAY 60
#define V_EARLY 6
constexpr int REC_THREADS = 256;
constexpr uint32_t POLL_LIMIT = 1u << 16;
constexpr int NREG = 24;
__host__ __device__ constexpr int reg_idx(int j) { return ((j & 3) - 1) * 8 + (j >> 2); }
constexpr int SM_WQ = 0;
constexpr int SM_WO = 65536;
constexpr int SM_X = SM_WO + 11 * 8192;
constexpr int SM_PARK0 = SM_X, SM_PARK1 = SM_X + 8192;
constexpr int SM_MEM = SM_X + 4 * 4096;
constexpr int SM_RED = SM_X + 8 * 4096;
constexpr int SM_V = SM_X + 12 * 4096;
constexpr int SM_K = SM_X + 14 * 4096;
constexpr int SM_QS = SM_X + 15 * 4096;
constexpr int SM_QK = SM_X + 65536;
constexpr int SM_SP = SM_QK + 2048;
constexpr int SM_VM = SM_SP + 2560;
constexpr int SM_O = SM_VM + 2048;
constexpr int SM_SUM = SM_O + 2048;
constexpr int SM_TBL = SM_SUM + 128;
constexpr int SM_BAR = SM_TBL + 512;
constexpr int SM_STAMP = SM_BAR + 224;
constexpr int REC_SMEM = SM_STAMP;
static_assert(REC_SMEM <= 232448, "shared memory");
enum { BAR_V = 0, BAR_X = 8, BAR_P0 = 16, BAR_WQ = 40, BAR_WO = 48, BAR_XG = 56, BAR_F0 = 88, BAR_F3 = 96, BAR_VF = 104,
       BAR_M = 112, BAR_GO = 144, BAR_PK = 152, BAR_VM = 160, BAR_SELF = 168, BAR_TPUB = 176, BAR_MIN = 176, BAR_PUB = 192 };

template <int V> struct IntC { static constexpr int value = V; };
template <int I, int N, typename F> __device__ __forceinline__ void sfor(F&& f) {
    if constexpr (I < N) { f(IntC<I>{}); sfor<I + 1, N>(f); }
}

struct RecParams {
    CUtensorMap tmW[3];
    CUtensorMap tmWo;
    CUtensorMap tmX;
    const __nv_bfloat16* mem0;
    __nv_bfloat16* qkv_tok;
    __nv_bfloat16* kv_mem;
    uint8_t* xchg;
    uint32_t* flags;
    uint32_t one[2];
    uint32_t* arrivals;
};

__device__ __forceinline__ void mma_a(float* d, const uint32_t* a, uint32_t b0, uint32_t b1) {
    mma16816(d, a[0], a[1], a[2], a[3], b0, b1);
}
__device__ __forceinline__ void ldsm4(uint32_t addr, uint32_t* r) { ldsm_x4(addr, r[0], r[1], r[2], r[3]); }
__device__ __forceinline__ void ldsm4t(uint32_t addr, uint32_t* r) { ldsm_x4_t(addr, r[0], r[1], r[2], r[3]); }
template <int OFF> __device__ __forceinline__ void repoll_v2(uint2& v, const uint8_t* p) {
    asm volatile("{\n.reg .pred q;\nsetp.eq.u32 q, %1, 0xFFFFFFFF;\n@q ld.relaxed.gpu.global.v2.b32 {%0,%1}, [%2+%3];\n}"
                 : "+r"(v.x), "+r"(v.y) : "l"(p), "n"(OFF) : "memory");
}
__device__ __forceinline__ uint32_t max3(uint32_t a, uint32_t b, uint32_t c) { return max(max(a, b), c); }
__device__ __forceinline__ uint32_t pub_slot(int s) { return (s & 1) * XCHG_SLOT + ((s >> 1) & 1) * PUB_BYTES; }

__device__ __forceinline__ uint8_t* xaddr(uint32_t lo, uint32_t hi) {
    uint64_t a;
    asm("mov.b64 %0, {%1, %2};" : "=l"(a) : "r"(lo), "r"(hi));
    return reinterpret_cast<uint8_t*>(a);
}
template <int N> __device__ __forceinline__ uint32_t delay_zero(uint32_t a) {
    uint32_t x = a;
    #pragma unroll
    for (int i = 0; i < N; i++) x = lds32_volatile(x);
    return x - a;
}
__device__ __forceinline__ uint32_t fresh(uint32_t x) { asm volatile("" : "+r"(x)); return x; }

template <int NT> __device__ __forceinline__ uint32_t wo_addr(uint32_t ao, uint32_t a3, int n) {
    return (n % NT == 2 ? a3 : ao + (n % NT) * 32768) + (n / NT) * 1024;
}
template <int NT, int PF>
__device__ __forceinline__ void wo_phase(uint32_t (&st)[8 * NT][4], uint32_t ao, uint32_t a3, uint32_t l16, uint32_t tbl, uint32_t sums,
                                         uint32_t slot, uint32_t xhi, uint32_t third, uint32_t xbar, uint32_t xpar, bool& x_ok) {
    constexpr int AHEAD = PF > 0 ? PF - NT : 10;
    uint32_t of[4][4];
    uint2 sm;
    uint4 t;
    ldsm4t(l16 + SM_O, of[0]);
    #pragma unroll
    for (int n = PF; n < AHEAD; n++) {
        ldsm4t(wo_addr<NT>(ao, a3, n), st[n]);
        if (n == 2 * NT - 1) ldsm4t(l16 + SM_O + 512, of[1]);
    }
    if (PF >= 2 * NT) ldsm4t(l16 + SM_O + 512, of[1]);
    float acc[NT][4];
    #pragma unroll
    for (int i = 0; i < NT; i++) { acc[i][0] = acc[i][1] = acc[i][2] = acc[i][3] = 0.f; }
    #pragma unroll
    for (int kk = 0; kk < 8; kk++) {
        #pragma unroll
        for (int i = 0; i < NT; i++) {
            const int n = kk * NT + i;
            mma_a(acc[i], st[n], of[kk >> 1][(kk & 1) * 2], of[kk >> 1][(kk & 1) * 2 + 1]);
            if (n + AHEAD >= PF && n + AHEAD < 8 * NT) ldsm4t(wo_addr<NT>(ao, a3, n + AHEAD), st[n + AHEAD]);
        }
        if (kk == 1 || kk == 3) ldsm4t(l16 + SM_O + ((kk >> 1) + 2) * 512, of[(kk >> 1) + 2]);
        if (kk == (NT == 3 ? 5 : 4)) {
            const uint32_t x = fresh(l16);
            sm = lds64(sums + ((x >> 1) & 0x18));
            t = lds128(tbl + ((x >> 3) & 0x30));
            x_ok = mbar_test_wait(xbar, xpar);
        }
    }
    const float i0 = rcp(__uint_as_float(sm.x)), i1 = rcp(__uint_as_float(sm.y));
    const uint32_t d = slot + ((fresh(l16) >> 1) & 0x38);
    const uint32_t pl[3] = {t.x + d, t.y + d, t.z + d};
    #pragma unroll
    for (int i = 0; i < NT; i++)
        asm volatile("{\n.reg .pred p;\nsetp.ne.u32 p, %3, 0;\n@p st.relaxed.gpu.global.v2.b32 [%0], {%1,%2};\n}"
                     ::"l"(xaddr(pl[i], xhi)), "r"(pack_bf16(acc[i][0] * i0, acc[i][1] * i1)), "r"(pack_bf16(acc[i][2] * i0, acc[i][3] * i1)),
                       "r"(i < 2 ? 1u : third) : "memory");
}

constexpr uint32_t SMEM_ORIGIN = 1024;
constexpr uint64_t DESC_BASE = (1ull << 16) | (0x40000040ull << 32);
template <int OFFB, int SCALE_D>
__device__ __forceinline__ void wgmma_n32_rs(float (&d)[16], const uint32_t* a, uint32_t one) {
    asm volatile(
        "{\n.reg .b64 db;\nmad.wide.u32 db, %20, %21, %22;\n"
        "wgmma.mma_async.sync.aligned.m64n32k16.f32.bf16.bf16 {%0,%1,%2,%3,%4,%5,%6,%7,%8,%9,%10,%11,%12,%13,%14,%15}, "
        "{%16,%17,%18,%19}, db, %23, 1, 1, 0;\n}"
        : "+f"(d[0]), "+f"(d[1]), "+f"(d[2]), "+f"(d[3]), "+f"(d[4]), "+f"(d[5]), "+f"(d[6]), "+f"(d[7]),
          "+f"(d[8]), "+f"(d[9]), "+f"(d[10]), "+f"(d[11]), "+f"(d[12]), "+f"(d[13]), "+f"(d[14]), "+f"(d[15])
        : "r"(a[0]), "r"(a[1]), "r"(a[2]), "r"(a[3]), "r"(one), "n"((SMEM_ORIGIN + OFFB) >> 4), "l"(DESC_BASE), "n"(SCALE_D));
}
template <int OFFA, int OFFB, int SCALE_D>
__device__ __forceinline__ void wgmma_n32_ss(float (&d)[16], uint32_t one) {
    asm volatile(
        "{\n.reg .b64 da, db;\nmad.wide.u32 da, %16, %17, %19;\nmad.wide.u32 db, %16, %18, %19;\n"
        "wgmma.mma_async.sync.aligned.m64n32k16.f32.bf16.bf16 {%0,%1,%2,%3,%4,%5,%6,%7,%8,%9,%10,%11,%12,%13,%14,%15}, "
        "da, db, %20, 1, 1, 1, 0;\n}"
        : "+f"(d[0]), "+f"(d[1]), "+f"(d[2]), "+f"(d[3]), "+f"(d[4]), "+f"(d[5]), "+f"(d[6]), "+f"(d[7]),
          "+f"(d[8]), "+f"(d[9]), "+f"(d[10]), "+f"(d[11]), "+f"(d[12]), "+f"(d[13]), "+f"(d[14]), "+f"(d[15])
        : "r"(one), "n"((SMEM_ORIGIN + OFFA) >> 4), "n"((SMEM_ORIGIN + OFFB) >> 4), "l"(DESC_BASE), "n"(SCALE_D));
}
template <int WG, int J0, int J1, int I, bool ACC, bool FENCE = true>
__device__ __forceinline__ void token_mma(float (&ta)[2][16], const uint32_t (&wr)[NREG][2][4], uint32_t one) {
    if (FENCE) asm volatile("wgmma.fence.sync.aligned;" ::: "memory");
    sfor<J0, J1>([&](auto J) {
        constexpr int j = J.value, c = j >> 2, offb = SM_X + WG * 32768 + c * 4096 + (j & 3) * 32, sc = (ACC || j != J0) ? 1 : 0;
        if constexpr ((j & 3) != 0) wgmma_n32_rs<offb, sc>(ta[I], wr[reg_idx(j)][I], one);
        else if constexpr (WG == 0 || (I == 1 && c >= 4)) wgmma_n32_ss<SM_WQ + WG * 32768 + I * 16384 + c * 2048, offb, sc>(ta[I], one);
        constexpr int m = I ? c : c - 4;
        if constexpr (WG == 0 && (j & 3) == 1 && m >= 0)
            wgmma_n32_ss<SM_WQ + 32768 + (1 - I) * 16384 + m * 2048, SM_X + 32768 + m * 4096, 1>(ta[I], one);
    });
    asm volatile("wgmma.commit_group.sync.aligned;" ::: "memory");
}
__device__ __forceinline__ void warp_arrive(uint32_t bar) {
    __syncwarp();
    if (elect_one()) mbar_arrive(bar);
}
__device__ __forceinline__ void remote_arrive(uint32_t bar, uint32_t rank) {
    asm volatile("mbarrier.arrive.relaxed.cluster.shared::cluster.b64 _, [%0];" ::"r"(mapa(bar, rank)) : "memory");
}
__device__ __forceinline__ void x_load(const RecParams& p, uint32_t sb, int sg, int g) {
    tma_load_3d_mc(sb + SM_X + g * 16384, &p.tmX, 0, sg * SEG, g * 4, sb + SM_BAR + BAR_XG + 8 * g, (uint16_t)7);
}

__device__ __forceinline__ void rec_steps(const RecParams& p, const uint32_t (&wr)[NREG][2][4], const uint32_t sb, const int warp,
                                          const int cta, const int head, const int rank) {
    const int wq = warp & 3, wg = warp >> 2;
    const uint32_t bar = sb + SM_BAR;
    const uint32_t xhi = (uint32_t)((uint64_t)p.xchg >> 32);
    const float sl2 = 0.08838834764831845f * 1.4426950408889634f;
    const bool has_unit = warp >= 5 && (warp < 7 || cta < 64);
    const bool qk = rank < 2;
    const uint32_t pa = rank == 2 ? 0 : rank + 1, pb = rank == 0 ? 2 : rank - 1;
    const uint32_t tbl = sb + SM_TBL + warp * 64;
    const bool att = (warp & 6) == 2;
    const int stile = warp < 5 ? warp : warp - 3;

    const uint32_t u_st = uniform(SM_QK - SM_WQ - wg * (32768 - 1024));
    const uint32_t u_xa = uniform(sb + (qk ? SM_SP + rank * 1280 + stile * 256 : SM_VM + warp * 256));
    const uint32_t u_key = uniform(!qk || att || warp == 7 ? 0 : sb + (warp == 4 ? SM_QK + 1024 : SM_K + stile * 1024));
    const uint32_t u_bx = uniform(bar + (qk ? BAR_X : BAR_VM)), u_bra = uniform(mapa(u_bx, pa)), u_brb = uniform(mapa(u_bx, pb));
    const uint32_t u_src = uniform(lds32_volatile(tbl + 44));
    const uint32_t u_free = uniform(mapa(bar + (warp == 5 ? BAR_VF : BAR_F0), warp == 5 ? 2 : 0));
    const uint32_t u_role = uniform((has_unit ? 1 : 0) | (att ? 2 : 0) | (wg == 1 || qk ? 4 : 0) | (!qk && warp == 0 ? 8 : 0) | (rank != 0 && warp == 1 ? 16 : 0) |
                                    (warp == 5 || warp == 6 ? 32 : 0));
    uint32_t l16, aq, ao;
    {
        const int lane = threadIdx.x & 31, mi = lane >> 3, r8 = lane & 7, r16 = (mi >> 1) * 8 + r8;
        l16 = opaque(sb + lane * 16);
        aq = opaque(sb + SM_WQ + wg * 32768 + r16 * 128 + (((wq * 2 + (mi & 1)) ^ r8) << 4));
        ao = opaque(sb + SM_WO + (warp >> 1) * 8192 + r16 * 64 + ((((warp & 1) * 2 + (mi & 1)) ^ ((r8 >> 1) & 3)) << 4));
    }

    uint32_t mphase = 0;
    bool x0_ok = false;
    #pragma unroll 1
    for (int s = 0;; s++) {
        const uint32_t par = s & 1;
        uint32_t at[16][4];
        auto at_early = [](int i) { return i < 2 || ((i & 1) == 1 && (i >> 1) <= AT_PF - 2); };
        auto at_prefetch = [&](bool first) {
            #pragma unroll
            for (int i = 0; i < 16; i++)
                if (at_early(i) && first == ((i & 1) == 1 && (i >> 1) < AT_FIRST)) ldsm4t(aq + (i & 1) * 16384 + (i >> 1) * 2048, at[i]);
        };
        auto att_stores = [&](bool tiles, bool rows) {
            if (warp == 4) {
                if (rows && !qk) mbar_wait_bounded(bar + BAR_VM, par);
                asm volatile("fence.proxy.async.shared::cta;" ::: "memory");
                if (elect_one()) {
                    if (tiles) {
                        __nv_bfloat16* dst = p.qkv_tok + ((size_t)s * NH + head) * (SEG * DH);
                        constexpr size_t MAT = (size_t)NSEG * NH * SEG * DH;
                        bulk_store(dst + (qk ? rank * (SEG * 64) : 2 * MAT), sb + (qk ? SM_QS : SM_V), 4096);
                        bulk_store(dst + (qk ? MAT + rank * (SEG * 64) : 2 * MAT + SEG * 64), sb + (qk ? SM_K : SM_V + 4096), 4096);
                    }
                    if (rows)
                        bulk_store(p.kv_mem + ((size_t)s * NH + head) * (MROWS * DH) + (qk ? rank * (MROWS * 64) : NSEG * NH * MROWS * DH),
                                   sb + (qk ? SM_QK + 1024 : SM_VM), qk ? 1024 : 2048);
                    bulk_commit();
                }
            }
        };
        if (wg == 0) {
            float ta[2][16];
            if (!x0_ok) mbar_wait_bounded(bar + BAR_XG, par);
            STAMP(6);
            auto park = [&](int i, uint32_t dst) {
                #pragma unroll
                for (int e = 0; e < 16; e++) asm volatile("" : "+f"(ta[i][e]));
                #pragma unroll
                for (int j = 0; j < 4; j++)
                    sts128(l16 + dst + j * 2048 + wq * 512, __float_as_uint(ta[i][4 * j]), __float_as_uint(ta[i][4 * j + 1]),
                           __float_as_uint(ta[i][4 * j + 2]), __float_as_uint(ta[i][4 * j + 3]));
            };
            token_mma<0, 0, 16, 0, false>(ta, wr, 1);
            mbar_wait_bounded(bar + BAR_XG + 8, par);
            mbar_wait_bounded(bar + BAR_XG + 16, par);
            at_prefetch(true);
            token_mma<0, 16, 32, 0, true>(ta, wr, p.one[1]);
            token_mma<0, 0, 12, 1, false, false>(ta, wr, p.one[0]);
            token_mma<0, 12, 16, 1, true, false>(ta, wr, p.one[0]);
            mbar_wait_bounded(bar + BAR_XG + 24, par);
            asm volatile("wgmma.wait_group.sync.aligned 1;" ::: "memory");
            park(0, SM_PARK0);
            token_mma<0, 16, 32, 1, true>(ta, wr, 1);
            warp_arrive(bar + BAR_GO);
            mbar_wait_bounded(bar + BAR_PUB, par);
            const uint4 tp = lds128(bar + BAR_TPUB);
            const uint32_t tgo = tp.y + max(max((int)(tp.z - tp.y), (int)(tp.w - tp.y)), 0) + FETCH_DELAY;
            asm volatile("wgmma.wait_group.sync.aligned 0;" ::: "memory");
            park(1, SM_PARK1);
            warp_arrive(bar + BAR_PK);
            const uint8_t* src = xaddr(u_src + pub_slot(s), xhi);
            auto fetch = [&]() {
                if (elect_one()) {
                    mbar_arrive_expect_tx(bar + BAR_M + 8 * wq, 4096);
                    bulk_load(sb + SM_MEM + wq * 4096, src, 4096, bar + BAR_M + 8 * wq);
                }
            };
            while ((int)(clock_lo() - tgo) < 0) {}
            fetch();
            STAMP(12);
            if (warp == 0 && elect_one()) {
                if (qk) mbar_arrive_expect_tx(bar + BAR_V, 8192);
                mbar_arrive_expect_tx(bar + BAR_X, qk ? 1280 : 2560);
                mbar_arrive_expect_tx(bar + BAR_VM, qk ? 2048 : 0);
            }
            at_prefetch(false);
            const uint32_t x = fresh(l16) - sb;
            const uint32_t ca = sb + SM_MEM + wq * 4096 + x * 2 + ((x >> 4) & 0x1C);
            #pragma unroll 1
            for (uint32_t n = 0; n < POLL_LIMIT; n++) {
                mbar_wait_bounded(bar + BAR_M + 8 * wq, mphase);
                mphase ^= 1;
                const uint32_t c0 = lds32_volatile(ca), c1 = lds32_volatile(ca + 1024), c2 = lds32_volatile(ca + 2048), c3 = lds32_volatile(ca + 3072);
                if (!__any_sync(~0u, max(max3(c0, c1, c2), c3) == SENT)) break;
                fetch();
            }
            STAMP(0);
            named_bar_sync(0, REC_THREADS);
            if (warp == 0 && rank == 0 && s + 1 < NSEG) {
                mbar_wait_bounded(bar + BAR_F0, par);
                if (elect_one()) x_load(p, sb, s + 1, 0);
            }
            if (u_role & 8) {
                asm volatile("fence.proxy.async.shared::cta;" ::: "memory");
                mbar_wait_bounded(bar + BAR_VF, par);
                if (s < NSEG - 1 && elect_one()) {
                    #pragma unroll
                    for (int r = 0; r < 2; r++)
                        asm volatile("cp.async.bulk.shared::cluster.shared::cta.mbarrier::complete_tx::bytes [%0], [%1], %2, [%3];"
                                     ::"r"(mapa(sb + SM_V, r)), "r"(sb + SM_V), "r"(8192), "r"(mapa(bar + BAR_V, r)) : "memory");
                }
            }
        } else {
            at_prefetch(true);
            if (s > 0) {
                if (u_role & 1) {
                    const uint32_t ln = (fresh(l16) >> 4) & 31;
                    const uint32_t ibl = lds32_volatile(tbl + 12) + (par ^ 1) * XCHG_SLOT + ln * 8;
                    const uint32_t publ = lds32_volatile(tbl + 28) + pub_slot(s) + (ln & 16) * 256 + (ln & 8) * 16 + (ln & 7) * 4;
                    const bool odd = ln & 8;
                    const uint8_t* ib = xaddr(ibl + delay_zero<POLL_DELAY>(bar + BAR_SELF), xhi);
                    STAMP(8);
                    uint2 v[8];
                    #pragma unroll
                    for (int i = 0; i < 8; i++) v[i] = make_uint2(SENT, SENT);
                    #pragma unroll 1
                    for (uint32_t n = 0; n < POLL_LIMIT; n++) {
                        sfor<0, 8>([&](auto I) { repoll_v2<I.value * 256>(v[I.value], ib); });
                        const uint32_t mx = max(max3(v[0].y, v[1].y, v[2].y), max3(max3(v[3].y, v[4].y, v[5].y), v[6].y, v[7].y));
                        if (!__any_sync(~0u, mx == SENT)) break;
                    }
                    STAMP(9);
                    const float a0 = ((bf16_lo(v[0].x) + bf16_lo(v[1].x)) + (bf16_lo(v[2].x) + bf16_lo(v[3].x))) +
                                     ((bf16_lo(v[4].x) + bf16_lo(v[5].x)) + (bf16_lo(v[6].x) + bf16_lo(v[7].x)));
                    const float a1 = ((bf16_hi(v[0].x) + bf16_hi(v[1].x)) + (bf16_hi(v[2].x) + bf16_hi(v[3].x))) +
                                     ((bf16_hi(v[4].x) + bf16_hi(v[5].x)) + (bf16_hi(v[6].x) + bf16_hi(v[7].x)));
                    const float a2 = ((bf16_lo(v[0].y) + bf16_lo(v[1].y)) + (bf16_lo(v[2].y) + bf16_lo(v[3].y))) +
                                     ((bf16_lo(v[4].y) + bf16_lo(v[5].y)) + (bf16_lo(v[6].y) + bf16_lo(v[7].y)));
                    const float a3 = ((bf16_hi(v[0].y) + bf16_hi(v[1].y)) + (bf16_hi(v[2].y) + bf16_hi(v[3].y))) +
                                     ((bf16_hi(v[4].y) + bf16_hi(v[5].y)) + (bf16_hi(v[6].y) + bf16_hi(v[7].y)));
                    float k0 = odd ? a2 : a0, k1 = odd ? a3 : a1;
                    k0 += __shfl_xor_sync(~0u, odd ? a0 : a2, 8);
                    k1 += __shfl_xor_sync(~0u, odd ? a1 : a3, 8);
                    k0 += __shfl_xor_sync(~0u, k0, 16);
                    k1 += __shfl_xor_sync(~0u, k1, 16);
                    st_relaxed_b32(xaddr(publ, xhi), pack_bf16(k0, k1));
                    STAMP(11);
                } else if (warp == 4) {
                    bulk_wait_read_all();
                    if (elect_one()) remote_arrive(bar + BAR_F3, 2);
                    if (!qk) {
                        mbar_wait_bounded(bar + BAR_F3, par ^ 1);
                        if (elect_one()) x_load(p, sb, s, 3);
                    }
                    if (elect_one()) {
                        bulk_wait_all();
                        signal_bulk(p.flags + F_PROGRESS + s - 1);
                    }
                    __syncwarp();
                    STAMP(10);
                }
            }
            float ta[2][16];
            uint32_t w[8];
            auto unpark = [&](int i, uint32_t src) {
                mbar_wait_bounded(bar + (i ? BAR_GO : BAR_PK), par);
                #pragma unroll
                for (int j = 0; j < 4; j++) {
                    const uint4 v = lds128(l16 + src + j * 2048 + wq * 512);
                    ta[i][4 * j] = __uint_as_float(v.x); ta[i][4 * j + 1] = __uint_as_float(v.y);
                    ta[i][4 * j + 2] = __uint_as_float(v.z); ta[i][4 * j + 3] = __uint_as_float(v.w);
                }
            };
            sts32(bar + BAR_TPUB + 4 * wq, clock32());
            if (warp != 4) warp_arrive(bar + BAR_PUB);
            unpark(1, SM_PARK0);
            STAMP(6);
            token_mma<1, 0, 16, 1, true>(ta, wr, 1);
            unpark(0, SM_PARK1);
            token_mma<1, 16, 32, 1, true>(ta, wr, 1);
            token_mma<1, 16, 32, 0, true>(ta, wr, 1);
            token_mma<1, 0, 16, 0, true, false>(ta, wr, 1);
            auto put_tile = [&](int m, const uint32_t (&q)[8]) {
                #pragma unroll
                for (int h = 0; h < 2; h++) {
                    if (qk) asm volatile("stmatrix.sync.aligned.m8n8.x4.trans.shared.b16 [%0], {%1,%2,%3,%4};"
                                         ::"r"(aq - (SM_WQ + 32768) + (m ? SM_K : SM_QS) + h * 2048), "r"(q[4 * h]), "r"(q[4 * h + 1]),
                                           "r"(q[4 * h + 2]), "r"(q[4 * h + 3]) : "memory");
                    else sts128(l16 + SM_V + wq * 2048 + m * 1024 + h * 512, q[4 * h], q[4 * h + 1], q[4 * h + 2], q[4 * h + 3]);
                }
            };
            auto pack_tile = [&](int i) {
                #pragma unroll
                for (int e = 0; e < 16; e++) asm volatile("" : "+f"(ta[i][e]));
                #pragma unroll
                for (int j = 0; j < 8; j++) w[j] = pack_bf16(ta[i][2 * j], ta[i][2 * j + 1]);
            };
            asm volatile("wgmma.wait_group.sync.aligned 2;" ::: "memory");
            pack_tile(1);
            at_prefetch(false);
            asm volatile("wgmma.wait_group.sync.aligned 1;" ::: "memory");
            if ((u_role & 32) && elect_one())
                asm volatile("mbarrier.arrive.relaxed.cluster.shared::cluster.b64 _, [%0];" ::"r"(u_free) : "memory");
            put_tile(0, w);
            asm volatile("wgmma.wait_group.sync.aligned 0;" ::: "memory");
            pack_tile(0);
            put_tile(1, w);
            STAMP(0);
            named_bar_sync(0, REC_THREADS);
            if (s == NSEG - 1) att_stores(true, false);
            STAMP(14);
        }
        const uint32_t mb = l16 + SM_MEM + wg * 8192;
        float acc[2][2][4];
        {
            uint32_t b[2][4];
            ldsm4t(mb, b[0]);
            ldsm4t(mb + 512, b[1]);
            #pragma unroll
            for (int i = 0; i < 4; i++)
                if (!at_early(i)) ldsm4t(aq + (i & 1) * 16384 + (i >> 1) * 2048, at[i]);
            STAMPD(1, b[0][0]);
            #pragma unroll
            for (int i = 0; i < 4; i++) { for (int e = 0; e < 4; e++) acc[i >> 1][i & 1][e] = 0.f; }
            #pragma unroll
            for (int u = 0; u < 16; u++) {
                #pragma unroll
                for (int h = 0; h < 2; h++) {
                    const int j = 2 * u + h;
                    #pragma unroll
                    for (int m = 0; m < 2; m++) {
                        if ((j & 3) == 0) mma_a(acc[h][m], at[(j >> 2) * 2 + m], b[u & 1][2 * h], b[u & 1][2 * h + 1]);
                        else mma_a(acc[h][m], wr[reg_idx(j)][m], b[u & 1][2 * h], b[u & 1][2 * h + 1]);
                    }
                }
                if (u + 2 < 16) ldsm4t(mb + (u + 2) * 512, b[u & 1]);
                if (u + 4 < 16 && !at_early(u + 4))
                    ldsm4t(aq + ((u + 4) & 1) * 16384 + ((u + 4) >> 1) * 2048, at[u + 4]);
            }
        }
        sts128(l16 + SM_RED + warp * 512, __float_as_uint(acc[0][1][0] + acc[1][1][0]), __float_as_uint(acc[0][1][1] + acc[1][1][1]),
               __float_as_uint(acc[0][1][2] + acc[1][1][2]), __float_as_uint(acc[0][1][3] + acc[1][1][3]));
        #pragma unroll
        for (int e = 0; e < 4; e++) acc[0][0][e] += acc[1][0][e];
        const uint32_t x16 = fresh(l16);
        const uint32_t sa = fresh((x16 & 0x70) * 8 + ((((x16 >> 3) & 0x30) ^ x16) & 0x70));
        const uint32_t sq = fresh(sa ^ ((((x16 >> 7) ^ (x16 >> 8)) & 1) * 0x30));
        const uint32_t x8 = (x16 & 0x1F0) >> 1;
        const uint32_t xra = fresh(x8 + __byte_perm(u_xa, u_bra, 0x7210)), xrb = fresh(x8 + __byte_perm(u_xa, u_brb, 0x7210));
        STAMP(2);
        named_bar_sync(1 + wq, 64);
        uint32_t p0, p1;
        {
            const uint4 v = lds128(l16 + SM_RED + (warp ^ 4) * 512);
            p0 = pack_bf16(acc[0][0][0] + __uint_as_float(v.x), acc[0][0][1] + __uint_as_float(v.y));
            p1 = pack_bf16(acc[0][0][2] + __uint_as_float(v.z), acc[0][0][3] + __uint_as_float(v.w));
        }
        auto send = [&](uint32_t y0, uint32_t y1) {
            st_async_v2(xra, y0, y1, u_bra);
            st_async_v2(xrb, y0, y1, u_brb);
            sts64(x8 + u_xa, y0, y1);
            warp_arrive(u_bx);
        };
        if (qk) {
            asm volatile("stmatrix.sync.aligned.m8n8.x2.trans.shared.b16 [%0], {%1,%2};" ::"r"(aq + u_st), "r"(p0), "r"(p1) : "memory");
            named_bar_sync(5, REC_THREADS);
            if (u_key != 0) {
                uint32_t qa[2][4], kf[2][4];
                ldsm4(sq + sb + SM_QK, qa[0]);
                ldsm4(sa + u_key, kf[0]);
                ldsm4((sq ^ 64) + sb + SM_QK, qa[1]);
                ldsm4((sa ^ 64) + u_key, kf[1]);
                float se[4] = {0.f, 0.f, 0.f, 0.f}, so[4] = {0.f, 0.f, 0.f, 0.f};
                #pragma unroll
                for (int u = 0; u < 2; u++) {
                    mma_a(se, qa[u], kf[u][0], kf[u][1]);
                    mma_a(so, qa[u], kf[u][2], kf[u][3]);
                }
                send(__float_as_uint(se[0] + so[2]), __float_as_uint(se[1] + so[3]));
            }
        } else {
            send(p0, p1);
        }
        STAMP(3);
        const uint32_t lane = (fresh(l16) >> 4) & 31;
        if (((s + 1) & 62) == 0) {
            if (s == NSEG - 1) { att_stores(false, true); break; }
            mbar_wait_bounded(bar + BAR_WO, 0);
            pdl_launch_dependents();
            PSTAMP(8);
        }
        const uint32_t slot = par * XCHG_SLOT;
        if (u_role & 2) {
            if (qk) mbar_wait_bounded(bar + BAR_V, par);
            uint32_t vt[2][4][4];
            auto v_load = [&](int i0, int i1) {
                #pragma unroll
                for (int i = i0; i < i1; i++) {
                    const uint4 v = lds128(l16 + SM_V + (warp & 1) * 1024 + (i & 3) * 2048 + (i >> 2) * 512);
                    vt[i >> 2][i & 3][0] = v.x; vt[i >> 2][i & 3][1] = v.y; vt[i >> 2][i & 3][2] = v.z; vt[i >> 2][i & 3][3] = v.w;
                }
            };
            v_load(0, V_EARLY);
            const uint32_t l8 = fresh(sb + lane * 8);
            mbar_wait_bounded(bar + BAR_X, par);
            STAMP(4);
            float sv[10];
            #pragma unroll
            for (int j = 0; j < 5; j++) {
                const uint2 a = lds64(l8 + SM_SP + j * 256), b = lds64(l8 + SM_SP + 1280 + j * 256);
                sv[2 * j] = __uint_as_float(a.x) + __uint_as_float(b.x);
                sv[2 * j + 1] = __uint_as_float(a.y) + __uint_as_float(b.y);
            }
            float mx = fmaxf(fmaxf(fmaxf(sv[0], sv[1]), fmaxf(sv[2], sv[3])), fmaxf(fmaxf(sv[4], sv[5]), fmaxf(sv[6], sv[7])));
            mx = fmaxf(mx, fmaxf(sv[8], sv[9]));
            const float m1 = __shfl_xor_sync(~0u, mx, 1), m2 = __shfl_xor_sync(~0u, mx, 2), m3 = __shfl_xor_sync(~0u, mx, 3);
            __syncwarp();
            v_load(V_EARLY, 8);
            const bool vm_ok = mbar_test_wait(bar + BAR_VM, par);
            mx = fmaxf(fmaxf(mx, m1), fmaxf(m2, m3));
            const float mo = mx * sl2;
            #pragma unroll
            for (int j = 0; j < 10; j++) sv[j] = ex2(fmaf(sv[j], sl2, -mo));
            const uint32_t e0 = pack_bf16(sv[0], sv[1]), e1 = pack_bf16(sv[2], sv[3]);
            const uint32_t e2 = pack_bf16(sv[4], sv[5]), e3 = pack_bf16(sv[6], sv[7]), em = pack_bf16(sv[8], sv[9]);
            float o[4][4];
            #pragma unroll
            for (int i = 0; i < 4; i++) {
                o[i][0] = o[i][1] = o[i][2] = o[i][3] = 0.f;
                mma_a(o[i], vt[0][i], e0, e1);
            }
            const float sum = (((sv[0] + sv[1]) + (sv[2] + sv[3])) + ((sv[4] + sv[5]) + (sv[6] + sv[7]))) + (sv[8] + sv[9]);
            if (!vm_ok) mbar_wait_bounded(bar + BAR_VM, par);
            uint2 vm[4];
            #pragma unroll
            for (int i = 0; i < 4; i++) {
                vm[i] = lds64(l8 + SM_VM + (warp & 1) * 1024 + i * 256);
                mma_a(o[i], vt[1][i], e2, e3);
            }
            #pragma unroll
            for (int i = 0; i < 4; i++) mma1688(o[i], vm[i].x, vm[i].y, em);
            {
                const float s1 = __shfl_xor_sync(~0u, sum, 1), s2 = __shfl_xor_sync(~0u, sum, 2), s3 = __shfl_xor_sync(~0u, sum, 3);
                sts32(sb + SM_SUM + (lane & 28), __float_as_uint((sum + s1) + (s2 + s3)));
            }
            #pragma unroll
            for (int i = 0; i < 4; i += 2)
                stsm_x4(l16 + SM_O + (warp & 1) * 1024 + i * 256, pack_bf16(o[i][0], o[i][1]), pack_bf16(o[i][2], o[i][3]),
                        pack_bf16(o[i + 1][0], o[i + 1][1]), pack_bf16(o[i + 1][2], o[i + 1][3]));
            STAMP(5);
            uint32_t st[16][4];
            named_bar_sync(6, REC_THREADS);
            wo_phase<2, 0>(st, ao, 0, l16, tbl, sb + SM_SUM, slot, xhi, 0, bar + BAR_XG, par ^ 1, x0_ok);
        } else {
            const uint32_t a3 = fresh(ao) + (wg == 0 ? 10 : 6) * 8192;
            uint32_t st[24][4];
            #pragma unroll
            for (int n = 0; n < WO_PFA; n++) ldsm4t(wo_addr<3>(ao, a3, n), st[n]);
            if (u_role & 1) {
                const uint32_t ln = (fresh(l16) >> 4) & 31;
                uint8_t* ib = xaddr(lds32_volatile(tbl + 12) + (par ^ 1) * XCHG_SLOT + ln * 16, xhi);
                #pragma unroll
                for (int i = 0; i < 4; i++) st_relaxed_v4(ib + i * 512, SENT);
                st_relaxed_b32(xaddr(lds32_volatile(tbl + 28) + pub_slot(s + 3) + (ln & 16) * 256 + (ln & 8) * 16 + (ln & 7) * 4, xhi), SENT);
            }
            if (warp == 1) {
                if (elect_one()) {
                    #pragma unroll
                    for (int g = 0; g < 4; g++) mbar_arrive_expect_tx(bar + BAR_XG + 8 * g, 16384);
                }
                if (s + 2 < NSEG && cta < 4 && elect_one())
                    asm volatile("cp.async.bulk.prefetch.tensor.3d.L2.global [%0, {%1, %2, %3}];"
                                 ::"l"(&p.tmX), "r"(0), "r"((s + 2) * SEG), "r"(cta * 4) : "memory");
            }
            mbar_wait_bounded(bar + BAR_X, par);
            { const uint32_t t0 = clock_lo(); while (clock_lo() - t0 < WO_PFB_DELAY) {} }
            #pragma unroll
            for (int n = WO_PFA; n < WO_PF; n++) ldsm4t(wo_addr<3>(ao, a3, n), st[n]);
            att_stores(true, true);
            if (u_role & 16) {
                mbar_wait_bounded(bar + BAR_VM, par);
                if (elect_one()) x_load(p, sb, s + 1, rank);
            }
            named_bar_sync(6, REC_THREADS);
            wo_phase<3, WO_PF>(st, ao, a3, l16, tbl, sb + SM_SUM, slot, xhi, u_role & 4, bar + BAR_XG, par ^ 1, x0_ok);
        }
        STAMP(7);
        if (wg == 0) named_bar_sync(9, REC_THREADS); else named_bar_arrive(9, REC_THREADS);
    }
    if (threadIdx.x == 128) KMARK(8);
    if (warp == 4) {
        if (elect_one()) {
            asm volatile("cp.async.bulk.wait_group 1;" ::: "memory");
            signal_bulk(p.flags + F_LASTTOK);
            bulk_wait_all();
            signal_bulk(p.flags + F_PROGRESS + NSEG - 1);
            KMARK(9);
        }
    } else if (warp == 0) {
        mbar_wait(bar + BAR_X, 1);
        mbar_wait(bar + BAR_VM, 1);
        if (rank == 0) mbar_wait(bar + BAR_F0, 1);
    }
}

__global__ void __launch_bounds__(REC_THREADS, 1) rec_kernel(const __grid_constant__ RecParams p) {
    extern __shared__ __align__(1024) uint8_t smem_raw[];
    const uint32_t sb = smem_u32(smem_raw);
    const int tid = threadIdx.x, lane = tid & 31;
    const int warp = __shfl_sync(~0u, tid >> 5, 0);
    const int cta = blockIdx.x, head = cta / 3, rank = cta % 3;
    const int wg = warp >> 2, wq = warp & 3;
    const uint32_t bar = sb + SM_BAR;
    uint8_t* const xb = p.xchg;
    const uint32_t xlo = (uint32_t)(uint64_t)xb;
    if ((sb & 0x3FFFF) != SMEM_ORIGIN) __trap();
    KENTER(1);
    auto w_box = [&](int part, int g, int i, uint32_t dst, uint32_t mb) {
        const int m = i ^ g;
        const CUtensorMap* tm = &p.tmW[rank == 2 ? 2 : m];
        const int col = head * DH + (rank == 2 ? m : rank) * 64, row = ((part + 1) & 3) * 16;
        tma_load_3d(dst, tm, col, row, g * 8, mb);
    };
    if (tid == 0) {
        mbar_init(bar + BAR_V, 1);
        for (int i = 0; i < 4; i++) { mbar_init(bar + BAR_XG + 8 * i, 1); mbar_init(bar + BAR_M + 8 * i, 1); }
        mbar_init(bar + BAR_GO, 4);
        mbar_init(bar + BAR_PUB, 3);
        mbar_init(bar + BAR_PK, 4);
        mbar_init(bar + BAR_VM, rank < 2 ? 1 : 9);
        mbar_init(bar + BAR_F0, 3);
        mbar_init(bar + BAR_F3, 3);
        mbar_init(bar + BAR_VF, 3);
        sts64(bar + BAR_MIN, ~0u, ~0u);
        mbar_init(bar + BAR_X, rank < 2 ? 6 : 1);
        for (int i = 0; i < 3; i++) mbar_init(bar + BAR_P0 + 8 * i, 1);
        mbar_init(bar + BAR_WQ, 1);
        mbar_init(bar + BAR_WO, 1);
        sts32(bar + BAR_SELF, bar + BAR_SELF);
        asm volatile("fence.mbarrier_init.release.cluster;" ::: "memory");
    }
    auto build_tables = [&](uint32_t av) {
        for (uint32_t n = 0; !__all_sync(~0u, (av >> 24) == 24); n++) {
            av = ld_acquire_b32(p.arrivals + (lane & 3));
            if (n > SPIN_LIMIT) __trap();
        }
        uint32_t cm[3];
        #pragma unroll
        for (int i = 0; i < 3; i++) {
            const int o = i * 32 + lane;
            cm[i] = __ballot_sync(~0u, __popc((__shfl_sync(~0u, av, o / 24) >> (o % 24 / 3 * 3)) & 7) >= 2);
        }
        auto color_of = [&](int o) { return ((o < 32 ? cm[0] : o < 64 ? cm[1] : cm[2]) >> (o & 31)) & 1u; };
        auto inbox = [&](int o, int byte) {
            uint32_t c = color_of(o);
            int ones = 0;
            #pragma unroll
            for (int i = 0; i < 3; i++) ones += __popc(o >= i * 32 + 32 ? cm[i] : (o > i * 32 ? cm[i] & ((1u << (o - i * 32)) - 1) : 0u));
            int idx = c ? ones : o - ones;
            if (idx >= INBOX_MAX) { idx = 2 * INBOX_MAX - 1 - idx; c ^= 1; }
            const uint32_t lin = idx * 6144 + byte, q = XCHG_INBOX + (lin >> 12) * 8192;
            return q + class_off(xlo + q, c) + (lin & 4095);
        };
        uint32_t off = 0;
        const int grp = (warp + 3) & 3;
        if (lane < 12) {
            const int i = lane >> 2, lt0 = rank * 6;
            const int o = i < 2 ? rank * 32 + warp * 4 + (lane & 3) : (lt0 + ((warp + 4) & 7)) * 4 + (lane & 3);
            off = inbox(min(o, 95), i * 2048 + head * 64);
        } else if (lane == 12) {
            off = inbox(cta, (grp % 3) * 2048);
        } else if (lane == 13) {
            int T;
            if (grp < 2) {
                T = (cta >> 5) * 22 + 8 * grp + ((cta & 31) >> 2);
            } else {
                const int tl = (cta & 63) >> 2;
                T = (tl / 6) * 22 + 16 + tl % 6;
            }
            off = XCHG_PUB + (T >> 4) * 8192 + (T & 15) * 256 + (cta & 3) * 32;
        } else if (lane == 14) {
            const uint32_t q = XCHG_PUB + wq * 8192;
            off = q + class_off(xlo + q, color_of(cta));
        }
        if (lane < 16) asm volatile("st.shared.b32 [%0], %1;" ::"r"(sb + SM_TBL + warp * 64 + (lane & 3) * 16 + (lane >> 2) * 4), "r"(xlo + off) : "memory");
    };
    if (tid >= 32 && tid < 37) asm volatile("prefetch.tensormap [%0];" ::"l"(&p.tmW[0] + (tid - 32)) : "memory");
    if (cta == 0) for (int i = tid; i < F_COUNT; i += REC_THREADS) p.flags[i] = 0;
    __syncthreads();
    auto stage = [](int part) { return ((part + 2) % 3) * 65536; };
    auto load_part = [&](int part) {
        mbar_arrive_expect_tx(bar + BAR_P0 + 8 * part, 65536);
        for (int u = 0; u < 4; u++) w_box(part, u >> 1, u & 1, sb + stage(part) + u * 16384, bar + BAR_P0 + 8 * part);
    };
    asm volatile("barrier.cluster.arrive.relaxed.aligned;" ::: "memory");
    uint4 img = make_uint4(SENT, SENT, SENT, SENT);
    if (cta >= 92) {
        const unsigned short* m = reinterpret_cast<const unsigned short*>(p.mem0) + (cta - 92) * 256 + tid;
        uint32_t w[4];
        #pragma unroll
        for (int i = 0; i < 4; i++) w[i] = (uint32_t)__ldg(m + 2 * i * DM) | ((uint32_t)__ldg(m + (2 * i + 1) * DM) << 16);
        img = make_uint4(w[0], w[1], w[2], w[3]);
    }
    {
        constexpr int NPAIR = (XCHG_SLOT + PUB_BYTES) / 8192;
        uint8_t* pr = xb + (4 + cta) * 8192;
        const uint32_t c0 = class_off(xlo + (4 + cta) * 8192, 0);
        #pragma unroll
        for (int c = 0; c < 2; c++) {
            const bool timed = lane == 0 || (lane == 8 && c == (warp & 1));
            reinterpret_cast<uint4*>(pr + (c0 ^ (c << 12)))[tid] = make_uint4(timed ? 0u : SENT, SENT, SENT, SENT);
        }
        __syncwarp();
        if (lane == 0) {
            uint32_t x = 0;
            for (int k = 0; k < 3; k++) {
                if (k == 0 && warp == 0) load_part(0);
                const uint32_t c = (k + warp) & 1, t0 = clock_after(x);
                x = atomicExch(reinterpret_cast<uint32_t*>(pr + (c0 ^ (c << 12)) + warp * 512 + (k >> 1) * 128 + x), SENT);
                const uint32_t lat = clock_after(x) - t0;
                asm volatile("red.shared.min.u32 [%0], %1;" ::"r"(bar + BAR_MIN + 4 * c), "r"(lat) : "memory");
            }
        }
        __syncwarp();
        if (cta >= 92 || 100 + cta < NPAIR) {
            if (cta >= 92) {
                if (img.x == SENT) img.x = 0x7FFF7FFFu;
                if (img.y == SENT) img.y = 0x7FFF7FFFu;
                if (img.z == SENT) img.z = 0x7FFF7FFFu;
                if (img.w == SENT) img.w = 0x7FFF7FFFu;
            }
            uint8_t* q = xb + (cta >= 92 ? cta - 92 : 100 + cta) * 8192;
            reinterpret_cast<uint4*>(q)[tid] = img;
            reinterpret_cast<uint4*>(q + 4096)[tid] = img;
        }
    }
    __syncthreads();
    PSTAMP(4);
    if (tid == 0) {
        for (int part = 1; part < 3; part++) load_part(part);
    }
    if (tid == 224) {
        const uint32_t c = lds32_volatile(bar + BAR_MIN) > lds32_volatile(bar + BAR_MIN + 4) ? 1 : 0;
        asm volatile("red.release.gpu.global.add.u32 [%0], %1;" ::"l"(p.arrivals + cta / 24), "r"((1u << 24) | (c << (cta % 24))) : "memory");
    }
    uint32_t wr[NREG][2][4];
    uint32_t arrived = 0;
    {
        const int mi = lane >> 3, r8 = lane & 7;
        const uint32_t a0 = sb + wg * 32768 + ((mi >> 1) * 8 + r8) * 128 + (((wq * 2 + (mi & 1)) ^ r8) << 4);
        #pragma unroll
        for (int part = 0; part < 3; part++) {
            mbar_wait_bounded(bar + BAR_P0 + 8 * part, 0);
            if (part == 0) arrived = ld_relaxed_b32(p.arrivals + (lane & 3));
            #pragma unroll
            for (int j = 0; j < 8; j++) {
                #pragma unroll
                for (int i = 0; i < 2; i++) ldsm4t(a0 + stage(part) + i * 16384 + j * 2048, wr[part * 8 + j][i]);
            }
            asm volatile("fence.proxy.async.shared::cta;" ::: "memory");
            __syncthreads();
            PSTAMP(5 + part);
            if (tid == 0) {
                if (part == 0) {
                    for (int g = 0; g < 4; g++) {
                        mbar_arrive_expect_tx(bar + BAR_XG + 8 * g, 16384);
                        tma_load_3d(sb + SM_X + g * 16384, &p.tmX, 0, 0, g * 4, bar + BAR_XG + 8 * g);
                    }
                } else if (part == 1) {
                    mbar_arrive_expect_tx(bar + BAR_WQ, 65536);
                    for (int u = 0; u < 4; u++) w_box(3, u >> 1, u & 1, sb + SM_WQ + u * 16384, bar + BAR_WQ);
                } else {
                    mbar_arrive_expect_tx(bar + BAR_WO, 11 * 8192);
                    tma_load_3d(sb + SM_WO, &p.tmWo, 0, head * DH, rank * 11, bar + BAR_WO);
                    if (cta < 4)
                        asm volatile("cp.async.bulk.prefetch.tensor.3d.L2.global [%0, {%1, %2, %3}];"
                                     ::"l"(&p.tmX), "r"(0), "r"(SEG), "r"(cta * 4) : "memory");
                }
            }
        }
    }
    build_tables(arrived);
    if (tid == 64) {
        uint32_t smid;
        asm volatile("mov.u32 %0, %%smid;" : "=r"(smid));
        if (smid < 384) atomicOr(p.flags + F_RECSM + (smid >> 5), 1u << (smid & 31));
    }
    __syncwarp();
    PSTAMP(9);
    mbar_wait(bar + BAR_WQ, 0);
    asm volatile("barrier.cluster.wait.aligned;" ::: "memory");

    rec_steps(p, wr, sb, warp, cta, head, rank);
    if (cta == 0 && tid < 4) p.arrivals[tid] = 0;
    if (tid == 128) KEXIT(1);
}

constexpr int ATT_SLOT = 28672;
constexpr int ATT_PAIRS = 8;
constexpr int ATT_BAR = ATT_PAIRS * ATT_SLOT;
constexpr int ATT_SMEM = ATT_BAR + ATT_PAIRS * 16;
constexpr int ATT_THREADS = ATT_PAIRS * 64;
struct AttnParams {
    CUtensorMap tmOa;
    CUtensorMap tmQb, tmKb;
    CUtensorMap tmOb;
    const __nv_bfloat16* qkv_tok;
    const __nv_bfloat16* kv_mem;
    uint32_t* flags;
};

__device__ __forceinline__ void tok_attn_warp(uint32_t base, int mh, int lane) {
    const uint32_t sq = base, sk = base + 8192, sv = base + 16384, skm = base + 24576, svm = skm + 2048;
    const int g = lane >> 2, c = lane & 3, mi = lane >> 3, r8 = lane & 7;
    const int ntile = mh ? 5 : 3;
    float sc[5][4];
    #pragma unroll
    for (int j = 0; j < 5; j++) { sc[j][0] = sc[j][1] = sc[j][2] = sc[j][3] = 0.f; }
    #pragma unroll
    for (int t2 = 0; t2 < 4; t2++) {
        uint32_t a[2][4];
        #pragma unroll
        for (int h = 0; h < 2; h++) {
            const int row = mh * 16 + (mi & 1) * 8 + r8, ch16 = 4 * t2 + 2 * h + (mi >> 1);
            ldsm_x4(sq + (ch16 >> 3) * 4096 + row * 128 + (((ch16 & 7) ^ r8) << 4), a[h][0], a[h][1], a[h][2], a[h][3]);
        }
        const int ch16 = 4 * t2 + mi;
        uint32_t b[5][4];
        #pragma unroll
        for (int j = 0; j < 5; j++) {
            if (j < ntile) {
                if (j == 0) ldsm_x4(skm + (ch16 >> 3) * 1024 + r8 * 128 + (((ch16 & 7) ^ r8) << 4), b[j][0], b[j][1], b[j][2], b[j][3]);
                else ldsm_x4(sk + (ch16 >> 3) * 4096 + ((j - 1) * 8 + r8) * 128 + (((ch16 & 7) ^ r8) << 4), b[j][0], b[j][1], b[j][2], b[j][3]);
            }
        }
        #pragma unroll
        for (int h = 0; h < 2; h++) {
            #pragma unroll
            for (int j = 0; j < 5; j++)
                if (j < ntile) mma16816(sc[j], a[h][0], a[h][1], a[h][2], a[h][3], b[j][2 * h], b[j][2 * h + 1]);
        }
    }
    const float sl2 = 0.08838834764831845f * 1.4426950408889634f;
    uint32_t pf[2][5];
    float inv[2];
    #pragma unroll
    for (int q = 0; q < 2; q++) {
        const int tok = mh * 16 + q * 8 + g;
        float v[10];
        #pragma unroll
        for (int j = 0; j < 5; j++) {
            #pragma unroll
            for (int e = 0; e < 2; e++) {
                const int key = (j - 1) * 8 + 2 * c + e;
                v[2 * j + e] = (j == 0 || key <= tok) ? sc[j][2 * q + e] : -INFINITY;
            }
        }
        float mx = v[0];
        #pragma unroll
        for (int j = 1; j < 10; j++) mx = fmaxf(mx, v[j]);
        mx = fmaxf(mx, __shfl_xor_sync(~0u, mx, 1));
        mx = fmaxf(mx, __shfl_xor_sync(~0u, mx, 2));
        const float mo = mx * sl2;
        float sum = 0.f;
        #pragma unroll
        for (int j = 0; j < 10; j++) { v[j] = ex2(fmaf(v[j], sl2, -mo)); sum += v[j]; }
        sum += __shfl_xor_sync(~0u, sum, 1);
        sum += __shfl_xor_sync(~0u, sum, 2);
        inv[q] = rcp(sum);
        #pragma unroll
        for (int j = 0; j < 5; j++) pf[q][j] = pack_bf16(v[2 * j], v[2 * j + 1]);
    }
    auto load_v = [&](int n4, uint32_t (&vm)[4], uint32_t (&vt)[4][4]) {
        const uint2 va = lds64(svm + n4 * 512 + lane * 8), vb = lds64(svm + n4 * 512 + 256 + lane * 8);
        vm[0] = va.x; vm[1] = va.y; vm[2] = vb.x; vm[3] = vb.y;
        #pragma unroll
        for (int u = 0; u < 4; u++) {
            const int dt = 2 * n4 + (u >> 1), kh = u & 1;
            const uint4 v = lds128(sv + (dt & 3) * 2048 + (dt >> 2) * 1024 + kh * 512 + lane * 16);
            vt[u & 2][2 * kh] = v.x; vt[u & 2][2 * kh + 1] = v.z;
            vt[(u & 2) + 1][2 * kh] = v.y; vt[(u & 2) + 1][2 * kh + 1] = v.w;
        }
    };
    uint32_t vm[2][4], vt[2][4][4];
    load_v(0, vm[0], vt[0]);
    #pragma unroll
    for (int n4 = 0; n4 < 4; n4++) {
        const int cur = n4 & 1;
        if (n4 + 1 < 4) load_v(n4 + 1, vm[cur ^ 1], vt[cur ^ 1]);
        float o[4][4];
        #pragma unroll
        for (int u = 0; u < 4; u++) {
            o[u][0] = o[u][1] = o[u][2] = o[u][3] = 0.f;
            mma16816(o[u], pf[0][1], pf[1][1], pf[0][2], pf[1][2], vt[cur][u][0], vt[cur][u][1]);
        }
        if (mh) {
            #pragma unroll
            for (int u = 0; u < 4; u++) mma16816(o[u], pf[0][3], pf[1][3], pf[0][4], pf[1][4], vt[cur][u][2], vt[cur][u][3]);
        }
        #pragma unroll
        for (int u = 0; u < 4; u++) mma1688(o[u], pf[0][0], pf[1][0], vm[cur][u]);
        #pragma unroll
        for (int u = 0; u < 4; u += 2) {
            const int row = mh * 16 + (mi & 1) * 8 + r8, nt = 4 * n4 + u + (mi >> 1);
            stsm_x4(sq + (nt >> 3) * 4096 + row * 128 + (((nt & 7) ^ r8) << 4),
                    pack_bf16(o[u][0] * inv[0], o[u][1] * inv[0]), pack_bf16(o[u][2] * inv[1], o[u][3] * inv[1]),
                    pack_bf16(o[u + 1][0] * inv[0], o[u + 1][1] * inv[0]), pack_bf16(o[u + 1][2] * inv[1], o[u + 1][3] * inv[1]));
        }
    }
}

__device__ __forceinline__ void b_attn_warp(uint32_t base, int hl, int idx0, int lane) {
    const uint32_t sq = base, sk = base + 8192, sv = base + 8192 + 9216;
    const int g = lane >> 2, c = lane & 3;
    auto addr = [&](uint32_t t, int row, int ch) { return t + row * 128 + ((ch ^ (row & 7)) << 4); };
    const float sl2 = 0.17677669529663687f * 1.4426950408889634f;
    #pragma unroll 2
    for (int blk = 0; blk < 4; blk++) {
        const int r0 = blk * 16;
        float sc[3][4];
        #pragma unroll
        for (int j = 0; j < 3; j++) { sc[j][0] = sc[j][1] = sc[j][2] = sc[j][3] = 0.f; }
        #pragma unroll
        for (int t = 0; t < 2; t++) {
            uint32_t a0, a1, a2, a3, b0, b1, b2, b3, d0, d1, d2, d3;
            const int mi = lane >> 3, r = lane & 7;
            ldsm_x4(addr(sq, r0 + (mi & 1) * 8 + r, hl * 4 + 2 * t + (mi >> 1)), a0, a1, a2, a3);
            ldsm_x4(addr(sk, r0 + (mi >> 1) * 8 + r, hl * 4 + 2 * t + (mi & 1)), b0, b1, b2, b3);
            ldsm_x4(addr(sk, r0 + 16 + r, hl * 4 + 2 * t + (mi & 1)), d0, d1, d2, d3);
            mma16816(sc[0], a0, a1, a2, a3, b0, b1);
            mma16816(sc[1], a0, a1, a2, a3, b2, b3);
            mma16816(sc[2], a0, a1, a2, a3, d0, d1);
        }
        uint32_t pf[2][3];
        float inv[2];
        #pragma unroll
        for (int r = 0; r < 2; r++) {
            const int u = r * 8 + g;
            float v[6];
            #pragma unroll
            for (int j = 0; j < 3; j++) {
                #pragma unroll
                for (int e = 0; e < 2; e++) {
                    const int key = j * 8 + 2 * c + e;
                    const bool ok = key > u && key <= u + 8 && idx0 + r0 - 8 + key >= 0;
                    v[2 * j + e] = ok ? sc[j][2 * r + e] : -INFINITY;
                }
            }
            float mx = fmaxf(fmaxf(fmaxf(v[0], v[1]), fmaxf(v[2], v[3])), fmaxf(v[4], v[5]));
            mx = fmaxf(mx, __shfl_xor_sync(~0u, mx, 1));
            mx = fmaxf(mx, __shfl_xor_sync(~0u, mx, 2));
            const float mo = mx * sl2;
            float sum = 0.f;
            #pragma unroll
            for (int j = 0; j < 6; j++) { v[j] = ex2(fmaf(v[j], sl2, -mo)); sum += v[j]; }
            sum += __shfl_xor_sync(~0u, sum, 1);
            sum += __shfl_xor_sync(~0u, sum, 2);
            inv[r] = rcp(sum);
            #pragma unroll
            for (int j = 0; j < 3; j++) pf[r][j] = pack_bf16(v[2 * j], v[2 * j + 1]);
        }
        uint32_t ow[4][2];
        {
            const int mi = lane >> 3, r = lane & 7;
            uint32_t vv[4][4];
            #pragma unroll
            for (int nt = 0; nt < 4; nt++)
                ldsm_x4_t(addr(sv, r0 + min(mi, 2) * 8 + r, hl * 4 + nt), vv[nt][0], vv[nt][1], vv[nt][2], vv[nt][3]);
            float o[4][4];
            #pragma unroll
            for (int nt = 0; nt < 4; nt++) {
                o[nt][0] = o[nt][1] = o[nt][2] = o[nt][3] = 0.f;
                mma16816(o[nt], pf[0][0], pf[1][0], pf[0][1], pf[1][1], vv[nt][0], vv[nt][1]);
            }
            #pragma unroll
            for (int nt = 0; nt < 4; nt++) mma1688(o[nt], pf[0][2], pf[1][2], vv[nt][2]);
            #pragma unroll
            for (int nt = 0; nt < 4; nt++) {
                ow[nt][0] = pack_bf16(o[nt][0] * inv[0], o[nt][1] * inv[0]);
                ow[nt][1] = pack_bf16(o[nt][2] * inv[1], o[nt][3] * inv[1]);
            }
        }
        #pragma unroll
        for (int u = 0; u < 4; u += 2) {
            const int mi = lane >> 3, r = lane & 7;
            stsm_x4(addr(sq, r0 + (mi & 1) * 8 + r, hl * 4 + u + (mi >> 1)), ow[u][0], ow[u][1], ow[u + 1][0], ow[u + 1][1]);
        }
    }
}

constexpr uint32_t QKVB_TARGET = 12 * 8;
constexpr uint32_t PROGRESS_TARGET = 96;
constexpr uint32_t OA_TARGET = 64, OB_TARGET = 32;
#define ATT_B0 8
#define ATT_BSTEP 2
constexpr int ATT_TASKS = (NSEG + 16) * 32;
static_assert(ATT_B0 + 16 * ATT_BSTEP <= NSEG, "order of the task groups");
__device__ __forceinline__ int att_group(int g, bool& isb) {
    constexpr int P = ATT_BSTEP + 1;
    const int q = g - ATT_B0;
    isb = q >= 0 && q < 16 * P && q % P == 0;
    return q < 0 ? g : q >= 16 * P ? g - 16 : isb ? q / P : g - q / P - 1;
}

__global__ void __launch_bounds__(ATT_THREADS, 1) attn_kernel(const __grid_constant__ AttnParams p) {
    extern __shared__ __align__(1024) uint8_t smem_raw[];
    const int tid = threadIdx.x, lane = tid & 31, warp = __shfl_sync(~0u, tid >> 5, 0);
    const int pair = warp >> 1, wi = warp & 1;
    const uint32_t base = smem_u32(smem_raw) + pair * ATT_SLOT, bar = smem_u32(smem_raw) + ATT_BAR + pair * 16;
    const bool leader = wi == 0 && lane == 0;
    if (tid == 0) pdl_launch_dependents();
    KENTER(3);
    uint32_t phase = 0;
    if (leader) {
        mbar_init(bar, 1);
        asm volatile("fence.mbarrier_init.release.cluster;" ::: "memory");
    }
    uint32_t* pending = nullptr;
    auto flush = [&]() {
        if (pending) {
            bulk_wait_all();
            signal_bulk(pending);
            if (pending == p.flags + F_OA + NSEG - 1) KMARK(14);
            pending = nullptr;
        }
    };
    int ready_a = -1, ready_b = -1;
    for (int task = pair * gridDim.x + blockIdx.x; task < ATT_TASKS; task += ATT_PAIRS * gridDim.x) {
        bool isb;
        const int grp = att_group(task >> 5, isb), i = task & 31;
        named_bar_sync(1 + pair, 64);
        if (leader) {
            {
                auto need = [&](const uint32_t* f, uint32_t target) {
                    if (ld_acquire_b32(f) < target) { flush(); wait_flag(f, target); }
                };
                if (isb) {
                    if (grp > ready_b) {
                        need(p.flags + F_QKVB + grp, QKVB_TARGET);
                        if (grp > 0) need(p.flags + F_QKVB + grp - 1, QKVB_TARGET);
                        asm volatile("fence.proxy.async.global;" ::: "memory");
                        ready_b = grp;
                    }
                    mbar_arrive_expect_tx(bar, 8192 + 2 * 9216);
                    tma_load_3d(base, &p.tmQb, (i >> 1) * 64, i & 1, grp * 64, bar);
                    tma_load_3d(base + 8192, &p.tmKb, DM + (i >> 1) * 64, i & 1, grp * 64 - 8, bar);
                    tma_load_3d(base + 8192 + 9216, &p.tmKb, 2 * DM + (i >> 1) * 64, i & 1, grp * 64 - 8, bar);
                } else {
                    if (grp > ready_a) {
                        need(p.flags + (grp == NSEG - 1 ? F_LASTTOK : F_PROGRESS + grp), PROGRESS_TARGET);
                        asm volatile("fence.proxy.async.global;" ::: "memory");
                        ready_a = grp;
                    }
                    if (grp == 63) KMARK(10);
                    mbar_arrive_expect_tx(bar, ATT_SLOT);
                    #pragma unroll
                    for (int w = 0; w < 3; w++)
                        bulk_load(base + w * 8192, p.qkv_tok + (((size_t)w * NSEG + grp) * NH + i) * (SEG * DH), 8192, bar);
                    if (grp == NSEG - 1) {
                        need(p.flags + F_PROGRESS + grp, PROGRESS_TARGET);
                        asm volatile("fence.proxy.async.global;" ::: "memory");
                    }
                    #pragma unroll
                    for (int w = 0; w < 2; w++)
                        bulk_load(base + 24576 + w * 2048, p.kv_mem + (((size_t)w * NSEG + grp) * NH + i) * (MROWS * DH), 2048, bar);
                }
            }
        }
        if (lane == 0) flush();
        __syncwarp();
        mbar_wait_sleep(bar, phase);
        phase ^= 1;
        if (isb) {
            b_attn_warp(base, wi, grp * 64, lane);
            asm volatile("fence.proxy.async.shared::cta;" ::: "memory");
            named_bar_sync(1 + pair, 64);
            if (wi == 1 && lane == 0) {
                asm volatile("cp.async.bulk.tensor.3d.global.shared::cta.bulk_group [%0, {%2, %3, %4}], [%1];"
                             ::"l"(&p.tmOb), "r"(base), "r"((i >> 1) * 64), "r"(i & 1), "r"(grp * 64) : "memory");
                pending = p.flags + F_OB + grp;
            }
        } else {
            if (grp == 63 && lane == 0) KMARK(11);
            tok_attn_warp(base, wi, lane);
            if (grp == 63 && lane == 0) KMARK(12);
            asm volatile("fence.proxy.async.shared::cta;" ::: "memory");
            __syncwarp();
            if (lane == 0) {
                #pragma unroll
                for (int h = 0; h < 2; h++) tma_store_2d(&p.tmOa, base + h * 4096 + wi * 2048, i * DH + h * 64, grp * SEG + wi * 16);
                pending = p.flags + F_OA + grp;
            }
        }
        if (lane == 0) { bulk_commit(); bulk_wait_read_all(); }
        __syncwarp();
    }
    if (lane == 0) { flush(); KEXIT(3); }
}

typedef CUresult (*EncodeFn)(CUtensorMap*, CUtensorMapDataType, cuuint32_t, void*, const cuuint64_t*, const cuuint64_t*,
                             const cuuint32_t*, const cuuint32_t*, CUtensorMapInterleave, CUtensorMapSwizzle,
                             CUtensorMapL2promotion, CUtensorMapFloatOOBfill);

void make_map_2d(EncodeFn enc, CUtensorMap* m, const void* ptr, uint64_t rows, uint64_t cols, uint32_t box_rows) {
    cuuint64_t dims[2] = {cols, rows};
    cuuint64_t strides[1] = {cols * 2};
    cuuint32_t box[2] = {64, box_rows};
    cuuint32_t es[2] = {1, 1};
    enc(m, CU_TENSOR_MAP_DATA_TYPE_BFLOAT16, 2, const_cast<void*>(ptr), dims, strides, box, es,
        CU_TENSOR_MAP_INTERLEAVE_NONE, CU_TENSOR_MAP_SWIZZLE_128B, CU_TENSOR_MAP_L2_PROMOTION_L2_256B,
        CU_TENSOR_MAP_FLOAT_OOB_FILL_NONE);
}
void make_map_b(EncodeFn enc, CUtensorMap* m, const void* ptr, uint64_t k, uint64_t n, uint32_t nblk, uint32_t box_rows = 64,
                uint32_t bc = 64) {
    cuuint64_t dims[3] = {bc, k, n / bc};
    cuuint64_t strides[2] = {n * 2, bc * 2};
    cuuint32_t box[3] = {bc, box_rows, nblk};
    cuuint32_t es[3] = {1, 1, 1};
    enc(m, CU_TENSOR_MAP_DATA_TYPE_BFLOAT16, 3, const_cast<void*>(ptr), dims, strides, box, es,
        CU_TENSOR_MAP_INTERLEAVE_NONE, bc == 64 ? CU_TENSOR_MAP_SWIZZLE_128B : CU_TENSOR_MAP_SWIZZLE_64B, CU_TENSOR_MAP_L2_PROMOTION_L2_256B,
        CU_TENSOR_MAP_FLOAT_OOB_FILL_NONE);
}

void make_map_parity(EncodeFn enc, CUtensorMap* m, const void* ptr, uint64_t cols, uint32_t box_rows) {
    cuuint64_t dims[3] = {cols, 2, S_TOK / 2};
    cuuint64_t strides[2] = {cols * 2, cols * 4};
    cuuint32_t box[3] = {64, 1, box_rows};
    cuuint32_t es[3] = {1, 1, 1};
    enc(m, CU_TENSOR_MAP_DATA_TYPE_BFLOAT16, 3, const_cast<void*>(ptr), dims, strides, box, es,
        CU_TENSOR_MAP_INTERLEAVE_NONE, CU_TENSOR_MAP_SWIZZLE_128B, CU_TENSOR_MAP_L2_PROMOTION_L2_128B,
        CU_TENSOR_MAP_FLOAT_OOB_FILL_NONE);
}
void make_map_w(EncodeFn enc, CUtensorMap* m, const void* ptr) {
    cuuint64_t dims[3] = {HD, 64, DM / 64};
    cuuint64_t strides[2] = {HD * 2, 64 * HD * 2};
    cuuint32_t box[3] = {64, 16, 8};
    cuuint32_t es[3] = {1, 1, 1};
    enc(m, CU_TENSOR_MAP_DATA_TYPE_BFLOAT16, 3, const_cast<void*>(ptr), dims, strides, box, es,
        CU_TENSOR_MAP_INTERLEAVE_NONE, CU_TENSOR_MAP_SWIZZLE_128B, CU_TENSOR_MAP_L2_PROMOTION_L2_256B,
        CU_TENSOR_MAP_FLOAT_OOB_FILL_NONE);
}

#define SIDE_ORDER 0
#define SERIAL_ATT_CTAS h.n_sm
#define N_TAIL_CTAS 28
#define N_SIDE_CTAS 28
#define N_ATT_CTAS 8
#define TAIL_BLOCK0 11

#define TAIL_SPARE 2
#define TAIL_KB2 30
#define TAIL_KB3 20
#define TAIL_BLOCK1 13
#define TAIL_BLOCK2 14

struct HostState {
    bool ready;
    bool overlap;
    int n_side, n_att, n_sm;
    SideParams seq_a, seq_b;
    const void* key[11];
    RecParams rec;
    SideParams side, tail;
    FinalParams fin;
    AttnParams attn;
    __nv_bfloat16 *qkv_tok, *kv_mem, *o_tok, *qkv_b, *o_b;
    uint8_t* xchg;
};
HostState g_host;

void setup(void* const* d_in, void* d_out) {
    HostState& h = g_host;
    void* fn = nullptr;
    cudaDriverEntryPointQueryResult qr;
    cudaGetDriverEntryPoint("cuTensorMapEncodeTiled", &fn, cudaEnableDefault, &qr);
    EncodeFn enc = reinterpret_cast<EncodeFn>(fn);
    void* ptr;
    cudaGetSymbolAddress(&ptr, g_qkv_tok); h.qkv_tok = (__nv_bfloat16*)ptr;
    cudaGetSymbolAddress(&ptr, g_kv_mem);  h.kv_mem = (__nv_bfloat16*)ptr;
    cudaGetSymbolAddress(&ptr, g_o_tok);   h.o_tok = (__nv_bfloat16*)ptr;
    cudaGetSymbolAddress(&ptr, g_qkv_b);   h.qkv_b = (__nv_bfloat16*)ptr;
    cudaGetSymbolAddress(&ptr, g_o_b);     h.o_b = (__nv_bfloat16*)ptr;
    cudaGetSymbolAddress(&ptr, g_xchg);    h.xchg = (uint8_t*)(((uint64_t)ptr + XCHG_BYTES - 1) & ~(uint64_t)(XCHG_BYTES - 1));
    cudaGetSymbolAddress(&ptr, g_flags);   uint32_t* flags = (uint32_t*)ptr;
    cudaGetSymbolAddress(&ptr, g_arrivals); uint32_t* arrivals = (uint32_t*)ptr;

    const void *xa = d_in[0], *mem0 = d_in[1], *wq = d_in[2], *wk = d_in[3], *wv = d_in[4], *wo = d_in[5];
    const void *xb = d_in[7], *wqkv = d_in[8], *wob = d_in[9];

    RecParams& r = h.rec;
    make_map_w(enc, &r.tmW[0], wq);
    make_map_w(enc, &r.tmW[1], wk);
    make_map_w(enc, &r.tmW[2], wv);
    make_map_b(enc, &r.tmWo, wo, HD, DM, 11, 128, 32);
    r.mem0 = (const __nv_bfloat16*)mem0;
    r.qkv_tok = h.qkv_tok; r.kv_mem = h.kv_mem; r.xchg = h.xchg;
    r.flags = flags; r.arrivals = arrivals; r.one[0] = r.one[1] = 1;
    make_map_b(enc, &r.tmX, xa, S_TOK, DM, 4, SEG);

    SideParams& sd = h.side;
    SideProb& p0 = sd.prob[0];
    make_map_2d(enc, &p0.tmA, xb, S_TOK, DM, BM);
    make_map_b(enc, &p0.tmB, wqkv, DM, 3 * DM, 4);
    make_map_2d(enc, &p0.tmC, h.qkv_b, S_TOK, 3 * DM, 16);
    p0.n_tiles = 3 * DM / 256; p0.k_blocks = DM / BK; p0.c_col0 = 0; p0.dep = nullptr; p0.dep_target = 0; p0.dep_n = 1; p0.sig = flags + F_QKVB;
    SideProb& p1 = sd.prob[1];
    make_map_2d(enc, &p1.tmA, h.o_tok, S_TOK, HD, BM);
    make_map_b(enc, &p1.tmB, wo, HD, DM, 4);
    make_map_2d(enc, &p1.tmC, d_out, S_TOK, 2 * DM, 16);
    p1.n_tiles = DM / 256; p1.k_blocks = HD / BK; p1.c_col0 = 0; p1.dep = flags + F_OA; p1.dep_target = OA_TARGET; p1.dep_n = 4; p1.sig = nullptr;
    SideProb& p2 = sd.prob[2];
    make_map_2d(enc, &p2.tmA, h.o_b, S_TOK, DM, BM);
    make_map_b(enc, &p2.tmB, wob, DM, DM, 4);
    p2.tmC = p1.tmC;
    p2.n_tiles = DM / 256; p2.k_blocks = DM / BK; p2.c_col0 = DM; p2.dep = flags + F_OB; p2.dep_target = OB_TARGET; p2.dep_n = 1; p2.sig = nullptr;
    p0.n_split = p0.n_tiles; p1.n_split = p1.n_tiles; p2.n_split = p2.n_tiles;
    p0.part = p1.part = p2.part = nullptr;
    p0.k_total = p0.k_blocks; p1.k_total = p1.k_blocks; p2.k_total = p2.k_blocks;
    if (SIDE_ORDER == 0) { sd.seg[0] = {0, 0, 16}; sd.seg[1] = {1, 0, TAIL_BLOCK0}; }
    else { sd.seg[0] = {1, 0, TAIL_BLOCK0}; sd.seg[1] = {0, 0, 16}; }
    sd.seg[2] = {2, 0, 16};
    sd.nseg = 3; sd.queue = flags + F_SIDEQ; sd.spare_seg = 3; sd.flags = flags;

    SideParams& tl = h.tail;
    tl.prob[0] = p1;
    make_map_b(enc, &tl.prob[0].tmB, wo, HD, DM, 2);
    cudaGetSymbolAddress(&ptr, g_part);
    for (int i = 0; i < 3; i++) {
        SideProb& q = tl.prob[i];
        q = tl.prob[0];
        q.n_tiles = (i + 1) * DM / 128; q.n_split = DM / 128; q.k_blocks = i == 0 ? HD / BK : i == 1 ? TAIL_KB2 : TAIL_KB3;
        q.part = i ? (float*)ptr : nullptr; q.part_flag = flags + F_PART;
    }
    tl.seg[0] = {0, TAIL_BLOCK0, TAIL_BLOCK1};
    tl.seg[1] = {1, TAIL_BLOCK1, TAIL_BLOCK2};
    tl.seg[2] = {2, TAIL_BLOCK2, 15};
    tl.nseg = 3; tl.queue = flags + F_TAILQ; tl.spare_seg = TAIL_SPARE; tl.flags = flags;

    make_map_2d(enc, &h.fin.tmA, h.o_tok, S_TOK, HD, SEG);
    h.fin.tmB = tl.prob[0].tmB; h.fin.out = (__nv_bfloat16*)d_out;
    h.fin.dep = flags + F_OA + 60; h.fin.dep_target = OA_TARGET; h.fin.mt = 15;

    make_map_2d(enc, &h.attn.tmOa, h.o_tok, S_TOK, HD, 16);
    make_map_parity(enc, &h.attn.tmQb, h.qkv_b, 3 * DM, 64);
    make_map_parity(enc, &h.attn.tmKb, h.qkv_b, 3 * DM, 72);
    make_map_parity(enc, &h.attn.tmOb, h.o_b, DM, 64);
    h.attn.qkv_tok = h.qkv_tok; h.attn.kv_mem = h.kv_mem; h.attn.flags = flags;

    int dev = 0, nsm = 0;
    cudaGetDevice(&dev);
    cudaDeviceGetAttribute(&nsm, cudaDevAttrMultiProcessorCount, dev);
    h.n_sm = nsm;
    h.overlap = nsm - 96 >= N_SIDE_CTAS + N_ATT_CTAS;
    h.n_side = N_SIDE_CTAS; h.n_att = N_ATT_CTAS;
    h.seq_a = sd;
    h.seq_a.seg[0] = {0, 0, 16};
    h.seq_a.nseg = 1;
    h.seq_b = sd;
    h.seq_b.seg[0] = {1, 0, 16};
    h.seq_b.seg[1] = {2, 0, 16};
    h.seq_b.nseg = 2; h.seq_b.queue = flags + F_TAILQ;

    cudaFuncSetAttribute(side_gemm_kernel<256>, cudaFuncAttributeMaxDynamicSharedMemorySize, GemmCfg<256>::SMEM);
    cudaFuncSetAttribute(side_gemm_kernel<128>, cudaFuncAttributeMaxDynamicSharedMemorySize, GemmCfg<128>::SMEM);
    cudaFuncSetAttribute(final_gemm_kernel, cudaFuncAttributeMaxDynamicSharedMemorySize, FIN_SMEM);
    cudaFuncSetAttribute(rec_kernel, cudaFuncAttributeMaxDynamicSharedMemorySize, REC_SMEM);
    cudaFuncSetAttribute(attn_kernel, cudaFuncAttributeMaxDynamicSharedMemorySize, ATT_SMEM);
    for (int i = 0; i < 10; i++) h.key[i] = d_in[i];
    h.key[10] = d_out;
    h.ready = true;
}

template <typename K, typename P>
void launch(K kernel, int grid, int block, int smem, cudaStream_t st, const P& prm, int cluster, bool pdl) {
    cudaLaunchConfig_t cfg = {};
    cfg.gridDim = dim3(grid); cfg.blockDim = dim3(block); cfg.dynamicSmemBytes = smem; cfg.stream = st;
    cudaLaunchAttribute at[2];
    int n = 0;
    if (cluster > 1) {
        at[n].id = cudaLaunchAttributeClusterDimension;
        at[n].val.clusterDim.x = cluster; at[n].val.clusterDim.y = 1; at[n].val.clusterDim.z = 1;
        n++;
    }
    if (pdl) {
        at[n].id = cudaLaunchAttributeProgrammaticStreamSerialization;
        at[n].val.programmaticStreamSerializationAllowed = 1;
        n++;
    }
    cfg.attrs = at; cfg.numAttrs = n;
    cudaLaunchKernelEx(&cfg, kernel, prm);
}

}

extern "C" void kernel_launch(void* const* d_in, const int* in_sizes, int n_in, void* d_out, int out_size) {
    HostState& h = g_host;
    bool same = h.ready;
    for (int i = 0; same && i < 10; i++) same = h.key[i] == d_in[i];
    if (!same || h.key[10] != d_out) setup(d_in, d_out);
    cudaStream_t st = cudaStreamPerThread;

    launch(rec_kernel, 96, REC_THREADS, REC_SMEM, st, h.rec, 3, false);
    {
        if (!h.overlap) {
            launch(side_gemm_kernel<256>, h.n_sm, 384, GemmCfg<256>::SMEM, st, h.seq_a, 1, false);
            launch(attn_kernel, SERIAL_ATT_CTAS, ATT_THREADS, ATT_SMEM, st, h.attn, 1, false);
            launch(side_gemm_kernel<256>, h.n_sm, 384, GemmCfg<256>::SMEM, st, h.seq_b, 1, false);
            return;
        }
    }
    launch(side_gemm_kernel<256>, h.n_side, 384, GemmCfg<256>::SMEM, st, h.side, 1, true);
    launch(attn_kernel, h.n_att, ATT_THREADS, ATT_SMEM, st, h.attn, 1, true);
    launch(side_gemm_kernel<128>, N_TAIL_CTAS, 384, GemmCfg<128>::SMEM, st, h.tail, 1, true);
    launch(final_gemm_kernel, 8 * FIN_SPLIT, 384, FIN_SMEM, st, h.fin, FIN_SPLIT, true);
}
```

```cpp
#include <cuda_runtime.h>
#include <cuda_bf16.h>
#include <cuda.h>
#include <stdint.h>

namespace {

constexpr int S_TOK = 2048;
constexpr int DM = 1024;
constexpr int NH = 32;
constexpr int DH = 128;
constexpr int HD = NH * DH;
constexpr int NSEG = 64;
constexpr int SEG = 32;
constexpr int MROWS = 8;
constexpr uint32_t SENT = 0xFFFFFFFFu;
constexpr uint32_t SPIN_LIMIT = 1u << 24;

__device__ __align__(1024) __nv_bfloat16 g_qkv_tok[3ull * NSEG * NH * SEG * DH];
__device__ __align__(1024) __nv_bfloat16 g_kv_mem[2ull * NSEG * NH * MROWS * DH];
__device__ __align__(1024) __nv_bfloat16 g_o_tok[(size_t)S_TOK * HD];
__device__ __align__(1024) __nv_bfloat16 g_qkv_b[(size_t)S_TOK * 3 * DM];
__device__ __align__(1024) __nv_bfloat16 g_o_b[(size_t)S_TOK * DM];
__device__ __align__(1024) float g_part[32 * 2 * 128 * 128];
constexpr int PUB_BYTES = 32768;
constexpr int XCHG_SLOT = 1 << 20;
constexpr int XCHG_PUB = 0, XCHG_INBOX = 2 * PUB_BYTES;
constexpr int INBOX_MAX = 80;
constexpr int XCHG_BYTES = 2 * XCHG_SLOT;
__device__ __align__(8192) uint8_t g_xchg[2 * XCHG_BYTES];
enum { F_LASTTOK = 0, F_RECSM = 4, F_PROGRESS = 16, F_QKVB = 80, F_OB = 96, F_OA = 112, F_PART = 176, F_SIDEQ = 208, F_TAILQ = 256, F_COUNT = 304 };
__device__ uint32_t g_flags[F_COUNT];
__device__ __align__(16) uint32_t g_arrivals[4];

#define STAMP(k) do {} while (0)
#define STAMPD(k, x) do {} while (0)
#define PSTAMP(k) do {} while (0)
#define KENTER(k) do {} while (0)
#define KEXIT(k) do {} while (0)
#define KMARK(k) do {} while (0)

__device__ __forceinline__ uint32_t class_off(uint64_t a, uint32_t c) {
    return ((__popc((uint32_t)a & 0xB3000u) ^ c) & 1u) << 12;
}
__device__ __forceinline__ uint32_t smem_u32(const void* p) { return (uint32_t)__cvta_generic_to_shared(p); }
__device__ __forceinline__ uint32_t pack_bf16(float lo, float hi) {
    uint32_t r;
    asm("cvt.rn.bf16x2.f32 %0, %1, %2;" : "=r"(r) : "f"(hi), "f"(lo));
    return r;
}
__device__ __forceinline__ float ex2(float x) {
    float y;
    asm("ex2.approx.ftz.f32 %0, %1;" : "=f"(y) : "f"(x));
    return y;
}
__device__ __forceinline__ float rcp(float x) {
    float y;
    asm("rcp.approx.ftz.f32 %0, %1;" : "=f"(y) : "f"(x));
    return y;
}
__device__ __forceinline__ uint32_t clock32() {
    uint32_t t;
    asm volatile("mov.u32 %0, %%clock;" : "=r"(t));
    return t;
}
__device__ __forceinline__ uint32_t clock_lo() {
    unsigned long long t;
    asm volatile("mov.u64 %0, %%clock64;" : "=l"(t));
    return (uint32_t)t;
}
__device__ __forceinline__ uint32_t clock_after(uint32_t x) {
    uint32_t t;
    asm volatile("{\n.reg .pred p;\nsetp.eq.u32 p, %1, 0x12345678;\n@p exit;\nmov.u32 %0, %%clock;\n}" : "=r"(t) : "r"(x) : "memory");
    return t;
}
__device__ __forceinline__ uint32_t opaque(uint32_t x) { return __shfl_sync(~0u, x, threadIdx.x & 31); }
__device__ __forceinline__ uint32_t uniform(uint32_t x) { return __shfl_sync(~0u, x + (threadIdx.x & 31), 0); }
__device__ __forceinline__ float bf16_lo(uint32_t w) { return __uint_as_float(w << 16); }
__device__ __forceinline__ float bf16_hi(uint32_t w) { return __uint_as_float(w & 0xFFFF0000u); }

__device__ __forceinline__ void mbar_init(uint32_t bar, uint32_t cnt) {
    asm volatile("mbarrier.init.shared::cta.b64 [%0], %1;" ::"r"(bar), "r"(cnt) : "memory");
}
__device__ __forceinline__ void mbar_arrive(uint32_t bar) {
    asm volatile("mbarrier.arrive.shared::cta.b64 _, [%0];" ::"r"(bar) : "memory");
}
__device__ __forceinline__ void mbar_arrive_expect_tx(uint32_t bar, uint32_t bytes) {
    asm volatile("mbarrier.arrive.expect_tx.shared::cta.b64 _, [%0], %1;" ::"r"(bar), "r"(bytes) : "memory");
}
__device__ __forceinline__ bool mbar_try_wait(uint32_t bar, uint32_t parity) {
    uint32_t ok;
    asm volatile(
        "{\n.reg .pred p;\n"
        "mbarrier.try_wait.parity.shared::cta.b64 p, [%1], %2;\n"
        "selp.u32 %0, 1, 0, p;\n}"
        : "=r"(ok) : "r"(bar), "r"(parity) : "memory");
    return ok != 0;
}
__device__ __forceinline__ bool mbar_test_wait(uint32_t bar, uint32_t parity) {
    uint32_t ok;
    asm volatile(
        "{\n.reg .pred p;\n"
        "mbarrier.test_wait.parity.shared::cta.b64 p, [%1], %2;\n"
        "selp.u32 %0, 1, 0, p;\n}"
        : "=r"(ok) : "r"(bar), "r"(parity) : "memory");
    return ok != 0;
}
__device__ __forceinline__ void mbar_wait(uint32_t bar, uint32_t parity) {
    uint32_t n = 0;
    while (!mbar_try_wait(bar, parity)) {
        if (++n > SPIN_LIMIT) __trap();
    }
}
__device__ __forceinline__ void mbar_wait_sleep(uint32_t bar, uint32_t parity) {
    uint32_t n = 0;
    while (!mbar_try_wait(bar, parity)) {
        __nanosleep(20);
        if (++n > SPIN_LIMIT) __trap();
    }
}
__device__ __forceinline__ void mbar_wait_bounded(uint32_t bar, uint32_t parity) {
    for (uint32_t n = 0; n < (1u << 20) && !mbar_try_wait(bar, parity); n++) {}
}
__device__ __forceinline__ bool elect_one() {
    uint32_t ok;
    asm volatile("{\n.reg .pred p;\nelect.sync _|p, 0xFFFFFFFF;\nselp.u32 %0, 1, 0, p;\n}" : "=r"(ok));
    return ok != 0;
}
__device__ __forceinline__ void named_bar_sync(int id, int nthreads) {
    asm volatile("bar.sync %0, %1;" ::"r"(id), "r"(nthreads) : "memory");
}
__device__ __forceinline__ void named_bar_arrive(int id, int nthreads) {
    asm volatile("bar.arrive %0, %1;" ::"r"(id), "r"(nthreads) : "memory");
}
__device__ __forceinline__ uint32_t mapa(uint32_t addr, uint32_t rank) {
    uint32_t r;
    asm volatile("mapa.shared::cluster.u32 %0, %1, %2;" : "=r"(r) : "r"(addr), "r"(rank));
    return r;
}

__device__ __forceinline__ void tma_load_2d(uint32_t dst, const CUtensorMap* tm, int c0, int c1, uint32_t bar) {
    asm volatile(
        "cp.async.bulk.tensor.2d.shared::cluster.global.mbarrier::complete_tx::bytes [%0], [%1, {%3, %4}], [%2];"
        ::"r"(dst), "l"(tm), "r"(bar), "r"(c0), "r"(c1) : "memory");
}
__device__ __forceinline__ void tma_load_3d(uint32_t dst, const CUtensorMap* tm, int c0, int c1, int c2, uint32_t bar) {
    asm volatile(
        "cp.async.bulk.tensor.3d.shared::cluster.global.mbarrier::complete_tx::bytes [%0], [%1, {%3, %4, %5}], [%2];"
        ::"r"(dst), "l"(tm), "r"(bar), "r"(c0), "r"(c1), "r"(c2) : "memory");
}
__device__ __forceinline__ void tma_load_3d_mc(uint32_t dst, const CUtensorMap* tm, int c0, int c1, int c2, uint32_t bar, uint16_t mask) {
    asm volatile(
        "cp.async.bulk.tensor.3d.shared::cluster.global.mbarrier::complete_tx::bytes.multicast::cluster [%0], [%1, {%3, %4, %5}], [%2], %6;"
        ::"r"(dst), "l"(tm), "r"(bar), "r"(c0), "r"(c1), "r"(c2), "h"(mask) : "memory");
}
__device__ __forceinline__ void tma_store_2d(const CUtensorMap* tm, uint32_t src, int c0, int c1) {
    asm volatile("cp.async.bulk.tensor.2d.global.shared::cta.bulk_group [%0, {%2, %3}], [%1];"
                 ::"l"(tm), "r"(src), "r"(c0), "r"(c1) : "memory");
}
__device__ __forceinline__ void bulk_store(void* dst, uint32_t src, uint32_t bytes) {
    asm volatile("cp.async.bulk.global.shared::cta.bulk_group [%0], [%1], %2;" ::"l"(dst), "r"(src), "r"(bytes) : "memory");
}
__device__ __forceinline__ void bulk_commit() { asm volatile("cp.async.bulk.commit_group;" ::: "memory"); }
__device__ __forceinline__ void bulk_wait_read_all() { asm volatile("cp.async.bulk.wait_group.read 0;" ::: "memory"); }
__device__ __forceinline__ void bulk_wait_all() { asm volatile("cp.async.bulk.wait_group 0;" ::: "memory"); }
__device__ __forceinline__ void bulk_load(uint32_t dst, const void* src, uint32_t bytes, uint32_t bar) {
    asm volatile("cp.async.bulk.shared::cluster.global.mbarrier::complete_tx::bytes [%0], [%1], %2, [%3];"
                 ::"r"(dst), "l"(src), "r"(bytes), "r"(bar) : "memory");
}

__device__ __forceinline__ void ldsm_x4(uint32_t addr, uint32_t& r0, uint32_t& r1, uint32_t& r2, uint32_t& r3) {
    asm volatile("ldmatrix.sync.aligned.m8n8.x4.shared.b16 {%0,%1,%2,%3}, [%4];"
                 : "=r"(r0), "=r"(r1), "=r"(r2), "=r"(r3) : "r"(addr) : "memory");
}
__device__ __forceinline__ void ldsm_x4_t(uint32_t addr, uint32_t& r0, uint32_t& r1, uint32_t& r2, uint32_t& r3) {
    asm volatile("ldmatrix.sync.aligned.m8n8.x4.trans.shared.b16 {%0,%1,%2,%3}, [%4];"
                 : "=r"(r0), "=r"(r1), "=r"(r2), "=r"(r3) : "r"(addr) : "memory");
}
__device__ __forceinline__ void stsm_x4(uint32_t addr, uint32_t r0, uint32_t r1, uint32_t r2, uint32_t r3) {
    asm volatile("stmatrix.sync.aligned.m8n8.x4.shared.b16 [%0], {%1,%2,%3,%4};"
                 ::"r"(addr), "r"(r0), "r"(r1), "r"(r2), "r"(r3) : "memory");
}
__device__ __forceinline__ void mma16816(float* d, uint32_t a0, uint32_t a1, uint32_t a2, uint32_t a3,
                                         uint32_t b0, uint32_t b1) {
    asm volatile(
        "mma.sync.aligned.m16n8k16.row.col.f32.bf16.bf16.f32 {%0,%1,%2,%3}, {%4,%5,%6,%7}, {%8,%9}, {%0,%1,%2,%3};"
        : "+f"(d[0]), "+f"(d[1]), "+f"(d[2]), "+f"(d[3])
        : "r"(a0), "r"(a1), "r"(a2), "r"(a3), "r"(b0), "r"(b1));
}
__device__ __forceinline__ void mma1688(float* d, uint32_t a0, uint32_t a1, uint32_t b0) {
    asm volatile("mma.sync.aligned.m16n8k8.row.col.f32.bf16.bf16.f32 {%0,%1,%2,%3}, {%4,%5}, {%6}, {%0,%1,%2,%3};"
                 : "+f"(d[0]), "+f"(d[1]), "+f"(d[2]), "+f"(d[3]) : "r"(a0), "r"(a1), "r"(b0));
}
__device__ __forceinline__ uint2 lds64(uint32_t addr) {
    uint2 v;
    asm volatile("ld.volatile.shared.v2.b32 {%0,%1}, [%2];" : "=r"(v.x), "=r"(v.y) : "r"(addr) : "memory");
    return v;
}
__device__ __forceinline__ uint4 lds128(uint32_t addr) {
    uint4 v;
    asm volatile("ld.volatile.shared.v4.b32 {%0,%1,%2,%3}, [%4];" : "=r"(v.x), "=r"(v.y), "=r"(v.z), "=r"(v.w) : "r"(addr) : "memory");
    return v;
}
__device__ __forceinline__ void sts32(uint32_t addr, uint32_t x) {
    asm volatile("st.volatile.shared.b32 [%0], %1;" ::"r"(addr), "r"(x) : "memory");
}
__device__ __forceinline__ void sts64(uint32_t addr, uint32_t x, uint32_t y) {
    asm volatile("st.volatile.shared.v2.b32 [%0], {%1,%2};" ::"r"(addr), "r"(x), "r"(y) : "memory");
}
__device__ __forceinline__ void sts128(uint32_t addr, uint32_t x, uint32_t y, uint32_t z, uint32_t w) {
    asm volatile("st.volatile.shared.v4.b32 [%0], {%1,%2,%3,%4};" ::"r"(addr), "r"(x), "r"(y), "r"(z), "r"(w) : "memory");
}
__device__ __forceinline__ void st_async_v2(uint32_t addr, uint32_t x, uint32_t y, uint32_t bar) {
    asm volatile("st.async.weak.shared::cluster.mbarrier::complete_tx::bytes.v2.b32 [%0], {%1,%2}, [%3];"
                 ::"r"(addr), "r"(x), "r"(y), "r"(bar) : "memory");
}
__device__ __forceinline__ void st_relaxed_v4(void* p, uint32_t x) {
    asm volatile("st.relaxed.gpu.global.v4.b32 [%0], {%1,%1,%1,%1};" ::"l"(p), "r"(x) : "memory");
}
__device__ __forceinline__ uint32_t ld_relaxed_b32(const void* p) {
    uint32_t v;
    asm volatile("ld.relaxed.gpu.global.b32 %0, [%1];" : "=r"(v) : "l"(p) : "memory");
    return v;
}
__device__ __forceinline__ uint32_t lds32_volatile(uint32_t addr) {
    uint32_t v;
    asm volatile("ld.volatile.shared.b32 %0, [%1];" : "=r"(v) : "r"(addr) : "memory");
    return v;
}
__device__ __forceinline__ void st_relaxed_b32(void* p, uint32_t x) {
    asm volatile("st.relaxed.gpu.global.b32 [%0], %1;" ::"l"(p), "r"(x) : "memory");
}

__device__ __forceinline__ uint32_t ld_acquire_b32(const void* p) {
    uint32_t v;
    asm volatile("ld.acquire.gpu.global.b32 %0, [%1];" : "=r"(v) : "l"(p) : "memory");
    return v;
}
__device__ __forceinline__ void wait_flag(const uint32_t* p, uint32_t target) {
    uint32_t n = 0;
    while (ld_acquire_b32(p) < target) {
        __nanosleep(64);
        if (++n > SPIN_LIMIT) __trap();
    }
}
__device__ __forceinline__ void signal_flag(uint32_t* p) {
    asm volatile("red.release.gpu.global.add.u32 [%0], 1;" ::"l"(p) : "memory");
}
__device__ __forceinline__ void signal_bulk(uint32_t* p) {
    asm volatile("red.relaxed.gpu.global.add.u32 [%0], 1;" ::"l"(p) : "memory");
}
__device__ __forceinline__ bool next_to_rec(const uint32_t* flags) {
    uint32_t smid;
    asm volatile("mov.u32 %0, %%smid;" : "=r"(smid));
    smid ^= 1;
    return smid < 384 && ((ld_relaxed_b32(flags + F_RECSM + (smid >> 5)) >> (smid & 31)) & 1);
}
__device__ __forceinline__ void pdl_launch_dependents() { asm volatile("griddepcontrol.launch_dependents;" ::: "memory"); }

constexpr int BM = 128, BK = 64;
constexpr int A_STAGE = BM * BK * 2;
template <int BN> struct GemmCfg {
    static constexpr int STAGES = BN == 256 ? 3 : 6;
    static constexpr int STAGE = A_STAGE + BK * BN * 2;
    static constexpr int EPI_WARP = 16 * BN * 2;
    static constexpr int SMEM = STAGES * STAGE + 8 * EPI_WARP + 1024 + 512;
};

struct SideProb {
    CUtensorMap tmA, tmB, tmC;
    int n_split;
    int n_tiles, k_blocks, k_total, c_col0;
    const uint32_t* dep;
    uint32_t dep_target;
    int dep_n;
    uint32_t* sig;
    float* part;
    uint32_t* part_flag;
};
struct SideSeg { int prob, m0, m1; };
constexpr int SIDE_MAX_SEG = 3;
struct SideParams {
    SideProb prob[3];
    SideSeg seg[SIDE_MAX_SEG];
    int nseg;
    int spare_seg;
    const uint32_t* flags;
    uint32_t* queue;
};
static_assert(sizeof(SideParams) <= 4096, "kernel parameter limit");

__device__ __forceinline__ uint64_t make_desc(uint32_t addr, uint32_t lbo, uint32_t sbo) {
    return (uint64_t)((addr & 0x3FFFF) >> 4) | ((uint64_t)(lbo >> 4) << 16) | ((uint64_t)(sbo >> 4) << 32) | (1ull << 62);
}

__device__ __forceinline__ void wgmma_m64n256k16(float (&d)[128], uint64_t da, uint64_t db, int scale_d) {
    asm volatile(
        "{\n.reg .pred p;\nsetp.ne.b32 p, %130, 0;\n"
        "wgmma.mma_async.sync.aligned.m64n256k16.f32.bf16.bf16 "
        "{%0,%1,%2,%3,%4,%5,%6,%7,%8,%9,%10,%11,%12,%13,%14,%15,"
        "%16,%17,%18,%19,%20,%21,%22,%23,%24,%25,%26,%27,%28,%29,%30,%31,"
        "%32,%33,%34,%35,%36,%37,%38,%39,%40,%41,%42,%43,%44,%45,%46,%47,"
        "%48,%49,%50,%51,%52,%53,%54,%55,%56,%57,%58,%59,%60,%61,%62,%63,"
        "%64,%65,%66,%67,%68,%69,%70,%71,%72,%73,%74,%75,%76,%77,%78,%79,"
        "%80,%81,%82,%83,%84,%85,%86,%87,%88,%89,%90,%91,%92,%93,%94,%95,"
        "%96,%97,%98,%99,%100,%101,%102,%103,%104,%105,%106,%107,%108,%109,%110,%111,"
        "%112,%113,%114,%115,%116,%117,%118,%119,%120,%121,%122,%123,%124,%125,%126,%127},"
        " %128, %129, p, 1, 1, 0, 1;\n}\n"
        : "+f"(d[0]), "+f"(d[1]), "+f"(d[2]), "+f"(d[3]), "+f"(d[4]), "+f"(d[5]), "+f"(d[6]), "+f"(d[7]),
          "+f"(d[8]), "+f"(d[9]), "+f"(d[10]), "+f"(d[11]), "+f"(d[12]), "+f"(d[13]), "+f"(d[14]), "+f"(d[15]),
          "+f"(d[16]), "+f"(d[17]), "+f"(d[18]), "+f"(d[19]), "+f"(d[20]), "+f"(d[21]), "+f"(d[22]), "+f"(d[23]),
          "+f"(d[24]), "+f"(d[25]), "+f"(d[26]), "+f"(d[27]), "+f"(d[28]), "+f"(d[29]), "+f"(d[30]), "+f"(d[31]),
          "+f"(d[32]), "+f"(d[33]), "+f"(d[34]), "+f"(d[35]), "+f"(d[36]), "+f"(d[37]), "+f"(d[38]), "+f"(d[39]),
          "+f"(d[40]), "+f"(d[41]), "+f"(d[42]), "+f"(d[43]), "+f"(d[44]), "+f"(d[45]), "+f"(d[46]), "+f"(d[47]),
          "+f"(d[48]), "+f"(d[49]), "+f"(d[50]), "+f"(d[51]), "+f"(d[52]), "+f"(d[53]), "+f"(d[54]), "+f"(d[55]),
          "+f"(d[56]), "+f"(d[57]), "+f"(d[58]), "+f"(d[59]), "+f"(d[60]), "+f"(d[61]), "+f"(d[62]), "+f"(d[63]),
          "+f"(d[64]), "+f"(d[65]), "+f"(d[66]), "+f"(d[67]), "+f"(d[68]), "+f"(d[69]), "+f"(d[70]), "+f"(d[71]),
          "+f"(d[72]), "+f"(d[73]), "+f"(d[74]), "+f"(d[75]), "+f"(d[76]), "+f"(d[77]), "+f"(d[78]), "+f"(d[79]),
          "+f"(d[80]), "+f"(d[81]), "+f"(d[82]), "+f"(d[83]), "+f"(d[84]), "+f"(d[85]), "+f"(d[86]), "+f"(d[87]),
          "+f"(d[88]), "+f"(d[89]), "+f"(d[90]), "+f"(d[91]), "+f"(d[92]), "+f"(d[93]), "+f"(d[94]), "+f"(d[95]),
          "+f"(d[96]), "+f"(d[97]), "+f"(d[98]), "+f"(d[99]), "+f"(d[100]), "+f"(d[101]), "+f"(d[102]), "+f"(d[103]),
          "+f"(d[104]), "+f"(d[105]), "+f"(d[106]), "+f"(d[107]), "+f"(d[108]), "+f"(d[109]), "+f"(d[110]), "+f"(d[111]),
          "+f"(d[112]), "+f"(d[113]), "+f"(d[114]), "+f"(d[115]), "+f"(d[116]), "+f"(d[117]), "+f"(d[118]), "+f"(d[119]),
          "+f"(d[120]), "+f"(d[121]), "+f"(d[122]), "+f"(d[123]), "+f"(d[124]), "+f"(d[125]), "+f"(d[126]), "+f"(d[127])
        : "l"(da), "l"(db), "r"(scale_d));
}

__device__ __forceinline__ void wgmma_m64n128k16(float (&d)[64], uint64_t da, uint64_t db, int scale_d) {
    asm volatile(
        "{\n.reg .pred p;\nsetp.ne.b32 p, %66, 0;\n"
        "wgmma.mma_async.sync.aligned.m64n128k16.f32.bf16.bf16 "
        "{%0,%1,%2,%3,%4,%5,%6,%7,%8,%9,%10,%11,%12,%13,%14,%15,"
        "%16,%17,%18,%19,%20,%21,%22,%23,%24,%25,%26,%27,%28,%29,%30,%31,"
        "%32,%33,%34,%35,%36,%37,%38,%39,%40,%41,%42,%43,%44,%45,%46,%47,"
        "%48,%49,%50,%51,%52,%53,%54,%55,%56,%57,%58,%59,%60,%61,%62,%63},"
        " %64, %65, p, 1, 1, 0, 1;\n}\n"
        : "+f"(d[0]), "+f"(d[1]), "+f"(d[2]), "+f"(d[3]), "+f"(d[4]), "+f"(d[5]), "+f"(d[6]), "+f"(d[7]),
          "+f"(d[8]), "+f"(d[9]), "+f"(d[10]), "+f"(d[11]), "+f"(d[12]), "+f"(d[13]), "+f"(d[14]), "+f"(d[15]),
          "+f"(d[16]), "+f"(d[17]), "+f"(d[18]), "+f"(d[19]), "+f"(d[20]), "+f"(d[21]), "+f"(d[22]), "+f"(d[23]),
          "+f"(d[24]), "+f"(d[25]), "+f"(d[26]), "+f"(d[27]), "+f"(d[28]), "+f"(d[29]), "+f"(d[30]), "+f"(d[31]),
          "+f"(d[32]), "+f"(d[33]), "+f"(d[34]), "+f"(d[35]), "+f"(d[36]), "+f"(d[37]), "+f"(d[38]), "+f"(d[39]),
          "+f"(d[40]), "+f"(d[41]), "+f"(d[42]), "+f"(d[43]), "+f"(d[44]), "+f"(d[45]), "+f"(d[46]), "+f"(d[47]),
          "+f"(d[48]), "+f"(d[49]), "+f"(d[50]), "+f"(d[51]), "+f"(d[52]), "+f"(d[53]), "+f"(d[54]), "+f"(d[55]),
          "+f"(d[56]), "+f"(d[57]), "+f"(d[58]), "+f"(d[59]), "+f"(d[60]), "+f"(d[61]), "+f"(d[62]), "+f"(d[63])
        : "l"(da), "l"(db), "r"(scale_d));
}
template <int BN> struct WgmmaOp;
template <> struct WgmmaOp<256> {
    static __device__ __forceinline__ void run(float (&d)[128], uint64_t a, uint64_t b, int sc) { wgmma_m64n256k16(d, a, b, sc); }
};
template <> struct WgmmaOp<128> {
    static __device__ __forceinline__ void run(float (&d)[64], uint64_t a, uint64_t b, int sc) { wgmma_m64n128k16(d, a, b, sc); }
};

struct StoreRec {
    uint64_t dst;
    uint64_t flag;
    int kind;
    int pad;
};
struct EpiCtx { uint32_t buf, rec, st_full, st_empty; uint32_t it; int lane; };
template <int N>
__device__ __forceinline__ void epi_hand_over(const float (&acc)[N], EpiCtx& e, uint64_t dst, uint64_t flag, int kind) {
    mbar_wait(e.st_empty, (e.it & 1) ^ 1);
    const int mi = e.lane >> 3, row = (mi & 1) * 8 + (e.lane & 7);
    #pragma unroll
    for (int j = 0; j < N / 4; j += 2) {
        const int chunk = (j & 7) + (mi >> 1);
        stsm_x4(e.buf + (j >> 3) * 2048 + row * 128 + ((chunk ^ (row & 7)) << 4),
                pack_bf16(acc[4 * j], acc[4 * j + 1]), pack_bf16(acc[4 * j + 2], acc[4 * j + 3]),
                pack_bf16(acc[4 * j + 4], acc[4 * j + 5]), pack_bf16(acc[4 * j + 6], acc[4 * j + 7]));
    }
    if (e.lane == 0) {
        asm volatile("st.shared.v2.b64 [%0], {%1, %2};" ::"r"(e.rec), "l"(dst), "l"(flag) : "memory");
        asm volatile("st.shared.b32 [%0], %1;" ::"r"(e.rec + 16), "r"(kind) : "memory");
    }
    asm volatile("fence.proxy.async.shared::cta;" ::: "memory");
    __syncwarp();
    if (e.lane == 0) mbar_arrive(e.st_full);
    e.it++;
}
__device__ __forceinline__ void epi_exit(EpiCtx& e) {
    mbar_wait(e.st_empty, (e.it & 1) ^ 1);
    if (e.lane == 0) {
        asm volatile("st.shared.b32 [%0], %1;" ::"r"(e.rec + 16), "r"(-1) : "memory");
        mbar_arrive(e.st_full);
    }
}
template <int BN>
__device__ __forceinline__ void gemm_mainloop(float (&acc)[BN / 2], int k_blocks, uint32_t sbase, uint32_t bar_base, int cw,
                                              bool elected, int& stage, uint32_t& phase) {
    using C = GemmCfg<BN>;
    auto release = [&](int st) { mbar_arrive(bar_base + 8 * (C::STAGES + st)); };
    int prev_stage = -1;
    for (int kb = 0; kb < k_blocks; kb++) {
        mbar_wait(bar_base + 8 * stage, phase);
        const uint32_t sa = sbase + stage * C::STAGE + cw * (64 * 128);
        const uint32_t sb = sbase + stage * C::STAGE + A_STAGE;
        asm volatile("wgmma.fence.sync.aligned;" ::: "memory");
        #pragma unroll
        for (int kk = 0; kk < BK / 16; kk++)
            WgmmaOp<BN>::run(acc, make_desc(sa + kk * 32, 16, 1024), make_desc(sb + kk * 2048, 8192, 1024), (kb | kk) != 0);
        asm volatile("wgmma.commit_group.sync.aligned;" ::: "memory");
        asm volatile("wgmma.wait_group.sync.aligned 1;" ::: "memory");
        if (prev_stage >= 0 && elected) release(prev_stage);
        prev_stage = stage;
        if (++stage == C::STAGES) { stage = 0; phase ^= 1; }
    }
    asm volatile("wgmma.wait_group.sync.aligned 0;" ::: "memory");
    if (elected) release(prev_stage);
}
template <int BN>
__device__ __forceinline__ void store_warp(uint32_t epi_base, uint32_t rec_base, uint32_t st_full, uint32_t st_empty, int lane,
                                           const uint8_t* tmaps, int tstride) {
    for (uint32_t it = 0;; it++) {
        mbar_wait(st_full, it & 1);
        uint64_t dst = 0, flag = 0;
        int kind = -1;
        if (lane < 8) {
            const uint32_t rec = rec_base + lane * 32;
            asm volatile("ld.volatile.shared.v2.b64 {%0, %1}, [%2];" : "=l"(dst), "=l"(flag) : "r"(rec) : "memory");
            kind = (int)lds32_volatile(rec + 16);
        }
        if (__shfl_sync(~0u, kind, 0) < 0) break;
        if (lane < 8) {
            const uint32_t buf = epi_base + lane * GemmCfg<BN>::EPI_WARP;
            #pragma unroll
            for (int q = 0; q < BN / 64; q++) {
                tma_store_2d(reinterpret_cast<const CUtensorMap*>(tmaps + (kind - 1) * tstride), buf + q * 2048,
                                  (int)(uint32_t)dst + q * 64, (int)(dst >> 32));
            }
            bulk_commit();
            bulk_wait_read_all();
            mbar_arrive(st_empty);
            if (flag) {
                bulk_wait_all();
                signal_bulk(reinterpret_cast<uint32_t*>(flag));
            }
        }
        __syncwarp();
    }
    if (lane < 8) bulk_wait_all();
}

#define SCHED_AHEAD 4
template <int BN>
__global__ void __launch_bounds__(384, 1) side_gemm_kernel(const __grid_constant__ SideParams p) {
    using C = GemmCfg<BN>;
    extern __shared__ uint8_t smem_raw[];
    const uint32_t sbase = (smem_u32(smem_raw) + 1023) & ~1023u;
    const uint32_t epi_base = sbase + C::STAGES * C::STAGE;
    const uint32_t bar_base = epi_base + 8 * C::EPI_WARP;
    const uint32_t tfull = bar_base + 16 * C::STAGES, tempty = tfull + 16, tslot = tempty + 16, twant = tslot + 8;
    const uint32_t st_full = bar_base + 192, st_empty = st_full + 8, rec_base = bar_base + 256;
    const int tid = threadIdx.x, wg = tid >> 7;
    if (tid == 0) {
        for (int s = 0; s < C::STAGES; s++) { mbar_init(bar_base + 8 * s, 1); mbar_init(bar_base + 8 * (C::STAGES + s), 2); }
        for (int s = 0; s < 2; s++) { mbar_init(tfull + 8 * s, 1); mbar_init(tempty + 8 * s, 3); }
        mbar_init(twant, 1);
        mbar_init(st_full, 8);
        mbar_init(st_empty, 8);
        asm volatile("fence.mbarrier_init.release.cluster;" ::: "memory");
        pdl_launch_dependents();
    }
    __syncthreads();
    KENTER(BN == 256 ? 2 : 4);

    if (wg == 0) {
        asm volatile("setmaxnreg.dec.sync.aligned.u32 40;");
        if (tid == 0) {
            int stage = 0; uint32_t phase = 1;
            for (uint32_t it = 0;; it++) {
                mbar_wait(tfull + 8 * (it & 1), (it >> 1) & 1);
                const int code = (int)lds32_volatile(tslot + 4 * (it & 1));
                mbar_arrive(tempty + 8 * (it & 1));
                if (code < 0) break;
                const SideProb& q = p.prob[code >> 16];
                const int mt = (code >> 8) & 255, nt = code & 255;
                asm volatile("fence.proxy.async.global;" ::: "memory");
                const int kb0 = nt / q.n_split * q.k_blocks, nkb = nt + q.n_split < q.n_tiles ? q.k_blocks : q.k_total - kb0;
                for (int kb = 0; kb < nkb; kb++) {
                    if (kb == nkb - SCHED_AHEAD) mbar_arrive(twant);
                    mbar_wait(bar_base + 8 * (C::STAGES + stage), phase);
                    const uint32_t sa = sbase + stage * C::STAGE, fb = bar_base + 8 * stage;
                    mbar_arrive_expect_tx(fb, C::STAGE);
                    const int k0 = (kb0 + kb) * BK;
                    tma_load_2d(sa, &q.tmA, k0, mt * BM, fb);
                    tma_load_3d(sa + A_STAGE, &q.tmB, 0, k0, nt % q.n_split * (BN / 64), fb);
                    if (++stage == C::STAGES) { stage = 0; phase ^= 1; }
                }
            }
        } else if (tid >= 64 && tid < 96) {
            const int lane = tid & 31;
            const bool spare = p.spare_seg < 3 && next_to_rec(p.flags);
            uint32_t ntl[2], tgt[2], prb[2];
            const uint32_t* dp[2];
            #pragma unroll
            for (int u = 0; u < 2; u++) {
                const int g = u * 2 + (lane >> 4), mt = lane & 15;
                const bool on = g < p.nseg && mt >= p.seg[g < p.nseg ? g : 0].m0 && mt < p.seg[g < p.nseg ? g : 0].m1;
                prb[u] = p.seg[on ? g : 0].prob;
                const SideProb& q = p.prob[prb[u]];
                ntl[u] = on && !(g >= p.spare_seg && spare) ? q.n_tiles : 0;
                tgt[u] = on && q.dep ? q.dep_target : 0;
                dp[u] = tgt[u] ? q.dep + (mt + 1) * q.dep_n - 1 : p.queue;
            }
            for (uint32_t it = 0;; it++) {
                if (it > 0) mbar_wait_sleep(twant, (it - 1) & 1);
                int code = -1;
                for (uint32_t tries = 0; code < 0; tries++) {
                    const uint32_t c0 = ld_relaxed_b32(p.queue + lane), c1 = ld_relaxed_b32(p.queue + 32 + (lane & 15));
                    const uint32_t d0 = ld_relaxed_b32(dp[0]), d1 = ld_relaxed_b32(dp[1]);
                    const uint64_t left = __ballot_sync(~0u, c0 < ntl[0]) | (uint64_t)__ballot_sync(~0u, c1 < ntl[1]) << 32;
                    uint64_t ready = left & (__ballot_sync(~0u, d0 >= tgt[0]) | (uint64_t)__ballot_sync(~0u, d1 >= tgt[1]) << 32);
                    if (!left) break;
                    if (!ready && (BN == 128 || (left >> (((__ffsll(left) - 1) & ~15) + 16)) == 0)) ready = left;
                    if (!ready) __nanosleep(200);
                    while (ready) {
                        const int e = __ffsll(ready) - 1;
                        const uint32_t n = __shfl_sync(~0u, e < 32 ? ntl[0] : ntl[1], e & 31), pr = __shfl_sync(~0u, e < 32 ? prb[0] : prb[1], e & 31);
                        uint32_t idx = 0;
                        if (lane == 0) idx = atomicAdd(p.queue + e, 1u);
                        idx = __shfl_sync(~0u, idx, 0);
                        if (idx < n) { code = (pr << 16) | ((e & 15) << 8) | idx; break; }
                        for (uint32_t k = idx / n; k > 0; k--) ready &= ready - 1;
                    }
                    if (tries > SPIN_LIMIT) __trap();
                }
                if (code >= 0) {
                    const SideProb& q = p.prob[code >> 16];
                    if (q.dep && lane < q.dep_n) wait_flag(q.dep + ((code >> 8) & 255) * q.dep_n + lane, q.dep_target);
                    __syncwarp();
                }
                if (lane == 0) {
                    mbar_wait(tempty + 8 * (it & 1), ((it >> 1) & 1) ^ 1);
                    asm volatile("st.shared.b32 [%0], %1;" ::"r"(tslot + 4 * (it & 1)), "r"(code) : "memory");
                    mbar_arrive(tfull + 8 * (it & 1));
                }
                __syncwarp();
                if (code < 0) break;
            }
        } else if (tid >= 32 && tid < 64) {
            store_warp<BN>(epi_base, rec_base, st_full, st_empty, tid & 31, reinterpret_cast<const uint8_t*>(&p.prob[0].tmC),
                           (int)sizeof(SideProb));
        }
    } else {
        asm volatile("setmaxnreg.inc.sync.aligned.u32 232;");
        const int cw = wg - 1, lane = tid & 31, wi = (tid >> 5) & 3;
        const bool elected = (tid & 127) == 0;
        int stage = 0; uint32_t phase = 0;
        float acc[BN / 2];
        EpiCtx ectx = {epi_base + (cw * 4 + wi) * C::EPI_WARP, rec_base + (cw * 4 + wi) * 32, st_full, st_empty, 0, lane};
        for (uint32_t it = 0;; it++) {
            mbar_wait(tfull + 8 * (it & 1), (it >> 1) & 1);
            const int code = (int)lds32_volatile(tslot + 4 * (it & 1));
            named_bar_sync(1 + cw, 128);
            if (elected) mbar_arrive(tempty + 8 * (it & 1));
            if (code < 0) break;
            const SideProb& q = p.prob[code >> 16];
            const int mt = (code >> 8) & 255, nt = code & 255;
            gemm_mainloop<BN>(acc, nt + q.n_split < q.n_tiles ? q.k_blocks : q.k_total - nt / q.n_split * q.k_blocks, sbase, bar_base, cw, elected, stage, phase);
            const int row0 = mt * BM + cw * 64 + wi * 16, ntc = nt % q.n_split;
            if (BN == 128 && q.part) {
                const int idx = (mt & 3) * q.n_split + ntc, item = nt / q.n_split, nprev = q.n_tiles / q.n_split - 1;
                float4* part = reinterpret_cast<float4*>(q.part) + (size_t)idx * 2 * (BM * BN / 4) + (tid - 128);
                if (mt == 14 && elected) KMARK(21);
                if (item < nprev) {
                    #pragma unroll
                    for (int j = 0; j < BN / 8; j++)
                        __stcg(part + item * (BM * BN / 4) + j * 256, make_float4(acc[4 * j], acc[4 * j + 1], acc[4 * j + 2], acc[4 * j + 3]));
                    __syncwarp();
                    if (lane == 0) signal_flag(q.part_flag + idx);
                    continue;
                }
                if (lane == 0) wait_flag(q.part_flag + idx, 8 * nprev);
                __syncwarp();
                if (mt == 14 && elected) KMARK(22);
                for (int u = 0; u < nprev; u++) {
                    #pragma unroll
                    for (int j = 0; j < BN / 8; j++) {
                        const float4 v = __ldcg(part + u * (BM * BN / 4) + j * 256);
                        acc[4 * j] += v.x; acc[4 * j + 1] += v.y; acc[4 * j + 2] += v.z; acc[4 * j + 3] += v.w;
                    }
                }
            }
            if (BN == 128 && mt == 14 && elected) KMARK(23);
            epi_hand_over(acc, ectx, ((uint64_t)row0 << 32) | (uint32_t)(q.c_col0 + ntc * BN), q.sig ? (uint64_t)(q.sig + mt) : 0, 1 + (code >> 16));
        }
        epi_exit(ectx);
        if (elected) KEXIT(BN == 256 ? 2 : 4);
    }
}

constexpr int FIN_SPLIT = 8, FIN_KB = HD / BK / FIN_SPLIT;
constexpr int FIN_A1 = FIN_KB * 16384;
constexpr int FIN_A0 = FIN_A1 + FIN_KB * 8192;
constexpr int FIN_BAR = FIN_A0 + 4 * 8192, FIN_SMEM = FIN_BAR + 256;
enum { FB_B = 0, FB_A1 = 64, FB_A0 = 128, FB_E0 = 160, FB_RDY = 192, FB_RED = 208 };
struct FinalParams {
    CUtensorMap tmA, tmB;
    __nv_bfloat16* out;
    const uint32_t* dep;
    uint32_t dep_target;
    int mt;
};
__global__ void __launch_bounds__(384, 1) final_gemm_kernel(const __grid_constant__ FinalParams p) {
    extern __shared__ __align__(1024) uint8_t smem_raw[];
    const uint32_t sbase = smem_u32(smem_raw), bar = sbase + FIN_BAR;
    const int tid = threadIdx.x, wg = tid >> 7;
    const int rank = blockIdx.x % FIN_SPLIT, nt = blockIdx.x / FIN_SPLIT;
    KENTER(5);
    if (tid == 0) {
        for (int s = 0; s < FIN_KB; s++) { mbar_init(bar + FB_B + 8 * s, 1); mbar_init(bar + FB_A1 + 8 * s, 1); }
        for (int s = 0; s < 4; s++) { mbar_init(bar + FB_A0 + 8 * s, 1); mbar_init(bar + FB_E0 + 8 * s, 1); }
        for (int h = 0; h < 2; h++) { mbar_init(bar + FB_RDY + 8 * h, FIN_SPLIT); mbar_init(bar + FB_RED + 8 * h, 1); }
        asm volatile("fence.mbarrier_init.release.cluster;" ::: "memory");
        for (int h = 0; h < 2; h++) mbar_arrive_expect_tx(bar + FB_RED + 8 * h, (FIN_SPLIT - 1) * 4096);
        pdl_launch_dependents();
    }
    __syncthreads();
    asm volatile("barrier.cluster.arrive.relaxed.aligned;" ::: "memory");
    if (wg == 0) {
        auto need = [&](int i) {
            uint32_t n = 0;
            while (ld_acquire_b32(p.dep + i) < p.dep_target) { if (++n > SPIN_LIMIT) __trap(); }
            asm volatile("fence.proxy.async.global;" ::: "memory");
        };
        auto a_load = [&](uint32_t dst, int kb, int seg, uint32_t mb) { tma_load_2d(dst, &p.tmA, (rank * FIN_KB + kb) * BK, p.mt * BM + seg * SEG, mb); };
        if (tid == 0) {
            auto b_load = [&](int kb) {
                mbar_arrive_expect_tx(bar + FB_B + 8 * kb, 16384);
                tma_load_3d(sbase + kb * 16384, &p.tmB, 0, (rank * FIN_KB + kb) * BK, nt * 2, bar + FB_B + 8 * kb);
            };
            const uint32_t f0 = ld_relaxed_b32(p.dep);
            b_load(0);
            need(1);
            if (f0 < p.dep_target) need(0);
            for (int kb = 0; kb < FIN_KB; kb++) {
                if (kb >= 4) mbar_wait(bar + FB_E0 + 8 * (kb & 3), 0);
                mbar_arrive_expect_tx(bar + FB_A0 + 8 * (kb & 3), 8192);
                for (int u = 0; u < 2; u++) a_load(sbase + FIN_A0 + (kb & 3) * 8192 + u * 4096, kb, u, bar + FB_A0 + 8 * (kb & 3));
                if (kb < 3) b_load(kb + 1);
                if (kb == 3) { b_load(4); b_load(5); }
                if (kb == 4 || kb == 5) b_load(kb + 2);
            }
        } else if (tid == 96) {
            need(3);
            for (int kb = 1; kb < FIN_KB; kb += 2) a_load(sbase + FIN_A1 + kb * 8192 + 4096, kb, 3, bar + FB_A1 + 8 * kb);
        } else if (tid == 64) {
            mbar_wait(bar + FB_B + 8 * 3, 0);
            need(2);
            for (int kb = 0; kb < FIN_KB; kb++) {
                mbar_arrive_expect_tx(bar + FB_A1 + 8 * kb, 8192);
                a_load(sbase + FIN_A1 + kb * 8192, kb, 2, bar + FB_A1 + 8 * kb);
            }
            need(3);
            KMARK(15);
            for (int kb = 0; kb < FIN_KB; kb += 2) a_load(sbase + FIN_A1 + kb * 8192 + 4096, kb, 3, bar + FB_A1 + 8 * kb);
        }
        __syncwarp();
        asm volatile("barrier.cluster.wait.aligned;" ::: "memory");
    } else {
        const int h = wg - 1, lane = tid & 31, wi = (tid >> 5) & 3, t128 = tid & 127;
        asm volatile("barrier.cluster.wait.aligned;" ::: "memory");
        float acc[64];
        for (int kb = 0; kb < FIN_KB; kb++) {
            mbar_wait(bar + FB_B + 8 * kb, 0);
            if (h == 0) mbar_wait(bar + FB_A0 + 8 * (kb & 3), kb >> 2); else mbar_wait(bar + FB_A1 + 8 * kb, 0);
            const uint32_t sa = sbase + (h == 0 ? FIN_A0 + (kb & 3) * 8192 : FIN_A1 + kb * 8192), sb = sbase + kb * 16384;
            asm volatile("wgmma.fence.sync.aligned;" ::: "memory");
            #pragma unroll
            for (int kk = 0; kk < BK / 16; kk++)
                wgmma_m64n128k16(acc, make_desc(sa + kk * 32, 16, 1024), make_desc(sb + kk * 2048, 8192, 1024), (kb | kk) != 0);
            asm volatile("wgmma.commit_group.sync.aligned;" ::: "memory");
            asm volatile("wgmma.wait_group.sync.aligned 1;" ::: "memory");
            if (h == 0 && kb >= 1 && kb <= 4 && t128 == 0) mbar_arrive(bar + FB_E0 + 8 * (kb - 1));
        }
        asm volatile("wgmma.wait_group.sync.aligned 0;" ::: "memory");
        const uint32_t red = sbase + FIN_A0;
        auto ready = [&](int i) {
            named_bar_sync(1, 128);
            if (t128 < FIN_SPLIT)
                asm volatile("mbarrier.arrive.relaxed.cluster.shared::cluster.b64 _, [%0];" ::"r"(mapa(bar + FB_RDY + 8 * i, t128)) : "memory");
        };
        if (tid == 256) KMARK(16);
        if (tid == 128) KMARK(19);
        if (h == 0) ready(0);
        mbar_wait(bar + FB_RDY + 8 * h, 0);
        if (tid == 256) KMARK(17);
        #pragma unroll
        for (int q = 0; q < FIN_SPLIT; q++) {
            if (q != rank) {
                const uint32_t dst = mapa(red + (rank - (rank > q ? 1 : 0)) * 4096 + t128 * 16, q), rb = mapa(bar + FB_RED + 8 * h, q);
                #pragma unroll
                for (int j = 0; j < 2; j++)
                    asm volatile("st.async.weak.shared::cluster.mbarrier::complete_tx::bytes.v4.f32 [%0], {%1,%2,%3,%4}, [%5];"
                                 ::"r"(dst + j * 2048), "f"(acc[8 * q + 4 * j]), "f"(acc[8 * q + 4 * j + 1]),
                                   "f"(acc[8 * q + 4 * j + 2]), "f"(acc[8 * q + 4 * j + 3]), "r"(rb) : "memory");
            }
        }
        float o[8];
        #pragma unroll
        for (int q = 0; q < FIN_SPLIT; q++)
            if (q == rank) {
                #pragma unroll
                for (int e = 0; e < 8; e++) o[e] = acc[8 * q + e];
            }
        mbar_wait(bar + FB_RED + 8 * h, 0);
        if (tid == 256) KMARK(18);
        if (tid == 128) KMARK(20);
        #pragma unroll
        for (int sl = 0; sl < FIN_SPLIT - 1; sl++) {
            #pragma unroll
            for (int j = 0; j < 2; j++) {
                const uint4 v = lds128(red + sl * 4096 + j * 2048 + t128 * 16);
                o[4 * j] += __uint_as_float(v.x); o[4 * j + 1] += __uint_as_float(v.y);
                o[4 * j + 2] += __uint_as_float(v.z); o[4 * j + 3] += __uint_as_float(v.w);
            }
        }
        if (h == 0) ready(1);
        __nv_bfloat16* dst = p.out + (size_t)(p.mt * BM + h * 64 + wi * 16 + (lane >> 2)) * (2 * DM) + nt * 128 + rank * 16 + (lane & 3) * 2;
        #pragma unroll
        for (int j = 0; j < 2; j++) {
            *reinterpret_cast<uint32_t*>(dst + j * 8) = pack_bf16(o[4 * j], o[4 * j + 1]);
            *reinterpret_cast<uint32_t*>(dst + (size_t)8 * (2 * DM) + j * 8) = pack_bf16(o[4 * j + 2], o[4 * j + 3]);
        }
        if (t128 == 0) KEXIT(5);
    }
}

#define POLL_DELAY 2
#define FETCH_DELAY 450
#define AT_PF 7
#define AT_FIRST 4
#define WO_PF 12
#define WO_PFA 6
#define WO_PFB_DELAY 60
#define V_EARLY 6
constexpr int REC_THREADS = 256;
constexpr uint32_t POLL_LIMIT = 1u << 16;
constexpr int NREG = 24;
__host__ __device__ constexpr int reg_idx(int j) { return ((j & 3) - 1) * 8 + (j >> 2); }
constexpr int SM_WQ = 0;
constexpr int SM_WO = 65536;
constexpr int SM_X = SM_WO + 11 * 8192;
constexpr int SM_PARK0 = SM_X, SM_PARK1 = SM_X + 8192;
constexpr int SM_MEM = SM_X + 4 * 4096;
constexpr int SM_RED = SM_X + 8 * 4096;
constexpr int SM_V = SM_X + 12 * 4096;
constexpr int SM_K = SM_X + 14 * 4096;
constexpr int SM_QS = SM_X + 15 * 4096;
constexpr int SM_QK = SM_X + 65536;
constexpr int SM_SP = SM_QK + 2048;
constexpr int SM_VM = SM_SP + 2560;
constexpr int SM_O = SM_VM + 2048;
constexpr int SM_SUM = SM_O + 2048;
constexpr int SM_TBL = SM_SUM + 128;
constexpr int SM_BAR = SM_TBL + 512;
constexpr int SM_STAMP = SM_BAR + 224;
constexpr int REC_SMEM = SM_STAMP;
static_assert(REC_SMEM <= 232448, "shared memory");
enum { BAR_V = 0, BAR_X = 8, BAR_P0 = 16, BAR_WQ = 40, BAR_WO = 48, BAR_XG = 56, BAR_F0 = 88, BAR_F3 = 96, BAR_VF = 104,
       BAR_M = 112, BAR_GO = 144, BAR_PK = 152, BAR_VM = 160, BAR_SELF = 168, BAR_TPUB = 176, BAR_MIN = 176, BAR_PUB = 192 };

template <int V> struct IntC { static constexpr int value = V; };
template <int I, int N, typename F> __device__ __forceinline__ void sfor(F&& f) {
    if constexpr (I < N) { f(IntC<I>{}); sfor<I + 1, N>(f); }
}

struct RecParams {
    CUtensorMap tmW[3];
    CUtensorMap tmWo;
    CUtensorMap tmX;
    const __nv_bfloat16* mem0;
    __nv_bfloat16* qkv_tok;
    __nv_bfloat16* kv_mem;
    uint8_t* xchg;
    uint32_t* flags;
    uint32_t one[2];
    uint32_t* arrivals;
};

__device__ __forceinline__ void mma_a(float* d, const uint32_t* a, uint32_t b0, uint32_t b1) {
    mma16816(d, a[0], a[1], a[2], a[3], b0, b1);
}
__device__ __forceinline__ void ldsm4(uint32_t addr, uint32_t* r) { ldsm_x4(addr, r[0], r[1], r[2], r[3]); }
__device__ __forceinline__ void ldsm4t(uint32_t addr, uint32_t* r) { ldsm_x4_t(addr, r[0], r[1], r[2], r[3]); }
template <int OFF> __device__ __forceinline__ void repoll_v2(uint2& v, const uint8_t* p) {
    asm volatile("{\n.reg .pred q;\nsetp.eq.u32 q, %1, 0xFFFFFFFF;\n@q ld.relaxed.gpu.global.v2.b32 {%0,%1}, [%2+%3];\n}"
                 : "+r"(v.x), "+r"(v.y) : "l"(p), "n"(OFF) : "memory");
}
__device__ __forceinline__ uint32_t max3(uint32_t a, uint32_t b, uint32_t c) { return max(max(a, b), c); }
__device__ __forceinline__ uint32_t pub_slot(int s) { return (s & 1) * XCHG_SLOT + ((s >> 1) & 1) * PUB_BYTES; }

__device__ __forceinline__ uint8_t* xaddr(uint32_t lo, uint32_t hi) {
    uint64_t a;
    asm("mov.b64 %0, {%1, %2};" : "=l"(a) : "r"(lo), "r"(hi));
    return reinterpret_cast<uint8_t*>(a);
}
template <int N> __device__ __forceinline__ uint32_t delay_zero(uint32_t a) {
    uint32_t x = a;
    #pragma unroll
    for (int i = 0; i < N; i++) x = lds32_volatile(x);
    return x - a;
}
__device__ __forceinline__ uint32_t fresh(uint32_t x) { asm volatile("" : "+r"(x)); return x; }

template <int NT> __device__ __forceinline__ uint32_t wo_addr(uint32_t ao, uint32_t a3, int n) {
    return (n % NT == 2 ? a3 : ao + (n % NT) * 32768) + (n / NT) * 1024;
}
template <int NT, int PF>
__device__ __forceinline__ void wo_phase(uint32_t (&st)[8 * NT][4], uint32_t ao, uint32_t a3, uint32_t l16, uint32_t tbl, uint32_t sums,
                                         uint32_t slot, uint32_t xhi, uint32_t third, uint32_t xbar, uint32_t xpar, bool& x_ok) {
    constexpr int AHEAD = PF > 0 ? PF - NT : 10;
    uint32_t of[4][4];
    uint2 sm;
    uint4 t;
    ldsm4t(l16 + SM_O, of[0]);
    #pragma unroll
    for (int n = PF; n < AHEAD; n++) {
        ldsm4t(wo_addr<NT>(ao, a3, n), st[n]);
        if (n == 2 * NT - 1) ldsm4t(l16 + SM_O + 512, of[1]);
    }
    if (PF >= 2 * NT) ldsm4t(l16 + SM_O + 512, of[1]);
    float acc[NT][4];
    #pragma unroll
    for (int i = 0; i < NT; i++) { acc[i][0] = acc[i][1] = acc[i][2] = acc[i][3] = 0.f; }
    #pragma unroll
    for (int kk = 0; kk < 8; kk++) {
        #pragma unroll
        for (int i = 0; i < NT; i++) {
            const int n = kk * NT + i;
            mma_a(acc[i], st[n], of[kk >> 1][(kk & 1) * 2], of[kk >> 1][(kk & 1) * 2 + 1]);
            if (n + AHEAD >= PF && n + AHEAD < 8 * NT) ldsm4t(wo_addr<NT>(ao, a3, n + AHEAD), st[n + AHEAD]);
        }
        if (kk == 1 || kk == 3) ldsm4t(l16 + SM_O + ((kk >> 1) + 2) * 512, of[(kk >> 1) + 2]);
        if (kk == (NT == 3 ? 5 : 4)) {
            const uint32_t x = fresh(l16);
            sm = lds64(sums + ((x >> 1) & 0x18));
            t = lds128(tbl + ((x >> 3) & 0x30));
            x_ok = mbar_test_wait(xbar, xpar);
        }
    }
    const float i0 = rcp(__uint_as_float(sm.x)), i1 = rcp(__uint_as_float(sm.y));
    const uint32_t d = slot + ((fresh(l16) >> 1) & 0x38);
    const uint32_t pl[3] = {t.x + d, t.y + d, t.z + d};
    #pragma unroll
    for (int i = 0; i < NT; i++)
        asm volatile("{\n.reg .pred p;\nsetp.ne.u32 p, %3, 0;\n@p st.relaxed.gpu.global.v2.b32 [%0], {%1,%2};\n}"
                     ::"l"(xaddr(pl[i], xhi)), "r"(pack_bf16(acc[i][0] * i0, acc[i][1] * i1)), "r"(pack_bf16(acc[i][2] * i0, acc[i][3] * i1)),
                       "r"(i < 2 ? 1u : third) : "memory");
}

constexpr uint32_t SMEM_ORIGIN = 1024;
constexpr uint64_t DESC_BASE = (1ull << 16) | (0x40000040ull << 32);
template <int OFFB, int SCALE_D>
__device__ __forceinline__ void wgmma_n32_rs(float (&d)[16], const uint32_t* a, uint32_t one) {
    asm volatile(
        "{\n.reg .b64 db;\nmad.wide.u32 db, %20, %21, %22;\n"
        "wgmma.mma_async.sync.aligned.m64n32k16.f32.bf16.bf16 {%0,%1,%2,%3,%4,%5,%6,%7,%8,%9,%10,%11,%12,%13,%14,%15}, "
        "{%16,%17,%18,%19}, db, %23, 1, 1, 0;\n}"
        : "+f"(d[0]), "+f"(d[1]), "+f"(d[2]), "+f"(d[3]), "+f"(d[4]), "+f"(d[5]), "+f"(d[6]), "+f"(d[7]),
          "+f"(d[8]), "+f"(d[9]), "+f"(d[10]), "+f"(d[11]), "+f"(d[12]), "+f"(d[13]), "+f"(d[14]), "+f"(d[15])
        : "r"(a[0]), "r"(a[1]), "r"(a[2]), "r"(a[3]), "r"(one), "n"((SMEM_ORIGIN + OFFB) >> 4), "l"(DESC_BASE), "n"(SCALE_D));
}
template <int OFFA, int OFFB, int SCALE_D>
__device__ __forceinline__ void wgmma_n32_ss(float (&d)[16], uint32_t one) {
    asm volatile(
        "{\n.reg .b64 da, db;\nmad.wide.u32 da, %16, %17, %19;\nmad.wide.u32 db, %16, %18, %19;\n"
        "wgmma.mma_async.sync.aligned.m64n32k16.f32.bf16.bf16 {%0,%1,%2,%3,%4,%5,%6,%7,%8,%9,%10,%11,%12,%13,%14,%15}, "
        "da, db, %20, 1, 1, 1, 0;\n}"
        : "+f"(d[0]), "+f"(d[1]), "+f"(d[2]), "+f"(d[3]), "+f"(d[4]), "+f"(d[5]), "+f"(d[6]), "+f"(d[7]),
          "+f"(d[8]), "+f"(d[9]), "+f"(d[10]), "+f"(d[11]), "+f"(d[12]), "+f"(d[13]), "+f"(d[14]), "+f"(d[15])
        : "r"(one), "n"((SMEM_ORIGIN + OFFA) >> 4), "n"((SMEM_ORIGIN + OFFB) >> 4), "l"(DESC_BASE), "n"(SCALE_D));
}
template <int WG, int J0, int J1, int I, bool ACC, bool FENCE = true>
__device__ __forceinline__ void token_mma(float (&ta)[2][16], const uint32_t (&wr)[NREG][2][4], uint32_t one) {
    if (FENCE) asm volatile("wgmma.fence.sync.aligned;" ::: "memory");
    sfor<J0, J1>([&](auto J) {
        constexpr int j = J.value, c = j >> 2, offb = SM_X + WG * 32768 + c * 4096 + (j & 3) * 32, sc = (ACC || j != J0) ? 1 : 0;
        if constexpr ((j & 3) != 0) wgmma_n32_rs<offb, sc>(ta[I], wr[reg_idx(j)][I], one);
        else if constexpr (WG == 0 || (I == 1 && c >= 4)) wgmma_n32_ss<SM_WQ + WG * 32768 + I * 16384 + c * 2048, offb, sc>(ta[I], one);
        constexpr int m = I ? c : c - 4;
        if constexpr (WG == 0 && (j & 3) == 1 && m >= 0)
            wgmma_n32_ss<SM_WQ + 32768 + (1 - I) * 16384 + m * 2048, SM_X + 32768 + m * 4096, 1>(ta[I], one);
    });
    asm volatile("wgmma.commit_group.sync.aligned;" ::: "memory");
}
__device__ __forceinline__ void warp_arrive(uint32_t bar) {
    __syncwarp();
    if (elect_one()) mbar_arrive(bar);
}
__device__ __forceinline__ void remote_arrive(uint32_t bar, uint32_t rank) {
    asm volatile("mbarrier.arrive.relaxed.cluster.shared::cluster.b64 _, [%0];" ::"r"(mapa(bar, rank)) : "memory");
}
__device__ __forceinline__ void x_load(const RecParams& p, uint32_t sb, int sg, int g) {
    tma_load_3d_mc(sb + SM_X + g * 16384, &p.tmX, 0, sg * SEG, g * 4, sb + SM_BAR + BAR_XG + 8 * g, (uint16_t)7);
}

__device__ __forceinline__ void rec_steps(const RecParams& p, const uint32_t (&wr)[NREG][2][4], const uint32_t sb, const int warp,
                                          const int cta, const int head, const int rank) {
    const int wq = warp & 3, wg = warp >> 2;
    const uint32_t bar = sb + SM_BAR;
    const uint32_t xhi = (uint32_t)((uint64_t)p.xchg >> 32);
    const float sl2 = 0.08838834764831845f * 1.4426950408889634f;
    const bool has_unit = warp >= 5 && (warp < 7 || cta < 64);
    const bool qk = rank < 2;
    const uint32_t pa = rank == 2 ? 0 : rank + 1, pb = rank == 0 ? 2 : rank - 1;
    const uint32_t tbl = sb + SM_TBL + warp * 64;
    const bool att = (warp & 6) == 2;
    const int stile = warp < 5 ? warp : warp - 3;

    const uint32_t u_xa = uniform(sb + (qk ? SM_SP + rank * 1280 + stile * 256 : SM_VM + warp * 256));
    const uint32_t u_key = uniform(!qk || att || warp == 7 ? 0 : sb + (warp == 4 ? SM_QK + 1024 : SM_K + stile * 1024));
    const uint32_t u_bx = uniform(bar + (qk ? BAR_X : BAR_VM)), u_bra = uniform(mapa(u_bx, pa)), u_brb = uniform(mapa(u_bx, pb));
    const uint32_t u_src = uniform(lds32_volatile(tbl + 44));
    const uint32_t u_role = uniform((has_unit ? 1 : 0) | (att ? 2 : 0) | (wg == 1 || qk ? 4 : 0) | (rank != 1 && warp == 0 ? 8 : 0) | (rank != 0 && warp == 1 ? 16 : 0) |
                                    (warp == 5 || warp == 6 ? 32 : 0));
    uint32_t l16, aq, ao;
    {
        const int lane = threadIdx.x & 31, mi = lane >> 3, r8 = lane & 7, r16 = (mi >> 1) * 8 + r8;
        l16 = opaque(sb + lane * 16);
        aq = opaque(sb + SM_WQ + wg * 32768 + r16 * 128 + (((wq * 2 + (mi & 1)) ^ r8) << 4));
        ao = opaque(sb + SM_WO + (warp >> 1) * 8192 + r16 * 64 + ((((warp & 1) * 2 + (mi & 1)) ^ ((r8 >> 1) & 3)) << 4));
    }

    uint32_t mphase = 0;
    bool x0_ok = false;
    #pragma unroll 1
    for (int s = 0;; s++) {
        const uint32_t par = s & 1;
        uint32_t at[16][4];
        auto at_early = [](int i) { return i < 2 || ((i & 1) == 1 && (i >> 1) < AT_PF - 1); };
        auto at_prefetch = [&](bool first) {
            #pragma unroll
            for (int i = 0; i < 16; i++)
                if (at_early(i) && first == ((i & 1) == 1 && (i >> 1) < AT_FIRST)) ldsm4t(aq + (i & 1) * 16384 + (i >> 1) * 2048, at[i]);
        };
        auto att_stores = [&](bool tiles, bool rows) {
            if (warp == 4) {
                if (rows && !qk) mbar_wait_bounded(bar + BAR_VM, par);
                asm volatile("fence.proxy.async.shared::cta;" ::: "memory");
                if (elect_one()) {
                    if (tiles) {
                        __nv_bfloat16* dst = p.qkv_tok + ((size_t)s * NH + head) * (SEG * DH);
                        constexpr size_t MAT = (size_t)NSEG * NH * SEG * DH;
                        bulk_store(dst + (qk ? rank * (SEG * 64) : 2 * MAT), sb + (qk ? SM_QS : SM_V), 4096);
                        bulk_store(dst + (qk ? MAT + rank * (SEG * 64) : 2 * MAT + SEG * 64), sb + (qk ? SM_K : SM_V + 4096), 4096);
                    }
                    if (rows)
                        bulk_store(p.kv_mem + ((size_t)s * NH + head) * (MROWS * DH) + (qk ? rank * (MROWS * 64) : NSEG * NH * MROWS * DH),
                                   sb + (qk ? SM_QK + 1024 : SM_VM), qk ? 1024 : 2048);
                    bulk_commit();
                }
            }
        };
        uint32_t b[16][4];
        if (wg == 0) {
            float ta[2][16];
            if (!x0_ok) mbar_wait_bounded(bar + BAR_XG, par);
            STAMP(6);
            auto park = [&](int i, uint32_t dst) {
                #pragma unroll
                for (int e = 0; e < 16; e++) asm volatile("" : "+f"(ta[i][e]));
                #pragma unroll
                for (int j = 0; j < 4; j++)
                    sts128(l16 + dst + j * 2048 + wq * 512, __float_as_uint(ta[i][4 * j]), __float_as_uint(ta[i][4 * j + 1]),
                           __float_as_uint(ta[i][4 * j + 2]), __float_as_uint(ta[i][4 * j + 3]));
            };
            token_mma<0, 0, 16, 0, false>(ta, wr, 1);
            mbar_wait_bounded(bar + BAR_XG + 8, par);
            mbar_wait_bounded(bar + BAR_XG + 16, par);
            at_prefetch(true);
            token_mma<0, 16, 32, 0, true>(ta, wr, p.one[1]);
            token_mma<0, 0, 12, 1, false, false>(ta, wr, p.one[0]);
            token_mma<0, 12, 16, 1, true, false>(ta, wr, p.one[0]);
            mbar_wait_bounded(bar + BAR_XG + 24, par);
            asm volatile("wgmma.wait_group.sync.aligned 1;" ::: "memory");
            park(0, SM_PARK0);
            token_mma<0, 16, 32, 1, true>(ta, wr, 1);
            warp_arrive(bar + BAR_GO);
            mbar_wait_bounded(bar + BAR_PUB, par);
            const uint4 tp = lds128(bar + BAR_TPUB);
            const uint32_t tgo = tp.y + max(max((int)(tp.z - tp.y), (int)(tp.w - tp.y)), 0) + FETCH_DELAY;
            asm volatile("wgmma.wait_group.sync.aligned 0;" ::: "memory");
            park(1, SM_PARK1);
            warp_arrive(bar + BAR_PK);
            const uint8_t* src = xaddr(u_src + pub_slot(s), xhi);
            auto fetch = [&]() {
                if (elect_one()) {
                    mbar_arrive_expect_tx(bar + BAR_M + 8 * wq, 4096);
                    bulk_load(sb + SM_MEM + wq * 4096, src, 4096, bar + BAR_M + 8 * wq);
                }
            };
            while ((int)(clock_lo() - tgo) < 0) {}
            fetch();
            STAMP(12);
            if (warp == 0 && elect_one()) {
                if (qk) mbar_arrive_expect_tx(bar + BAR_V, 8192);
                mbar_arrive_expect_tx(bar + BAR_X, qk ? 1280 : 2560);
                mbar_arrive_expect_tx(bar + BAR_VM, qk ? 2048 : 0);
            }
            at_prefetch(false);
            const uint32_t x = fresh(l16) - sb;
            const uint32_t ca = sb + SM_MEM + wq * 4096 + x * 2 + ((x >> 4) & 0x1C);
            #pragma unroll 1
            for (uint32_t n = 0; n < POLL_LIMIT; n++) {
                mbar_wait_bounded(bar + BAR_M + 8 * wq, mphase);
                mphase ^= 1;
                const uint32_t c0 = lds32_volatile(ca), c1 = lds32_volatile(ca + 1024), c2 = lds32_volatile(ca + 2048), c3 = lds32_volatile(ca + 3072);
                if (!__any_sync(~0u, max(max3(c0, c1, c2), c3) == SENT)) break;
                fetch();
            }
            STAMP(0);
            named_bar_sync(10, 128);
            #pragma unroll
            for (int u = 0; u < 2; u++) ldsm4t(l16 + SM_MEM + u * 512, b[u]);
            named_bar_sync(0, REC_THREADS);
            if (u_role & 8) {
                if (!qk) asm volatile("fence.proxy.async.shared::cta;" ::: "memory");
                mbar_wait_bounded(bar + (qk ? BAR_F0 : BAR_VF), par);
                if (s < NSEG - 1 && elect_one()) {
                    if (qk) {
                        x_load(p, sb, s + 1, 0);
                    } else {
                        #pragma unroll
                        for (int r = 0; r < 2; r++)
                            asm volatile("cp.async.bulk.shared::cluster.shared::cta.mbarrier::complete_tx::bytes [%0], [%1], %2, [%3];"
                                         ::"r"(mapa(sb + SM_V, r)), "r"(sb + SM_V), "r"(8192), "r"(mapa(bar + BAR_V, r)) : "memory");
                    }
                }
            }
        } else {
            at_prefetch(true);
            if (s > 0) {
                if (u_role & 1) {
                    const uint32_t ln = (fresh(l16) >> 4) & 31;
                    const uint32_t ibl = lds32_volatile(tbl + 12) + (par ^ 1) * XCHG_SLOT + ln * 8;
                    const uint32_t publ = lds32_volatile(tbl + 28) + pub_slot(s) + (ln & 16) * 256 + (ln & 8) * 16 + (ln & 7) * 4;
                    const bool odd = ln & 8;
                    const uint8_t* ib = xaddr(ibl + delay_zero<POLL_DELAY>(bar + BAR_SELF), xhi);
                    STAMP(8);
                    uint2 v[8];
                    #pragma unroll
                    for (int i = 0; i < 8; i++) v[i] = make_uint2(SENT, SENT);
                    #pragma unroll 1
                    for (uint32_t n = 0; n < POLL_LIMIT; n++) {
                        sfor<0, 8>([&](auto I) { repoll_v2<I.value * 256>(v[I.value], ib); });
                        const uint32_t mx = max(max3(v[0].y, v[1].y, v[2].y), max3(max3(v[3].y, v[4].y, v[5].y), v[6].y, v[7].y));
                        if (!__any_sync(~0u, mx == SENT)) break;
                    }
                    STAMP(9);
                    const float a0 = ((bf16_lo(v[0].x) + bf16_lo(v[1].x)) + (bf16_lo(v[2].x) + bf16_lo(v[3].x))) +
                                     ((bf16_lo(v[4].x) + bf16_lo(v[5].x)) + (bf16_lo(v[6].x) + bf16_lo(v[7].x)));
                    const float a1 = ((bf16_hi(v[0].x) + bf16_hi(v[1].x)) + (bf16_hi(v[2].x) + bf16_hi(v[3].x))) +
                                     ((bf16_hi(v[4].x) + bf16_hi(v[5].x)) + (bf16_hi(v[6].x) + bf16_hi(v[7].x)));
                    const float a2 = ((bf16_lo(v[0].y) + bf16_lo(v[1].y)) + (bf16_lo(v[2].y) + bf16_lo(v[3].y))) +
                                     ((bf16_lo(v[4].y) + bf16_lo(v[5].y)) + (bf16_lo(v[6].y) + bf16_lo(v[7].y)));
                    const float a3 = ((bf16_hi(v[0].y) + bf16_hi(v[1].y)) + (bf16_hi(v[2].y) + bf16_hi(v[3].y))) +
                                     ((bf16_hi(v[4].y) + bf16_hi(v[5].y)) + (bf16_hi(v[6].y) + bf16_hi(v[7].y)));
                    float k0 = odd ? a2 : a0, k1 = odd ? a3 : a1;
                    k0 += __shfl_xor_sync(~0u, odd ? a0 : a2, 8);
                    k1 += __shfl_xor_sync(~0u, odd ? a1 : a3, 8);
                    k0 += __shfl_xor_sync(~0u, k0, 16);
                    k1 += __shfl_xor_sync(~0u, k1, 16);
                    st_relaxed_b32(xaddr(publ, xhi), pack_bf16(k0, k1));
                    STAMP(11);
                } else if (warp == 4) {
                    bulk_wait_read_all();
                    if (elect_one()) remote_arrive(bar + BAR_F3, 2);
                    if (!qk) {
                        mbar_wait_bounded(bar + BAR_F3, par ^ 1);
                        if (elect_one()) x_load(p, sb, s, 3);
                    }
                    if (elect_one()) {
                        bulk_wait_all();
                        signal_bulk(p.flags + F_PROGRESS + s - 1);
                    }
                    __syncwarp();
                    STAMP(10);
                }
            }
            float ta[2][16];
            uint32_t w[8];
            auto unpark = [&](int i, uint32_t src) {
                mbar_wait_bounded(bar + (i ? BAR_GO : BAR_PK), par);
                #pragma unroll
                for (int j = 0; j < 4; j++) {
                    const uint4 v = lds128(l16 + src + j * 2048 + wq * 512);
                    ta[i][4 * j] = __uint_as_float(v.x); ta[i][4 * j + 1] = __uint_as_float(v.y);
                    ta[i][4 * j + 2] = __uint_as_float(v.z); ta[i][4 * j + 3] = __uint_as_float(v.w);
                }
            };
            sts32(bar + BAR_TPUB + 4 * wq, clock32());
            if (warp != 4) warp_arrive(bar + BAR_PUB);
            unpark(1, SM_PARK0);
            STAMP(6);
            token_mma<1, 0, 16, 1, true>(ta, wr, 1);
            unpark(0, SM_PARK1);
            token_mma<1, 16, 32, 1, true>(ta, wr, 1);
            token_mma<1, 16, 32, 0, true>(ta, wr, 1);
            token_mma<1, 0, 16, 0, true, false>(ta, wr, 1);
            auto put_tile = [&](int m, const uint32_t (&q)[8]) {
                #pragma unroll
                for (int h = 0; h < 2; h++) {
                    if (qk) asm volatile("stmatrix.sync.aligned.m8n8.x4.trans.shared.b16 [%0], {%1,%2,%3,%4};"
                                         ::"r"(aq - (SM_WQ + 32768) + (m ? SM_K : SM_QS) + h * 2048), "r"(q[4 * h]), "r"(q[4 * h + 1]),
                                           "r"(q[4 * h + 2]), "r"(q[4 * h + 3]) : "memory");
                    else sts128(l16 + SM_V + wq * 2048 + m * 1024 + h * 512, q[4 * h], q[4 * h + 1], q[4 * h + 2], q[4 * h + 3]);
                }
            };
            auto pack_tile = [&](int i) {
                #pragma unroll
                for (int e = 0; e < 16; e++) asm volatile("" : "+f"(ta[i][e]));
                #pragma unroll
                for (int j = 0; j < 8; j++) w[j] = pack_bf16(ta[i][2 * j], ta[i][2 * j + 1]);
            };
            asm volatile("wgmma.wait_group.sync.aligned 2;" ::: "memory");
            pack_tile(1);
            at_prefetch(false);
            asm volatile("wgmma.wait_group.sync.aligned 1;" ::: "memory");
            if (u_role & 32) {
                const uint32_t a_free = lds32_volatile(tbl + 60);
                if (elect_one()) asm volatile("mbarrier.arrive.relaxed.cluster.shared::cluster.b64 _, [%0];" ::"r"(a_free) : "memory");
            }
            put_tile(0, w);
            asm volatile("wgmma.wait_group.sync.aligned 0;" ::: "memory");
            pack_tile(0);
            put_tile(1, w);
            STAMP(0);
            named_bar_sync(0, REC_THREADS);
            #pragma unroll
            for (int u = 0; u < 2; u++) ldsm4t(l16 + SM_MEM + 8192 + u * 512, b[u]);
            if (s == NSEG - 1) att_stores(true, false);
            STAMP(14);
        }
        const uint32_t mb = l16 + SM_MEM + wg * 8192;
        float acc[2][2][4];
        {
            #pragma unroll
            for (int i = 0; i < 4; i++)
                if (!at_early(i)) ldsm4t(aq + (i & 1) * 16384 + (i >> 1) * 2048, at[i]);
            STAMPD(1, b[0][0]);
            #pragma unroll
            for (int i = 0; i < 4; i++) { for (int e = 0; e < 4; e++) acc[i >> 1][i & 1][e] = 0.f; }
            #pragma unroll
            for (int u = 0; u < 16; u++) {
                #pragma unroll
                for (int h = 0; h < 2; h++) {
                    const int j = 2 * u + h;
                    #pragma unroll
                    for (int m = 0; m < 2; m++) {
                        if ((j & 3) == 0) mma_a(acc[h][m], at[(j >> 2) * 2 + m], b[u][2 * h], b[u][2 * h + 1]);
                        else mma_a(acc[h][m], wr[reg_idx(j)][m], b[u][2 * h], b[u][2 * h + 1]);
                    }
                }
                #pragma unroll
                for (int v = u + 2 + (u > 2); v <= u + 2 + (u >= 2); v++)
                    if (v < 16) ldsm4t(mb + v * 512, b[v]);
                #pragma unroll
                for (int i = u + 4 + 2 * (u > 6); i <= u + 4 + 2 * (u >= 6); i++)
                    if (i < 16 && !at_early(i)) ldsm4t(aq + (i & 1) * 16384 + (i >> 1) * 2048, at[i]);
            }
        }
        sts128(l16 + SM_RED + warp * 512, __float_as_uint(acc[0][1][0] + acc[1][1][0]), __float_as_uint(acc[0][1][1] + acc[1][1][1]),
               __float_as_uint(acc[0][1][2] + acc[1][1][2]), __float_as_uint(acc[0][1][3] + acc[1][1][3]));
        #pragma unroll
        for (int e = 0; e < 4; e++) acc[0][0][e] += acc[1][0][e];
        const uint32_t x16 = fresh(l16);
        const uint32_t sa = fresh((x16 & 0x70) * 8 + ((((x16 >> 3) & 0x30) ^ x16) & 0x70));
        const uint32_t sq = fresh(sa ^ ((((x16 >> 7) ^ (x16 >> 8)) & 1) * 0x30));
        const uint32_t x8 = (x16 & 0x1F0) >> 1;
        const uint32_t ast = fresh(fresh(aq) - wg * (32768 - 1024)) + (SM_QK - SM_WQ);
        const uint32_t xra = fresh(x8 + __byte_perm(u_xa, u_bra, 0x7210)), xrb = fresh(x8 + __byte_perm(u_xa, u_brb, 0x7210));
        STAMP(2);
        named_bar_sync(1 + wq, 64);
        uint32_t p0, p1;
        {
            const uint4 v = lds128(l16 + SM_RED + (warp ^ 4) * 512);
            p0 = pack_bf16(acc[0][0][0] + __uint_as_float(v.x), acc[0][0][1] + __uint_as_float(v.y));
            p1 = pack_bf16(acc[0][0][2] + __uint_as_float(v.z), acc[0][0][3] + __uint_as_float(v.w));
        }
        auto send = [&](uint32_t y0, uint32_t y1) {
            st_async_v2(xra, y0, y1, u_bra);
            st_async_v2(xrb, y0, y1, u_brb);
            sts64(x8 + u_xa, y0, y1);
            warp_arrive(u_bx);
        };
        if (qk) {
            asm volatile("stmatrix.sync.aligned.m8n8.x2.trans.shared.b16 [%0], {%1,%2};" ::"r"(ast), "r"(p0), "r"(p1) : "memory");
            named_bar_sync(5, REC_THREADS);
            if (u_key != 0) {
                uint32_t qa[2][4], kf[2][4];
                ldsm4(sq + sb + SM_QK, qa[0]);
                ldsm4(sa + u_key, kf[0]);
                ldsm4((sq ^ 64) + sb + SM_QK, qa[1]);
                ldsm4((sa ^ 64) + u_key, kf[1]);
                float se[4] = {0.f, 0.f, 0.f, 0.f}, so[4] = {0.f, 0.f, 0.f, 0.f};
                #pragma unroll
                for (int u = 0; u < 2; u++) {
                    mma_a(se, qa[u], kf[u][0], kf[u][1]);
                    mma_a(so, qa[u], kf[u][2], kf[u][3]);
                }
                send(__float_as_uint(se[0] + so[2]), __float_as_uint(se[1] + so[3]));
            }
        } else {
            send(p0, p1);
        }
        STAMP(3);
        const uint32_t lane = (fresh(l16) >> 4) & 31;
        if (((s + 1) & 62) == 0) {
            if (s == NSEG - 1) { att_stores(false, true); break; }
            mbar_wait_bounded(bar + BAR_WO, 0);
            pdl_launch_dependents();
            PSTAMP(8);
        }
        const uint32_t slot = par * XCHG_SLOT;
        if (u_role & 2) {
            if (qk) mbar_wait_bounded(bar + BAR_V, par);
            uint32_t vt[2][4][4];
            auto v_load = [&](int i0, int i1) {
                #pragma unroll
                for (int i = i0; i < i1; i++) {
                    const uint4 v = lds128(l16 + SM_V + (warp & 1) * 1024 + (i & 3) * 2048 + (i >> 2) * 512);
                    vt[i >> 2][i & 3][0] = v.x; vt[i >> 2][i & 3][1] = v.y; vt[i >> 2][i & 3][2] = v.z; vt[i >> 2][i & 3][3] = v.w;
                }
            };
            v_load(0, V_EARLY);
            const uint32_t l8 = fresh(sb + lane * 8);
            mbar_wait_bounded(bar + BAR_X, par);
            STAMP(4);
            float sv[10];
            #pragma unroll
            for (int j = 0; j < 5; j++) {
                const uint2 a = lds64(l8 + SM_SP + j * 256), b = lds64(l8 + SM_SP + 1280 + j * 256);
                sv[2 * j] = __uint_as_float(a.x) + __uint_as_float(b.x);
                sv[2 * j + 1] = __uint_as_float(a.y) + __uint_as_float(b.y);
            }
            float mx = fmaxf(fmaxf(fmaxf(sv[0], sv[1]), fmaxf(sv[2], sv[3])), fmaxf(fmaxf(sv[4], sv[5]), fmaxf(sv[6], sv[7])));
            mx = fmaxf(mx, fmaxf(sv[8], sv[9]));
            const float m1 = __shfl_xor_sync(~0u, mx, 1), m2 = __shfl_xor_sync(~0u, mx, 2), m3 = __shfl_xor_sync(~0u, mx, 3);
            __syncwarp();
            v_load(V_EARLY, 8);
            const bool vm_ok = mbar_test_wait(bar + BAR_VM, par);
            mx = fmaxf(fmaxf(mx, m1), fmaxf(m2, m3));
            const float mo = mx * sl2;
            #pragma unroll
            for (int j = 0; j < 10; j++) sv[j] = ex2(fmaf(sv[j], sl2, -mo));
            const uint32_t e0 = pack_bf16(sv[0], sv[1]), e1 = pack_bf16(sv[2], sv[3]);
            const uint32_t e2 = pack_bf16(sv[4], sv[5]), e3 = pack_bf16(sv[6], sv[7]), em = pack_bf16(sv[8], sv[9]);
            float o[4][4];
            #pragma unroll
            for (int i = 0; i < 4; i++) {
                o[i][0] = o[i][1] = o[i][2] = o[i][3] = 0.f;
                mma_a(o[i], vt[0][i], e0, e1);
            }
            const float sum = (((sv[0] + sv[1]) + (sv[2] + sv[3])) + ((sv[4] + sv[5]) + (sv[6] + sv[7]))) + (sv[8] + sv[9]);
            if (!vm_ok) mbar_wait_bounded(bar + BAR_VM, par);
            uint2 vm[4];
            #pragma unroll
            for (int i = 0; i < 4; i++) {
                vm[i] = lds64(l8 + SM_VM + (warp & 1) * 1024 + i * 256);
                mma_a(o[i], vt[1][i], e2, e3);
            }
            #pragma unroll
            for (int i = 0; i < 4; i++) mma1688(o[i], vm[i].x, vm[i].y, em);
            {
                const float s1 = __shfl_xor_sync(~0u, sum, 1), s2 = __shfl_xor_sync(~0u, sum, 2), s3 = __shfl_xor_sync(~0u, sum, 3);
                sts32(sb + SM_SUM + (lane & 28), __float_as_uint((sum + s1) + (s2 + s3)));
            }
            #pragma unroll
            for (int i = 0; i < 4; i += 2)
                stsm_x4(l16 + SM_O + (warp & 1) * 1024 + i * 256, pack_bf16(o[i][0], o[i][1]), pack_bf16(o[i][2], o[i][3]),
                        pack_bf16(o[i + 1][0], o[i + 1][1]), pack_bf16(o[i + 1][2], o[i + 1][3]));
            STAMP(5);
            uint32_t st[16][4];
            named_bar_sync(6, REC_THREADS);
            wo_phase<2, 0>(st, ao, 0, l16, tbl, sb + SM_SUM, slot, xhi, 0, bar + BAR_XG, par ^ 1, x0_ok);
        } else {
            const uint32_t a3 = fresh(ao) + (wg == 0 ? 10 : 6) * 8192;
            uint32_t st[24][4];
            #pragma unroll
            for (int n = 0; n < WO_PFA; n++) ldsm4t(wo_addr<3>(ao, a3, n), st[n]);
            if (u_role & 1) {
                const uint32_t ln = (fresh(l16) >> 4) & 31;
                uint8_t* ib = xaddr(lds32_volatile(tbl + 12) + (par ^ 1) * XCHG_SLOT + ln * 16, xhi);
                #pragma unroll
                for (int i = 0; i < 4; i++) st_relaxed_v4(ib + i * 512, SENT);
                st_relaxed_b32(xaddr(lds32_volatile(tbl + 28) + pub_slot(s + 3) + (ln & 16) * 256 + (ln & 8) * 16 + (ln & 7) * 4, xhi), SENT);
            }
            if (warp == 1) {
                if (elect_one()) {
                    #pragma unroll
                    for (int g = 0; g < 4; g++) mbar_arrive_expect_tx(bar + BAR_XG + 8 * g, 16384);
                }
                if (s + 2 < NSEG && cta < 4 && elect_one())
                    asm volatile("cp.async.bulk.prefetch.tensor.3d.L2.global [%0, {%1, %2, %3}];"
                                 ::"l"(&p.tmX), "r"(0), "r"((s + 2) * SEG), "r"(cta * 4) : "memory");
            }
            mbar_wait_bounded(bar + BAR_X, par);
            { const uint32_t t0 = clock_lo(); while (clock_lo() - t0 < WO_PFB_DELAY) {} }
            #pragma unroll
            for (int n = WO_PFA; n < WO_PF; n++) ldsm4t(wo_addr<3>(ao, a3, n), st[n]);
            att_stores(true, true);
            if (u_role & 16) {
                mbar_wait_bounded(bar + BAR_VM, par);
                if (elect_one()) x_load(p, sb, s + 1, rank);
            }
            named_bar_sync(6, REC_THREADS);
            wo_phase<3, WO_PF>(st, ao, a3, l16, tbl, sb + SM_SUM, slot, xhi, u_role & 4, bar + BAR_XG, par ^ 1, x0_ok);
        }
        STAMP(7);
        if (wg == 0) named_bar_sync(9, REC_THREADS); else named_bar_arrive(9, REC_THREADS);
    }
    if (threadIdx.x == 128) KMARK(8);
    if (warp == 4) {
        if (elect_one()) {
            asm volatile("cp.async.bulk.wait_group 1;" ::: "memory");
            signal_bulk(p.flags + F_LASTTOK);
            bulk_wait_all();
            signal_bulk(p.flags + F_PROGRESS + NSEG - 1);
            KMARK(9);
        }
    } else if (warp == 0) {
        mbar_wait(bar + BAR_X, 1);
        mbar_wait(bar + BAR_VM, 1);
        if (rank == 0) mbar_wait(bar + BAR_F0, 1);
    }
}

__global__ void __launch_bounds__(REC_THREADS, 1) rec_kernel(const __grid_constant__ RecParams p) {
    extern __shared__ __align__(1024) uint8_t smem_raw[];
    const uint32_t sb = smem_u32(smem_raw);
    const int tid = threadIdx.x, lane = tid & 31;
    const int warp = __shfl_sync(~0u, tid >> 5, 0);
    const int cta = blockIdx.x, head = cta / 3, rank = cta % 3;
    const int wg = warp >> 2, wq = warp & 3;
    const uint32_t bar = sb + SM_BAR;
    uint8_t* const xb = p.xchg;
    const uint32_t xlo = (uint32_t)(uint64_t)xb;
    if ((sb & 0x3FFFF) != SMEM_ORIGIN) __trap();
    KENTER(1);
    auto w_box = [&](int part, int g, int i, uint32_t dst, uint32_t mb) {
        const int m = i ^ g;
        const CUtensorMap* tm = &p.tmW[rank == 2 ? 2 : m];
        const int col = head * DH + (rank == 2 ? m : rank) * 64, row = ((part + 1) & 3) * 16;
        tma_load_3d(dst, tm, col, row, g * 8, mb);
    };
    if (tid == 0) {
        mbar_init(bar + BAR_V, 1);
        for (int i = 0; i < 4; i++) { mbar_init(bar + BAR_XG + 8 * i, 1); mbar_init(bar + BAR_M + 8 * i, 1); }
        mbar_init(bar + BAR_GO, 4);
        mbar_init(bar + BAR_PUB, 3);
        mbar_init(bar + BAR_PK, 4);
        mbar_init(bar + BAR_VM, rank < 2 ? 1 : 9);
        mbar_init(bar + BAR_F0, 3);
        mbar_init(bar + BAR_F3, 3);
        mbar_init(bar + BAR_VF, 3);
        sts64(bar + BAR_MIN, ~0u, ~0u);
        mbar_init(bar + BAR_X, rank < 2 ? 6 : 1);
        for (int i = 0; i < 3; i++) mbar_init(bar + BAR_P0 + 8 * i, 1);
        mbar_init(bar + BAR_WQ, 1);
        mbar_init(bar + BAR_WO, 1);
        sts32(bar + BAR_SELF, bar + BAR_SELF);
        asm volatile("fence.mbarrier_init.release.cluster;" ::: "memory");
    }
    auto build_tables = [&](uint32_t av) {
        for (uint32_t n = 0; !__all_sync(~0u, (av >> 24) == 24); n++) {
            av = ld_acquire_b32(p.arrivals + (lane & 3));
            if (n > SPIN_LIMIT) __trap();
        }
        uint32_t cm[3];
        #pragma unroll
        for (int i = 0; i < 3; i++) {
            const int o = i * 32 + lane;
            cm[i] = __ballot_sync(~0u, __popc((__shfl_sync(~0u, av, o / 24) >> (o % 24 / 3 * 3)) & 7) >= 2);
        }
        auto color_of = [&](int o) { return ((o < 32 ? cm[0] : o < 64 ? cm[1] : cm[2]) >> (o & 31)) & 1u; };
        auto inbox = [&](int o, int byte) {
            uint32_t c = color_of(o);
            int ones = 0;
            #pragma unroll
            for (int i = 0; i < 3; i++) ones += __popc(o >= i * 32 + 32 ? cm[i] : (o > i * 32 ? cm[i] & ((1u << (o - i * 32)) - 1) : 0u));
            int idx = c ? ones : o - ones;
            if (idx >= INBOX_MAX) { idx = 2 * INBOX_MAX - 1 - idx; c ^= 1; }
            const uint32_t lin = idx * 6144 + byte, q = XCHG_INBOX + (lin >> 12) * 8192;
            return q + class_off(xlo + q, c) + (lin & 4095);
        };
        uint32_t off = 0;
        const int grp = (warp + 3) & 3;
        if (lane < 12) {
            const int i = lane >> 2, lt0 = rank * 6;
            const int o = i < 2 ? rank * 32 + warp * 4 + (lane & 3) : (lt0 + ((warp + 4) & 7)) * 4 + (lane & 3);
            off = inbox(min(o, 95), i * 2048 + head * 64);
        } else if (lane == 12) {
            off = inbox(cta, (grp % 3) * 2048);
        } else if (lane == 13) {
            int T;
            if (grp < 2) {
                T = (cta >> 5) * 22 + 8 * grp + ((cta & 31) >> 2);
            } else {
                const int tl = (cta & 63) >> 2;
                T = (tl / 6) * 22 + 16 + tl % 6;
            }
            off = XCHG_PUB + (T >> 4) * 8192 + (T & 15) * 256 + (cta & 3) * 32;
        } else if (lane == 14) {
            const uint32_t q = XCHG_PUB + wq * 8192;
            off = q + class_off(xlo + q, color_of(cta));
        }
        if (lane == 15) off = mapa(bar + (warp == 5 ? BAR_VF : BAR_F0), warp == 5 ? 2 : 0) - xlo;
        if (lane < 16) asm volatile("st.shared.b32 [%0], %1;" ::"r"(sb + SM_TBL + warp * 64 + (lane & 3) * 16 + (lane >> 2) * 4), "r"(xlo + off) : "memory");
    };
    if (tid >= 32 && tid < 37) asm volatile("prefetch.tensormap [%0];" ::"l"(&p.tmW[0] + (tid - 32)) : "memory");
    if (cta == 0) for (int i = tid; i < F_COUNT; i += REC_THREADS) p.flags[i] = 0;
    __syncthreads();
    auto stage = [](int part) { return ((part + 2) % 3) * 65536; };
    auto load_part = [&](int part) {
        mbar_arrive_expect_tx(bar + BAR_P0 + 8 * part, 65536);
        for (int u = 0; u < 4; u++) w_box(part, u >> 1, u & 1, sb + stage(part) + u * 16384, bar + BAR_P0 + 8 * part);
    };
    asm volatile("barrier.cluster.arrive.relaxed.aligned;" ::: "memory");
    uint4 img = make_uint4(SENT, SENT, SENT, SENT);
    if (cta >= 92) {
        const unsigned short* m = reinterpret_cast<const unsigned short*>(p.mem0) + (cta - 92) * 256 + tid;
        uint32_t w[4];
        #pragma unroll
        for (int i = 0; i < 4; i++) w[i] = (uint32_t)__ldg(m + 2 * i * DM) | ((uint32_t)__ldg(m + (2 * i + 1) * DM) << 16);
        img = make_uint4(w[0], w[1], w[2], w[3]);
    }
    {
        constexpr int NPAIR = (XCHG_SLOT + PUB_BYTES) / 8192;
        uint8_t* pr = xb + (4 + cta) * 8192;
        const uint32_t c0 = class_off(xlo + (4 + cta) * 8192, 0);
        #pragma unroll
        for (int c = 0; c < 2; c++) {
            const bool timed = lane == 0 || (lane == 8 && c == (warp & 1));
            reinterpret_cast<uint4*>(pr + (c0 ^ (c << 12)))[tid] = make_uint4(timed ? 0u : SENT, SENT, SENT, SENT);
        }
        __syncwarp();
        if (lane == 0) {
            uint32_t x = 0;
            for (int k = 0; k < 3; k++) {
                if (k == 0 && warp == 0) load_part(0);
                const uint32_t c = (k + warp) & 1, t0 = clock_after(x);
                x = atomicExch(reinterpret_cast<uint32_t*>(pr + (c0 ^ (c << 12)) + warp * 512 + (k >> 1) * 128 + x), SENT);
                const uint32_t lat = clock_after(x) - t0;
                asm volatile("red.shared.min.u32 [%0], %1;" ::"r"(bar + BAR_MIN + 4 * c), "r"(lat) : "memory");
            }
        }
        __syncwarp();
        if (cta >= 92 || 100 + cta < NPAIR) {
            if (cta >= 92) {
                if (img.x == SENT) img.x = 0x7FFF7FFFu;
                if (img.y == SENT) img.y = 0x7FFF7FFFu;
                if (img.z == SENT) img.z = 0x7FFF7FFFu;
                if (img.w == SENT) img.w = 0x7FFF7FFFu;
            }
            uint8_t* q = xb + (cta >= 92 ? cta - 92 : 100 + cta) * 8192;
            reinterpret_cast<uint4*>(q)[tid] = img;
            reinterpret_cast<uint4*>(q + 4096)[tid] = img;
        }
    }
    __syncthreads();
    PSTAMP(4);
    if (tid == 0) {
        for (int part = 1; part < 3; part++) load_part(part);
    }
    if (tid == 224) {
        const uint32_t c = lds32_volatile(bar + BAR_MIN) > lds32_volatile(bar + BAR_MIN + 4) ? 1 : 0;
        asm volatile("red.release.gpu.global.add.u32 [%0], %1;" ::"l"(p.arrivals + cta / 24), "r"((1u << 24) | (c << (cta % 24))) : "memory");
    }
    uint32_t wr[NREG][2][4];
    uint32_t arrived = 0;
    {
        const int mi = lane >> 3, r8 = lane & 7;
        const uint32_t a0 = sb + wg * 32768 + ((mi >> 1) * 8 + r8) * 128 + (((wq * 2 + (mi & 1)) ^ r8) << 4);
        #pragma unroll
        for (int part = 0; part < 3; part++) {
            mbar_wait_bounded(bar + BAR_P0 + 8 * part, 0);
            if (part == 0) arrived = ld_relaxed_b32(p.arrivals + (lane & 3));
            #pragma unroll
            for (int j = 0; j < 8; j++) {
                #pragma unroll
                for (int i = 0; i < 2; i++) ldsm4t(a0 + stage(part) + i * 16384 + j * 2048, wr[part * 8 + j][i]);
            }
            asm volatile("fence.proxy.async.shared::cta;" ::: "memory");
            __syncthreads();
            PSTAMP(5 + part);
            if (tid == 0) {
                if (part == 0) {
                    for (int g = 0; g < 4; g++) {
                        mbar_arrive_expect_tx(bar + BAR_XG + 8 * g, 16384);
                        tma_load_3d(sb + SM_X + g * 16384, &p.tmX, 0, 0, g * 4, bar + BAR_XG + 8 * g);
                    }
                } else if (part == 1) {
                    mbar_arrive_expect_tx(bar + BAR_WQ, 65536);
                    for (int u = 0; u < 4; u++) w_box(3, u >> 1, u & 1, sb + SM_WQ + u * 16384, bar + BAR_WQ);
                } else {
                    mbar_arrive_expect_tx(bar + BAR_WO, 11 * 8192);
                    tma_load_3d(sb + SM_WO, &p.tmWo, 0, head * DH, rank * 11, bar + BAR_WO);
                    if (cta < 4)
                        asm volatile("cp.async.bulk.prefetch.tensor.3d.L2.global [%0, {%1, %2, %3}];"
                                     ::"l"(&p.tmX), "r"(0), "r"(SEG), "r"(cta * 4) : "memory");
                }
            }
        }
    }
    build_tables(arrived);
    if (tid == 64) {
        uint32_t smid;
        asm volatile("mov.u32 %0, %%smid;" : "=r"(smid));
        if (smid < 384) atomicOr(p.flags + F_RECSM + (smid >> 5), 1u << (smid & 31));
    }
    __syncwarp();
    PSTAMP(9);
    mbar_wait(bar + BAR_WQ, 0);
    asm volatile("barrier.cluster.wait.aligned;" ::: "memory");

    rec_steps(p, wr, sb, warp, cta, head, rank);
    if (cta == 0 && tid < 4) p.arrivals[tid] = 0;
    if (tid == 128) KEXIT(1);
}

constexpr int ATT_SLOT = 28672;
constexpr int ATT_PAIRS = 8;
constexpr int ATT_BAR = ATT_PAIRS * ATT_SLOT;
constexpr int ATT_SMEM = ATT_BAR + ATT_PAIRS * 16;
constexpr int ATT_THREADS = ATT_PAIRS * 64;
struct AttnParams {
    CUtensorMap tmOa;
    CUtensorMap tmQb, tmKb;
    CUtensorMap tmOb;
    const __nv_bfloat16* qkv_tok;
    const __nv_bfloat16* kv_mem;
    uint32_t* flags;
};

__device__ __forceinline__ void tok_attn_warp(uint32_t base, int mh, int lane) {
    const uint32_t sq = base, sk = base + 8192, sv = base + 16384, skm = base + 24576, svm = skm + 2048;
    const int g = lane >> 2, c = lane & 3, mi = lane >> 3, r8 = lane & 7;
    const int ntile = mh ? 5 : 3;
    float sc[5][4];
    #pragma unroll
    for (int j = 0; j < 5; j++) { sc[j][0] = sc[j][1] = sc[j][2] = sc[j][3] = 0.f; }
    #pragma unroll
    for (int t2 = 0; t2 < 4; t2++) {
        uint32_t a[2][4];
        #pragma unroll
        for (int h = 0; h < 2; h++) {
            const int row = mh * 16 + (mi & 1) * 8 + r8, ch16 = 4 * t2 + 2 * h + (mi >> 1);
            ldsm_x4(sq + (ch16 >> 3) * 4096 + row * 128 + (((ch16 & 7) ^ r8) << 4), a[h][0], a[h][1], a[h][2], a[h][3]);
        }
        const int ch16 = 4 * t2 + mi;
        uint32_t b[5][4];
        #pragma unroll
        for (int j = 0; j < 5; j++) {
            if (j < ntile) {
                if (j == 0) ldsm_x4(skm + (ch16 >> 3) * 1024 + r8 * 128 + (((ch16 & 7) ^ r8) << 4), b[j][0], b[j][1], b[j][2], b[j][3]);
                else ldsm_x4(sk + (ch16 >> 3) * 4096 + ((j - 1) * 8 + r8) * 128 + (((ch16 & 7) ^ r8) << 4), b[j][0], b[j][1], b[j][2], b[j][3]);
            }
        }
        #pragma unroll
        for (int h = 0; h < 2; h++) {
            #pragma unroll
            for (int j = 0; j < 5; j++)
                if (j < ntile) mma16816(sc[j], a[h][0], a[h][1], a[h][2], a[h][3], b[j][2 * h], b[j][2 * h + 1]);
        }
    }
    const float sl2 = 0.08838834764831845f * 1.4426950408889634f;
    uint32_t pf[2][5];
    float inv[2];
    #pragma unroll
    for (int q = 0; q < 2; q++) {
        const int tok = mh * 16 + q * 8 + g;
        float v[10];
        #pragma unroll
        for (int j = 0; j < 5; j++) {
            #pragma unroll
            for (int e = 0; e < 2; e++) {
                const int key = (j - 1) * 8 + 2 * c + e;
                v[2 * j + e] = (j == 0 || key <= tok) ? sc[j][2 * q + e] : -INFINITY;
            }
        }
        float mx = v[0];
        #pragma unroll
        for (int j = 1; j < 10; j++) mx = fmaxf(mx, v[j]);
        mx = fmaxf(mx, __shfl_xor_sync(~0u, mx, 1));
        mx = fmaxf(mx, __shfl_xor_sync(~0u, mx, 2));
        const float mo = mx * sl2;
        float sum = 0.f;
        #pragma unroll
        for (int j = 0; j < 10; j++) { v[j] = ex2(fmaf(v[j], sl2, -mo)); sum += v[j]; }
        sum += __shfl_xor_sync(~0u, sum, 1);
        sum += __shfl_xor_sync(~0u, sum, 2);
        inv[q] = rcp(sum);
        #pragma unroll
        for (int j = 0; j < 5; j++) pf[q][j] = pack_bf16(v[2 * j], v[2 * j + 1]);
    }
    auto load_v = [&](int n4, uint32_t (&vm)[4], uint32_t (&vt)[4][4]) {
        const uint2 va = lds64(svm + n4 * 512 + lane * 8), vb = lds64(svm + n4 * 512 + 256 + lane * 8);
        vm[0] = va.x; vm[1] = va.y; vm[2] = vb.x; vm[3] = vb.y;
        #pragma unroll
        for (int u = 0; u < 4; u++) {
            const int dt = 2 * n4 + (u >> 1), kh = u & 1;
            const uint4 v = lds128(sv + (dt & 3) * 2048 + (dt >> 2) * 1024 + kh * 512 + lane * 16);
            vt[u & 2][2 * kh] = v.x; vt[u & 2][2 * kh + 1] = v.z;
            vt[(u & 2) + 1][2 * kh] = v.y; vt[(u & 2) + 1][2 * kh + 1] = v.w;
        }
    };
    uint32_t vm[2][4], vt[2][4][4];
    load_v(0, vm[0], vt[0]);
    #pragma unroll
    for (int n4 = 0; n4 < 4; n4++) {
        const int cur = n4 & 1;
        if (n4 + 1 < 4) load_v(n4 + 1, vm[cur ^ 1], vt[cur ^ 1]);
        float o[4][4];
        #pragma unroll
        for (int u = 0; u < 4; u++) {
            o[u][0] = o[u][1] = o[u][2] = o[u][3] = 0.f;
            mma16816(o[u], pf[0][1], pf[1][1], pf[0][2], pf[1][2], vt[cur][u][0], vt[cur][u][1]);
        }
        if (mh) {
            #pragma unroll
            for (int u = 0; u < 4; u++) mma16816(o[u], pf[0][3], pf[1][3], pf[0][4], pf[1][4], vt[cur][u][2], vt[cur][u][3]);
        }
        #pragma unroll
        for (int u = 0; u < 4; u++) mma1688(o[u], pf[0][0], pf[1][0], vm[cur][u]);
        #pragma unroll
        for (int u = 0; u < 4; u += 2) {
            const int row = mh * 16 + (mi & 1) * 8 + r8, nt = 4 * n4 + u + (mi >> 1);
            stsm_x4(sq + (nt >> 3) * 4096 + row * 128 + (((nt & 7) ^ r8) << 4),
                    pack_bf16(o[u][0] * inv[0], o[u][1] * inv[0]), pack_bf16(o[u][2] * inv[1], o[u][3] * inv[1]),
                    pack_bf16(o[u + 1][0] * inv[0], o[u + 1][1] * inv[0]), pack_bf16(o[u + 1][2] * inv[1], o[u + 1][3] * inv[1]));
        }
    }
}

__device__ __forceinline__ void b_attn_warp(uint32_t base, int hl, int idx0, int lane) {
    const uint32_t sq = base, sk = base + 8192, sv = base + 8192 + 9216;
    const int g = lane >> 2, c = lane & 3;
    auto addr = [&](uint32_t t, int row, int ch) { return t + row * 128 + ((ch ^ (row & 7)) << 4); };
    const float sl2 = 0.17677669529663687f * 1.4426950408889634f;
    #pragma unroll 2
    for (int blk = 0; blk < 4; blk++) {
        const int r0 = blk * 16;
        float sc[3][4];
        #pragma unroll
        for (int j = 0; j < 3; j++) { sc[j][0] = sc[j][1] = sc[j][2] = sc[j][3] = 0.f; }
        #pragma unroll
        for (int t = 0; t < 2; t++) {
            uint32_t a0, a1, a2, a3, b0, b1, b2, b3, d0, d1, d2, d3;
            const int mi = lane >> 3, r = lane & 7;
            ldsm_x4(addr(sq, r0 + (mi & 1) * 8 + r, hl * 4 + 2 * t + (mi >> 1)), a0, a1, a2, a3);
            ldsm_x4(addr(sk, r0 + (mi >> 1) * 8 + r, hl * 4 + 2 * t + (mi & 1)), b0, b1, b2, b3);
            ldsm_x4(addr(sk, r0 + 16 + r, hl * 4 + 2 * t + (mi & 1)), d0, d1, d2, d3);
            mma16816(sc[0], a0, a1, a2, a3, b0, b1);
            mma16816(sc[1], a0, a1, a2, a3, b2, b3);
            mma16816(sc[2], a0, a1, a2, a3, d0, d1);
        }
        uint32_t pf[2][3];
        float inv[2];
        #pragma unroll
        for (int r = 0; r < 2; r++) {
            const int u = r * 8 + g;
            float v[6];
            #pragma unroll
            for (int j = 0; j < 3; j++) {
                #pragma unroll
                for (int e = 0; e < 2; e++) {
                    const int key = j * 8 + 2 * c + e;
                    const bool ok = key > u && key <= u + 8 && idx0 + r0 - 8 + key >= 0;
                    v[2 * j + e] = ok ? sc[j][2 * r + e] : -INFINITY;
                }
            }
            float mx = fmaxf(fmaxf(fmaxf(v[0], v[1]), fmaxf(v[2], v[3])), fmaxf(v[4], v[5]));
            mx = fmaxf(mx, __shfl_xor_sync(~0u, mx, 1));
            mx = fmaxf(mx, __shfl_xor_sync(~0u, mx, 2));
            const float mo = mx * sl2;
            float sum = 0.f;
            #pragma unroll
            for (int j = 0; j < 6; j++) { v[j] = ex2(fmaf(v[j], sl2, -mo)); sum += v[j]; }
            sum += __shfl_xor_sync(~0u, sum, 1);
            sum += __shfl_xor_sync(~0u, sum, 2);
            inv[r] = rcp(sum);
            #pragma unroll
            for (int j = 0; j < 3; j++) pf[r][j] = pack_bf16(v[2 * j], v[2 * j + 1]);
        }
        uint32_t ow[4][2];
        {
            const int mi = lane >> 3, r = lane & 7;
            uint32_t vv[4][4];
            #pragma unroll
            for (int nt = 0; nt < 4; nt++)
                ldsm_x4_t(addr(sv, r0 + min(mi, 2) * 8 + r, hl * 4 + nt), vv[nt][0], vv[nt][1], vv[nt][2], vv[nt][3]);
            float o[4][4];
            #pragma unroll
            for (int nt = 0; nt < 4; nt++) {
                o[nt][0] = o[nt][1] = o[nt][2] = o[nt][3] = 0.f;
                mma16816(o[nt], pf[0][0], pf[1][0], pf[0][1], pf[1][1], vv[nt][0], vv[nt][1]);
            }
            #pragma unroll
            for (int nt = 0; nt < 4; nt++) mma1688(o[nt], pf[0][2], pf[1][2], vv[nt][2]);
            #pragma unroll
            for (int nt = 0; nt < 4; nt++) {
                ow[nt][0] = pack_bf16(o[nt][0] * inv[0], o[nt][1] * inv[0]);
                ow[nt][1] = pack_bf16(o[nt][2] * inv[1], o[nt][3] * inv[1]);
            }
        }
        #pragma unroll
        for (int u = 0; u < 4; u += 2) {
            const int mi = lane >> 3, r = lane & 7;
            stsm_x4(addr(sq, r0 + (mi & 1) * 8 + r, hl * 4 + u + (mi >> 1)), ow[u][0], ow[u][1], ow[u + 1][0], ow[u + 1][1]);
        }
    }
}

constexpr uint32_t QKVB_TARGET = 12 * 8;
constexpr uint32_t PROGRESS_TARGET = 96;
constexpr uint32_t OA_TARGET = 64, OB_TARGET = 32;
#define ATT_B0 8
#define ATT_BSTEP 2
constexpr int ATT_TASKS = (NSEG + 16) * 32;
static_assert(ATT_B0 + 16 * ATT_BSTEP <= NSEG, "order of the task groups");
__device__ __forceinline__ int att_group(int g, bool& isb) {
    constexpr int P = ATT_BSTEP + 1;
    const int q = g - ATT_B0;
    isb = q >= 0 && q < 16 * P && q % P == 0;
    return q < 0 ? g : q >= 16 * P ? g - 16 : isb ? q / P : g - q / P - 1;
}

__global__ void __launch_bounds__(ATT_THREADS, 1) attn_kernel(const __grid_constant__ AttnParams p) {
    extern __shared__ __align__(1024) uint8_t smem_raw[];
    const int tid = threadIdx.x, lane = tid & 31, warp = __shfl_sync(~0u, tid >> 5, 0);
    const int pair = warp >> 1, wi = warp & 1;
    const uint32_t base = smem_u32(smem_raw) + pair * ATT_SLOT, bar = smem_u32(smem_raw) + ATT_BAR + pair * 16;
    const bool leader = wi == 0 && lane == 0;
    if (tid == 0) pdl_launch_dependents();
    KENTER(3);
    uint32_t phase = 0;
    if (leader) {
        mbar_init(bar, 1);
        asm volatile("fence.mbarrier_init.release.cluster;" ::: "memory");
    }
    uint32_t* pending = nullptr;
    auto flush = [&]() {
        if (pending) {
            bulk_wait_all();
            signal_bulk(pending);
            if (pending == p.flags + F_OA + NSEG - 1) KMARK(14);
            pending = nullptr;
        }
    };
    int ready_a = -1, ready_b = -1;
    for (int task = pair * gridDim.x + blockIdx.x; task < ATT_TASKS; task += ATT_PAIRS * gridDim.x) {
        bool isb;
        const int grp = att_group(task >> 5, isb), i = task & 31;
        named_bar_sync(1 + pair, 64);
        if (leader) {
            {
                auto need = [&](const uint32_t* f, uint32_t target) {
                    if (ld_acquire_b32(f) < target) { flush(); wait_flag(f, target); }
                };
                if (isb) {
                    if (grp > ready_b) {
                        need(p.flags + F_QKVB + grp, QKVB_TARGET);
                        if (grp > 0) need(p.flags + F_QKVB + grp - 1, QKVB_TARGET);
                        asm volatile("fence.proxy.async.global;" ::: "memory");
                        ready_b = grp;
                    }
                    mbar_arrive_expect_tx(bar, 8192 + 2 * 9216);
                    tma_load_3d(base, &p.tmQb, (i >> 1) * 64, i & 1, grp * 64, bar);
                    tma_load_3d(base + 8192, &p.tmKb, DM + (i >> 1) * 64, i & 1, grp * 64 - 8, bar);
                    tma_load_3d(base + 8192 + 9216, &p.tmKb, 2 * DM + (i >> 1) * 64, i & 1, grp * 64 - 8, bar);
                } else {
                    if (grp > ready_a) {
                        need(p.flags + (grp == NSEG - 1 ? F_LASTTOK : F_PROGRESS + grp), PROGRESS_TARGET);
                        asm volatile("fence.proxy.async.global;" ::: "memory");
                        ready_a = grp;
                    }
                    if (grp == 63) KMARK(10);
                    mbar_arrive_expect_tx(bar, ATT_SLOT);
                    #pragma unroll
                    for (int w = 0; w < 3; w++)
                        bulk_load(base + w * 8192, p.qkv_tok + (((size_t)w * NSEG + grp) * NH + i) * (SEG * DH), 8192, bar);
                    if (grp == NSEG - 1) {
                        need(p.flags + F_PROGRESS + grp, PROGRESS_TARGET);
                        asm volatile("fence.proxy.async.global;" ::: "memory");
                    }
                    #pragma unroll
                    for (int w = 0; w < 2; w++)
                        bulk_load(base + 24576 + w * 2048, p.kv_mem + (((size_t)w * NSEG + grp) * NH + i) * (MROWS * DH), 2048, bar);
                }
            }
        }
        if (lane == 0) flush();
        __syncwarp();
        mbar_wait_sleep(bar, phase);
        phase ^= 1;
        if (isb) {
            b_attn_warp(base, wi, grp * 64, lane);
            asm volatile("fence.proxy.async.shared::cta;" ::: "memory");
            named_bar_sync(1 + pair, 64);
            if (wi == 1 && lane == 0) {
                asm volatile("cp.async.bulk.tensor.3d.global.shared::cta.bulk_group [%0, {%2, %3, %4}], [%1];"
                             ::"l"(&p.tmOb), "r"(base), "r"((i >> 1) * 64), "r"(i & 1), "r"(grp * 64) : "memory");
                pending = p.flags + F_OB + grp;
            }
        } else {
            if (grp == 63 && lane == 0) KMARK(11);
            tok_attn_warp(base, wi, lane);
            if (grp == 63 && lane == 0) KMARK(12);
            asm volatile("fence.proxy.async.shared::cta;" ::: "memory");
            __syncwarp();
            if (lane == 0) {
                #pragma unroll
                for (int h = 0; h < 2; h++) tma_store_2d(&p.tmOa, base + h * 4096 + wi * 2048, i * DH + h * 64, grp * SEG + wi * 16);
                pending = p.flags + F_OA + grp;
            }
        }
        if (lane == 0) { bulk_commit(); bulk_wait_read_all(); }
        __syncwarp();
    }
    if (lane == 0) { flush(); KEXIT(3); }
}

typedef CUresult (*EncodeFn)(CUtensorMap*, CUtensorMapDataType, cuuint32_t, void*, const cuuint64_t*, const cuuint64_t*,
                             const cuuint32_t*, const cuuint32_t*, CUtensorMapInterleave, CUtensorMapSwizzle,
                             CUtensorMapL2promotion, CUtensorMapFloatOOBfill);

void make_map_2d(EncodeFn enc, CUtensorMap* m, const void* ptr, uint64_t rows, uint64_t cols, uint32_t box_rows) {
    cuuint64_t dims[2] = {cols, rows};
    cuuint64_t strides[1] = {cols * 2};
    cuuint32_t box[2] = {64, box_rows};
    cuuint32_t es[2] = {1, 1};
    enc(m, CU_TENSOR_MAP_DATA_TYPE_BFLOAT16, 2, const_cast<void*>(ptr), dims, strides, box, es,
        CU_TENSOR_MAP_INTERLEAVE_NONE, CU_TENSOR_MAP_SWIZZLE_128B, CU_TENSOR_MAP_L2_PROMOTION_L2_256B,
        CU_TENSOR_MAP_FLOAT_OOB_FILL_NONE);
}
void make_map_b(EncodeFn enc, CUtensorMap* m, const void* ptr, uint64_t k, uint64_t n, uint32_t nblk, uint32_t box_rows = 64,
                uint32_t bc = 64) {
    cuuint64_t dims[3] = {bc, k, n / bc};
    cuuint64_t strides[2] = {n * 2, bc * 2};
    cuuint32_t box[3] = {bc, box_rows, nblk};
    cuuint32_t es[3] = {1, 1, 1};
    enc(m, CU_TENSOR_MAP_DATA_TYPE_BFLOAT16, 3, const_cast<void*>(ptr), dims, strides, box, es,
        CU_TENSOR_MAP_INTERLEAVE_NONE, bc == 64 ? CU_TENSOR_MAP_SWIZZLE_128B : CU_TENSOR_MAP_SWIZZLE_64B, CU_TENSOR_MAP_L2_PROMOTION_L2_256B,
        CU_TENSOR_MAP_FLOAT_OOB_FILL_NONE);
}

void make_map_parity(EncodeFn enc, CUtensorMap* m, const void* ptr, uint64_t cols, uint32_t box_rows) {
    cuuint64_t dims[3] = {cols, 2, S_TOK / 2};
    cuuint64_t strides[2] = {cols * 2, cols * 4};
    cuuint32_t box[3] = {64, 1, box_rows};
    cuuint32_t es[3] = {1, 1, 1};
    enc(m, CU_TENSOR_MAP_DATA_TYPE_BFLOAT16, 3, const_cast<void*>(ptr), dims, strides, box, es,
        CU_TENSOR_MAP_INTERLEAVE_NONE, CU_TENSOR_MAP_SWIZZLE_128B, CU_TENSOR_MAP_L2_PROMOTION_L2_128B,
        CU_TENSOR_MAP_FLOAT_OOB_FILL_NONE);
}
void make_map_w(EncodeFn enc, CUtensorMap* m, const void* ptr) {
    cuuint64_t dims[3] = {HD, 64, DM / 64};
    cuuint64_t strides[2] = {HD * 2, 64 * HD * 2};
    cuuint32_t box[3] = {64, 16, 8};
    cuuint32_t es[3] = {1, 1, 1};
    enc(m, CU_TENSOR_MAP_DATA_TYPE_BFLOAT16, 3, const_cast<void*>(ptr), dims, strides, box, es,
        CU_TENSOR_MAP_INTERLEAVE_NONE, CU_TENSOR_MAP_SWIZZLE_128B, CU_TENSOR_MAP_L2_PROMOTION_L2_256B,
        CU_TENSOR_MAP_FLOAT_OOB_FILL_NONE);
}

#define SIDE_ORDER 0
#define SERIAL_ATT_CTAS h.n_sm
#define N_TAIL_CTAS 28
#define N_SIDE_CTAS 28
#define N_ATT_CTAS 8
#define TAIL_BLOCK0 11

#define TAIL_SPARE 2
#define TAIL_KB2 30
#define TAIL_KB3 20
#define TAIL_BLOCK1 13
#define TAIL_BLOCK2 14

struct HostState {
    bool ready;
    bool overlap;
    int n_side, n_att, n_sm;
    SideParams seq_a, seq_b;
    const void* key[11];
    RecParams rec;
    SideParams side, tail;
    FinalParams fin;
    AttnParams attn;
    __nv_bfloat16 *qkv_tok, *kv_mem, *o_tok, *qkv_b, *o_b;
    uint8_t* xchg;
};
HostState g_host;

void setup(void* const* d_in, void* d_out) {
    HostState& h = g_host;
    void* fn = nullptr;
    cudaDriverEntryPointQueryResult qr;
    cudaGetDriverEntryPoint("cuTensorMapEncodeTiled", &fn, cudaEnableDefault, &qr);
    EncodeFn enc = reinterpret_cast<EncodeFn>(fn);
    void* ptr;
    cudaGetSymbolAddress(&ptr, g_qkv_tok); h.qkv_tok = (__nv_bfloat16*)ptr;
    cudaGetSymbolAddress(&ptr, g_kv_mem);  h.kv_mem = (__nv_bfloat16*)ptr;
    cudaGetSymbolAddress(&ptr, g_o_tok);   h.o_tok = (__nv_bfloat16*)ptr;
    cudaGetSymbolAddress(&ptr, g_qkv_b);   h.qkv_b = (__nv_bfloat16*)ptr;
    cudaGetSymbolAddress(&ptr, g_o_b);     h.o_b = (__nv_bfloat16*)ptr;
    cudaGetSymbolAddress(&ptr, g_xchg);    h.xchg = (uint8_t*)(((uint64_t)ptr + XCHG_BYTES - 1) & ~(uint64_t)(XCHG_BYTES - 1));
    cudaGetSymbolAddress(&ptr, g_flags);   uint32_t* flags = (uint32_t*)ptr;
    cudaGetSymbolAddress(&ptr, g_arrivals); uint32_t* arrivals = (uint32_t*)ptr;

    const void *xa = d_in[0], *mem0 = d_in[1], *wq = d_in[2], *wk = d_in[3], *wv = d_in[4], *wo = d_in[5];
    const void *xb = d_in[7], *wqkv = d_in[8], *wob = d_in[9];

    RecParams& r = h.rec;
    make_map_w(enc, &r.tmW[0], wq);
    make_map_w(enc, &r.tmW[1], wk);
    make_map_w(enc, &r.tmW[2], wv);
    make_map_b(enc, &r.tmWo, wo, HD, DM, 11, 128, 32);
    r.mem0 = (const __nv_bfloat16*)mem0;
    r.qkv_tok = h.qkv_tok; r.kv_mem = h.kv_mem; r.xchg = h.xchg;
    r.flags = flags; r.arrivals = arrivals; r.one[0] = r.one[1] = 1;
    make_map_b(enc, &r.tmX, xa, S_TOK, DM, 4, SEG);

    SideParams& sd = h.side;
    SideProb& p0 = sd.prob[0];
    make_map_2d(enc, &p0.tmA, xb, S_TOK, DM, BM);
    make_map_b(enc, &p0.tmB, wqkv, DM, 3 * DM, 4);
    make_map_2d(enc, &p0.tmC, h.qkv_b, S_TOK, 3 * DM, 16);
    p0.n_tiles = 3 * DM / 256; p0.k_blocks = DM / BK; p0.c_col0 = 0; p0.dep = nullptr; p0.dep_target = 0; p0.dep_n = 1; p0.sig = flags + F_QKVB;
    SideProb& p1 = sd.prob[1];
    make_map_2d(enc, &p1.tmA, h.o_tok, S_TOK, HD, BM);
    make_map_b(enc, &p1.tmB, wo, HD, DM, 4);
    make_map_2d(enc, &p1.tmC, d_out, S_TOK, 2 * DM, 16);
    p1.n_tiles = DM / 256; p1.k_blocks = HD / BK; p1.c_col0 = 0; p1.dep = flags + F_OA; p1.dep_target = OA_TARGET; p1.dep_n = 4; p1.sig = nullptr;
    SideProb& p2 = sd.prob[2];
    make_map_2d(enc, &p2.tmA, h.o_b, S_TOK, DM, BM);
    make_map_b(enc, &p2.tmB, wob, DM, DM, 4);
    p2.tmC = p1.tmC;
    p2.n_tiles = DM / 256; p2.k_blocks = DM / BK; p2.c_col0 = DM; p2.dep = flags + F_OB; p2.dep_target = OB_TARGET; p2.dep_n = 1; p2.sig = nullptr;
    p0.n_split = p0.n_tiles; p1.n_split = p1.n_tiles; p2.n_split = p2.n_tiles;
    p0.part = p1.part = p2.part = nullptr;
    p0.k_total = p0.k_blocks; p1.k_total = p1.k_blocks; p2.k_total = p2.k_blocks;
    if (SIDE_ORDER == 0) { sd.seg[0] = {0, 0, 16}; sd.seg[1] = {1, 0, TAIL_BLOCK0}; }
    else { sd.seg[0] = {1, 0, TAIL_BLOCK0}; sd.seg[1] = {0, 0, 16}; }
    sd.seg[2] = {2, 0, 16};
    sd.nseg = 3; sd.queue = flags + F_SIDEQ; sd.spare_seg = 3; sd.flags = flags;

    SideParams& tl = h.tail;
    tl.prob[0] = p1;
    make_map_b(enc, &tl.prob[0].tmB, wo, HD, DM, 2);
    cudaGetSymbolAddress(&ptr, g_part);
    for (int i = 0; i < 3; i++) {
        SideProb& q = tl.prob[i];
        q = tl.prob[0];
        q.n_tiles = (i + 1) * DM / 128; q.n_split = DM / 128; q.k_blocks = i == 0 ? HD / BK : i == 1 ? TAIL_KB2 : TAIL_KB3;
        q.part = i ? (float*)ptr : nullptr; q.part_flag = flags + F_PART;
    }
    tl.seg[0] = {0, TAIL_BLOCK0, TAIL_BLOCK1};
    tl.seg[1] = {1, TAIL_BLOCK1, TAIL_BLOCK2};
    tl.seg[2] = {2, TAIL_BLOCK2, 15};
    tl.nseg = 3; tl.queue = flags + F_TAILQ; tl.spare_seg = TAIL_SPARE; tl.flags = flags;

    make_map_2d(enc, &h.fin.tmA, h.o_tok, S_TOK, HD, SEG);
    h.fin.tmB = tl.prob[0].tmB; h.fin.out = (__nv_bfloat16*)d_out;
    h.fin.dep = flags + F_OA + 60; h.fin.dep_target = OA_TARGET; h.fin.mt = 15;

    make_map_2d(enc, &h.attn.tmOa, h.o_tok, S_TOK, HD, 16);
    make_map_parity(enc, &h.attn.tmQb, h.qkv_b, 3 * DM, 64);
    make_map_parity(enc, &h.attn.tmKb, h.qkv_b, 3 * DM, 72);
    make_map_parity(enc, &h.attn.tmOb, h.o_b, DM, 64);
    h.attn.qkv_tok = h.qkv_tok; h.attn.kv_mem = h.kv_mem; h.attn.flags = flags;

    int dev = 0, nsm = 0;
    cudaGetDevice(&dev);
    cudaDeviceGetAttribute(&nsm, cudaDevAttrMultiProcessorCount, dev);
    h.n_sm = nsm;
    h.overlap = nsm - 96 >= N_SIDE_CTAS + N_ATT_CTAS;
    h.n_side = N_SIDE_CTAS; h.n_att = N_ATT_CTAS;
    h.seq_a = sd;
    h.seq_a.seg[0] = {0, 0, 16};
    h.seq_a.nseg = 1;
    h.seq_b = sd;
    h.seq_b.seg[0] = {1, 0, 16};
    h.seq_b.seg[1] = {2, 0, 16};
    h.seq_b.nseg = 2; h.seq_b.queue = flags + F_TAILQ;

    cudaFuncSetAttribute(side_gemm_kernel<256>, cudaFuncAttributeMaxDynamicSharedMemorySize, GemmCfg<256>::SMEM);
    cudaFuncSetAttribute(side_gemm_kernel<128>, cudaFuncAttributeMaxDynamicSharedMemorySize, GemmCfg<128>::SMEM);
    cudaFuncSetAttribute(final_gemm_kernel, cudaFuncAttributeMaxDynamicSharedMemorySize, FIN_SMEM);
    cudaFuncSetAttribute(rec_kernel, cudaFuncAttributeMaxDynamicSharedMemorySize, REC_SMEM);
    cudaFuncSetAttribute(attn_kernel, cudaFuncAttributeMaxDynamicSharedMemorySize, ATT_SMEM);
    for (int i = 0; i < 10; i++) h.key[i] = d_in[i];
    h.key[10] = d_out;
    h.ready = true;
}

template <typename K, typename P>
void launch(K kernel, int grid, int block, int smem, cudaStream_t st, const P& prm, int cluster, bool pdl) {
    cudaLaunchConfig_t cfg = {};
    cfg.gridDim = dim3(grid); cfg.blockDim = dim3(block); cfg.dynamicSmemBytes = smem; cfg.stream = st;
    cudaLaunchAttribute at[2];
    int n = 0;
    if (cluster > 1) {
        at[n].id = cudaLaunchAttributeClusterDimension;
        at[n].val.clusterDim.x = cluster; at[n].val.clusterDim.y = 1; at[n].val.clusterDim.z = 1;
        n++;
    }
    if (pdl) {
        at[n].id = cudaLaunchAttributeProgrammaticStreamSerialization;
        at[n].val.programmaticStreamSerializationAllowed = 1;
        n++;
    }
    cfg.attrs = at; cfg.numAttrs = n;
    cudaLaunchKernelEx(&cfg, kernel, prm);
}

}

extern "C" void kernel_launch(void* const* d_in, const int* in_sizes, int n_in, void* d_out, int out_size) {
    HostState& h = g_host;
    bool same = h.ready;
    for (int i = 0; same && i < 10; i++) same = h.key[i] == d_in[i];
    if (!same || h.key[10] != d_out) setup(d_in, d_out);
    cudaStream_t st = cudaStreamPerThread;

    launch(rec_kernel, 96, REC_THREADS, REC_SMEM, st, h.rec, 3, false);
    {
        if (!h.overlap) {
            launch(side_gemm_kernel<256>, h.n_sm, 384, GemmCfg<256>::SMEM, st, h.seq_a, 1, false);
            launch(attn_kernel, SERIAL_ATT_CTAS, ATT_THREADS, ATT_SMEM, st, h.attn, 1, false);
            launch(side_gemm_kernel<256>, h.n_sm, 384, GemmCfg<256>::SMEM, st, h.seq_b, 1, false);
            return;
        }
    }
    launch(side_gemm_kernel<256>, h.n_side, 384, GemmCfg<256>::SMEM, st, h.side, 1, true);
    launch(attn_kernel, h.n_att, ATT_THREADS, ATT_SMEM, st, h.attn, 1, true);
    launch(side_gemm_kernel<128>, N_TAIL_CTAS, 384, GemmCfg<128>::SMEM, st, h.tail, 1, true);
    launch(final_gemm_kernel, 8 * FIN_SPLIT, 384, FIN_SMEM, st, h.fin, FIN_SPLIT, true);
}
```

```cpp
#include <cuda_runtime.h>
#include <cuda_bf16.h>
#include <cuda.h>
#include <stdint.h>

namespace {

constexpr int S_TOK = 2048;
constexpr int DM = 1024;
constexpr int NH = 32;
constexpr int DH = 128;
constexpr int HD = NH * DH;
constexpr int NSEG = 64;
constexpr int SEG = 32;
constexpr int MROWS = 8;
constexpr uint32_t SENT = 0xFFFFFFFFu;
constexpr uint32_t SPIN_LIMIT = 1u << 24;

__device__ __align__(1024) __nv_bfloat16 g_qkv_tok[3ull * NSEG * NH * SEG * DH];
__device__ __align__(1024) __nv_bfloat16 g_kv_mem[2ull * NSEG * NH * MROWS * DH];
__device__ __align__(1024) __nv_bfloat16 g_o_tok[(size_t)S_TOK * HD];
__device__ __align__(1024) __nv_bfloat16 g_qkv_b[(size_t)S_TOK * 3 * DM];
__device__ __align__(1024) __nv_bfloat16 g_o_b[(size_t)S_TOK * DM];
__device__ __align__(1024) float g_part[32 * 2 * 128 * 128];
constexpr int PUB_BYTES = 32768;
constexpr int XCHG_SLOT = 1 << 20;
constexpr int XCHG_PUB = 0, XCHG_INBOX = 2 * PUB_BYTES;
constexpr int INBOX_MAX = 80;
constexpr int XCHG_BYTES = 2 * XCHG_SLOT;
__device__ __align__(8192) uint8_t g_xchg[2 * XCHG_BYTES];
enum { F_LASTTOK = 0, F_RECSM = 4, F_PROGRESS = 16, F_QKVB = 80, F_OB = 96, F_OA = 112, F_PART = 176, F_SIDEQ = 208, F_TAILQ = 256, F_COUNT = 304 };
__device__ uint32_t g_flags[F_COUNT];
__device__ __align__(16) uint32_t g_arrivals[4];

#define STAMP(k) do {} while (0)
#define STAMPD(k, x) do {} while (0)
#define PSTAMP(k) do {} while (0)
#define KENTER(k) do {} while (0)
#define KEXIT(k) do {} while (0)
#define KMARK(k) do {} while (0)

__device__ __forceinline__ uint32_t class_off(uint64_t a, uint32_t c) {
    return ((__popc((uint32_t)a & 0xB3000u) ^ c) & 1u) << 12;
}
__device__ __forceinline__ uint32_t smem_u32(const void* p) { return (uint32_t)__cvta_generic_to_shared(p); }
__device__ __forceinline__ uint32_t pack_bf16(float lo, float hi) {
    uint32_t r;
    asm("cvt.rn.bf16x2.f32 %0, %1, %2;" : "=r"(r) : "f"(hi), "f"(lo));
    return r;
}
__device__ __forceinline__ float ex2(float x) {
    float y;
    asm("ex2.approx.ftz.f32 %0, %1;" : "=f"(y) : "f"(x));
    return y;
}
__device__ __forceinline__ float rcp(float x) {
    float y;
    asm("rcp.approx.ftz.f32 %0, %1;" : "=f"(y) : "f"(x));
    return y;
}
__device__ __forceinline__ uint32_t clock32() {
    uint32_t t;
    asm volatile("mov.u32 %0, %%clock;" : "=r"(t));
    return t;
}
__device__ __forceinline__ uint32_t clock_lo() {
    unsigned long long t;
    asm volatile("mov.u64 %0, %%clock64;" : "=l"(t));
    return (uint32_t)t;
}
__device__ __forceinline__ uint32_t clock_after(uint32_t x) {
    uint32_t t;
    asm volatile("{\n.reg .pred p;\nsetp.eq.u32 p, %1, 0x12345678;\n@p exit;\nmov.u32 %0, %%clock;\n}" : "=r"(t) : "r"(x) : "memory");
    return t;
}
__device__ __forceinline__ uint32_t opaque(uint32_t x) { return __shfl_sync(~0u, x, threadIdx.x & 31); }
__device__ __forceinline__ uint32_t uniform(uint32_t x) { return __shfl_sync(~0u, x + (threadIdx.x & 31), 0); }
__device__ __forceinline__ float bf16_lo(uint32_t w) { return __uint_as_float(w << 16); }
__device__ __forceinline__ float bf16_hi(uint32_t w) { return __uint_as_float(w & 0xFFFF0000u); }

__device__ __forceinline__ void mbar_init(uint32_t bar, uint32_t cnt) {
    asm volatile("mbarrier.init.shared::cta.b64 [%0], %1;" ::"r"(bar), "r"(cnt) : "memory");
}
__device__ __forceinline__ void mbar_arrive(uint32_t bar) {
    asm volatile("mbarrier.arrive.shared::cta.b64 _, [%0];" ::"r"(bar) : "memory");
}
__device__ __forceinline__ void mbar_arrive_expect_tx(uint32_t bar, uint32_t bytes) {
    asm volatile("mbarrier.arrive.expect_tx.shared::cta.b64 _, [%0], %1;" ::"r"(bar), "r"(bytes) : "memory");
}
__device__ __forceinline__ bool mbar_try_wait(uint32_t bar, uint32_t parity) {
    uint32_t ok;
    asm volatile(
        "{\n.reg .pred p;\n"
        "mbarrier.try_wait.parity.shared::cta.b64 p, [%1], %2;\n"
        "selp.u32 %0, 1, 0, p;\n}"
        : "=r"(ok) : "r"(bar), "r"(parity) : "memory");
    return ok != 0;
}
__device__ __forceinline__ bool mbar_test_wait(uint32_t bar, uint32_t parity) {
    uint32_t ok;
    asm volatile(
        "{\n.reg .pred p;\n"
        "mbarrier.test_wait.parity.shared::cta.b64 p, [%1], %2;\n"
        "selp.u32 %0, 1, 0, p;\n}"
        : "=r"(ok) : "r"(bar), "r"(parity) : "memory");
    return ok != 0;
}
__device__ __forceinline__ void mbar_wait(uint32_t bar, uint32_t parity) {
    uint32_t n = 0;
    while (!mbar_try_wait(bar, parity)) {
        if (++n > SPIN_LIMIT) __trap();
    }
}
__device__ __forceinline__ void mbar_wait_sleep(uint32_t bar, uint32_t parity) {
    uint32_t n = 0;
    while (!mbar_try_wait(bar, parity)) {
        __nanosleep(20);
        if (++n > SPIN_LIMIT) __trap();
    }
}
__device__ __forceinline__ void mbar_wait_bounded(uint32_t bar, uint32_t parity) {
    for (uint32_t n = 0; n < (1u << 20) && !mbar_try_wait(bar, parity); n++) {}
}
__device__ __forceinline__ bool elect_one() {
    uint32_t ok;
    asm volatile("{\n.reg .pred p;\nelect.sync _|p, 0xFFFFFFFF;\nselp.u32 %0, 1, 0, p;\n}" : "=r"(ok));
    return ok != 0;
}
__device__ __forceinline__ void named_bar_sync(int id, int nthreads) {
    asm volatile("bar.sync %0, %1;" ::"r"(id), "r"(nthreads) : "memory");
}
__device__ __forceinline__ uint32_t mapa(uint32_t addr, uint32_t rank) {
    uint32_t r;
    asm volatile("mapa.shared::cluster.u32 %0, %1, %2;" : "=r"(r) : "r"(addr), "r"(rank));
    return r;
}

__device__ __forceinline__ void tma_load_2d(uint32_t dst, const CUtensorMap* tm, int c0, int c1, uint32_t bar) {
    asm volatile(
        "cp.async.bulk.tensor.2d.shared::cluster.global.mbarrier::complete_tx::bytes [%0], [%1, {%3, %4}], [%2];"
        ::"r"(dst), "l"(tm), "r"(bar), "r"(c0), "r"(c1) : "memory");
}
__device__ __forceinline__ void tma_load_3d(uint32_t dst, const CUtensorMap* tm, int c0, int c1, int c2, uint32_t bar) {
    asm volatile(
        "cp.async.bulk.tensor.3d.shared::cluster.global.mbarrier::complete_tx::bytes [%0], [%1, {%3, %4, %5}], [%2];"
        ::"r"(dst), "l"(tm), "r"(bar), "r"(c0), "r"(c1), "r"(c2) : "memory");
}
__device__ __forceinline__ void tma_store_2d(const CUtensorMap* tm, uint32_t src, int c0, int c1) {
    asm volatile("cp.async.bulk.tensor.2d.global.shared::cta.bulk_group [%0, {%2, %3}], [%1];"
                 ::"l"(tm), "r"(src), "r"(c0), "r"(c1) : "memory");
}
__device__ __forceinline__ void bulk_store(void* dst, uint32_t src, uint32_t bytes) {
    asm volatile("cp.async.bulk.global.shared::cta.bulk_group [%0], [%1], %2;" ::"l"(dst), "r"(src), "r"(bytes) : "memory");
}
__device__ __forceinline__ void bulk_commit() { asm volatile("cp.async.bulk.commit_group;" ::: "memory"); }
__device__ __forceinline__ void bulk_wait_read_all() { asm volatile("cp.async.bulk.wait_group.read 0;" ::: "memory"); }
__device__ __forceinline__ void bulk_wait_all() { asm volatile("cp.async.bulk.wait_group 0;" ::: "memory"); }
__device__ __forceinline__ void bulk_load(uint32_t dst, const void* src, uint32_t bytes, uint32_t bar) {
    asm volatile("cp.async.bulk.shared::cluster.global.mbarrier::complete_tx::bytes [%0], [%1], %2, [%3];"
                 ::"r"(dst), "l"(src), "r"(bytes), "r"(bar) : "memory");
}

__device__ __forceinline__ void ldsm_x4(uint32_t addr, uint32_t& r0, uint32_t& r1, uint32_t& r2, uint32_t& r3) {
    asm volatile("ldmatrix.sync.aligned.m8n8.x4.shared.b16 {%0,%1,%2,%3}, [%4];"
                 : "=r"(r0), "=r"(r1), "=r"(r2), "=r"(r3) : "r"(addr) : "memory");
}
__device__ __forceinline__ void ldsm_x4_t(uint32_t addr, uint32_t& r0, uint32_t& r1, uint32_t& r2, uint32_t& r3) {
    asm volatile("ldmatrix.sync.aligned.m8n8.x4.trans.shared.b16 {%0,%1,%2,%3}, [%4];"
                 : "=r"(r0), "=r"(r1), "=r"(r2), "=r"(r3) : "r"(addr) : "memory");
}
__device__ __forceinline__ void stsm_x4(uint32_t addr, uint32_t r0, uint32_t r1, uint32_t r2, uint32_t r3) {
    asm volatile("stmatrix.sync.aligned.m8n8.x4.shared.b16 [%0], {%1,%2,%3,%4};"
                 ::"r"(addr), "r"(r0), "r"(r1), "r"(r2), "r"(r3) : "memory");
}
__device__ __forceinline__ void mma16816(float* d, uint32_t a0, uint32_t a1, uint32_t a2, uint32_t a3,
                                         uint32_t b0, uint32_t b1) {
    asm volatile(
        "mma.sync.aligned.m16n8k16.row.col.f32.bf16.bf16.f32 {%0,%1,%2,%3}, {%4,%5,%6,%7}, {%8,%9}, {%0,%1,%2,%3};"
        : "+f"(d[0]), "+f"(d[1]), "+f"(d[2]), "+f"(d[3])
        : "r"(a0), "r"(a1), "r"(a2), "r"(a3), "r"(b0), "r"(b1));
}
__device__ __forceinline__ void mma1688(float* d, uint32_t a0, uint32_t a1, uint32_t b0) {
    asm volatile("mma.sync.aligned.m16n8k8.row.col.f32.bf16.bf16.f32 {%0,%1,%2,%3}, {%4,%5}, {%6}, {%0,%1,%2,%3};"
                 : "+f"(d[0]), "+f"(d[1]), "+f"(d[2]), "+f"(d[3]) : "r"(a0), "r"(a1), "r"(b0));
}
__device__ __forceinline__ uint2 lds64(uint32_t addr) {
    uint2 v;
    asm volatile("ld.volatile.shared.v2.b32 {%0,%1}, [%2];" : "=r"(v.x), "=r"(v.y) : "r"(addr) : "memory");
    return v;
}
__device__ __forceinline__ uint4 lds128(uint32_t addr) {
    uint4 v;
    asm volatile("ld.volatile.shared.v4.b32 {%0,%1,%2,%3}, [%4];" : "=r"(v.x), "=r"(v.y), "=r"(v.z), "=r"(v.w) : "r"(addr) : "memory");
    return v;
}
__device__ __forceinline__ void sts32(uint32_t addr, uint32_t x) {
    asm volatile("st.volatile.shared.b32 [%0], %1;" ::"r"(addr), "r"(x) : "memory");
}
__device__ __forceinline__ void sts64(uint32_t addr, uint32_t x, uint32_t y) {
    asm volatile("st.volatile.shared.v2.b32 [%0], {%1,%2};" ::"r"(addr), "r"(x), "r"(y) : "memory");
}
__device__ __forceinline__ void sts128(uint32_t addr, uint32_t x, uint32_t y, uint32_t z, uint32_t w) {
    asm volatile("st.volatile.shared.v4.b32 [%0], {%1,%2,%3,%4};" ::"r"(addr), "r"(x), "r"(y), "r"(z), "r"(w) : "memory");
}
__device__ __forceinline__ void st_async_v2(uint32_t addr, uint32_t x, uint32_t y, uint32_t bar) {
    asm volatile("st.async.weak.shared::cluster.mbarrier::complete_tx::bytes.v2.b32 [%0], {%1,%2}, [%3];"
                 ::"r"(addr), "r"(x), "r"(y), "r"(bar) : "memory");
}
__device__ __forceinline__ void st_relaxed_v4(void* p, uint32_t x) {
    asm volatile("st.relaxed.gpu.global.v4.b32 [%0], {%1,%1,%1,%1};" ::"l"(p), "r"(x) : "memory");
}
__device__ __forceinline__ uint32_t ld_relaxed_b32(const void* p) {
    uint32_t v;
    asm volatile("ld.relaxed.gpu.global.b32 %0, [%1];" : "=r"(v) : "l"(p) : "memory");
    return v;
}
__device__ __forceinline__ uint32_t lds32_volatile(uint32_t addr) {
    uint32_t v;
    asm volatile("ld.volatile.shared.b32 %0, [%1];" : "=r"(v) : "r"(addr) : "memory");
    return v;
}
__device__ __forceinline__ void st_relaxed_b32(void* p, uint32_t x) {
    asm volatile("st.relaxed.gpu.global.b32 [%0], %1;" ::"l"(p), "r"(x) : "memory");
}

__device__ __forceinline__ uint32_t ld_acquire_b32(const void* p) {
    uint32_t v;
    asm volatile("ld.acquire.gpu.global.b32 %0, [%1];" : "=r"(v) : "l"(p) : "memory");
    return v;
}
__device__ __forceinline__ void wait_flag(const uint32_t* p, uint32_t target) {
    uint32_t n = 0;
    while (ld_acquire_b32(p) < target) {
        __nanosleep(64);
        if (++n > SPIN_LIMIT) __trap();
    }
}
__device__ __forceinline__ void signal_flag(uint32_t* p) {
    asm volatile("red.release.gpu.global.add.u32 [%0], 1;" ::"l"(p) : "memory");
}
__device__ __forceinline__ void signal_bulk(uint32_t* p) {
    asm volatile("red.relaxed.gpu.global.add.u32 [%0], 1;" ::"l"(p) : "memory");
}
__device__ __forceinline__ bool next_to_rec(const uint32_t* flags) {
    uint32_t smid;
    asm volatile("mov.u32 %0, %%smid;" : "=r"(smid));
    smid ^= 1;
    return smid < 384 && ((ld_relaxed_b32(flags + F_RECSM + (smid >> 5)) >> (smid & 31)) & 1);
}
__device__ __forceinline__ void pdl_launch_dependents() { asm volatile("griddepcontrol.launch_dependents;" ::: "memory"); }

constexpr int BM = 128, BK = 64;
constexpr int A_STAGE = BM * BK * 2;
template <int BN> struct GemmCfg {
    static constexpr int STAGES = BN == 256 ? 3 : 6;
    static constexpr int STAGE = A_STAGE + BK * BN * 2;
    static constexpr int EPI_WARP = 16 * BN * 2;
    static constexpr int SMEM = STAGES * STAGE + 8 * EPI_WARP + 1024 + 512;
};

struct SideProb {
    CUtensorMap tmA, tmB, tmC;
    int n_split;
    int n_tiles, k_blocks, k_total, c_col0;
    const uint32_t* dep;
    uint32_t dep_target;
    int dep_n;
    uint32_t* sig;
    float* part;
    uint32_t* part_flag;
};
struct SideSeg { int prob, m0, m1; };
constexpr int SIDE_MAX_SEG = 3;
struct SideParams {
    SideProb prob[3];
    SideSeg seg[SIDE_MAX_SEG];
    int nseg;
    int spare_seg;
    const uint32_t* flags;
    uint32_t* queue;
};
static_assert(sizeof(SideParams) <= 4096, "kernel parameter limit");

__device__ __forceinline__ uint64_t make_desc(uint32_t addr, uint32_t lbo, uint32_t sbo) {
    return (uint64_t)((addr & 0x3FFFF) >> 4) | ((uint64_t)(lbo >> 4) << 16) | ((uint64_t)(sbo >> 4) << 32) | (1ull << 62);
}

__device__ __forceinline__ void wgmma_m64n256k16(float (&d)[128], uint64_t da, uint64_t db, int scale_d) {
    asm volatile(
        "{\n.reg .pred p;\nsetp.ne.b32 p, %130, 0;\n"
        "wgmma.mma_async.sync.aligned.m64n256k16.f32.bf16.bf16 "
        "{%0,%1,%2,%3,%4,%5,%6,%7,%8,%9,%10,%11,%12,%13,%14,%15,"
        "%16,%17,%18,%19,%20,%21,%22,%23,%24,%25,%26,%27,%28,%29,%30,%31,"
        "%32,%33,%34,%35,%36,%37,%38,%39,%40,%41,%42,%43,%44,%45,%46,%47,"
        "%48,%49,%50,%51,%52,%53,%54,%55,%56,%57,%58,%59,%60,%61,%62,%63,"
        "%64,%65,%66,%67,%68,%69,%70,%71,%72,%73,%74,%75,%76,%77,%78,%79,"
        "%80,%81,%82,%83,%84,%85,%86,%87,%88,%89,%90,%91,%92,%93,%94,%95,"
        "%96,%97,%98,%99,%100,%101,%102,%103,%104,%105,%106,%107,%108,%109,%110,%111,"
        "%112,%113,%114,%115,%116,%117,%118,%119,%120,%121,%122,%123,%124,%125,%126,%127},"
        " %128, %129, p, 1, 1, 0, 1;\n}\n"
        : "+f"(d[0]), "+f"(d[1]), "+f"(d[2]), "+f"(d[3]), "+f"(d[4]), "+f"(d[5]), "+f"(d[6]), "+f"(d[7]),
          "+f"(d[8]), "+f"(d[9]), "+f"(d[10]), "+f"(d[11]), "+f"(d[12]), "+f"(d[13]), "+f"(d[14]), "+f"(d[15]),
          "+f"(d[16]), "+f"(d[17]), "+f"(d[18]), "+f"(d[19]), "+f"(d[20]), "+f"(d[21]), "+f"(d[22]), "+f"(d[23]),
          "+f"(d[24]), "+f"(d[25]), "+f"(d[26]), "+f"(d[27]), "+f"(d[28]), "+f"(d[29]), "+f"(d[30]), "+f"(d[31]),
          "+f"(d[32]), "+f"(d[33]), "+f"(d[34]), "+f"(d[35]), "+f"(d[36]), "+f"(d[37]), "+f"(d[38]), "+f"(d[39]),
          "+f"(d[40]), "+f"(d[41]), "+f"(d[42]), "+f"(d[43]), "+f"(d[44]), "+f"(d[45]), "+f"(d[46]), "+f"(d[47]),
          "+f"(d[48]), "+f"(d[49]), "+f"(d[50]), "+f"(d[51]), "+f"(d[52]), "+f"(d[53]), "+f"(d[54]), "+f"(d[55]),
          "+f"(d[56]), "+f"(d[57]), "+f"(d[58]), "+f"(d[59]), "+f"(d[60]), "+f"(d[61]), "+f"(d[62]), "+f"(d[63]),
          "+f"(d[64]), "+f"(d[65]), "+f"(d[66]), "+f"(d[67]), "+f"(d[68]), "+f"(d[69]), "+f"(d[70]), "+f"(d[71]),
          "+f"(d[72]), "+f"(d[73]), "+f"(d[74]), "+f"(d[75]), "+f"(d[76]), "+f"(d[77]), "+f"(d[78]), "+f"(d[79]),
          "+f"(d[80]), "+f"(d[81]), "+f"(d[82]), "+f"(d[83]), "+f"(d[84]), "+f"(d[85]), "+f"(d[86]), "+f"(d[87]),
          "+f"(d[88]), "+f"(d[89]), "+f"(d[90]), "+f"(d[91]), "+f"(d[92]), "+f"(d[93]), "+f"(d[94]), "+f"(d[95]),
          "+f"(d[96]), "+f"(d[97]), "+f"(d[98]), "+f"(d[99]), "+f"(d[100]), "+f"(d[101]), "+f"(d[102]), "+f"(d[103]),
          "+f"(d[104]), "+f"(d[105]), "+f"(d[106]), "+f"(d[107]), "+f"(d[108]), "+f"(d[109]), "+f"(d[110]), "+f"(d[111]),
          "+f"(d[112]), "+f"(d[113]), "+f"(d[114]), "+f"(d[115]), "+f"(d[116]), "+f"(d[117]), "+f"(d[118]), "+f"(d[119]),
          "+f"(d[120]), "+f"(d[121]), "+f"(d[122]), "+f"(d[123]), "+f"(d[124]), "+f"(d[125]), "+f"(d[126]), "+f"(d[127])
        : "l"(da), "l"(db), "r"(scale_d));
}

__device__ __forceinline__ void wgmma_m64n128k16(float (&d)[64], uint64_t da, uint64_t db, int scale_d) {
    asm volatile(
        "{\n.reg .pred p;\nsetp.ne.b32 p, %66, 0;\n"
        "wgmma.mma_async.sync.aligned.m64n128k16.f32.bf16.bf16 "
        "{%0,%1,%2,%3,%4,%5,%6,%7,%8,%9,%10,%11,%12,%13,%14,%15,"
        "%16,%17,%18,%19,%20,%21,%22,%23,%24,%25,%26,%27,%28,%29,%30,%31,"
        "%32,%33,%34,%35,%36,%37,%38,%39,%40,%41,%42,%43,%44,%45,%46,%47,"
        "%48,%49,%50,%51,%52,%53,%54,%55,%56,%57,%58,%59,%60,%61,%62,%63},"
        " %64, %65, p, 1, 1, 0, 1;\n}\n"
        : "+f"(d[0]), "+f"(d[1]), "+f"(d[2]), "+f"(d[3]), "+f"(d[4]), "+f"(d[5]), "+f"(d[6]), "+f"(d[7]),
          "+f"(d[8]), "+f"(d[9]), "+f"(d[10]), "+f"(d[11]), "+f"(d[12]), "+f"(d[13]), "+f"(d[14]), "+f"(d[15]),
          "+f"(d[16]), "+f"(d[17]), "+f"(d[18]), "+f"(d[19]), "+f"(d[20]), "+f"(d[21]), "+f"(d[22]), "+f"(d[23]),
          "+f"(d[24]), "+f"(d[25]), "+f"(d[26]), "+f"(d[27]), "+f"(d[28]), "+f"(d[29]), "+f"(d[30]), "+f"(d[31]),
          "+f"(d[32]), "+f"(d[33]), "+f"(d[34]), "+f"(d[35]), "+f"(d[36]), "+f"(d[37]), "+f"(d[38]), "+f"(d[39]),
          "+f"(d[40]), "+f"(d[41]), "+f"(d[42]), "+f"(d[43]), "+f"(d[44]), "+f"(d[45]), "+f"(d[46]), "+f"(d[47]),
          "+f"(d[48]), "+f"(d[49]), "+f"(d[50]), "+f"(d[51]), "+f"(d[52]), "+f"(d[53]), "+f"(d[54]), "+f"(d[55]),
          "+f"(d[56]), "+f"(d[57]), "+f"(d[58]), "+f"(d[59]), "+f"(d[60]), "+f"(d[61]), "+f"(d[62]), "+f"(d[63])
        : "l"(da), "l"(db), "r"(scale_d));
}
template <int BN> struct WgmmaOp;
template <> struct WgmmaOp<256> {
    static __device__ __forceinline__ void run(float (&d)[128], uint64_t a, uint64_t b, int sc) { wgmma_m64n256k16(d, a, b, sc); }
};
template <> struct WgmmaOp<128> {
    static __device__ __forceinline__ void run(float (&d)[64], uint64_t a, uint64_t b, int sc) { wgmma_m64n128k16(d, a, b, sc); }
};

struct StoreRec {
    uint64_t dst;
    uint64_t flag;
    int kind;
    int pad;
};
struct EpiCtx { uint32_t buf, rec, st_full, st_empty; uint32_t it; int lane; };
template <int N>
__device__ __forceinline__ void epi_hand_over(const float (&acc)[N], EpiCtx& e, uint64_t dst, uint64_t flag, int kind) {
    mbar_wait(e.st_empty, (e.it & 1) ^ 1);
    const int mi = e.lane >> 3, row = (mi & 1) * 8 + (e.lane & 7);
    #pragma unroll
    for (int j = 0; j < N / 4; j += 2) {
        const int chunk = (j & 7) + (mi >> 1);
        stsm_x4(e.buf + (j >> 3) * 2048 + row * 128 + ((chunk ^ (row & 7)) << 4),
                pack_bf16(acc[4 * j], acc[4 * j + 1]), pack_bf16(acc[4 * j + 2], acc[4 * j + 3]),
                pack_bf16(acc[4 * j + 4], acc[4 * j + 5]), pack_bf16(acc[4 * j + 6], acc[4 * j + 7]));
    }
    if (e.lane == 0) {
        asm volatile("st.shared.v2.b64 [%0], {%1, %2};" ::"r"(e.rec), "l"(dst), "l"(flag) : "memory");
        asm volatile("st.shared.b32 [%0], %1;" ::"r"(e.rec + 16), "r"(kind) : "memory");
    }
    asm volatile("fence.proxy.async.shared::cta;" ::: "memory");
    __syncwarp();
    if (e.lane == 0) mbar_arrive(e.st_full);
    e.it++;
}
__device__ __forceinline__ void epi_exit(EpiCtx& e) {
    mbar_wait(e.st_empty, (e.it & 1) ^ 1);
    if (e.lane == 0) {
        asm volatile("st.shared.b32 [%0], %1;" ::"r"(e.rec + 16), "r"(-1) : "memory");
        mbar_arrive(e.st_full);
    }
}
template <int BN>
__device__ __forceinline__ void gemm_mainloop(float (&acc)[BN / 2], int k_blocks, uint32_t sbase, uint32_t bar_base, int cw,
                                              bool elected, int& stage, uint32_t& phase) {
    using C = GemmCfg<BN>;
    auto release = [&](int st) { mbar_arrive(bar_base + 8 * (C::STAGES + st)); };
    int prev_stage = -1;
    for (int kb = 0; kb < k_blocks; kb++) {
        mbar_wait(bar_base + 8 * stage, phase);
        const uint32_t sa = sbase + stage * C::STAGE + cw * (64 * 128);
        const uint32_t sb = sbase + stage * C::STAGE + A_STAGE;
        asm volatile("wgmma.fence.sync.aligned;" ::: "memory");
        #pragma unroll
        for (int kk = 0; kk < BK / 16; kk++)
            WgmmaOp<BN>::run(acc, make_desc(sa + kk * 32, 16, 1024), make_desc(sb + kk * 2048, 8192, 1024), (kb | kk) != 0);
        asm volatile("wgmma.commit_group.sync.aligned;" ::: "memory");
        asm volatile("wgmma.wait_group.sync.aligned 1;" ::: "memory");
        if (prev_stage >= 0 && elected) release(prev_stage);
        prev_stage = stage;
        if (++stage == C::STAGES) { stage = 0; phase ^= 1; }
    }
    asm volatile("wgmma.wait_group.sync.aligned 0;" ::: "memory");
    if (elected) release(prev_stage);
}
template <int BN>
__device__ __forceinline__ void store_warp(uint32_t epi_base, uint32_t rec_base, uint32_t st_full, uint32_t st_empty, int lane,
                                           const uint8_t* tmaps, int tstride) {
    for (uint32_t it = 0;; it++) {
        mbar_wait(st_full, it & 1);
        uint64_t dst = 0, flag = 0;
        int kind = -1;
        if (lane < 8) {
            const uint32_t rec = rec_base + lane * 32;
            asm volatile("ld.volatile.shared.v2.b64 {%0, %1}, [%2];" : "=l"(dst), "=l"(flag) : "r"(rec) : "memory");
            kind = (int)lds32_volatile(rec + 16);
        }
        if (__shfl_sync(~0u, kind, 0) < 0) break;
        if (lane < 8) {
            const uint32_t buf = epi_base + lane * GemmCfg<BN>::EPI_WARP;
            #pragma unroll
            for (int q = 0; q < BN / 64; q++) {
                tma_store_2d(reinterpret_cast<const CUtensorMap*>(tmaps + (kind - 1) * tstride), buf + q * 2048,
                                  (int)(uint32_t)dst + q * 64, (int)(dst >> 32));
            }
            bulk_commit();
            bulk_wait_read_all();
            mbar_arrive(st_empty);
            if (flag) {
                bulk_wait_all();
                signal_bulk(reinterpret_cast<uint32_t*>(flag));
            }
        }
        __syncwarp();
    }
    if (lane < 8) bulk_wait_all();
}

#define SCHED_AHEAD 4
template <int BN>
__global__ void __launch_bounds__(384, 1) side_gemm_kernel(const __grid_constant__ SideParams p) {
    using C = GemmCfg<BN>;
    extern __shared__ uint8_t smem_raw[];
    const uint32_t sbase = (smem_u32(smem_raw) + 1023) & ~1023u;
    const uint32_t epi_base = sbase + C::STAGES * C::STAGE;
    const uint32_t bar_base = epi_base + 8 * C::EPI_WARP;
    const uint32_t tfull = bar_base + 16 * C::STAGES, tempty = tfull + 16, tslot = tempty + 16, twant = tslot + 8;
    const uint32_t st_full = bar_base + 192, st_empty = st_full + 8, rec_base = bar_base + 256;
    const int tid = threadIdx.x, wg = tid >> 7;
    if (tid == 0) {
        for (int s = 0; s < C::STAGES; s++) { mbar_init(bar_base + 8 * s, 1); mbar_init(bar_base + 8 * (C::STAGES + s), 2); }
        for (int s = 0; s < 2; s++) { mbar_init(tfull + 8 * s, 1); mbar_init(tempty + 8 * s, 3); }
        mbar_init(twant, 1);
        mbar_init(st_full, 8);
        mbar_init(st_empty, 8);
        asm volatile("fence.mbarrier_init.release.cluster;" ::: "memory");
        pdl_launch_dependents();
    }
    __syncthreads();
    KENTER(BN == 256 ? 2 : 4);

    if (wg == 0) {
        asm volatile("setmaxnreg.dec.sync.aligned.u32 40;");
        if (tid == 0) {
            int stage = 0; uint32_t phase = 1;
            for (uint32_t it = 0;; it++) {
                mbar_wait(tfull + 8 * (it & 1), (it >> 1) & 1);
                const int code = (int)lds32_volatile(tslot + 4 * (it & 1));
                mbar_arrive(tempty + 8 * (it & 1));
                if (code < 0) break;
                const SideProb& q = p.prob[code >> 16];
                const int mt = (code >> 8) & 255, nt = code & 255;
                asm volatile("fence.proxy.async.global;" ::: "memory");
                const int kb0 = nt / q.n_split * q.k_blocks, nkb = nt + q.n_split < q.n_tiles ? q.k_blocks : q.k_total - kb0;
                for (int kb = 0; kb < nkb; kb++) {
                    if (kb == nkb - SCHED_AHEAD) mbar_arrive(twant);
                    mbar_wait(bar_base + 8 * (C::STAGES + stage), phase);
                    const uint32_t sa = sbase + stage * C::STAGE, fb = bar_base + 8 * stage;
                    mbar_arrive_expect_tx(fb, C::STAGE);
                    const int k0 = (kb0 + kb) * BK;
                    tma_load_2d(sa, &q.tmA, k0, mt * BM, fb);
                    tma_load_3d(sa + A_STAGE, &q.tmB, 0, k0, nt % q.n_split * (BN / 64), fb);
                    if (++stage == C::STAGES) { stage = 0; phase ^= 1; }
                }
            }
        } else if (tid >= 64 && tid < 96) {
            const int lane = tid & 31;
            const bool spare = p.spare_seg < 3 && next_to_rec(p.flags);
            uint32_t ntl[2], tgt[2], prb[2];
            const uint32_t* dp[2];
            #pragma unroll
            for (int u = 0; u < 2; u++) {
                const int g = u * 2 + (lane >> 4), mt = lane & 15;
                const bool on = g < p.nseg && mt >= p.seg[g < p.nseg ? g : 0].m0 && mt < p.seg[g < p.nseg ? g : 0].m1;
                prb[u] = p.seg[on ? g : 0].prob;
                const SideProb& q = p.prob[prb[u]];
                ntl[u] = on && !(g >= p.spare_seg && spare) ? q.n_tiles : 0;
                tgt[u] = on && q.dep ? q.dep_target : 0;
                dp[u] = tgt[u] ? q.dep + (mt + 1) * q.dep_n - 1 : p.queue;
            }
            for (uint32_t it = 0;; it++) {
                if (it > 0) mbar_wait_sleep(twant, (it - 1) & 1);
                int code = -1;
                for (uint32_t tries = 0; code < 0; tries++) {
                    const uint32_t c0 = ld_relaxed_b32(p.queue + lane), c1 = ld_relaxed_b32(p.queue + 32 + (lane & 15));
                    const uint32_t d0 = ld_relaxed_b32(dp[0]), d1 = ld_relaxed_b32(dp[1]);
                    const uint64_t left = __ballot_sync(~0u, c0 < ntl[0]) | (uint64_t)__ballot_sync(~0u, c1 < ntl[1]) << 32;
                    uint64_t ready = left & (__ballot_sync(~0u, d0 >= tgt[0]) | (uint64_t)__ballot_sync(~0u, d1 >= tgt[1]) << 32);
                    if (!left) break;
                    if (!ready && (BN == 128 || (left >> (((__ffsll(left) - 1) & ~15) + 16)) == 0)) ready = left;
                    if (!ready) __nanosleep(200);
                    while (ready) {
                        const int e = __ffsll(ready) - 1;
                        const uint32_t n = __shfl_sync(~0u, e < 32 ? ntl[0] : ntl[1], e & 31), pr = __shfl_sync(~0u, e < 32 ? prb[0] : prb[1], e & 31);
                        uint32_t idx = 0;
                        if (lane == 0) idx = atomicAdd(p.queue + e, 1u);
                        idx = __shfl_sync(~0u, idx, 0);
                        if (idx < n) { code = (pr << 16) | ((e & 15) << 8) | idx; break; }
                        for (uint32_t k = idx / n; k > 0; k--) ready &= ready - 1;
                    }
                    if (tries > SPIN_LIMIT) __trap();
                }
                if (code >= 0) {
                    const SideProb& q = p.prob[code >> 16];
                    if (q.dep && lane < q.dep_n) wait_flag(q.dep + ((code >> 8) & 255) * q.dep_n + lane, q.dep_target);
                    __syncwarp();
                }
                if (lane == 0) {
                    mbar_wait(tempty + 8 * (it & 1), ((it >> 1) & 1) ^ 1);
                    asm volatile("st.shared.b32 [%0], %1;" ::"r"(tslot + 4 * (it & 1)), "r"(code) : "memory");
                    mbar_arrive(tfull + 8 * (it & 1));
                }
                __syncwarp();
                if (code < 0) break;
            }
        } else if (tid >= 32 && tid < 64) {
            store_warp<BN>(epi_base, rec_base, st_full, st_empty, tid & 31, reinterpret_cast<const uint8_t*>(&p.prob[0].tmC),
                           (int)sizeof(SideProb));
        }
    } else {
        asm volatile("setmaxnreg.inc.sync.aligned.u32 232;");
        const int cw = wg - 1, lane = tid & 31, wi = (tid >> 5) & 3;
        const bool elected = (tid & 127) == 0;
        int stage = 0; uint32_t phase = 0;
        float acc[BN / 2];
        EpiCtx ectx = {epi_base + (cw * 4 + wi) * C::EPI_WARP, rec_base + (cw * 4 + wi) * 32, st_full, st_empty, 0, lane};
        for (uint32_t it = 0;; it++) {
            mbar_wait(tfull + 8 * (it & 1), (it >> 1) & 1);
            const int code = (int)lds32_volatile(tslot + 4 * (it & 1));
            named_bar_sync(1 + cw, 128);
            if (elected) mbar_arrive(tempty + 8 * (it & 1));
            if (code < 0) break;
            const SideProb& q = p.prob[code >> 16];
            const int mt = (code >> 8) & 255, nt = code & 255;
            gemm_mainloop<BN>(acc, nt + q.n_split < q.n_tiles ? q.k_blocks : q.k_total - nt / q.n_split * q.k_blocks, sbase, bar_base, cw, elected, stage, phase);
            const int row0 = mt * BM + cw * 64 + wi * 16, ntc = nt % q.n_split;
            if (BN == 128 && q.part) {
                const int idx = (mt & 3) * q.n_split + ntc, item = nt / q.n_split, nprev = q.n_tiles / q.n_split - 1;
                float4* part = reinterpret_cast<float4*>(q.part) + (size_t)idx * 2 * (BM * BN / 4) + (tid - 128);
                if (mt == 14 && elected) KMARK(21);
                if (item < nprev) {
                    #pragma unroll
                    for (int j = 0; j < BN / 8; j++)
                        __stcg(part + item * (BM * BN / 4) + j * 256, make_float4(acc[4 * j], acc[4 * j + 1], acc[4 * j + 2], acc[4 * j + 3]));
                    __syncwarp();
                    if (lane == 0) signal_flag(q.part_flag + idx);
                    continue;
                }
                if (lane == 0) wait_flag(q.part_flag + idx, 8 * nprev);
                __syncwarp();
                if (mt == 14 && elected) KMARK(22);
                for (int u = 0; u < nprev; u++) {
                    #pragma unroll
                    for (int j = 0; j < BN / 8; j++) {
                        const float4 v = __ldcg(part + u * (BM * BN / 4) + j * 256);
                        acc[4 * j] += v.x; acc[4 * j + 1] += v.y; acc[4 * j + 2] += v.z; acc[4 * j + 3] += v.w;
                    }
                }
            }
            if (BN == 128 && mt == 14 && elected) KMARK(23);
            epi_hand_over(acc, ectx, ((uint64_t)row0 << 32) | (uint32_t)(q.c_col0 + ntc * BN), q.sig ? (uint64_t)(q.sig + mt) : 0, 1 + (code >> 16));
        }
        epi_exit(ectx);
        if (elected) KEXIT(BN == 256 ? 2 : 4);
    }
}

constexpr int FIN_SPLIT = 8, FIN_KB = HD / BK / FIN_SPLIT;
constexpr int FIN_A1 = FIN_KB * 16384;
constexpr int FIN_A0 = FIN_A1 + FIN_KB * 8192;
constexpr int FIN_BAR = FIN_A0 + 4 * 8192, FIN_SMEM = FIN_BAR + 256;
enum { FB_B = 0, FB_A1 = 64, FB_A0 = 128, FB_E0 = 160, FB_RDY = 192, FB_RED = 208 };
struct FinalParams {
    CUtensorMap tmA, tmB;
    __nv_bfloat16* out;
    const uint32_t* dep;
    uint32_t dep_target;
    int mt;
};
__global__ void __launch_bounds__(384, 1) final_gemm_kernel(const __grid_constant__ FinalParams p) {
    extern __shared__ __align__(1024) uint8_t smem_raw[];
    const uint32_t sbase = smem_u32(smem_raw), bar = sbase + FIN_BAR;
    const int tid = threadIdx.x, wg = tid >> 7;
    const int rank = blockIdx.x % FIN_SPLIT, nt = blockIdx.x / FIN_SPLIT;
    KENTER(5);
    if (tid == 0) {
        for (int s = 0; s < FIN_KB; s++) { mbar_init(bar + FB_B + 8 * s, 1); mbar_init(bar + FB_A1 + 8 * s, 1); }
        for (int s = 0; s < 4; s++) { mbar_init(bar + FB_A0 + 8 * s, 1); mbar_init(bar + FB_E0 + 8 * s, 1); }
        for (int h = 0; h < 2; h++) { mbar_init(bar + FB_RDY + 8 * h, FIN_SPLIT); mbar_init(bar + FB_RED + 8 * h, 1); }
        asm volatile("fence.mbarrier_init.release.cluster;" ::: "memory");
        for (int h = 0; h < 2; h++) mbar_arrive_expect_tx(bar + FB_RED + 8 * h, (FIN_SPLIT - 1) * 4096);
        pdl_launch_dependents();
    }
    __syncthreads();
    asm volatile("barrier.cluster.arrive.relaxed.aligned;" ::: "memory");
    if (wg == 0) {
        auto need = [&](int i) {
            uint32_t n = 0;
            while (ld_acquire_b32(p.dep + i) < p.dep_target) { if (++n > SPIN_LIMIT) __trap(); }
            asm volatile("fence.proxy.async.global;" ::: "memory");
        };
        auto a_load = [&](uint32_t dst, int kb, int seg, uint32_t mb) { tma_load_2d(dst, &p.tmA, (rank * FIN_KB + kb) * BK, p.mt * BM + seg * SEG, mb); };
        if (tid == 0) {
            auto b_load = [&](int kb) {
                mbar_arrive_expect_tx(bar + FB_B + 8 * kb, 16384);
                tma_load_3d(sbase + kb * 16384, &p.tmB, 0, (rank * FIN_KB + kb) * BK, nt * 2, bar + FB_B + 8 * kb);
            };
            const uint32_t f0 = ld_relaxed_b32(p.dep);
            b_load(0);
            need(1);
            if (f0 < p.dep_target) need(0);
            for (int kb = 0; kb < FIN_KB; kb++) {
                if (kb >= 4) mbar_wait(bar + FB_E0 + 8 * (kb & 3), 0);
                mbar_arrive_expect_tx(bar + FB_A0 + 8 * (kb & 3), 8192);
                for (int u = 0; u < 2; u++) a_load(sbase + FIN_A0 + (kb & 3) * 8192 + u * 4096, kb, u, bar + FB_A0 + 8 * (kb & 3));
                if (kb < 3) b_load(kb + 1);
                if (kb == 3) { b_load(4); b_load(5); }
                if (kb == 4 || kb == 5) b_load(kb + 2);
            }
        } else if (tid == 96) {
            need(3);
            for (int kb = 1; kb < FIN_KB; kb += 2) a_load(sbase + FIN_A1 + kb * 8192 + 4096, kb, 3, bar + FB_A1 + 8 * kb);
        } else if (tid == 64) {
            mbar_wait(bar + FB_B + 8 * 3, 0);
            need(2);
            for (int kb = 0; kb < FIN_KB; kb++) {
                mbar_arrive_expect_tx(bar + FB_A1 + 8 * kb, 8192);
                a_load(sbase + FIN_A1 + kb * 8192, kb, 2, bar + FB_A1 + 8 * kb);
            }
            need(3);
            KMARK(15);
            for (int kb = 0; kb < FIN_KB; kb += 2) a_load(sbase + FIN_A1 + kb * 8192 + 4096, kb, 3, bar + FB_A1 + 8 * kb);
        }
        __syncwarp();
        asm volatile("barrier.cluster.wait.aligned;" ::: "memory");
    } else {
        const int h = wg - 1, lane = tid & 31, wi = (tid >> 5) & 3, t128 = tid & 127;
        asm volatile("barrier.cluster.wait.aligned;" ::: "memory");
        float acc[64];
        for (int kb = 0; kb < FIN_KB; kb++) {
            mbar_wait(bar + FB_B + 8 * kb, 0);
            if (h == 0) mbar_wait(bar + FB_A0 + 8 * (kb & 3), kb >> 2); else mbar_wait(bar + FB_A1 + 8 * kb, 0);
            const uint32_t sa = sbase + (h == 0 ? FIN_A0 + (kb & 3) * 8192 : FIN_A1 + kb * 8192), sb = sbase + kb * 16384;
            asm volatile("wgmma.fence.sync.aligned;" ::: "memory");
            #pragma unroll
            for (int kk = 0; kk < BK / 16; kk++)
                wgmma_m64n128k16(acc, make_desc(sa + kk * 32, 16, 1024), make_desc(sb + kk * 2048, 8192, 1024), (kb | kk) != 0);
            asm volatile("wgmma.commit_group.sync.aligned;" ::: "memory");
            asm volatile("wgmma.wait_group.sync.aligned 1;" ::: "memory");
            if (h == 0 && kb >= 1 && kb <= 4 && t128 == 0) mbar_arrive(bar + FB_E0 + 8 * (kb - 1));
        }
        asm volatile("wgmma.wait_group.sync.aligned 0;" ::: "memory");
        const uint32_t red = sbase + FIN_A0;
        auto ready = [&](int i) {
            named_bar_sync(1, 128);
            if (t128 < FIN_SPLIT)
                asm volatile("mbarrier.arrive.relaxed.cluster.shared::cluster.b64 _, [%0];" ::"r"(mapa(bar + FB_RDY + 8 * i, t128)) : "memory");
        };
        if (tid == 256) KMARK(16);
        if (tid == 128) KMARK(19);
        if (h == 0) ready(0);
        mbar_wait(bar + FB_RDY + 8 * h, 0);
        if (tid == 256) KMARK(17);
        #pragma unroll
        for (int q = 0; q < FIN_SPLIT; q++) {
            if (q != rank) {
                const uint32_t dst = mapa(red + (rank - (rank > q ? 1 : 0)) * 4096 + t128 * 16, q), rb = mapa(bar + FB_RED + 8 * h, q);
                #pragma unroll
                for (int j = 0; j < 2; j++)
                    asm volatile("st.async.weak.shared::cluster.mbarrier::complete_tx::bytes.v4.f32 [%0], {%1,%2,%3,%4}, [%5];"
                                 ::"r"(dst + j * 2048), "f"(acc[8 * q + 4 * j]), "f"(acc[8 * q + 4 * j + 1]),
                                   "f"(acc[8 * q + 4 * j + 2]), "f"(acc[8 * q + 4 * j + 3]), "r"(rb) : "memory");
            }
        }
        float o[8];
        #pragma unroll
        for (int q = 0; q < FIN_SPLIT; q++)
            if (q == rank) {
                #pragma unroll
                for (int e = 0; e < 8; e++) o[e] = acc[8 * q + e];
            }
        mbar_wait(bar + FB_RED + 8 * h, 0);
        if (tid == 256) KMARK(18);
        if (tid == 128) KMARK(20);
        #pragma unroll
        for (int sl = 0; sl < FIN_SPLIT - 1; sl++) {
            #pragma unroll
            for (int j = 0; j < 2; j++) {
                const uint4 v = lds128(red + sl * 4096 + j * 2048 + t128 * 16);
                o[4 * j] += __uint_as_float(v.x); o[4 * j + 1] += __uint_as_float(v.y);
                o[4 * j + 2] += __uint_as_float(v.z); o[4 * j + 3] += __uint_as_float(v.w);
            }
        }
        if (h == 0) ready(1);
        __nv_bfloat16* dst = p.out + (size_t)(p.mt * BM + h * 64 + wi * 16 + (lane >> 2)) * (2 * DM) + nt * 128 + rank * 16 + (lane & 3) * 2;
        #pragma unroll
        for (int j = 0; j < 2; j++) {
            *reinterpret_cast<uint32_t*>(dst + j * 8) = pack_bf16(o[4 * j], o[4 * j + 1]);
            *reinterpret_cast<uint32_t*>(dst + (size_t)8 * (2 * DM) + j * 8) = pack_bf16(o[4 * j + 2], o[4 * j + 3]);
        }
        if (t128 == 0) KEXIT(5);
    }
}

#define POLL_DELAY 2
#define FETCH_DELAY 450
#define AT_PF 7
#define AT_FIRST 4
#define WO_PF 12
#define WO_PFA 6
#define WO_PFB_DELAY 60
#define V_EARLY 6
constexpr int REC_THREADS = 256;
constexpr uint32_t POLL_LIMIT = 1u << 16;
constexpr int NREG = 24;
__host__ __device__ constexpr int reg_idx(int j) { return ((j & 3) - 1) * 8 + (j >> 2); }
constexpr int SM_WQ = 0;
constexpr int SM_WO = 65536;
constexpr int SM_X = SM_WO + 11 * 8192;
constexpr int SM_PARK0 = SM_X, SM_PARK1 = SM_X + 8192;
constexpr int SM_MEM = SM_X + 4 * 4096;
constexpr int SM_RED = SM_X + 8 * 4096;
constexpr int SM_V = SM_X + 12 * 4096;
constexpr int SM_K = SM_X + 14 * 4096;
constexpr int SM_QS = SM_X + 15 * 4096;
constexpr int SM_QK = SM_X + 65536;
constexpr int SM_SP = SM_QK + 2048;
constexpr int SM_VM = SM_SP + 2560;
constexpr int SM_O = SM_VM + 2048;
constexpr int SM_SUM = SM_O + 2048;
constexpr int SM_TBL = SM_SUM + 128;
constexpr int SM_BAR = SM_TBL + 512;
constexpr int SM_STAMP = SM_BAR + 224;
constexpr int REC_SMEM = SM_STAMP;
static_assert(REC_SMEM <= 232448, "shared memory");
enum { BAR_V = 0, BAR_X = 8, BAR_P0 = 16, BAR_WQ = 40, BAR_WO = 48, BAR_XG = 56, BAR_F0 = 88, BAR_F3 = 96, BAR_VF = 104,
       BAR_M = 112, BAR_GO = 144, BAR_PK = 152, BAR_VM = 160, BAR_SELF = 168, BAR_TPUB = 176, BAR_MIN = 176, BAR_PUB = 192 };

template <int V> struct IntC { static constexpr int value = V; };
template <int I, int N, typename F> __device__ __forceinline__ void sfor(F&& f) {
    if constexpr (I < N) { f(IntC<I>{}); sfor<I + 1, N>(f); }
}

struct RecParams {
    CUtensorMap tmW[3];
    CUtensorMap tmWo;
    CUtensorMap tmX;
    const __nv_bfloat16* mem0;
    __nv_bfloat16* qkv_tok;
    __nv_bfloat16* kv_mem;
    uint8_t* xchg;
    uint32_t* flags;
    uint32_t one[2];
    uint32_t* arrivals;
};

__device__ __forceinline__ void mma_a(float* d, const uint32_t* a, uint32_t b0, uint32_t b1) {
    mma16816(d, a[0], a[1], a[2], a[3], b0, b1);
}
__device__ __forceinline__ void ldsm4(uint32_t addr, uint32_t* r) { ldsm_x4(addr, r[0], r[1], r[2], r[3]); }
__device__ __forceinline__ void ldsm4t(uint32_t addr, uint32_t* r) { ldsm_x4_t(addr, r[0], r[1], r[2], r[3]); }
template <int OFF> __device__ __forceinline__ void repoll_v2(uint2& v, const uint8_t* p) {
    asm volatile("{\n.reg .pred q;\nsetp.eq.u32 q, %1, 0xFFFFFFFF;\n@q ld.relaxed.gpu.global.v2.b32 {%0,%1}, [%2+%3];\n}"
                 : "+r"(v.x), "+r"(v.y) : "l"(p), "n"(OFF) : "memory");
}
__device__ __forceinline__ uint32_t max3(uint32_t a, uint32_t b, uint32_t c) { return max(max(a, b), c); }
__device__ __forceinline__ uint32_t pub_slot(int s) { return (s & 1) * XCHG_SLOT + ((s >> 1) & 1) * PUB_BYTES; }

__device__ __forceinline__ uint8_t* xaddr(uint32_t lo, uint32_t hi) {
    uint64_t a;
    asm("mov.b64 %0, {%1, %2};" : "=l"(a) : "r"(lo), "r"(hi));
    return reinterpret_cast<uint8_t*>(a);
}
template <int N> __device__ __forceinline__ uint32_t delay_zero(uint32_t a) {
    uint32_t x = a;
    #pragma unroll
    for (int i = 0; i < N; i++) x = lds32_volatile(x);
    return x - a;
}
__device__ __forceinline__ uint32_t fresh(uint32_t x) { asm volatile("" : "+r"(x)); return x; }

__device__ __forceinline__ void sched_fence(uint32_t& x, uint32_t zero) { x ^= clock32() & zero; }

template <int NT> __device__ __forceinline__ uint32_t wo_addr(uint32_t ao, uint32_t a3, int n) {
    return (n % NT == 2 ? a3 : ao + (n % NT) * 32768) + (n / NT) * 1024;
}
template <int NT, int PF>
__device__ __forceinline__ void wo_phase(uint32_t (&st)[8 * NT][4], uint32_t ao, uint32_t a3, uint32_t l16, uint32_t tbl, uint32_t sums,
                                         uint32_t slot, uint32_t xhi, uint32_t third, uint32_t xbar, uint32_t xpar, bool& x_ok, uint32_t wg, uint32_t zero, uint32_t& tok) {
    constexpr int AHEAD = PF > 0 ? PF - NT : 10;
    uint32_t of[4][4];
    uint2 sm;
    uint4 t;
    ldsm4t(l16 + SM_O, of[0]);
    #pragma unroll
    for (int n = PF; n < AHEAD; n++) {
        ldsm4t(wo_addr<NT>(ao, a3, n), st[n]);
        if (n == 2 * NT - 1) ldsm4t(l16 + SM_O + 512, of[1]);
    }
    if (PF >= 2 * NT) ldsm4t(l16 + SM_O + 512, of[1]);
    float acc[NT][4];
    #pragma unroll
    for (int i = 0; i < NT; i++) { acc[i][0] = acc[i][1] = acc[i][2] = acc[i][3] = 0.f; }
    #pragma unroll
    for (int kk = 0; kk < 8; kk++) {
        #pragma unroll
        for (int i = 0; i < NT; i++) {
            const int n = kk * NT + i;
            mma_a(acc[i], st[n], of[kk >> 1][(kk & 1) * 2], of[kk >> 1][(kk & 1) * 2 + 1]);
            if (n + AHEAD >= PF && n + AHEAD < 8 * NT) ldsm4t(wo_addr<NT>(ao, a3, n + AHEAD), st[n + AHEAD]);
        }
        if (kk == 1 || kk == 3) ldsm4t(l16 + SM_O + ((kk >> 1) + 2) * 512, of[(kk >> 1) + 2]);
        if (kk == (NT == 3 ? 5 : 4)) {
            const uint32_t x = fresh(l16);
            sm = lds64(sums + ((x >> 1) & 0x18));
            t = lds128(tbl + ((x >> 3) & 0x30));
            x_ok = mbar_test_wait(xbar, xpar);
        }
    }
    if (NT == 3) {
        sched_fence(tok, zero);
        asm volatile("{\n.reg .pred p;\nsetp.ne.u32 p, %0, 0;\n@p bar.arrive 9, 256;\n}" ::"r"(wg) : "memory");
    }
    const float i0 = rcp(__uint_as_float(sm.x)), i1 = rcp(__uint_as_float(sm.y));
    const uint32_t d = slot + ((fresh(l16) >> 1) & 0x38);
    const uint32_t pl[3] = {t.x + d, t.y + d, t.z + d};
    #pragma unroll
    for (int i = 0; i < NT; i++)
        asm volatile("{\n.reg .pred p;\nsetp.ne.u32 p, %3, 0;\n@p st.relaxed.gpu.global.v2.b32 [%0], {%1,%2};\n}"
                     ::"l"(xaddr(pl[i], xhi)), "r"(pack_bf16(acc[i][0] * i0, acc[i][1] * i1)), "r"(pack_bf16(acc[i][2] * i0, acc[i][3] * i1)),
                       "r"(i < 2 ? 1u : third) : "memory");
}

constexpr uint32_t SMEM_ORIGIN = 1024;
constexpr uint64_t DESC_BASE = (1ull << 16) | (0x40000040ull << 32);
template <int OFFB, int SCALE_D>
__device__ __forceinline__ void wgmma_n32_rs(float (&d)[16], const uint32_t* a, uint32_t one) {
    asm volatile(
        "{\n.reg .b64 db;\nmad.wide.u32 db, %20, %21, %22;\n"
        "wgmma.mma_async.sync.aligned.m64n32k16.f32.bf16.bf16 {%0,%1,%2,%3,%4,%5,%6,%7,%8,%9,%10,%11,%12,%13,%14,%15}, "
        "{%16,%17,%18,%19}, db, %23, 1, 1, 0;\n}"
        : "+f"(d[0]), "+f"(d[1]), "+f"(d[2]), "+f"(d[3]), "+f"(d[4]), "+f"(d[5]), "+f"(d[6]), "+f"(d[7]),
          "+f"(d[8]), "+f"(d[9]), "+f"(d[10]), "+f"(d[11]), "+f"(d[12]), "+f"(d[13]), "+f"(d[14]), "+f"(d[15])
        : "r"(a[0]), "r"(a[1]), "r"(a[2]), "r"(a[3]), "r"(one), "n"((SMEM_ORIGIN + OFFB) >> 4), "l"(DESC_BASE), "n"(SCALE_D));
}
template <int OFFA, int OFFB, int SCALE_D>
__device__ __forceinline__ void wgmma_n32_ss(float (&d)[16], uint32_t one) {
    asm volatile(
        "{\n.reg .b64 da, db;\nmad.wide.u32 da, %16, %17, %19;\nmad.wide.u32 db, %16, %18, %19;\n"
        "wgmma.mma_async.sync.aligned.m64n32k16.f32.bf16.bf16 {%0,%1,%2,%3,%4,%5,%6,%7,%8,%9,%10,%11,%12,%13,%14,%15}, "
        "da, db, %20, 1, 1, 1, 0;\n}"
        : "+f"(d[0]), "+f"(d[1]), "+f"(d[2]), "+f"(d[3]), "+f"(d[4]), "+f"(d[5]), "+f"(d[6]), "+f"(d[7]),
          "+f"(d[8]), "+f"(d[9]), "+f"(d[10]), "+f"(d[11]), "+f"(d[12]), "+f"(d[13]), "+f"(d[14]), "+f"(d[15])
        : "r"(one), "n"((SMEM_ORIGIN + OFFA) >> 4), "n"((SMEM_ORIGIN + OFFB) >> 4), "l"(DESC_BASE), "n"(SCALE_D));
}
template <int WG, int J0, int J1, int I, bool ACC, bool FENCE = true>
__device__ __forceinline__ void token_mma(float (&ta)[2][16], const uint32_t (&wr)[NREG][2][4], uint32_t one) {
    if (FENCE) asm volatile("wgmma.fence.sync.aligned;" ::: "memory");
    sfor<J0, J1>([&](auto J) {
        constexpr int j = J.value, c = j >> 2, offb = SM_X + WG * 32768 + c * 4096 + (j & 3) * 32, sc = (ACC || j != J0) ? 1 : 0;
        if constexpr ((j & 3) != 0) wgmma_n32_rs<offb, sc>(ta[I], wr[reg_idx(j)][I], one);
        else if constexpr (WG == 0 || (I == 1 && c >= 4)) wgmma_n32_ss<SM_WQ + WG * 32768 + I * 16384 + c * 2048, offb, sc>(ta[I], one);
        constexpr int m = I ? c : c - 4;
        if constexpr (WG == 0 && (j & 3) == 1 && m >= 0)
            wgmma_n32_ss<SM_WQ + 32768 + (1 - I) * 16384 + m * 2048, SM_X + 32768 + m * 4096, 1>(ta[I], one);
    });
    asm volatile("wgmma.commit_group.sync.aligned;" ::: "memory");
}
__device__ __forceinline__ void warp_arrive(uint32_t bar) {
    __syncwarp();
    if (elect_one()) mbar_arrive(bar);
    __syncwarp();
}
__device__ __forceinline__ void remote_arrive(uint32_t bar, uint32_t rank) {
    asm volatile("mbarrier.arrive.relaxed.cluster.shared::cluster.b64 _, [%0];" ::"r"(mapa(bar, rank)) : "memory");
}
__device__ __forceinline__ void x_load(const RecParams& p, uint32_t sb, int sg, int g) {
    asm volatile("{\n.reg .pred p;\nelect.sync _|p, 0xFFFFFFFF;\n"
                 "@p cp.async.bulk.tensor.3d.shared::cluster.global.mbarrier::complete_tx::bytes.multicast::cluster [%0], [%1, {%3, %4, %5}], [%2], %6;\nbar.warp.sync 0xFFFFFFFF;\n}"
                 ::"r"(sb + SM_X + g * 16384), "l"(&p.tmX), "r"(sb + SM_BAR + BAR_XG + 8 * g), "r"(0), "r"(sg * SEG), "r"(g * 4), "h"((uint16_t)7) : "memory");
}

__device__ __forceinline__ void rec_steps(const RecParams& p, const uint32_t (&wr)[NREG][2][4], const uint32_t sb, const int warp,
                                          const int cta, const int head, const int rank) {
    const int wq = warp & 3, wg = warp >> 2;
    const uint32_t bar = sb + SM_BAR;
    const uint32_t xhi = (uint32_t)((uint64_t)p.xchg >> 32);
    const float sl2 = 0.08838834764831845f * 1.4426950408889634f;
    const bool has_unit = warp >= 5 && (warp < 7 || cta < 64);
    const bool qk = rank < 2;
    const uint32_t pa = rank == 2 ? 0 : rank + 1, pb = rank == 0 ? 2 : rank - 1;
    const uint32_t tbl = sb + SM_TBL + warp * 64;
    const bool att = (warp & 6) == 2;
    const int stile = warp < 5 ? warp : warp - 3;

    const uint32_t u_xa = uniform(sb + (qk ? SM_SP + rank * 1280 + stile * 256 : SM_VM + warp * 256));
    const uint32_t u_key = uniform(!qk || att || warp == 7 ? 0 : sb + (warp == 4 ? SM_QK + 1024 : SM_K + stile * 1024));
    const uint32_t u_bx = uniform(bar + (qk ? BAR_X : BAR_VM)), u_bra = uniform(mapa(u_bx, pa)), u_brb = uniform(mapa(u_bx, pb));
    const uint32_t u_src = uniform(lds32_volatile(tbl + 44));
    const uint32_t u_role = uniform((has_unit ? 1 : 0) | (att ? 2 : 0) | (wg == 1 || qk ? 4 : 0) | (rank != 1 && warp == 0 ? 8 : 0) | (rank != 0 && warp == 1 ? 16 : 0) |
                                    (warp == 5 || warp == 6 ? 32 : 0));
    uint32_t l16, aq, ao;
    {
        const int lane = threadIdx.x & 31, mi = lane >> 3, r8 = lane & 7, r16 = (mi >> 1) * 8 + r8;
        l16 = opaque(sb + lane * 16);
        aq = opaque(sb + SM_WQ + wg * 32768 + r16 * 128 + (((wq * 2 + (mi & 1)) ^ r8) << 4));
        ao = opaque(sb + SM_WO + (warp >> 1) * 8192 + r16 * 64 + ((((warp & 1) * 2 + (mi & 1)) ^ ((r8 >> 1) & 3)) << 4));
    }

    uint32_t mphase = 0;
    bool x0_ok = false;
    #pragma unroll 1
    for (int s = 0;; s++) {
        const uint32_t par = s & 1;
        uint32_t at[16][4];
        auto at_early = [](int i) { return i < 2 || ((i & 1) == 1 && (i >> 1) < AT_PF - 1); };
        auto at_prefetch = [&](bool first) {
            #pragma unroll
            for (int i = 0; i < 16; i++)
                if (at_early(i) && first == ((i & 1) == 1 && (i >> 1) < AT_FIRST)) ldsm4t(aq + (i & 1) * 16384 + (i >> 1) * 2048, at[i]);
        };
        auto att_stores = [&](bool tiles, bool rows) {
            if (warp == 4) {
                if (rows && !qk) mbar_wait_bounded(bar + BAR_VM, par);
                asm volatile("fence.proxy.async.shared::cta;" ::: "memory");
                if (elect_one()) {
                    if (tiles) {
                        __nv_bfloat16* dst = p.qkv_tok + ((size_t)s * NH + head) * (SEG * DH);
                        constexpr size_t MAT = (size_t)NSEG * NH * SEG * DH;
                        bulk_store(dst + (qk ? rank * (SEG * 64) : 2 * MAT), sb + (qk ? SM_QS : SM_V), 4096);
                        bulk_store(dst + (qk ? MAT + rank * (SEG * 64) : 2 * MAT + SEG * 64), sb + (qk ? SM_K : SM_V + 4096), 4096);
                    }
                    if (rows)
                        bulk_store(p.kv_mem + ((size_t)s * NH + head) * (MROWS * DH) + (qk ? rank * (MROWS * 64) : NSEG * NH * MROWS * DH),
                                   sb + (qk ? SM_QK + 1024 : SM_VM), qk ? 1024 : 2048);
                    bulk_commit();
                }
            }
        };
        uint32_t b[16][4];
        if (wg == 0) {
            float ta[2][16];
            if (!x0_ok) mbar_wait_bounded(bar + BAR_XG, par);
            STAMP(6);
            auto park = [&](int i, uint32_t dst) {
                #pragma unroll
                for (int e = 0; e < 16; e++) asm volatile("" : "+f"(ta[i][e]));
                #pragma unroll
                for (int j = 0; j < 4; j++)
                    sts128(l16 + dst + j * 2048 + wq * 512, __float_as_uint(ta[i][4 * j]), __float_as_uint(ta[i][4 * j + 1]),
                           __float_as_uint(ta[i][4 * j + 2]), __float_as_uint(ta[i][4 * j + 3]));
            };
            token_mma<0, 0, 16, 0, false>(ta, wr, 1);
            mbar_wait_bounded(bar + BAR_XG + 8, par);
            mbar_wait_bounded(bar + BAR_XG + 16, par);
            at_prefetch(true);
            token_mma<0, 16, 32, 0, true>(ta, wr, p.one[1]);
            token_mma<0, 0, 12, 1, false, false>(ta, wr, p.one[0]);
            token_mma<0, 12, 16, 1, true, false>(ta, wr, p.one[0]);
            mbar_wait_bounded(bar + BAR_XG + 24, par);
            asm volatile("wgmma.wait_group.sync.aligned 1;" ::: "memory");
            park(0, SM_PARK0);
            token_mma<0, 16, 32, 1, true>(ta, wr, 1);
            warp_arrive(bar + BAR_GO);
            mbar_wait_bounded(bar + BAR_PUB, par);
            const uint4 tp = lds128(bar + BAR_TPUB);
            const uint32_t tgo = tp.y + max(max((int)(tp.z - tp.y), (int)(tp.w - tp.y)), 0) + FETCH_DELAY;
            asm volatile("wgmma.wait_group.sync.aligned 0;" ::: "memory");
            park(1, SM_PARK1);
            warp_arrive(bar + BAR_PK);
            const uint8_t* src = xaddr(u_src + pub_slot(s), xhi);
            auto fetch = [&]() {
                if (elect_one()) {
                    mbar_arrive_expect_tx(bar + BAR_M + 8 * wq, 4096);
                    bulk_load(sb + SM_MEM + wq * 4096, src, 4096, bar + BAR_M + 8 * wq);
                }
            };
            while ((int)(clock_lo() - tgo) < 0) {}
            fetch();
            STAMP(12);
            if (warp == 0 && elect_one()) {
                if (qk) mbar_arrive_expect_tx(bar + BAR_V, 8192);
                mbar_arrive_expect_tx(bar + BAR_X, qk ? 1280 : 2560);
                mbar_arrive_expect_tx(bar + BAR_VM, qk ? 2048 : 0);
            }
            at_prefetch(false);
            const uint32_t x = fresh(l16) - sb;
            const uint32_t ca = sb + SM_MEM + wq * 4096 + x * 2 + ((x >> 4) & 0x1C);
            #pragma unroll 1
            for (uint32_t n = 0; n < POLL_LIMIT; n++) {
                mbar_wait_bounded(bar + BAR_M + 8 * wq, mphase);
                mphase ^= 1;
                const uint32_t c0 = lds32_volatile(ca), c1 = lds32_volatile(ca + 1024), c2 = lds32_volatile(ca + 2048), c3 = lds32_volatile(ca + 3072);
                if (!__any_sync(~0u, max(max3(c0, c1, c2), c3) == SENT)) break;
                fetch();
            }
            STAMP(0);
            named_bar_sync(10, 128);
            #pragma unroll
            for (int u = 0; u < 2; u++) ldsm4t(l16 + SM_MEM + u * 512, b[u]);
            if (!(u_role & 8) || s == NSEG - 1) {
                named_bar_sync(0, REC_THREADS);
            } else if (!qk) {
                const uint32_t d0 = mapa(sb + SM_V, 0), d1 = mapa(sb + SM_V, 1), b0 = mapa(bar + BAR_V, 0), b1 = mapa(bar + BAR_V, 1);
                named_bar_sync(0, REC_THREADS);
                const bool ok = mbar_test_wait(bar + BAR_VF, par);
                asm volatile("fence.proxy.async.shared::cta;" ::: "memory");
                if (!ok) mbar_wait_bounded(bar + BAR_VF, par);
                asm volatile("{\n.reg .pred p;\nelect.sync _|p, 0xFFFFFFFF;\n"
                             "@p cp.async.bulk.shared::cluster.shared::cta.mbarrier::complete_tx::bytes [%0], [%4], 8192, [%1];\n"
                             "@p cp.async.bulk.shared::cluster.shared::cta.mbarrier::complete_tx::bytes [%2], [%4], 8192, [%3];\nbar.warp.sync 0xFFFFFFFF;\n}"
                             ::"r"(d0), "r"(b0), "r"(d1), "r"(b1), "r"(sb + SM_V) : "memory");
            } else {
                named_bar_sync(0, REC_THREADS);
                mbar_wait_bounded(bar + BAR_F0, par);
                x_load(p, sb, s + 1, 0);
            }
        } else {
            at_prefetch(true);
            if (s > 0) {
                if (u_role & 1) {
                    const uint32_t ln = (fresh(l16) >> 4) & 31;
                    const uint32_t ibl = lds32_volatile(tbl + 12) + (par ^ 1) * XCHG_SLOT + ln * 8;
                    const uint32_t publ = lds32_volatile(tbl + 28) + pub_slot(s) + (ln & 16) * 256 + (ln & 8) * 16 + (ln & 7) * 4;
                    const bool odd = ln & 8;
                    const uint8_t* ib = xaddr(ibl + delay_zero<POLL_DELAY>(bar + BAR_SELF), xhi);
                    STAMP(8);
                    uint2 v[8];
                    #pragma unroll
                    for (int i = 0; i < 8; i++) v[i] = make_uint2(SENT, SENT);
                    #pragma unroll 1
                    for (uint32_t n = 0; n < POLL_LIMIT; n++) {
                        sfor<0, 8>([&](auto I) { repoll_v2<I.value * 256>(v[I.value], ib); });
                        const uint32_t mx = max(max3(v[0].y, v[1].y, v[2].y), max3(max3(v[3].y, v[4].y, v[5].y), v[6].y, v[7].y));
                        if (!__any_sync(~0u, mx == SENT)) break;
                    }
                    STAMP(9);
                    const float a0 = ((bf16_lo(v[0].x) + bf16_lo(v[1].x)) + (bf16_lo(v[2].x) + bf16_lo(v[3].x))) +
                                     ((bf16_lo(v[4].x) + bf16_lo(v[5].x)) + (bf16_lo(v[6].x) + bf16_lo(v[7].x)));
                    const float a1 = ((bf16_hi(v[0].x) + bf16_hi(v[1].x)) + (bf16_hi(v[2].x) + bf16_hi(v[3].x))) +
                                     ((bf16_hi(v[4].x) + bf16_hi(v[5].x)) + (bf16_hi(v[6].x) + bf16_hi(v[7].x)));
                    const float a2 = ((bf16_lo(v[0].y) + bf16_lo(v[1].y)) + (bf16_lo(v[2].y) + bf16_lo(v[3].y))) +
                                     ((bf16_lo(v[4].y) + bf16_lo(v[5].y)) + (bf16_lo(v[6].y) + bf16_lo(v[7].y)));
                    const float a3 = ((bf16_hi(v[0].y) + bf16_hi(v[1].y)) + (bf16_hi(v[2].y) + bf16_hi(v[3].y))) +
                                     ((bf16_hi(v[4].y) + bf16_hi(v[5].y)) + (bf16_hi(v[6].y) + bf16_hi(v[7].y)));
                    float k0 = odd ? a2 : a0, k1 = odd ? a3 : a1;
                    k0 += __shfl_xor_sync(~0u, odd ? a0 : a2, 8);
                    k1 += __shfl_xor_sync(~0u, odd ? a1 : a3, 8);
                    k0 += __shfl_xor_sync(~0u, k0, 16);
                    k1 += __shfl_xor_sync(~0u, k1, 16);
                    st_relaxed_b32(xaddr(publ, xhi), pack_bf16(k0, k1));
                    STAMP(11);
                } else if (warp == 4) {
                    bulk_wait_read_all();
                    if (elect_one()) remote_arrive(bar + BAR_F3, 2);
                    if (!qk) {
                        mbar_wait_bounded(bar + BAR_F3, par ^ 1);
                        x_load(p, sb, s, 3);
                    }
                    if (elect_one()) {
                        bulk_wait_all();
                        signal_bulk(p.flags + F_PROGRESS + s - 1);
                    }
                    __syncwarp();
                    STAMP(10);
                }
            }
            float ta[2][16];
            uint32_t w[8];
            auto unpark = [&](int i, uint32_t src) {
                mbar_wait_bounded(bar + (i ? BAR_GO : BAR_PK), par);
                #pragma unroll
                for (int j = 0; j < 4; j++) {
                    const uint4 v = lds128(l16 + src + j * 2048 + wq * 512);
                    ta[i][4 * j] = __uint_as_float(v.x); ta[i][4 * j + 1] = __uint_as_float(v.y);
                    ta[i][4 * j + 2] = __uint_as_float(v.z); ta[i][4 * j + 3] = __uint_as_float(v.w);
                }
            };
            sts32(bar + BAR_TPUB + 4 * wq, clock32());
            if (warp != 4) warp_arrive(bar + BAR_PUB);
            unpark(1, SM_PARK0);
            STAMP(6);
            token_mma<1, 0, 16, 1, true>(ta, wr, 1);
            unpark(0, SM_PARK1);
            token_mma<1, 16, 32, 1, true>(ta, wr, 1);
            token_mma<1, 16, 32, 0, true>(ta, wr, 1);
            token_mma<1, 0, 16, 0, true, false>(ta, wr, 1);
            auto put_tile = [&](int m, const uint32_t (&q)[8]) {
                #pragma unroll
                for (int h = 0; h < 2; h++) {
                    if (qk) asm volatile("stmatrix.sync.aligned.m8n8.x4.trans.shared.b16 [%0], {%1,%2,%3,%4};"
                                         ::"r"(aq - (SM_WQ + 32768) + (m ? SM_K : SM_QS) + h * 2048), "r"(q[4 * h]), "r"(q[4 * h + 1]),
                                           "r"(q[4 * h + 2]), "r"(q[4 * h + 3]) : "memory");
                    else sts128(l16 + SM_V + wq * 2048 + m * 1024 + h * 512, q[4 * h], q[4 * h + 1], q[4 * h + 2], q[4 * h + 3]);
                }
            };
            auto pack_tile = [&](int i) {
                #pragma unroll
                for (int e = 0; e < 16; e++) asm volatile("" : "+f"(ta[i][e]));
                #pragma unroll
                for (int j = 0; j < 8; j++) w[j] = pack_bf16(ta[i][2 * j], ta[i][2 * j + 1]);
            };
            asm volatile("wgmma.wait_group.sync.aligned 2;" ::: "memory");
            pack_tile(1);
            at_prefetch(false);
            asm volatile("wgmma.wait_group.sync.aligned 1;" ::: "memory");
            if (u_role & 32) {
                const uint32_t a_free = lds32_volatile(tbl + 60);
                if (elect_one()) asm volatile("mbarrier.arrive.relaxed.cluster.shared::cluster.b64 _, [%0];" ::"r"(a_free) : "memory");
            }
            put_tile(0, w);
            asm volatile("wgmma.wait_group.sync.aligned 0;" ::: "memory");
            pack_tile(0);
            put_tile(1, w);
            STAMP(0);
            named_bar_sync(0, REC_THREADS);
            #pragma unroll
            for (int u = 0; u < 2; u++) ldsm4t(l16 + SM_MEM + 8192 + u * 512, b[u]);
            if (s == NSEG - 1) att_stores(true, false);
            STAMP(14);
        }
        const uint32_t mb = l16 + SM_MEM + wg * 8192;
        float acc[2][2][4];
        {
            #pragma unroll
            for (int i = 0; i < 4; i++)
                if (!at_early(i)) ldsm4t(aq + (i & 1) * 16384 + (i >> 1) * 2048, at[i]);
            STAMPD(1, b[0][0]);
            #pragma unroll
            for (int i = 0; i < 4; i++) { for (int e = 0; e < 4; e++) acc[i >> 1][i & 1][e] = 0.f; }
            #pragma unroll
            for (int u = 0; u < 16; u++) {
                #pragma unroll
                for (int h = 0; h < 2; h++) {
                    const int j = 2 * u + h;
                    #pragma unroll
                    for (int m = 0; m < 2; m++) {
                        if ((j & 3) == 0) mma_a(acc[h][m], at[(j >> 2) * 2 + m], b[u][2 * h], b[u][2 * h + 1]);
                        else mma_a(acc[h][m], wr[reg_idx(j)][m], b[u][2 * h], b[u][2 * h + 1]);
                    }
                }
                #pragma unroll
                for (int v = u + 2 + (u > 2); v <= u + 2 + (u >= 2); v++)
                    if (v < 16) ldsm4t(mb + v * 512, b[v]);
                #pragma unroll
                for (int i = u + 4 + 2 * (u > 6); i <= u + 4 + 2 * (u >= 6); i++)
                    if (i < 16 && !at_early(i)) ldsm4t(aq + (i & 1) * 16384 + (i >> 1) * 2048, at[i]);
            }
        }
        sts128(l16 + SM_RED + warp * 512, __float_as_uint(acc[0][1][0] + acc[1][1][0]), __float_as_uint(acc[0][1][1] + acc[1][1][1]),
               __float_as_uint(acc[0][1][2] + acc[1][1][2]), __float_as_uint(acc[0][1][3] + acc[1][1][3]));
        #pragma unroll
        for (int e = 0; e < 4; e++) acc[0][0][e] += acc[1][0][e];
        const uint32_t x16 = fresh(l16);
        const uint32_t sa = fresh((x16 & 0x70) * 8 + ((((x16 >> 3) & 0x30) ^ x16) & 0x70));
        const uint32_t sq = fresh(sa ^ ((((x16 >> 7) ^ (x16 >> 8)) & 1) * 0x30));
        const uint32_t x8 = (x16 & 0x1F0) >> 1;
        const uint32_t ast = fresh(fresh(aq) - wg * (32768 - 1024)) + (SM_QK - SM_WQ);
        const uint32_t xra = fresh(x8 + __byte_perm(u_xa, u_bra, 0x7210)), xrb = fresh(x8 + __byte_perm(u_xa, u_brb, 0x7210));
        STAMP(2);
        named_bar_sync(1 + wq, 64);
        uint32_t p0, p1;
        {
            const uint4 v = lds128(l16 + SM_RED + (warp ^ 4) * 512);
            p0 = pack_bf16(acc[0][0][0] + __uint_as_float(v.x), acc[0][0][1] + __uint_as_float(v.y));
            p1 = pack_bf16(acc[0][0][2] + __uint_as_float(v.z), acc[0][0][3] + __uint_as_float(v.w));
        }
        auto send = [&](uint32_t y0, uint32_t y1) {
            st_async_v2(xra, y0, y1, u_bra);
            st_async_v2(xrb, y0, y1, u_brb);
            sts64(x8 + u_xa, y0, y1);
            warp_arrive(u_bx);
        };
        if (qk) {
            asm volatile("stmatrix.sync.aligned.m8n8.x2.trans.shared.b16 [%0], {%1,%2};" ::"r"(ast), "r"(p0), "r"(p1) : "memory");
            named_bar_sync(5, REC_THREADS);
            if (u_key != 0) {
                uint32_t qa[2][4], kf[2][4];
                ldsm4(sq + sb + SM_QK, qa[0]);
                ldsm4(sa + u_key, kf[0]);
                ldsm4((sq ^ 64) + sb + SM_QK, qa[1]);
                ldsm4((sa ^ 64) + u_key, kf[1]);
                float se[4] = {0.f, 0.f, 0.f, 0.f}, so[4] = {0.f, 0.f, 0.f, 0.f};
                #pragma unroll
                for (int u = 0; u < 2; u++) {
                    mma_a(se, qa[u], kf[u][0], kf[u][1]);
                    mma_a(so, qa[u], kf[u][2], kf[u][3]);
                }
                send(__float_as_uint(se[0] + so[2]), __float_as_uint(se[1] + so[3]));
            }
        } else {
            send(p0, p1);
        }
        STAMP(3);
        const uint32_t lane = (fresh(l16) >> 4) & 31;
        if (((s + 1) & 62) == 0) {
            if (s == NSEG - 1) { att_stores(false, true); break; }
            mbar_wait_bounded(bar + BAR_WO, 0);
            pdl_launch_dependents();
            PSTAMP(8);
        }
        const uint32_t slot = par * XCHG_SLOT;
        if (u_role & 2) {
            if (qk) mbar_wait_bounded(bar + BAR_V, par);
            uint32_t vt[2][4][4];
            auto v_load = [&](int i0, int i1) {
                #pragma unroll
                for (int i = i0; i < i1; i++) {
                    const uint4 v = lds128(l16 + SM_V + (warp & 1) * 1024 + (i & 3) * 2048 + (i >> 2) * 512);
                    vt[i >> 2][i & 3][0] = v.x; vt[i >> 2][i & 3][1] = v.y; vt[i >> 2][i & 3][2] = v.z; vt[i >> 2][i & 3][3] = v.w;
                }
            };
            v_load(0, V_EARLY);
            const uint32_t l8 = fresh(sb + lane * 8);
            mbar_wait_bounded(bar + BAR_X, par);
            STAMP(4);
            float sv[10];
            #pragma unroll
            for (int j = 0; j < 5; j++) {
                const uint2 a = lds64(l8 + SM_SP + j * 256), b = lds64(l8 + SM_SP + 1280 + j * 256);
                sv[2 * j] = __uint_as_float(a.x) + __uint_as_float(b.x);
                sv[2 * j + 1] = __uint_as_float(a.y) + __uint_as_float(b.y);
            }
            float mx = fmaxf(fmaxf(fmaxf(sv[0], sv[1]), fmaxf(sv[2], sv[3])), fmaxf(fmaxf(sv[4], sv[5]), fmaxf(sv[6], sv[7])));
            mx = fmaxf(mx, fmaxf(sv[8], sv[9]));
            const float m1 = __shfl_xor_sync(~0u, mx, 1), m2 = __shfl_xor_sync(~0u, mx, 2), m3 = __shfl_xor_sync(~0u, mx, 3);
            __syncwarp();
            v_load(V_EARLY, 8);
            const bool vm_ok = mbar_test_wait(bar + BAR_VM, par);
            mx = fmaxf(fmaxf(mx, m1), fmaxf(m2, m3));
            const float mo = mx * sl2;
            #pragma unroll
            for (int j = 0; j < 10; j++) sv[j] = ex2(fmaf(sv[j], sl2, -mo));
            const uint32_t e0 = pack_bf16(sv[0], sv[1]), e1 = pack_bf16(sv[2], sv[3]);
            const uint32_t e2 = pack_bf16(sv[4], sv[5]), e3 = pack_bf16(sv[6], sv[7]), em = pack_bf16(sv[8], sv[9]);
            float o[4][4];
            #pragma unroll
            for (int i = 0; i < 4; i++) {
                o[i][0] = o[i][1] = o[i][2] = o[i][3] = 0.f;
                mma_a(o[i], vt[0][i], e0, e1);
            }
            const float sum = (((sv[0] + sv[1]) + (sv[2] + sv[3])) + ((sv[4] + sv[5]) + (sv[6] + sv[7]))) + (sv[8] + sv[9]);
            if (!vm_ok) mbar_wait_bounded(bar + BAR_VM, par);
            uint2 vm[4];
            #pragma unroll
            for (int i = 0; i < 4; i++) {
                vm[i] = lds64(l8 + SM_VM + (warp & 1) * 1024 + i * 256);
                mma_a(o[i], vt[1][i], e2, e3);
            }
            #pragma unroll
            for (int i = 0; i < 4; i++) mma1688(o[i], vm[i].x, vm[i].y, em);
            {
                const float s1 = __shfl_xor_sync(~0u, sum, 1), s2 = __shfl_xor_sync(~0u, sum, 2), s3 = __shfl_xor_sync(~0u, sum, 3);
                sts32(sb + SM_SUM + (lane & 28), __float_as_uint((sum + s1) + (s2 + s3)));
            }
            #pragma unroll
            for (int i = 0; i < 4; i += 2)
                stsm_x4(l16 + SM_O + (warp & 1) * 1024 + i * 256, pack_bf16(o[i][0], o[i][1]), pack_bf16(o[i][2], o[i][3]),
                        pack_bf16(o[i + 1][0], o[i + 1][1]), pack_bf16(o[i + 1][2], o[i + 1][3]));
            STAMP(5);
            uint32_t st[16][4];
            named_bar_sync(6, REC_THREADS);
            wo_phase<2, 0>(st, ao, 0, l16, tbl, sb + SM_SUM, slot, xhi, 0, bar + BAR_XG, par ^ 1, x0_ok, wg, p.one[0] - 1, aq);
        } else {
            const uint32_t a3 = fresh(ao) + (wg == 0 ? 10 : 6) * 8192;
            uint32_t st[24][4];
            #pragma unroll
            for (int n = 0; n < WO_PFA; n++) ldsm4t(wo_addr<3>(ao, a3, n), st[n]);
            if (u_role & 1) {
                const uint32_t ln = (fresh(l16) >> 4) & 31;
                uint8_t* ib = xaddr(lds32_volatile(tbl + 12) + (par ^ 1) * XCHG_SLOT + ln * 16, xhi);
                #pragma unroll
                for (int i = 0; i < 4; i++) st_relaxed_v4(ib + i * 512, SENT);
                st_relaxed_b32(xaddr(lds32_volatile(tbl + 28) + pub_slot(s + 3) + (ln & 16) * 256 + (ln & 8) * 16 + (ln & 7) * 4, xhi), SENT);
            }
            if (warp == 1) {
                if (elect_one()) {
                    #pragma unroll
                    for (int g = 0; g < 4; g++) mbar_arrive_expect_tx(bar + BAR_XG + 8 * g, 16384);
                }
                if (s + 2 < NSEG && cta < 4 && elect_one())
                    asm volatile("cp.async.bulk.prefetch.tensor.3d.L2.global [%0, {%1, %2, %3}];"
                                 ::"l"(&p.tmX), "r"(0), "r"((s + 2) * SEG), "r"(cta * 4) : "memory");
            }
            mbar_wait_bounded(bar + BAR_X, par);
            { const uint32_t t0 = clock_lo(); while (clock_lo() - t0 < WO_PFB_DELAY) {} }
            #pragma unroll
            for (int n = WO_PFA; n < WO_PF; n++) ldsm4t(wo_addr<3>(ao, a3, n), st[n]);
            att_stores(true, true);
            if (u_role & 16) {
                mbar_wait_bounded(bar + BAR_VM, par);
                x_load(p, sb, s + 1, rank);
            }
            named_bar_sync(6, REC_THREADS);
            wo_phase<3, WO_PF>(st, ao, a3, l16, tbl, sb + SM_SUM, slot, xhi, u_role & 4, bar + BAR_XG, par ^ 1, x0_ok, wg, p.one[0] - 1, aq);
        }
        STAMP(7);
        if (wg == 0) named_bar_sync(9, REC_THREADS);
    }
    if (threadIdx.x == 128) KMARK(8);
    if (warp == 4) {
        if (elect_one()) {
            asm volatile("cp.async.bulk.wait_group 1;" ::: "memory");
            signal_bulk(p.flags + F_LASTTOK);
            bulk_wait_all();
            signal_bulk(p.flags + F_PROGRESS + NSEG - 1);
            KMARK(9);
        }
    } else if (warp == 0) {
        mbar_wait(bar + BAR_X, 1);
        mbar_wait(bar + BAR_VM, 1);
        if (rank != 1) mbar_wait(bar + (qk ? BAR_F0 : BAR_VF), 1);
    }
}

__global__ void __launch_bounds__(REC_THREADS, 1) rec_kernel(const __grid_constant__ RecParams p) {
    extern __shared__ __align__(1024) uint8_t smem_raw[];
    const uint32_t sb = smem_u32(smem_raw);
    const int tid = threadIdx.x, lane = tid & 31;
    const int warp = __shfl_sync(~0u, tid >> 5, 0);
    const int cta = blockIdx.x, head = cta / 3, rank = cta % 3;
    const int wg = warp >> 2, wq = warp & 3;
    const uint32_t bar = sb + SM_BAR;
    uint8_t* const xb = p.xchg;
    const uint32_t xlo = (uint32_t)(uint64_t)xb;
    if ((sb & 0x3FFFF) != SMEM_ORIGIN) __trap();
    KENTER(1);
    auto w_box = [&](int part, int g, int i, uint32_t dst, uint32_t mb) {
        const int m = i ^ g;
        const CUtensorMap* tm = &p.tmW[rank == 2 ? 2 : m];
        const int col = head * DH + (rank == 2 ? m : rank) * 64, row = ((part + 1) & 3) * 16;
        tma_load_3d(dst, tm, col, row, g * 8, mb);
    };
    if (tid == 0) {
        mbar_init(bar + BAR_V, 1);
        for (int i = 0; i < 4; i++) { mbar_init(bar + BAR_XG + 8 * i, 1); mbar_init(bar + BAR_M + 8 * i, 1); }
        mbar_init(bar + BAR_GO, 4);
        mbar_init(bar + BAR_PUB, 3);
        mbar_init(bar + BAR_PK, 4);
        mbar_init(bar + BAR_VM, rank < 2 ? 1 : 9);
        mbar_init(bar + BAR_F0, 3);
        mbar_init(bar + BAR_F3, 3);
        mbar_init(bar + BAR_VF, 3);
        sts64(bar + BAR_MIN, ~0u, ~0u);
        mbar_init(bar + BAR_X, rank < 2 ? 6 : 1);
        for (int i = 0; i < 3; i++) mbar_init(bar + BAR_P0 + 8 * i, 1);
        mbar_init(bar + BAR_WQ, 1);
        mbar_init(bar + BAR_WO, 1);
        sts32(bar + BAR_SELF, bar + BAR_SELF);
        asm volatile("fence.mbarrier_init.release.cluster;" ::: "memory");
    }
    auto build_tables = [&](uint32_t av) {
        for (uint32_t n = 0; !__all_sync(~0u, (av >> 24) == 24); n++) {
            av = ld_acquire_b32(p.arrivals + (lane & 3));
            if (n > SPIN_LIMIT) __trap();
        }
        uint32_t cm[3];
        #pragma unroll
        for (int i = 0; i < 3; i++) {
            const int o = i * 32 + lane;
            cm[i] = __ballot_sync(~0u, __popc((__shfl_sync(~0u, av, o / 24) >> (o % 24 / 3 * 3)) & 7) >= 2);
        }
        auto color_of = [&](int o) { return ((o < 32 ? cm[0] : o < 64 ? cm[1] : cm[2]) >> (o & 31)) & 1u; };
        auto inbox = [&](int o, int byte) {
            uint32_t c = color_of(o);
            int ones = 0;
            #pragma unroll
            for (int i = 0; i < 3; i++) ones += __popc(o >= i * 32 + 32 ? cm[i] : (o > i * 32 ? cm[i] & ((1u << (o - i * 32)) - 1) : 0u));
            int idx = c ? ones : o - ones;
            if (idx >= INBOX_MAX) { idx = 2 * INBOX_MAX - 1 - idx; c ^= 1; }
            const uint32_t lin = idx * 6144 + byte, q = XCHG_INBOX + (lin >> 12) * 8192;
            return q + class_off(xlo + q, c) + (lin & 4095);
        };
        uint32_t off = 0;
        const int grp = (warp + 3) & 3;
        if (lane < 12) {
            const int i = lane >> 2, lt0 = rank * 6;
            const int o = i < 2 ? rank * 32 + warp * 4 + (lane & 3) : (lt0 + ((warp + 4) & 7)) * 4 + (lane & 3);
            off = inbox(min(o, 95), i * 2048 + head * 64);
        } else if (lane == 12) {
            off = inbox(cta, (grp % 3) * 2048);
        } else if (lane == 13) {
            int T;
            if (grp < 2) {
                T = (cta >> 5) * 22 + 8 * grp + ((cta & 31) >> 2);
            } else {
                const int tl = (cta & 63) >> 2;
                T = (tl / 6) * 22 + 16 + tl % 6;
            }
            off = XCHG_PUB + (T >> 4) * 8192 + (T & 15) * 256 + (cta & 3) * 32;
        } else if (lane == 14) {
            const uint32_t q = XCHG_PUB + wq * 8192;
            off = q + class_off(xlo + q, color_of(cta));
        }
        if (lane == 15) off = mapa(bar + (warp == 5 ? BAR_VF : BAR_F0), warp == 5 ? 2 : 0) - xlo;
        if (lane < 16) asm volatile("st.shared.b32 [%0], %1;" ::"r"(sb + SM_TBL + warp * 64 + (lane & 3) * 16 + (lane >> 2) * 4), "r"(xlo + off) : "memory");
    };
    if (tid >= 32 && tid < 37) asm volatile("prefetch.tensormap [%0];" ::"l"(&p.tmW[0] + (tid - 32)) : "memory");
    if (cta == 0) for (int i = tid; i < F_COUNT; i += REC_THREADS) p.flags[i] = 0;
    __syncthreads();
    auto stage = [](int part) { return ((part + 2) % 3) * 65536; };
    auto load_part = [&](int part) {
        mbar_arrive_expect_tx(bar + BAR_P0 + 8 * part, 65536);
        for (int u = 0; u < 4; u++) w_box(part, u >> 1, u & 1, sb + stage(part) + u * 16384, bar + BAR_P0 + 8 * part);
    };
    asm volatile("barrier.cluster.arrive.relaxed.aligned;" ::: "memory");
    uint4 img = make_uint4(SENT, SENT, SENT, SENT);
    if (cta >= 92) {
        const unsigned short* m = reinterpret_cast<const unsigned short*>(p.mem0) + (cta - 92) * 256 + tid;
        uint32_t w[4];
        #pragma unroll
        for (int i = 0; i < 4; i++) w[i] = (uint32_t)__ldg(m + 2 * i * DM) | ((uint32_t)__ldg(m + (2 * i + 1) * DM) << 16);
        img = make_uint4(w[0], w[1], w[2], w[3]);
    }
    {
        constexpr int NPAIR = (XCHG_SLOT + PUB_BYTES) / 8192;
        uint8_t* pr = xb + (4 + cta) * 8192;
        const uint32_t c0 = class_off(xlo + (4 + cta) * 8192, 0);
        #pragma unroll
        for (int c = 0; c < 2; c++) {
            const bool timed = lane == 0 || (lane == 8 && c == (warp & 1));
            reinterpret_cast<uint4*>(pr + (c0 ^ (c << 12)))[tid] = make_uint4(timed ? 0u : SENT, SENT, SENT, SENT);
        }
        __syncwarp();
        if (lane == 0) {
            uint32_t x = 0;
            for (int k = 0; k < 3; k++) {
                if (k == 0 && warp == 0) load_part(0);
                const uint32_t c = (k + warp) & 1, t0 = clock_after(x);
                x = atomicExch(reinterpret_cast<uint32_t*>(pr + (c0 ^ (c << 12)) + warp * 512 + (k >> 1) * 128 + x), SENT);
                const uint32_t lat = clock_after(x) - t0;
                asm volatile("red.shared.min.u32 [%0], %1;" ::"r"(bar + BAR_MIN + 4 * c), "r"(lat) : "memory");
            }
        }
        __syncwarp();
        if (cta >= 92 || 100 + cta < NPAIR) {
            if (cta >= 92) {
                if (img.x == SENT) img.x = 0x7FFF7FFFu;
                if (img.y == SENT) img.y = 0x7FFF7FFFu;
                if (img.z == SENT) img.z = 0x7FFF7FFFu;
                if (img.w == SENT) img.w = 0x7FFF7FFFu;
            }
            uint8_t* q = xb + (cta >= 92 ? cta - 92 : 100 + cta) * 8192;
            reinterpret_cast<uint4*>(q)[tid] = img;
            reinterpret_cast<uint4*>(q + 4096)[tid] = img;
        }
    }
    __syncthreads();
    PSTAMP(4);
    if (tid == 0) {
        for (int part = 1; part < 3; part++) load_part(part);
    }
    if (tid == 224) {
        const uint32_t c = lds32_volatile(bar + BAR_MIN) > lds32_volatile(bar + BAR_MIN + 4) ? 1 : 0;
        asm volatile("red.release.gpu.global.add.u32 [%0], %1;" ::"l"(p.arrivals + cta / 24), "r"((1u << 24) | (c << (cta % 24))) : "memory");
    }
    uint32_t wr[NREG][2][4];
    uint32_t arrived = 0;
    {
        const int mi = lane >> 3, r8 = lane & 7;
        const uint32_t a0 = sb + wg * 32768 + ((mi >> 1) * 8 + r8) * 128 + (((wq * 2 + (mi & 1)) ^ r8) << 4);
        #pragma unroll
        for (int part = 0; part < 3; part++) {
            mbar_wait_bounded(bar + BAR_P0 + 8 * part, 0);
            if (part == 0) arrived = ld_relaxed_b32(p.arrivals + (lane & 3));
            #pragma unroll
            for (int j = 0; j < 8; j++) {
                #pragma unroll
                for (int i = 0; i < 2; i++) ldsm4t(a0 + stage(part) + i * 16384 + j * 2048, wr[part * 8 + j][i]);
            }
            asm volatile("fence.proxy.async.shared::cta;" ::: "memory");
            __syncthreads();
            PSTAMP(5 + part);
            if (tid == 0) {
                if (part == 0) {
                    for (int g = 0; g < 4; g++) {
                        mbar_arrive_expect_tx(bar + BAR_XG + 8 * g, 16384);
                        tma_load_3d(sb + SM_X + g * 16384, &p.tmX, 0, 0, g * 4, bar + BAR_XG + 8 * g);
                    }
                } else if (part == 1) {
                    mbar_arrive_expect_tx(bar + BAR_WQ, 65536);
                    for (int u = 0; u < 4; u++) w_box(3, u >> 1, u & 1, sb + SM_WQ + u * 16384, bar + BAR_WQ);
                } else {
                    mbar_arrive_expect_tx(bar + BAR_WO, 11 * 8192);
                    tma_load_3d(sb + SM_WO, &p.tmWo, 0, head * DH, rank * 11, bar + BAR_WO);
                    if (cta < 4)
                        asm volatile("cp.async.bulk.prefetch.tensor.3d.L2.global [%0, {%1, %2, %3}];"
                                     ::"l"(&p.tmX), "r"(0), "r"(SEG), "r"(cta * 4) : "memory");
                }
            }
        }
    }
    build_tables(arrived);
    if (tid == 64) {
        uint32_t smid;
        asm volatile("mov.u32 %0, %%smid;" : "=r"(smid));
        if (smid < 384) atomicOr(p.flags + F_RECSM + (smid >> 5), 1u << (smid & 31));
    }
    __syncwarp();
    PSTAMP(9);
    mbar_wait(bar + BAR_WQ, 0);
    asm volatile("barrier.cluster.wait.aligned;" ::: "memory");

    rec_steps(p, wr, sb, warp, cta, head, rank);
    if (cta == 0 && tid < 4) p.arrivals[tid] = 0;
    if (tid == 128) KEXIT(1);
}

constexpr int ATT_SLOT = 28672;
constexpr int ATT_PAIRS = 8;
constexpr int ATT_BAR = ATT_PAIRS * ATT_SLOT;
constexpr int ATT_SMEM = ATT_BAR + ATT_PAIRS * 16;
constexpr int ATT_THREADS = ATT_PAIRS * 64;
struct AttnParams {
    CUtensorMap tmOa;
    CUtensorMap tmQb, tmKb;
    CUtensorMap tmOb;
    const __nv_bfloat16* qkv_tok;
    const __nv_bfloat16* kv_mem;
    uint32_t* flags;
};

__device__ __forceinline__ void tok_attn_warp(uint32_t base, int mh, int lane) {
    const uint32_t sq = base, sk = base + 8192, sv = base + 16384, skm = base + 24576, svm = skm + 2048;
    const int g = lane >> 2, c = lane & 3, mi = lane >> 3, r8 = lane & 7;
    const int ntile = mh ? 5 : 3;
    float sc[5][4];
    #pragma unroll
    for (int j = 0; j < 5; j++) { sc[j][0] = sc[j][1] = sc[j][2] = sc[j][3] = 0.f; }
    #pragma unroll
    for (int t2 = 0; t2 < 4; t2++) {
        uint32_t a[2][4];
        #pragma unroll
        for (int h = 0; h < 2; h++) {
            const int row = mh * 16 + (mi & 1) * 8 + r8, ch16 = 4 * t2 + 2 * h + (mi >> 1);
            ldsm_x4(sq + (ch16 >> 3) * 4096 + row * 128 + (((ch16 & 7) ^ r8) << 4), a[h][0], a[h][1], a[h][2], a[h][3]);
        }
        const int ch16 = 4 * t2 + mi;
        uint32_t b[5][4];
        #pragma unroll
        for (int j = 0; j < 5; j++) {
            if (j < ntile) {
                if (j == 0) ldsm_x4(skm + (ch16 >> 3) * 1024 + r8 * 128 + (((ch16 & 7) ^ r8) << 4), b[j][0], b[j][1], b[j][2], b[j][3]);
                else ldsm_x4(sk + (ch16 >> 3) * 4096 + ((j - 1) * 8 + r8) * 128 + (((ch16 & 7) ^ r8) << 4), b[j][0], b[j][1], b[j][2], b[j][3]);
            }
        }
        #pragma unroll
        for (int h = 0; h < 2; h++) {
            #pragma unroll
            for (int j = 0; j < 5; j++)
                if (j < ntile) mma16816(sc[j], a[h][0], a[h][1], a[h][2], a[h][3], b[j][2 * h], b[j][2 * h + 1]);
        }
    }
    const float sl2 = 0.08838834764831845f * 1.4426950408889634f;
    uint32_t pf[2][5];
    float inv[2];
    #pragma unroll
    for (int q = 0; q < 2; q++) {
        const int tok = mh * 16 + q * 8 + g;
        float v[10];
        #pragma unroll
        for (int j = 0; j < 5; j++) {
            #pragma unroll
            for (int e = 0; e < 2; e++) {
                const int key = (j - 1) * 8 + 2 * c + e;
                v[2 * j + e] = (j == 0 || key <= tok) ? sc[j][2 * q + e] : -INFINITY;
            }
        }
        float mx = v[0];
        #pragma unroll
        for (int j = 1; j < 10; j++) mx = fmaxf(mx, v[j]);
        mx = fmaxf(mx, __shfl_xor_sync(~0u, mx, 1));
        mx = fmaxf(mx, __shfl_xor_sync(~0u, mx, 2));
        const float mo = mx * sl2;
        float sum = 0.f;
        #pragma unroll
        for (int j = 0; j < 10; j++) { v[j] = ex2(fmaf(v[j], sl2, -mo)); sum += v[j]; }
        sum += __shfl_xor_sync(~0u, sum, 1);
        sum += __shfl_xor_sync(~0u, sum, 2);
        inv[q] = rcp(sum);
        #pragma unroll
        for (int j = 0; j < 5; j++) pf[q][j] = pack_bf16(v[2 * j], v[2 * j + 1]);
    }
    auto load_v = [&](int n4, uint32_t (&vm)[4], uint32_t (&vt)[4][4]) {
        const uint2 va = lds64(svm + n4 * 512 + lane * 8), vb = lds64(svm + n4 * 512 + 256 + lane * 8);
        vm[0] = va.x; vm[1] = va.y; vm[2] = vb.x; vm[3] = vb.y;
        #pragma unroll
        for (int u = 0; u < 4; u++) {
            const int dt = 2 * n4 + (u >> 1), kh = u & 1;
            const uint4 v = lds128(sv + (dt & 3) * 2048 + (dt >> 2) * 1024 + kh * 512 + lane * 16);
            vt[u & 2][2 * kh] = v.x; vt[u & 2][2 * kh + 1] = v.z;
            vt[(u & 2) + 1][2 * kh] = v.y; vt[(u & 2) + 1][2 * kh + 1] = v.w;
        }
    };
    uint32_t vm[2][4], vt[2][4][4];
    load_v(0, vm[0], vt[0]);
    #pragma unroll
    for (int n4 = 0; n4 < 4; n4++) {
        const int cur = n4 & 1;
        if (n4 + 1 < 4) load_v(n4 + 1, vm[cur ^ 1], vt[cur ^ 1]);
        float o[4][4];
        #pragma unroll
        for (int u = 0; u < 4; u++) {
            o[u][0] = o[u][1] = o[u][2] = o[u][3] = 0.f;
            mma16816(o[u], pf[0][1], pf[1][1], pf[0][2], pf[1][2], vt[cur][u][0], vt[cur][u][1]);
        }
        if (mh) {
            #pragma unroll
            for (int u = 0; u < 4; u++) mma16816(o[u], pf[0][3], pf[1][3], pf[0][4], pf[1][4], vt[cur][u][2], vt[cur][u][3]);
        }
        #pragma unroll
        for (int u = 0; u < 4; u++) mma1688(o[u], pf[0][0], pf[1][0], vm[cur][u]);
        #pragma unroll
        for (int u = 0; u < 4; u += 2) {
            const int row = mh * 16 + (mi & 1) * 8 + r8, nt = 4 * n4 + u + (mi >> 1);
            stsm_x4(sq + (nt >> 3) * 4096 + row * 128 + (((nt & 7) ^ r8) << 4),
                    pack_bf16(o[u][0] * inv[0], o[u][1] * inv[0]), pack_bf16(o[u][2] * inv[1], o[u][3] * inv[1]),
                    pack_bf16(o[u + 1][0] * inv[0], o[u + 1][1] * inv[0]), pack_bf16(o[u + 1][2] * inv[1], o[u + 1][3] * inv[1]));
        }
    }
}

__device__ __forceinline__ void b_attn_warp(uint32_t base, int hl, int idx0, int lane) {
    const uint32_t sq = base, sk = base + 8192, sv = base + 8192 + 9216;
    const int g = lane >> 2, c = lane & 3;
    auto addr = [&](uint32_t t, int row, int ch) { return t + row * 128 + ((ch ^ (row & 7)) << 4); };
    const float sl2 = 0.17677669529663687f * 1.4426950408889634f;
    #pragma unroll 2
    for (int blk = 0; blk < 4; blk++) {
        const int r0 = blk * 16;
        float sc[3][4];
        #pragma unroll
        for (int j = 0; j < 3; j++) { sc[j][0] = sc[j][1] = sc[j][2] = sc[j][3] = 0.f; }
        #pragma unroll
        for (int t = 0; t < 2; t++) {
            uint32_t a0, a1, a2, a3, b0, b1, b2, b3, d0, d1, d2, d3;
            const int mi = lane >> 3, r = lane & 7;
            ldsm_x4(addr(sq, r0 + (mi & 1) * 8 + r, hl * 4 + 2 * t + (mi >> 1)), a0, a1, a2, a3);
            ldsm_x4(addr(sk, r0 + (mi >> 1) * 8 + r, hl * 4 + 2 * t + (mi & 1)), b0, b1, b2, b3);
            ldsm_x4(addr(sk, r0 + 16 + r, hl * 4 + 2 * t + (mi & 1)), d0, d1, d2, d3);
            mma16816(sc[0], a0, a1, a2, a3, b0, b1);
            mma16816(sc[1], a0, a1, a2, a3, b2, b3);
            mma16816(sc[2], a0, a1, a2, a3, d0, d1);
        }
        uint32_t pf[2][3];
        float inv[2];
        #pragma unroll
        for (int r = 0; r < 2; r++) {
            const int u = r * 8 + g;
            float v[6];
            #pragma unroll
            for (int j = 0; j < 3; j++) {
                #pragma unroll
                for (int e = 0; e < 2; e++) {
                    const int key = j * 8 + 2 * c + e;
                    const bool ok = key > u && key <= u + 8 && idx0 + r0 - 8 + key >= 0;
                    v[2 * j + e] = ok ? sc[j][2 * r + e] : -INFINITY;
                }
            }
            float mx = fmaxf(fmaxf(fmaxf(v[0], v[1]), fmaxf(v[2], v[3])), fmaxf(v[4], v[5]));
            mx = fmaxf(mx, __shfl_xor_sync(~0u, mx, 1));
            mx = fmaxf(mx, __shfl_xor_sync(~0u, mx, 2));
            const float mo = mx * sl2;
            float sum = 0.f;
            #pragma unroll
            for (int j = 0; j < 6; j++) { v[j] = ex2(fmaf(v[j], sl2, -mo)); sum += v[j]; }
            sum += __shfl_xor_sync(~0u, sum, 1);
            sum += __shfl_xor_sync(~0u, sum, 2);
            inv[r] = rcp(sum);
            #pragma unroll
            for (int j = 0; j < 3; j++) pf[r][j] = pack_bf16(v[2 * j], v[2 * j + 1]);
        }
        uint32_t ow[4][2];
        {
            const int mi = lane >> 3, r = lane & 7;
            uint32_t vv[4][4];
            #pragma unroll
            for (int nt = 0; nt < 4; nt++)
                ldsm_x4_t(addr(sv, r0 + min(mi, 2) * 8 + r, hl * 4 + nt), vv[nt][0], vv[nt][1], vv[nt][2], vv[nt][3]);
            float o[4][4];
            #pragma unroll
            for (int nt = 0; nt < 4; nt++) {
                o[nt][0] = o[nt][1] = o[nt][2] = o[nt][3] = 0.f;
                mma16816(o[nt], pf[0][0], pf[1][0], pf[0][1], pf[1][1], vv[nt][0], vv[nt][1]);
            }
            #pragma unroll
            for (int nt = 0; nt < 4; nt++) mma1688(o[nt], pf[0][2], pf[1][2], vv[nt][2]);
            #pragma unroll
            for (int nt = 0; nt < 4; nt++) {
                ow[nt][0] = pack_bf16(o[nt][0] * inv[0], o[nt][1] * inv[0]);
                ow[nt][1] = pack_bf16(o[nt][2] * inv[1], o[nt][3] * inv[1]);
            }
        }
        #pragma unroll
        for (int u = 0; u < 4; u += 2) {
            const int mi = lane >> 3, r = lane & 7;
            stsm_x4(addr(sq, r0 + (mi & 1) * 8 + r, hl * 4 + u + (mi >> 1)), ow[u][0], ow[u][1], ow[u + 1][0], ow[u + 1][1]);
        }
    }
}

constexpr uint32_t QKVB_TARGET = 12 * 8;
constexpr uint32_t PROGRESS_TARGET = 96;
constexpr uint32_t OA_TARGET = 64, OB_TARGET = 32;
#define ATT_B0 8
#define ATT_BSTEP 2
constexpr int ATT_TASKS = (NSEG + 16) * 32;
static_assert(ATT_B0 + 16 * ATT_BSTEP <= NSEG, "order of the task groups");
__device__ __forceinline__ int att_group(int g, bool& isb) {
    constexpr int P = ATT_BSTEP + 1;
    const int q = g - ATT_B0;
    isb = q >= 0 && q < 16 * P && q % P == 0;
    return q < 0 ? g : q >= 16 * P ? g - 16 : isb ? q / P : g - q / P - 1;
}

__global__ void __launch_bounds__(ATT_THREADS, 1) attn_kernel(const __grid_constant__ AttnParams p) {
    extern __shared__ __align__(1024) uint8_t smem_raw[];
    const int tid = threadIdx.x, lane = tid & 31, warp = __shfl_sync(~0u, tid >> 5, 0);
    const int pair = warp >> 1, wi = warp & 1;
    const uint32_t base = smem_u32(smem_raw) + pair * ATT_SLOT, bar = smem_u32(smem_raw) + ATT_BAR + pair * 16;
    const bool leader = wi == 0 && lane == 0;
    if (tid == 0) pdl_launch_dependents();
    KENTER(3);
    uint32_t phase = 0;
    if (leader) {
        mbar_init(bar, 1);
        asm volatile("fence.mbarrier_init.release.cluster;" ::: "memory");
    }
    uint32_t* pending = nullptr;
    auto flush = [&]() {
        if (pending) {
            bulk_wait_all();
            signal_bulk(pending);
            if (pending == p.flags + F_OA + NSEG - 1) KMARK(14);
            pending = nullptr;
        }
    };
    int ready_a = -1, ready_b = -1;
    for (int task = pair * gridDim.x + blockIdx.x; task < ATT_TASKS; task += ATT_PAIRS * gridDim.x) {
        bool isb;
        const int grp = att_group(task >> 5, isb), i = task & 31;
        named_bar_sync(1 + pair, 64);
        if (leader) {
            {
                auto need = [&](const uint32_t* f, uint32_t target) {
                    if (ld_acquire_b32(f) < target) { flush(); wait_flag(f, target); }
                };
                if (isb) {
                    if (grp > ready_b) {
                        need(p.flags + F_QKVB + grp, QKVB_TARGET);
                        if (grp > 0) need(p.flags + F_QKVB + grp - 1, QKVB_TARGET);
                        asm volatile("fence.proxy.async.global;" ::: "memory");
                        ready_b = grp;
                    }
                    mbar_arrive_expect_tx(bar, 8192 + 2 * 9216);
                    tma_load_3d(base, &p.tmQb, (i >> 1) * 64, i & 1, grp * 64, bar);
                    tma_load_3d(base + 8192, &p.tmKb, DM + (i >> 1) * 64, i & 1, grp * 64 - 8, bar);
                    tma_load_3d(base + 8192 + 9216, &p.tmKb, 2 * DM + (i >> 1) * 64, i & 1, grp * 64 - 8, bar);
                } else {
                    if (grp > ready_a) {
                        need(p.flags + (grp == NSEG - 1 ? F_LASTTOK : F_PROGRESS + grp), PROGRESS_TARGET);
                        asm volatile("fence.proxy.async.global;" ::: "memory");
                        ready_a = grp;
                    }
                    if (grp == 63) KMARK(10);
                    mbar_arrive_expect_tx(bar, ATT_SLOT);
                    #pragma unroll
                    for (int w = 0; w < 3; w++)
                        bulk_load(base + w * 8192, p.qkv_tok + (((size_t)w * NSEG + grp) * NH + i) * (SEG * DH), 8192, bar);
                    if (grp == NSEG - 1) {
                        need(p.flags + F_PROGRESS + grp, PROGRESS_TARGET);
                        asm volatile("fence.proxy.async.global;" ::: "memory");
                    }
                    #pragma unroll
                    for (int w = 0; w < 2; w++)
                        bulk_load(base + 24576 + w * 2048, p.kv_mem + (((size_t)w * NSEG + grp) * NH + i) * (MROWS * DH), 2048, bar);
                }
            }
        }
        if (lane == 0) flush();
        __syncwarp();
        mbar_wait_sleep(bar, phase);
        phase ^= 1;
        if (isb) {
            b_attn_warp(base, wi, grp * 64, lane);
            asm volatile("fence.proxy.async.shared::cta;" ::: "memory");
            named_bar_sync(1 + pair, 64);
            if (wi == 1 && lane == 0) {
                asm volatile("cp.async.bulk.tensor.3d.global.shared::cta.bulk_group [%0, {%2, %3, %4}], [%1];"
                             ::"l"(&p.tmOb), "r"(base), "r"((i >> 1) * 64), "r"(i & 1), "r"(grp * 64) : "memory");
                pending = p.flags + F_OB + grp;
            }
        } else {
            if (grp == 63 && lane == 0) KMARK(11);
            tok_attn_warp(base, wi, lane);
            if (grp == 63 && lane == 0) KMARK(12);
            asm volatile("fence.proxy.async.shared::cta;" ::: "memory");
            __syncwarp();
            if (lane == 0) {
                #pragma unroll
                for (int h = 0; h < 2; h++) tma_store_2d(&p.tmOa, base + h * 4096 + wi * 2048, i * DH + h * 64, grp * SEG + wi * 16);
                pending = p.flags + F_OA + grp;
            }
        }
        if (lane == 0) { bulk_commit(); bulk_wait_read_all(); }
        __syncwarp();
    }
    if (lane == 0) { flush(); KEXIT(3); }
}

typedef CUresult (*EncodeFn)(CUtensorMap*, CUtensorMapDataType, cuuint32_t, void*, const cuuint64_t*, const cuuint64_t*,
                             const cuuint32_t*, const cuuint32_t*, CUtensorMapInterleave, CUtensorMapSwizzle,
                             CUtensorMapL2promotion, CUtensorMapFloatOOBfill);

void make_map_2d(EncodeFn enc, CUtensorMap* m, const void* ptr, uint64_t rows, uint64_t cols, uint32_t box_rows) {
    cuuint64_t dims[2] = {cols, rows};
    cuuint64_t strides[1] = {cols * 2};
    cuuint32_t box[2] = {64, box_rows};
    cuuint32_t es[2] = {1, 1};
    enc(m, CU_TENSOR_MAP_DATA_TYPE_BFLOAT16, 2, const_cast<void*>(ptr), dims, strides, box, es,
        CU_TENSOR_MAP_INTERLEAVE_NONE, CU_TENSOR_MAP_SWIZZLE_128B, CU_TENSOR_MAP_L2_PROMOTION_L2_256B,
        CU_TENSOR_MAP_FLOAT_OOB_FILL_NONE);
}
void make_map_b(EncodeFn enc, CUtensorMap* m, const void* ptr, uint64_t k, uint64_t n, uint32_t nblk, uint32_t box_rows = 64,
                uint32_t bc = 64) {
    cuuint64_t dims[3] = {bc, k, n / bc};
    cuuint64_t strides[2] = {n * 2, bc * 2};
    cuuint32_t box[3] = {bc, box_rows, nblk};
    cuuint32_t es[3] = {1, 1, 1};
    enc(m, CU_TENSOR_MAP_DATA_TYPE_BFLOAT16, 3, const_cast<void*>(ptr), dims, strides, box, es,
        CU_TENSOR_MAP_INTERLEAVE_NONE, bc == 64 ? CU_TENSOR_MAP_SWIZZLE_128B : CU_TENSOR_MAP_SWIZZLE_64B, CU_TENSOR_MAP_L2_PROMOTION_L2_256B,
        CU_TENSOR_MAP_FLOAT_OOB_FILL_NONE);
}

void make_map_parity(EncodeFn enc, CUtensorMap* m, const void* ptr, uint64_t cols, uint32_t box_rows) {
    cuuint64_t dims[3] = {cols, 2, S_TOK / 2};
    cuuint64_t strides[2] = {cols * 2, cols * 4};
    cuuint32_t box[3] = {64, 1, box_rows};
    cuuint32_t es[3] = {1, 1, 1};
    enc(m, CU_TENSOR_MAP_DATA_TYPE_BFLOAT16, 3, const_cast<void*>(ptr), dims, strides, box, es,
        CU_TENSOR_MAP_INTERLEAVE_NONE, CU_TENSOR_MAP_SWIZZLE_128B, CU_TENSOR_MAP_L2_PROMOTION_L2_128B,
        CU_TENSOR_MAP_FLOAT_OOB_FILL_NONE);
}
void make_map_w(EncodeFn enc, CUtensorMap* m, const void* ptr) {
    cuuint64_t dims[3] = {HD, 64, DM / 64};
    cuuint64_t strides[2] = {HD * 2, 64 * HD * 2};
    cuuint32_t box[3] = {64, 16, 8};
    cuuint32_t es[3] = {1, 1, 1};
    enc(m, CU_TENSOR_MAP_DATA_TYPE_BFLOAT16, 3, const_cast<void*>(ptr), dims, strides, box, es,
        CU_TENSOR_MAP_INTERLEAVE_NONE, CU_TENSOR_MAP_SWIZZLE_128B, CU_TENSOR_MAP_L2_PROMOTION_L2_256B,
        CU_TENSOR_MAP_FLOAT_OOB_FILL_NONE);
}

#define SIDE_ORDER 0
#define SERIAL_ATT_CTAS h.n_sm
#define N_TAIL_CTAS 28
#define N_SIDE_CTAS 28
#define N_ATT_CTAS 8
#define TAIL_BLOCK0 11

#define TAIL_SPARE 2
#define TAIL_KB2 30
#define TAIL_KB3 20
#define TAIL_BLOCK1 13
#define TAIL_BLOCK2 14

struct HostState {
    bool ready;
    bool overlap;
    int n_side, n_att, n_sm;
    SideParams seq_a, seq_b;
    const void* key[11];
    RecParams rec;
    SideParams side, tail;
    FinalParams fin;
    AttnParams attn;
    __nv_bfloat16 *qkv_tok, *kv_mem, *o_tok, *qkv_b, *o_b;
    uint8_t* xchg;
};
HostState g_host;

void setup(void* const* d_in, void* d_out) {
    HostState& h = g_host;
    void* fn = nullptr;
    cudaDriverEntryPointQueryResult qr;
    cudaGetDriverEntryPoint("cuTensorMapEncodeTiled", &fn, cudaEnableDefault, &qr);
    EncodeFn enc = reinterpret_cast<EncodeFn>(fn);
    void* ptr;
    cudaGetSymbolAddress(&ptr, g_qkv_tok); h.qkv_tok = (__nv_bfloat16*)ptr;
    cudaGetSymbolAddress(&ptr, g_kv_mem);  h.kv_mem = (__nv_bfloat16*)ptr;
    cudaGetSymbolAddress(&ptr, g_o_tok);   h.o_tok = (__nv_bfloat16*)ptr;
    cudaGetSymbolAddress(&ptr, g_qkv_b);   h.qkv_b = (__nv_bfloat16*)ptr;
    cudaGetSymbolAddress(&ptr, g_o_b);     h.o_b = (__nv_bfloat16*)ptr;
    cudaGetSymbolAddress(&ptr, g_xchg);    h.xchg = (uint8_t*)(((uint64_t)ptr + XCHG_BYTES - 1) & ~(uint64_t)(XCHG_BYTES - 1));
    cudaGetSymbolAddress(&ptr, g_flags);   uint32_t* flags = (uint32_t*)ptr;
    cudaGetSymbolAddress(&ptr, g_arrivals); uint32_t* arrivals = (uint32_t*)ptr;

    const void *xa = d_in[0], *mem0 = d_in[1], *wq = d_in[2], *wk = d_in[3], *wv = d_in[4], *wo = d_in[5];
    const void *xb = d_in[7], *wqkv = d_in[8], *wob = d_in[9];

    RecParams& r = h.rec;
    make_map_w(enc, &r.tmW[0], wq);
    make_map_w(enc, &r.tmW[1], wk);
    make_map_w(enc, &r.tmW[2], wv);
    make_map_b(enc, &r.tmWo, wo, HD, DM, 11, 128, 32);
    r.mem0 = (const __nv_bfloat16*)mem0;
    r.qkv_tok = h.qkv_tok; r.kv_mem = h.kv_mem; r.xchg = h.xchg;
    r.flags = flags; r.arrivals = arrivals; r.one[0] = r.one[1] = 1;
    make_map_b(enc, &r.tmX, xa, S_TOK, DM, 4, SEG);

    SideParams& sd = h.side;
    SideProb& p0 = sd.prob[0];
    make_map_2d(enc, &p0.tmA, xb, S_TOK, DM, BM);
    make_map_b(enc, &p0.tmB, wqkv, DM, 3 * DM, 4);
    make_map_2d(enc, &p0.tmC, h.qkv_b, S_TOK, 3 * DM, 16);
    p0.n_tiles = 3 * DM / 256; p0.k_blocks = DM / BK; p0.c_col0 = 0; p0.dep = nullptr; p0.dep_target = 0; p0.dep_n = 1; p0.sig = flags + F_QKVB;
    SideProb& p1 = sd.prob[1];
    make_map_2d(enc, &p1.tmA, h.o_tok, S_TOK, HD, BM);
    make_map_b(enc, &p1.tmB, wo, HD, DM, 4);
    make_map_2d(enc, &p1.tmC, d_out, S_TOK, 2 * DM, 16);
    p1.n_tiles = DM / 256; p1.k_blocks = HD / BK; p1.c_col0 = 0; p1.dep = flags + F_OA; p1.dep_target = OA_TARGET; p1.dep_n = 4; p1.sig = nullptr;
    SideProb& p2 = sd.prob[2];
    make_map_2d(enc, &p2.tmA, h.o_b, S_TOK, DM, BM);
    make_map_b(enc, &p2.tmB, wob, DM, DM, 4);
    p2.tmC = p1.tmC;
    p2.n_tiles = DM / 256; p2.k_blocks = DM / BK; p2.c_col0 = DM; p2.dep = flags + F_OB; p2.dep_target = OB_TARGET; p2.dep_n = 1; p2.sig = nullptr;
    p0.n_split = p0.n_tiles; p1.n_split = p1.n_tiles; p2.n_split = p2.n_tiles;
    p0.part = p1.part = p2.part = nullptr;
    p0.k_total = p0.k_blocks; p1.k_total = p1.k_blocks; p2.k_total = p2.k_blocks;
    if (SIDE_ORDER == 0) { sd.seg[0] = {0, 0, 16}; sd.seg[1] = {1, 0, TAIL_BLOCK0}; }
    else { sd.seg[0] = {1, 0, TAIL_BLOCK0}; sd.seg[1] = {0, 0, 16}; }
    sd.seg[2] = {2, 0, 16};
    sd.nseg = 3; sd.queue = flags + F_SIDEQ; sd.spare_seg = 3; sd.flags = flags;

    SideParams& tl = h.tail;
    tl.prob[0] = p1;
    make_map_b(enc, &tl.prob[0].tmB, wo, HD, DM, 2);
    cudaGetSymbolAddress(&ptr, g_part);
    for (int i = 0; i < 3; i++) {
        SideProb& q = tl.prob[i];
        q = tl.prob[0];
        q.n_tiles = (i + 1) * DM / 128; q.n_split = DM / 128; q.k_blocks = i == 0 ? HD / BK : i == 1 ? TAIL_KB2 : TAIL_KB3;
        q.part = i ? (float*)ptr : nullptr; q.part_flag = flags + F_PART;
    }
    tl.seg[0] = {0, TAIL_BLOCK0, TAIL_BLOCK1};
    tl.seg[1] = {1, TAIL_BLOCK1, TAIL_BLOCK2};
    tl.seg[2] = {2, TAIL_BLOCK2, 15};
    tl.nseg = 3; tl.queue = flags + F_TAILQ; tl.spare_seg = TAIL_SPARE; tl.flags = flags;

    make_map_2d(enc, &h.fin.tmA, h.o_tok, S_TOK, HD, SEG);
    h.fin.tmB = tl.prob[0].tmB; h.fin.out = (__nv_bfloat16*)d_out;
    h.fin.dep = flags + F_OA + 60; h.fin.dep_target = OA_TARGET; h.fin.mt = 15;

    make_map_2d(enc, &h.attn.tmOa, h.o_tok, S_TOK, HD, 16);
    make_map_parity(enc, &h.attn.tmQb, h.qkv_b, 3 * DM, 64);
    make_map_parity(enc, &h.attn.tmKb, h.qkv_b, 3 * DM, 72);
    make_map_parity(enc, &h.attn.tmOb, h.o_b, DM, 64);
    h.attn.qkv_tok = h.qkv_tok; h.attn.kv_mem = h.kv_mem; h.attn.flags = flags;

    int dev = 0, nsm = 0;
    cudaGetDevice(&dev);
    cudaDeviceGetAttribute(&nsm, cudaDevAttrMultiProcessorCount, dev);
    h.n_sm = nsm;
    h.overlap = nsm - 96 >= N_SIDE_CTAS + N_ATT_CTAS;
    h.n_side = N_SIDE_CTAS; h.n_att = N_ATT_CTAS;
    h.seq_a = sd;
    h.seq_a.seg[0] = {0, 0, 16};
    h.seq_a.nseg = 1;
    h.seq_b = sd;
    h.seq_b.seg[0] = {1, 0, 16};
    h.seq_b.seg[1] = {2, 0, 16};
    h.seq_b.nseg = 2; h.seq_b.queue = flags + F_TAILQ;

    cudaFuncSetAttribute(side_gemm_kernel<256>, cudaFuncAttributeMaxDynamicSharedMemorySize, GemmCfg<256>::SMEM);
    cudaFuncSetAttribute(side_gemm_kernel<128>, cudaFuncAttributeMaxDynamicSharedMemorySize, GemmCfg<128>::SMEM);
    cudaFuncSetAttribute(final_gemm_kernel, cudaFuncAttributeMaxDynamicSharedMemorySize, FIN_SMEM);
    cudaFuncSetAttribute(rec_kernel, cudaFuncAttributeMaxDynamicSharedMemorySize, REC_SMEM);
    cudaFuncSetAttribute(attn_kernel, cudaFuncAttributeMaxDynamicSharedMemorySize, ATT_SMEM);
    for (int i = 0; i < 10; i++) h.key[i] = d_in[i];
    h.key[10] = d_out;
    h.ready = true;
}

template <typename K, typename P>
void launch(K kernel, int grid, int block, int smem, cudaStream_t st, const P& prm, int cluster, bool pdl) {
    cudaLaunchConfig_t cfg = {};
    cfg.gridDim = dim3(grid); cfg.blockDim = dim3(block); cfg.dynamicSmemBytes = smem; cfg.stream = st;
    cudaLaunchAttribute at[2];
    int n = 0;
    if (cluster > 1) {
        at[n].id = cudaLaunchAttributeClusterDimension;
        at[n].val.clusterDim.x = cluster; at[n].val.clusterDim.y = 1; at[n].val.clusterDim.z = 1;
        n++;
    }
    if (pdl) {
        at[n].id = cudaLaunchAttributeProgrammaticStreamSerialization;
        at[n].val.programmaticStreamSerializationAllowed = 1;
        n++;
    }
    cfg.attrs = at; cfg.numAttrs = n;
    cudaLaunchKernelEx(&cfg, kernel, prm);
}

}

extern "C" void kernel_launch(void* const* d_in, const int* in_sizes, int n_in, void* d_out, int out_size) {
    HostState& h = g_host;
    bool same = h.ready;
    for (int i = 0; same && i < 10; i++) same = h.key[i] == d_in[i];
    if (!same || h.key[10] != d_out) setup(d_in, d_out);
    cudaStream_t st = cudaStreamPerThread;

    launch(rec_kernel, 96, REC_THREADS, REC_SMEM, st, h.rec, 3, false);
    {
        if (!h.overlap) {
            launch(side_gemm_kernel<256>, h.n_sm, 384, GemmCfg<256>::SMEM, st, h.seq_a, 1, false);
            launch(attn_kernel, SERIAL_ATT_CTAS, ATT_THREADS, ATT_SMEM, st, h.attn, 1, false);
            launch(side_gemm_kernel<256>, h.n_sm, 384, GemmCfg<256>::SMEM, st, h.seq_b, 1, false);
            return;
        }
    }
    launch(side_gemm_kernel<256>, h.n_side, 384, GemmCfg<256>::SMEM, st, h.side, 1, true);
    launch(attn_kernel, h.n_att, ATT_THREADS, ATT_SMEM, st, h.attn, 1, true);
    launch(side_gemm_kernel<128>, N_TAIL_CTAS, 384, GemmCfg<128>::SMEM, st, h.tail, 1, true);
    launch(final_gemm_kernel, 8 * FIN_SPLIT, 384, FIN_SMEM, st, h.fin, FIN_SPLIT, true);
}
```

```cpp
#include <cuda_runtime.h>
#include <cuda_bf16.h>
#include <cuda.h>
#include <stdint.h>

namespace {

constexpr int S_TOK = 2048;
constexpr int DM = 1024;
constexpr int NH = 32;
constexpr int DH = 128;
constexpr int HD = NH * DH;
constexpr int NSEG = 64;
constexpr int SEG = 32;
constexpr int MROWS = 8;
constexpr uint32_t SENT = 0xFFFFFFFFu;
constexpr uint32_t SPIN_LIMIT = 1u << 24;

__device__ __align__(1024) __nv_bfloat16 g_qkv_tok[3ull * NSEG * NH * SEG * DH];
__device__ __align__(1024) __nv_bfloat16 g_kv_mem[2ull * NSEG * NH * MROWS * DH];
__device__ __align__(1024) __nv_bfloat16 g_o_tok[(size_t)S_TOK * HD];
__device__ __align__(1024) __nv_bfloat16 g_qkv_b[(size_t)S_TOK * 3 * DM];
__device__ __align__(1024) __nv_bfloat16 g_o_b[(size_t)S_TOK * DM];
__device__ __align__(1024) float g_part[32 * 2 * 128 * 128];
constexpr int PUB_BYTES = 32768;
constexpr int XCHG_SLOT = 1 << 20;
constexpr int XCHG_PUB = 0, XCHG_INBOX = 2 * PUB_BYTES;
constexpr int INBOX_MAX = 80;
constexpr int XCHG_BYTES = 2 * XCHG_SLOT;
__device__ __align__(8192) uint8_t g_xchg[2 * XCHG_BYTES];
enum { F_LASTTOK = 0, F_RECSM = 4, F_PROGRESS = 16, F_QKVB = 80, F_OB = 96, F_OA = 112, F_PART = 176, F_SIDEQ = 208, F_TAILQ = 256, F_COUNT = 304 };
__device__ uint32_t g_flags[F_COUNT];
__device__ __align__(16) uint32_t g_arrivals[4];

#define STAMP(k) do {} while (0)
#define STAMPD(k, x) do {} while (0)
#define PSTAMP(k) do {} while (0)
#define KENTER(k) do {} while (0)
#define KEXIT(k) do {} while (0)
#define KMARK(k) do {} while (0)

__device__ __forceinline__ uint32_t class_off(uint64_t a, uint32_t c) {
    return ((__popc((uint32_t)a & 0xB3000u) ^ c) & 1u) << 12;
}
__device__ __forceinline__ uint32_t smem_u32(const void* p) { return (uint32_t)__cvta_generic_to_shared(p); }
__device__ __forceinline__ uint32_t pack_bf16(float lo, float hi) {
    uint32_t r;
    asm("cvt.rn.bf16x2.f32 %0, %1, %2;" : "=r"(r) : "f"(hi), "f"(lo));
    return r;
}
__device__ __forceinline__ float ex2(float x) {
    float y;
    asm("ex2.approx.ftz.f32 %0, %1;" : "=f"(y) : "f"(x));
    return y;
}
__device__ __forceinline__ float rcp(float x) {
    float y;
    asm("rcp.approx.ftz.f32 %0, %1;" : "=f"(y) : "f"(x));
    return y;
}
__device__ __forceinline__ uint32_t clock32() {
    uint32_t t;
    asm volatile("mov.u32 %0, %%clock;" : "=r"(t));
    return t;
}
__device__ __forceinline__ uint32_t clock_lo() {
    unsigned long long t;
    asm volatile("mov.u64 %0, %%clock64;" : "=l"(t));
    return (uint32_t)t;
}
__device__ __forceinline__ uint32_t clock_after(uint32_t x) {
    uint32_t t;
    asm volatile("{\n.reg .pred p;\nsetp.eq.u32 p, %1, 0x12345678;\n@p exit;\nmov.u32 %0, %%clock;\n}" : "=r"(t) : "r"(x) : "memory");
    return t;
}
__device__ __forceinline__ uint32_t opaque(uint32_t x) { return __shfl_sync(~0u, x, threadIdx.x & 31); }
__device__ __forceinline__ uint32_t uniform(uint32_t x) { return __shfl_sync(~0u, x + (threadIdx.x & 31), 0); }
__device__ __forceinline__ float bf16_lo(uint32_t w) { return __uint_as_float(w << 16); }
__device__ __forceinline__ float bf16_hi(uint32_t w) { return __uint_as_float(w & 0xFFFF0000u); }

__device__ __forceinline__ void mbar_init(uint32_t bar, uint32_t cnt) {
    asm volatile("mbarrier.init.shared::cta.b64 [%0], %1;" ::"r"(bar), "r"(cnt) : "memory");
}
__device__ __forceinline__ void mbar_arrive(uint32_t bar) {
    asm volatile("mbarrier.arrive.shared::cta.b64 _, [%0];" ::"r"(bar) : "memory");
}
__device__ __forceinline__ void mbar_arrive_expect_tx(uint32_t bar, uint32_t bytes) {
    asm volatile("mbarrier.arrive.expect_tx.shared::cta.b64 _, [%0], %1;" ::"r"(bar), "r"(bytes) : "memory");
}
__device__ __forceinline__ bool mbar_try_wait(uint32_t bar, uint32_t parity) {
    uint32_t ok;
    asm volatile(
        "{\n.reg .pred p;\n"
        "mbarrier.try_wait.parity.shared::cta.b64 p, [%1], %2;\n"
        "selp.u32 %0, 1, 0, p;\n}"
        : "=r"(ok) : "r"(bar), "r"(parity) : "memory");
    return ok != 0;
}
__device__ __forceinline__ bool mbar_test_wait(uint32_t bar, uint32_t parity) {
    uint32_t ok;
    asm volatile(
        "{\n.reg .pred p;\n"
        "mbarrier.test_wait.parity.shared::cta.b64 p, [%1], %2;\n"
        "selp.u32 %0, 1, 0, p;\n}"
        : "=r"(ok) : "r"(bar), "r"(parity) : "memory");
    return ok != 0;
}
__device__ __forceinline__ void mbar_wait(uint32_t bar, uint32_t parity) {
    uint32_t n = 0;
    while (!mbar_try_wait(bar, parity)) {
        if (++n > SPIN_LIMIT) __trap();
    }
}
__device__ __forceinline__ void mbar_wait_sleep(uint32_t bar, uint32_t parity) {
    uint32_t n = 0;
    while (!mbar_try_wait(bar, parity)) {
        __nanosleep(20);
        if (++n > SPIN_LIMIT) __trap();
    }
}
__device__ __forceinline__ void mbar_wait_bounded(uint32_t bar, uint32_t parity) {
    for (uint32_t n = 0; n < (1u << 20) && !mbar_try_wait(bar, parity); n++) {}
}
__device__ __forceinline__ bool elect_one() {
    uint32_t ok;
    asm volatile("{\n.reg .pred p;\nelect.sync _|p, 0xFFFFFFFF;\nselp.u32 %0, 1, 0, p;\n}" : "=r"(ok));
    return ok != 0;
}
__device__ __forceinline__ void named_bar_sync(int id, int nthreads) {
    asm volatile("bar.sync %0, %1;" ::"r"(id), "r"(nthreads) : "memory");
}
__device__ __forceinline__ uint32_t mapa(uint32_t addr, uint32_t rank) {
    uint32_t r;
    asm volatile("mapa.shared::cluster.u32 %0, %1, %2;" : "=r"(r) : "r"(addr), "r"(rank));
    return r;
}

__device__ __forceinline__ void tma_load_2d(uint32_t dst, const CUtensorMap* tm, int c0, int c1, uint32_t bar) {
    asm volatile(
        "cp.async.bulk.tensor.2d.shared::cluster.global.mbarrier::complete_tx::bytes [%0], [%1, {%3, %4}], [%2];"
        ::"r"(dst), "l"(tm), "r"(bar), "r"(c0), "r"(c1) : "memory");
}
__device__ __forceinline__ void tma_load_3d(uint32_t dst, const CUtensorMap* tm, int c0, int c1, int c2, uint32_t bar) {
    asm volatile(
        "cp.async.bulk.tensor.3d.shared::cluster.global.mbarrier::complete_tx::bytes [%0], [%1, {%3, %4, %5}], [%2];"
        ::"r"(dst), "l"(tm), "r"(bar), "r"(c0), "r"(c1), "r"(c2) : "memory");
}
__device__ __forceinline__ void tma_store_2d(const CUtensorMap* tm, uint32_t src, int c0, int c1) {
    asm volatile("cp.async.bulk.tensor.2d.global.shared::cta.bulk_group [%0, {%2, %3}], [%1];"
                 ::"l"(tm), "r"(src), "r"(c0), "r"(c1) : "memory");
}
__device__ __forceinline__ void bulk_store(void* dst, uint32_t src, uint32_t bytes) {
    asm volatile("cp.async.bulk.global.shared::cta.bulk_group [%0], [%1], %2;" ::"l"(dst), "r"(src), "r"(bytes) : "memory");
}
__device__ __forceinline__ void bulk_commit() { asm volatile("cp.async.bulk.commit_group;" ::: "memory"); }
__device__ __forceinline__ void bulk_wait_read_all() { asm volatile("cp.async.bulk.wait_group.read 0;" ::: "memory"); }
__device__ __forceinline__ void bulk_wait_all() { asm volatile("cp.async.bulk.wait_group 0;" ::: "memory"); }
__device__ __forceinline__ void bulk_load(uint32_t dst, const void* src, uint32_t bytes, uint32_t bar) {
    asm volatile("cp.async.bulk.shared::cluster.global.mbarrier::complete_tx::bytes [%0], [%1], %2, [%3];"
                 ::"r"(dst), "l"(src), "r"(bytes), "r"(bar) : "memory");
}

__device__ __forceinline__ void ldsm_x4(uint32_t addr, uint32_t& r0, uint32_t& r1, uint32_t& r2, uint32_t& r3) {
    asm volatile("ldmatrix.sync.aligned.m8n8.x4.shared.b16 {%0,%1,%2,%3}, [%4];"
                 : "=r"(r0), "=r"(r1), "=r"(r2), "=r"(r3) : "r"(addr) : "memory");
}
__device__ __forceinline__ void ldsm_x4_t(uint32_t addr, uint32_t& r0, uint32_t& r1, uint32_t& r2, uint32_t& r3) {
    asm volatile("ldmatrix.sync.aligned.m8n8.x4.trans.shared.b16 {%0,%1,%2,%3}, [%4];"
                 : "=r"(r0), "=r"(r1), "=r"(r2), "=r"(r3) : "r"(addr) : "memory");
}
__device__ __forceinline__ void stsm_x4(uint32_t addr, uint32_t r0, uint32_t r1, uint32_t r2, uint32_t r3) {
    asm volatile("stmatrix.sync.aligned.m8n8.x4.shared.b16 [%0], {%1,%2,%3,%4};"
                 ::"r"(addr), "r"(r0), "r"(r1), "r"(r2), "r"(r3) : "memory");
}
__device__ __forceinline__ void mma16816(float* d, uint32_t a0, uint32_t a1, uint32_t a2, uint32_t a3,
                                         uint32_t b0, uint32_t b1) {
    asm volatile(
        "mma.sync.aligned.m16n8k16.row.col.f32.bf16.bf16.f32 {%0,%1,%2,%3}, {%4,%5,%6,%7}, {%8,%9}, {%0,%1,%2,%3};"
        : "+f"(d[0]), "+f"(d[1]), "+f"(d[2]), "+f"(d[3])
        : "r"(a0), "r"(a1), "r"(a2), "r"(a3), "r"(b0), "r"(b1));
}
__device__ __forceinline__ void mma1688(float* d, uint32_t a0, uint32_t a1, uint32_t b0) {
    asm volatile("mma.sync.aligned.m16n8k8.row.col.f32.bf16.bf16.f32 {%0,%1,%2,%3}, {%4,%5}, {%6}, {%0,%1,%2,%3};"
                 : "+f"(d[0]), "+f"(d[1]), "+f"(d[2]), "+f"(d[3]) : "r"(a0), "r"(a1), "r"(b0));
}
__device__ __forceinline__ uint2 lds64(uint32_t addr) {
    uint2 v;
    asm volatile("ld.volatile.shared.v2.b32 {%0,%1}, [%2];" : "=r"(v.x), "=r"(v.y) : "r"(addr) : "memory");
    return v;
}
__device__ __forceinline__ uint4 lds128(uint32_t addr) {
    uint4 v;
    asm volatile("ld.volatile.shared.v4.b32 {%0,%1,%2,%3}, [%4];" : "=r"(v.x), "=r"(v.y), "=r"(v.z), "=r"(v.w) : "r"(addr) : "memory");
    return v;
}
__device__ __forceinline__ void sts32(uint32_t addr, uint32_t x) {
    asm volatile("st.volatile.shared.b32 [%0], %1;" ::"r"(addr), "r"(x) : "memory");
}
__device__ __forceinline__ void sts64(uint32_t addr, uint32_t x, uint32_t y) {
    asm volatile("st.volatile.shared.v2.b32 [%0], {%1,%2};" ::"r"(addr), "r"(x), "r"(y) : "memory");
}
__device__ __forceinline__ void sts128(uint32_t addr, uint32_t x, uint32_t y, uint32_t z, uint32_t w) {
    asm volatile("st.volatile.shared.v4.b32 [%0], {%1,%2,%3,%4};" ::"r"(addr), "r"(x), "r"(y), "r"(z), "r"(w) : "memory");
}
__device__ __forceinline__ void st_async_v2(uint32_t addr, uint32_t x, uint32_t y, uint32_t bar) {
    asm volatile("st.async.weak.shared::cluster.mbarrier::complete_tx::bytes.v2.b32 [%0], {%1,%2}, [%3];"
                 ::"r"(addr), "r"(x), "r"(y), "r"(bar) : "memory");
}
__device__ __forceinline__ void st_relaxed_v4(void* p, uint32_t x) {
    asm volatile("st.relaxed.gpu.global.v4.b32 [%0], {%1,%1,%1,%1};" ::"l"(p), "r"(x) : "memory");
}
__device__ __forceinline__ uint32_t ld_relaxed_b32(const void* p) {
    uint32_t v;
    asm volatile("ld.relaxed.gpu.global.b32 %0, [%1];" : "=r"(v) : "l"(p) : "memory");
    return v;
}
__device__ __forceinline__ uint32_t lds32_volatile(uint32_t addr) {
    uint32_t v;
    asm volatile("ld.volatile.shared.b32 %0, [%1];" : "=r"(v) : "r"(addr) : "memory");
    return v;
}
__device__ __forceinline__ void st_relaxed_b32(void* p, uint32_t x) {
    asm volatile("st.relaxed.gpu.global.b32 [%0], %1;" ::"l"(p), "r"(x) : "memory");
}

__device__ __forceinline__ uint32_t ld_acquire_b32(const void* p) {
    uint32_t v;
    asm volatile("ld.acquire.gpu.global.b32 %0, [%1];" : "=r"(v) : "l"(p) : "memory");
    return v;
}
__device__ __forceinline__ void wait_flag(const uint32_t* p, uint32_t target) {
    uint32_t n = 0;
    while (ld_acquire_b32(p) < target) {
        __nanosleep(64);
        if (++n > SPIN_LIMIT) __trap();
    }
}
__device__ __forceinline__ void signal_flag(uint32_t* p) {
    asm volatile("red.release.gpu.global.add.u32 [%0], 1;" ::"l"(p) : "memory");
}
__device__ __forceinline__ void signal_bulk(uint32_t* p) {
    asm volatile("red.relaxed.gpu.global.add.u32 [%0], 1;" ::"l"(p) : "memory");
}
__device__ __forceinline__ bool next_to_rec(const uint32_t* flags) {
    uint32_t smid;
    asm volatile("mov.u32 %0, %%smid;" : "=r"(smid));
    smid ^= 1;
    return smid < 384 && ((ld_relaxed_b32(flags + F_RECSM + (smid >> 5)) >> (smid & 31)) & 1);
}
__device__ __forceinline__ void pdl_launch_dependents() { asm volatile("griddepcontrol.launch_dependents;" ::: "memory"); }

constexpr int BM = 128, BK = 64;
constexpr int A_STAGE = BM * BK * 2;
template <int BN> struct GemmCfg {
    static constexpr int STAGES = BN == 256 ? 3 : 6;
    static constexpr int STAGE = A_STAGE + BK * BN * 2;
    static constexpr int EPI_WARP = 16 * BN * 2;
    static constexpr int SMEM = STAGES * STAGE + 8 * EPI_WARP + 1024 + 512;
};

struct SideProb {
    CUtensorMap tmA, tmB, tmC;
    int n_split;
    int n_tiles, k_blocks, k_total, c_col0;
    const uint32_t* dep;
    uint32_t dep_target;
    int dep_n;
    uint32_t* sig;
    float* part;
    uint32_t* part_flag;
};
struct SideSeg { int prob, m0, m1; };
constexpr int SIDE_MAX_SEG = 3;
struct SideParams {
    SideProb prob[3];
    SideSeg seg[SIDE_MAX_SEG];
    int nseg;
    int spare_seg;
    const uint32_t* flags;
    uint32_t* queue;
};
static_assert(sizeof(SideParams) <= 4096, "kernel parameter limit");

__device__ __forceinline__ uint64_t make_desc(uint32_t addr, uint32_t lbo, uint32_t sbo) {
    return (uint64_t)((addr & 0x3FFFF) >> 4) | ((uint64_t)(lbo >> 4) << 16) | ((uint64_t)(sbo >> 4) << 32) | (1ull << 62);
}

__device__ __forceinline__ void wgmma_m64n256k16(float (&d)[128], uint64_t da, uint64_t db, int scale_d) {
    asm volatile(
        "{\n.reg .pred p;\nsetp.ne.b32 p, %130, 0;\n"
        "wgmma.mma_async.sync.aligned.m64n256k16.f32.bf16.bf16 "
        "{%0,%1,%2,%3,%4,%5,%6,%7,%8,%9,%10,%11,%12,%13,%14,%15,"
        "%16,%17,%18,%19,%20,%21,%22,%23,%24,%25,%26,%27,%28,%29,%30,%31,"
        "%32,%33,%34,%35,%36,%37,%38,%39,%40,%41,%42,%43,%44,%45,%46,%47,"
        "%48,%49,%50,%51,%52,%53,%54,%55,%56,%57,%58,%59,%60,%61,%62,%63,"
        "%64,%65,%66,%67,%68,%69,%70,%71,%72,%73,%74,%75,%76,%77,%78,%79,"
        "%80,%81,%82,%83,%84,%85,%86,%87,%88,%89,%90,%91,%92,%93,%94,%95,"
        "%96,%97,%98,%99,%100,%101,%102,%103,%104,%105,%106,%107,%108,%109,%110,%111,"
        "%112,%113,%114,%115,%116,%117,%118,%119,%120,%121,%122,%123,%124,%125,%126,%127},"
        " %128, %129, p, 1, 1, 0, 1;\n}\n"
        : "+f"(d[0]), "+f"(d[1]), "+f"(d[2]), "+f"(d[3]), "+f"(d[4]), "+f"(d[5]), "+f"(d[6]), "+f"(d[7]),
          "+f"(d[8]), "+f"(d[9]), "+f"(d[10]), "+f"(d[11]), "+f"(d[12]), "+f"(d[13]), "+f"(d[14]), "+f"(d[15]),
          "+f"(d[16]), "+f"(d[17]), "+f"(d[18]), "+f"(d[19]), "+f"(d[20]), "+f"(d[21]), "+f"(d[22]), "+f"(d[23]),
          "+f"(d[24]), "+f"(d[25]), "+f"(d[26]), "+f"(d[27]), "+f"(d[28]), "+f"(d[29]), "+f"(d[30]), "+f"(d[31]),
          "+f"(d[32]), "+f"(d[33]), "+f"(d[34]), "+f"(d[35]), "+f"(d[36]), "+f"(d[37]), "+f"(d[38]), "+f"(d[39]),
          "+f"(d[40]), "+f"(d[41]), "+f"(d[42]), "+f"(d[43]), "+f"(d[44]), "+f"(d[45]), "+f"(d[46]), "+f"(d[47]),
          "+f"(d[48]), "+f"(d[49]), "+f"(d[50]), "+f"(d[51]), "+f"(d[52]), "+f"(d[53]), "+f"(d[54]), "+f"(d[55]),
          "+f"(d[56]), "+f"(d[57]), "+f"(d[58]), "+f"(d[59]), "+f"(d[60]), "+f"(d[61]), "+f"(d[62]), "+f"(d[63]),
          "+f"(d[64]), "+f"(d[65]), "+f"(d[66]), "+f"(d[67]), "+f"(d[68]), "+f"(d[69]), "+f"(d[70]), "+f"(d[71]),
          "+f"(d[72]), "+f"(d[73]), "+f"(d[74]), "+f"(d[75]), "+f"(d[76]), "+f"(d[77]), "+f"(d[78]), "+f"(d[79]),
          "+f"(d[80]), "+f"(d[81]), "+f"(d[82]), "+f"(d[83]), "+f"(d[84]), "+f"(d[85]), "+f"(d[86]), "+f"(d[87]),
          "+f"(d[88]), "+f"(d[89]), "+f"(d[90]), "+f"(d[91]), "+f"(d[92]), "+f"(d[93]), "+f"(d[94]), "+f"(d[95]),
          "+f"(d[96]), "+f"(d[97]), "+f"(d[98]), "+f"(d[99]), "+f"(d[100]), "+f"(d[101]), "+f"(d[102]), "+f"(d[103]),
          "+f"(d[104]), "+f"(d[105]), "+f"(d[106]), "+f"(d[107]), "+f"(d[108]), "+f"(d[109]), "+f"(d[110]), "+f"(d[111]),
          "+f"(d[112]), "+f"(d[113]), "+f"(d[114]), "+f"(d[115]), "+f"(d[116]), "+f"(d[117]), "+f"(d[118]), "+f"(d[119]),
          "+f"(d[120]), "+f"(d[121]), "+f"(d[122]), "+f"(d[123]), "+f"(d[124]), "+f"(d[125]), "+f"(d[126]), "+f"(d[127])
        : "l"(da), "l"(db), "r"(scale_d));
}

__device__ __forceinline__ void wgmma_m64n128k16(float (&d)[64], uint64_t da, uint64_t db, int scale_d) {
    asm volatile(
        "{\n.reg .pred p;\nsetp.ne.b32 p, %66, 0;\n"
        "wgmma.mma_async.sync.aligned.m64n128k16.f32.bf16.bf16 "
        "{%0,%1,%2,%3,%4,%5,%6,%7,%8,%9,%10,%11,%12,%13,%14,%15,"
        "%16,%17,%18,%19,%20,%21,%22,%23,%24,%25,%26,%27,%28,%29,%30,%31,"
        "%32,%33,%34,%35,%36,%37,%38,%39,%40,%41,%42,%43,%44,%45,%46,%47,"
        "%48,%49,%50,%51,%52,%53,%54,%55,%56,%57,%58,%59,%60,%61,%62,%63},"
        " %64, %65, p, 1, 1, 0, 1;\n}\n"
        : "+f"(d[0]), "+f"(d[1]), "+f"(d[2]), "+f"(d[3]), "+f"(d[4]), "+f"(d[5]), "+f"(d[6]), "+f"(d[7]),
          "+f"(d[8]), "+f"(d[9]), "+f"(d[10]), "+f"(d[11]), "+f"(d[12]), "+f"(d[13]), "+f"(d[14]), "+f"(d[15]),
          "+f"(d[16]), "+f"(d[17]), "+f"(d[18]), "+f"(d[19]), "+f"(d[20]), "+f"(d[21]), "+f"(d[22]), "+f"(d[23]),
          "+f"(d[24]), "+f"(d[25]), "+f"(d[26]), "+f"(d[27]), "+f"(d[28]), "+f"(d[29]), "+f"(d[30]), "+f"(d[31]),
          "+f"(d[32]), "+f"(d[33]), "+f"(d[34]), "+f"(d[35]), "+f"(d[36]), "+f"(d[37]), "+f"(d[38]), "+f"(d[39]),
          "+f"(d[40]), "+f"(d[41]), "+f"(d[42]), "+f"(d[43]), "+f"(d[44]), "+f"(d[45]), "+f"(d[46]), "+f"(d[47]),
          "+f"(d[48]), "+f"(d[49]), "+f"(d[50]), "+f"(d[51]), "+f"(d[52]), "+f"(d[53]), "+f"(d[54]), "+f"(d[55]),
          "+f"(d[56]), "+f"(d[57]), "+f"(d[58]), "+f"(d[59]), "+f"(d[60]), "+f"(d[61]), "+f"(d[62]), "+f"(d[63])
        : "l"(da), "l"(db), "r"(scale_d));
}
template <int BN> struct WgmmaOp;
template <> struct WgmmaOp<256> {
    static __device__ __forceinline__ void run(float (&d)[128], uint64_t a, uint64_t b, int sc) { wgmma_m64n256k16(d, a, b, sc); }
};
template <> struct WgmmaOp<128> {
    static __device__ __forceinline__ void run(float (&d)[64], uint64_t a, uint64_t b, int sc) { wgmma_m64n128k16(d, a, b, sc); }
};

struct StoreRec {
    uint64_t dst;
    uint64_t flag;
    int kind;
    int pad;
};
struct EpiCtx { uint32_t buf, rec, st_full, st_empty; uint32_t it; int lane; };
template <int N>
__device__ __forceinline__ void epi_hand_over(const float (&acc)[N], EpiCtx& e, uint64_t dst, uint64_t flag, int kind) {
    mbar_wait(e.st_empty, (e.it & 1) ^ 1);
    const int mi = e.lane >> 3, row = (mi & 1) * 8 + (e.lane & 7);
    #pragma unroll
    for (int j = 0; j < N / 4; j += 2) {
        const int chunk = (j & 7) + (mi >> 1);
        stsm_x4(e.buf + (j >> 3) * 2048 + row * 128 + ((chunk ^ (row & 7)) << 4),
                pack_bf16(acc[4 * j], acc[4 * j + 1]), pack_bf16(acc[4 * j + 2], acc[4 * j + 3]),
                pack_bf16(acc[4 * j + 4], acc[4 * j + 5]), pack_bf16(acc[4 * j + 6], acc[4 * j + 7]));
    }
    if (e.lane == 0) {
        asm volatile("st.shared.v2.b64 [%0], {%1, %2};" ::"r"(e.rec), "l"(dst), "l"(flag) : "memory");
        asm volatile("st.shared.b32 [%0], %1;" ::"r"(e.rec + 16), "r"(kind) : "memory");
    }
    asm volatile("fence.proxy.async.shared::cta;" ::: "memory");
    __syncwarp();
    if (e.lane == 0) mbar_arrive(e.st_full);
    e.it++;
}
__device__ __forceinline__ void epi_exit(EpiCtx& e) {
    mbar_wait(e.st_empty, (e.it & 1) ^ 1);
    if (e.lane == 0) {
        asm volatile("st.shared.b32 [%0], %1;" ::"r"(e.rec + 16), "r"(-1) : "memory");
        mbar_arrive(e.st_full);
    }
}
template <int BN>
__device__ __forceinline__ void gemm_mainloop(float (&acc)[BN / 2], int k_blocks, uint32_t sbase, uint32_t bar_base, int cw,
                                              bool elected, int& stage, uint32_t& phase) {
    using C = GemmCfg<BN>;
    auto release = [&](int st) { mbar_arrive(bar_base + 8 * (C::STAGES + st)); };
    int prev_stage = -1;
    for (int kb = 0; kb < k_blocks; kb++) {
        mbar_wait(bar_base + 8 * stage, phase);
        const uint32_t sa = sbase + stage * C::STAGE + cw * (64 * 128);
        const uint32_t sb = sbase + stage * C::STAGE + A_STAGE;
        asm volatile("wgmma.fence.sync.aligned;" ::: "memory");
        #pragma unroll
        for (int kk = 0; kk < BK / 16; kk++)
            WgmmaOp<BN>::run(acc, make_desc(sa + kk * 32, 16, 1024), make_desc(sb + kk * 2048, 8192, 1024), (kb | kk) != 0);
        asm volatile("wgmma.commit_group.sync.aligned;" ::: "memory");
        asm volatile("wgmma.wait_group.sync.aligned 1;" ::: "memory");
        if (prev_stage >= 0 && elected) release(prev_stage);
        prev_stage = stage;
        if (++stage == C::STAGES) { stage = 0; phase ^= 1; }
    }
    asm volatile("wgmma.wait_group.sync.aligned 0;" ::: "memory");
    if (elected) release(prev_stage);
}
template <int BN>
__device__ __forceinline__ void store_warp(uint32_t epi_base, uint32_t rec_base, uint32_t st_full, uint32_t st_empty, int lane,
                                           const uint8_t* tmaps, int tstride) {
    for (uint32_t it = 0;; it++) {
        mbar_wait(st_full, it & 1);
        uint64_t dst = 0, flag = 0;
        int kind = -1;
        if (lane < 8) {
            const uint32_t rec = rec_base + lane * 32;
            asm volatile("ld.volatile.shared.v2.b64 {%0, %1}, [%2];" : "=l"(dst), "=l"(flag) : "r"(rec) : "memory");
            kind = (int)lds32_volatile(rec + 16);
        }
        if (__shfl_sync(~0u, kind, 0) < 0) break;
        if (lane < 8) {
            const uint32_t buf = epi_base + lane * GemmCfg<BN>::EPI_WARP;
            #pragma unroll
            for (int q = 0; q < BN / 64; q++) {
                tma_store_2d(reinterpret_cast<const CUtensorMap*>(tmaps + (kind - 1) * tstride), buf + q * 2048,
                                  (int)(uint32_t)dst + q * 64, (int)(dst >> 32));
            }
            bulk_commit();
            bulk_wait_read_all();
            mbar_arrive(st_empty);
            if (flag) {
                bulk_wait_all();
                signal_bulk(reinterpret_cast<uint32_t*>(flag));
            }
        }
        __syncwarp();
    }
    if (lane < 8) bulk_wait_all();
}

#define SCHED_AHEAD 4
template <int BN>
__global__ void __launch_bounds__(384, 1) side_gemm_kernel(const __grid_constant__ SideParams p) {
    using C = GemmCfg<BN>;
    extern __shared__ uint8_t smem_raw[];
    const uint32_t sbase = (smem_u32(smem_raw) + 1023) & ~1023u;
    const uint32_t epi_base = sbase + C::STAGES * C::STAGE;
    const uint32_t bar_base = epi_base + 8 * C::EPI_WARP;
    const uint32_t tfull = bar_base + 16 * C::STAGES, tempty = tfull + 16, tslot = tempty + 16, twant = tslot + 8;
    const uint32_t st_full = bar_base + 192, st_empty = st_full + 8, rec_base = bar_base + 256;
    const int tid = threadIdx.x, wg = tid >> 7;
    if (tid == 0) {
        for (int s = 0; s < C::STAGES; s++) { mbar_init(bar_base + 8 * s, 1); mbar_init(bar_base + 8 * (C::STAGES + s), 2); }
        for (int s = 0; s < 2; s++) { mbar_init(tfull + 8 * s, 1); mbar_init(tempty + 8 * s, 3); }
        mbar_init(twant, 1);
        mbar_init(st_full, 8);
        mbar_init(st_empty, 8);
        asm volatile("fence.mbarrier_init.release.cluster;" ::: "memory");
        pdl_launch_dependents();
    }
    __syncthreads();
    KENTER(BN == 256 ? 2 : 4);

    if (wg == 0) {
        asm volatile("setmaxnreg.dec.sync.aligned.u32 40;");
        if (tid == 0) {
            int stage = 0; uint32_t phase = 1;
            for (uint32_t it = 0;; it++) {
                mbar_wait(tfull + 8 * (it & 1), (it >> 1) & 1);
                const int code = (int)lds32_volatile(tslot + 4 * (it & 1));
                mbar_arrive(tempty + 8 * (it & 1));
                if (code < 0) break;
                const SideProb& q = p.prob[code >> 16];
                const int mt = (code >> 8) & 255, nt = code & 255;
                asm volatile("fence.proxy.async.global;" ::: "memory");
                const int kb0 = nt / q.n_split * q.k_blocks, nkb = nt + q.n_split < q.n_tiles ? q.k_blocks : q.k_total - kb0;
                for (int kb = 0; kb < nkb; kb++) {
                    if (kb == nkb - SCHED_AHEAD) mbar_arrive(twant);
                    mbar_wait(bar_base + 8 * (C::STAGES + stage), phase);
                    const uint32_t sa = sbase + stage * C::STAGE, fb = bar_base + 8 * stage;
                    mbar_arrive_expect_tx(fb, C::STAGE);
                    const int k0 = (kb0 + kb) * BK;
                    tma_load_2d(sa, &q.tmA, k0, mt * BM, fb);
                    tma_load_3d(sa + A_STAGE, &q.tmB, 0, k0, nt % q.n_split * (BN / 64), fb);
                    if (++stage == C::STAGES) { stage = 0; phase ^= 1; }
                }
            }
        } else if (tid >= 64 && tid < 96) {
            const int lane = tid & 31;
            const bool spare = p.spare_seg < 3 && next_to_rec(p.flags);
            uint32_t ntl[2], tgt[2], prb[2];
            const uint32_t* dp[2];
            #pragma unroll
            for (int u = 0; u < 2; u++) {
                const int g = u * 2 + (lane >> 4), mt = lane & 15;
                const bool on = g < p.nseg && mt >= p.seg[g < p.nseg ? g : 0].m0 && mt < p.seg[g < p.nseg ? g : 0].m1;
                prb[u] = p.seg[on ? g : 0].prob;
                const SideProb& q = p.prob[prb[u]];
                ntl[u] = on && !(g >= p.spare_seg && spare) ? q.n_tiles : 0;
                tgt[u] = on && q.dep ? q.dep_target : 0;
                dp[u] = tgt[u] ? q.dep + (mt + 1) * q.dep_n - 1 : p.queue;
            }
            for (uint32_t it = 0;; it++) {
                if (it > 0) mbar_wait_sleep(twant, (it - 1) & 1);
                int code = -1;
                for (uint32_t tries = 0; code < 0; tries++) {
                    const uint32_t c0 = ld_relaxed_b32(p.queue + lane), c1 = ld_relaxed_b32(p.queue + 32 + (lane & 15));
                    const uint32_t d0 = ld_relaxed_b32(dp[0]), d1 = ld_relaxed_b32(dp[1]);
                    const uint64_t left = __ballot_sync(~0u, c0 < ntl[0]) | (uint64_t)__ballot_sync(~0u, c1 < ntl[1]) << 32;
                    uint64_t ready = left & (__ballot_sync(~0u, d0 >= tgt[0]) | (uint64_t)__ballot_sync(~0u, d1 >= tgt[1]) << 32);
                    if (!left) break;
                    if (!ready && (BN == 128 || (left >> (((__ffsll(left) - 1) & ~15) + 16)) == 0)) ready = left;
                    if (!ready) __nanosleep(200);
                    while (ready) {
                        const int e = __ffsll(ready) - 1;
                        const uint32_t n = __shfl_sync(~0u, e < 32 ? ntl[0] : ntl[1], e & 31), pr = __shfl_sync(~0u, e < 32 ? prb[0] : prb[1], e & 31);
                        uint32_t idx = 0;
                        if (lane == 0) idx = atomicAdd(p.queue + e, 1u);
                        idx = __shfl_sync(~0u, idx, 0);
                        if (idx < n) { code = (pr << 16) | ((e & 15) << 8) | idx; break; }
                        for (uint32_t k = idx / n; k > 0; k--) ready &= ready - 1;
                    }
                    if (tries > SPIN_LIMIT) __trap();
                }
                if (code >= 0) {
                    const SideProb& q = p.prob[code >> 16];
                    if (q.dep && lane < q.dep_n) wait_flag(q.dep + ((code >> 8) & 255) * q.dep_n + lane, q.dep_target);
                    __syncwarp();
                }
                if (lane == 0) {
                    mbar_wait(tempty + 8 * (it & 1), ((it >> 1) & 1) ^ 1);
                    asm volatile("st.shared.b32 [%0], %1;" ::"r"(tslot + 4 * (it & 1)), "r"(code) : "memory");
                    mbar_arrive(tfull + 8 * (it & 1));
                }
                __syncwarp();
                if (code < 0) break;
            }
        } else if (tid >= 32 && tid < 64) {
            store_warp<BN>(epi_base, rec_base, st_full, st_empty, tid & 31, reinterpret_cast<const uint8_t*>(&p.prob[0].tmC),
                           (int)sizeof(SideProb));
        }
    } else {
        asm volatile("setmaxnreg.inc.sync.aligned.u32 232;");
        const int cw = wg - 1, lane = tid & 31, wi = (tid >> 5) & 3;
        const bool elected = (tid & 127) == 0;
        int stage = 0; uint32_t phase = 0;
        float acc[BN / 2];
        EpiCtx ectx = {epi_base + (cw * 4 + wi) * C::EPI_WARP, rec_base + (cw * 4 + wi) * 32, st_full, st_empty, 0, lane};
        for (uint32_t it = 0;; it++) {
            mbar_wait(tfull + 8 * (it & 1), (it >> 1) & 1);
            const int code = (int)lds32_volatile(tslot + 4 * (it & 1));
            named_bar_sync(1 + cw, 128);
            if (elected) mbar_arrive(tempty + 8 * (it & 1));
            if (code < 0) break;
            const SideProb& q = p.prob[code >> 16];
            const int mt = (code >> 8) & 255, nt = code & 255;
            gemm_mainloop<BN>(acc, nt + q.n_split < q.n_tiles ? q.k_blocks : q.k_total - nt / q.n_split * q.k_blocks, sbase, bar_base, cw, elected, stage, phase);
            const int row0 = mt * BM + cw * 64 + wi * 16, ntc = nt % q.n_split;
            if (BN == 128 && q.part) {
                const int idx = (mt & 3) * q.n_split + ntc, item = nt / q.n_split, nprev = q.n_tiles / q.n_split - 1;
                float4* part = reinterpret_cast<float4*>(q.part) + (size_t)idx * 2 * (BM * BN / 4) + (tid - 128);
                if (mt == 14 && elected) KMARK(21);
                if (item < nprev) {
                    #pragma unroll
                    for (int j = 0; j < BN / 8; j++)
                        __stcg(part + item * (BM * BN / 4) + j * 256, make_float4(acc[4 * j], acc[4 * j + 1], acc[4 * j + 2], acc[4 * j + 3]));
                    __syncwarp();
                    if (lane == 0) signal_flag(q.part_flag + idx);
                    continue;
                }
                if (lane == 0) wait_flag(q.part_flag + idx, 8 * nprev);
                __syncwarp();
                if (mt == 14 && elected) KMARK(22);
                for (int u = 0; u < nprev; u++) {
                    #pragma unroll
                    for (int j = 0; j < BN / 8; j++) {
                        const float4 v = __ldcg(part + u * (BM * BN / 4) + j * 256);
                        acc[4 * j] += v.x; acc[4 * j + 1] += v.y; acc[4 * j + 2] += v.z; acc[4 * j + 3] += v.w;
                    }
                }
            }
            if (BN == 128 && mt == 14 && elected) KMARK(23);
            epi_hand_over(acc, ectx, ((uint64_t)row0 << 32) | (uint32_t)(q.c_col0 + ntc * BN), q.sig ? (uint64_t)(q.sig + mt) : 0, 1 + (code >> 16));
        }
        epi_exit(ectx);
        if (elected) KEXIT(BN == 256 ? 2 : 4);
    }
}

constexpr int FIN_SPLIT = 8, FIN_KB = HD / BK / FIN_SPLIT;
constexpr int FIN_A1 = FIN_KB * 16384;
constexpr int FIN_A0 = FIN_A1 + FIN_KB * 8192;
constexpr int FIN_BAR = FIN_A0 + 4 * 8192, FIN_SMEM = FIN_BAR + 256;
enum { FB_B = 0, FB_A1 = 64, FB_A0 = 128, FB_E0 = 160, FB_RDY = 192, FB_RED = 208 };
struct FinalParams {
    CUtensorMap tmA, tmB;
    __nv_bfloat16* out;
    const uint32_t* dep;
    uint32_t dep_target;
    int mt;
};
__global__ void __launch_bounds__(384, 1) final_gemm_kernel(const __grid_constant__ FinalParams p) {
    extern __shared__ __align__(1024) uint8_t smem_raw[];
    const uint32_t sbase = smem_u32(smem_raw), bar = sbase + FIN_BAR;
    const int tid = threadIdx.x, wg = tid >> 7;
    const int rank = blockIdx.x % FIN_SPLIT, nt = blockIdx.x / FIN_SPLIT;
    KENTER(5);
    if (tid == 0) {
        for (int s = 0; s < FIN_KB; s++) { mbar_init(bar + FB_B + 8 * s, 1); mbar_init(bar + FB_A1 + 8 * s, 1); }
        for (int s = 0; s < 4; s++) { mbar_init(bar + FB_A0 + 8 * s, 1); mbar_init(bar + FB_E0 + 8 * s, 1); }
        for (int h = 0; h < 2; h++) { mbar_init(bar + FB_RDY + 8 * h, FIN_SPLIT); mbar_init(bar + FB_RED + 8 * h, 1); }
        asm volatile("fence.mbarrier_init.release.cluster;" ::: "memory");
        for (int h = 0; h < 2; h++) mbar_arrive_expect_tx(bar + FB_RED + 8 * h, (FIN_SPLIT - 1) * 4096);
        pdl_launch_dependents();
    }
    __syncthreads();
    asm volatile("barrier.cluster.arrive.relaxed.aligned;" ::: "memory");
    if (wg == 0) {
        auto need = [&](int i) {
            uint32_t n = 0;
            while (ld_acquire_b32(p.dep + i) < p.dep_target) { if (++n > SPIN_LIMIT) __trap(); }
            asm volatile("fence.proxy.async.global;" ::: "memory");
        };
        auto a_load = [&](uint32_t dst, int kb, int seg, uint32_t mb) { tma_load_2d(dst, &p.tmA, (rank * FIN_KB + kb) * BK, p.mt * BM + seg * SEG, mb); };
        if (tid == 0) {
            auto b_load = [&](int kb) {
                mbar_arrive_expect_tx(bar + FB_B + 8 * kb, 16384);
                tma_load_3d(sbase + kb * 16384, &p.tmB, 0, (rank * FIN_KB + kb) * BK, nt * 2, bar + FB_B + 8 * kb);
            };
            const uint32_t f0 = ld_relaxed_b32(p.dep);
            b_load(0);
            need(1);
            if (f0 < p.dep_target) need(0);
            for (int kb = 0; kb < FIN_KB; kb++) {
                if (kb >= 4) mbar_wait(bar + FB_E0 + 8 * (kb & 3), 0);
                mbar_arrive_expect_tx(bar + FB_A0 + 8 * (kb & 3), 8192);
                for (int u = 0; u < 2; u++) a_load(sbase + FIN_A0 + (kb & 3) * 8192 + u * 4096, kb, u, bar + FB_A0 + 8 * (kb & 3));
                if (kb < 3) b_load(kb + 1);
                if (kb == 3) { b_load(4); b_load(5); }
                if (kb == 4 || kb == 5) b_load(kb + 2);
            }
        } else if (tid == 96) {
            need(3);
            for (int kb = 1; kb < FIN_KB; kb += 2) a_load(sbase + FIN_A1 + kb * 8192 + 4096, kb, 3, bar + FB_A1 + 8 * kb);
        } else if (tid == 64) {
            mbar_wait(bar + FB_B + 8 * 3, 0);
            need(2);
            for (int kb = 0; kb < FIN_KB; kb++) {
                mbar_arrive_expect_tx(bar + FB_A1 + 8 * kb, 8192);
                a_load(sbase + FIN_A1 + kb * 8192, kb, 2, bar + FB_A1 + 8 * kb);
            }
            need(3);
            KMARK(15);
            for (int kb = 0; kb < FIN_KB; kb += 2) a_load(sbase + FIN_A1 + kb * 8192 + 4096, kb, 3, bar + FB_A1 + 8 * kb);
        }
        __syncwarp();
        asm volatile("barrier.cluster.wait.aligned;" ::: "memory");
    } else {
        const int h = wg - 1, lane = tid & 31, wi = (tid >> 5) & 3, t128 = tid & 127;
        asm volatile("barrier.cluster.wait.aligned;" ::: "memory");
        float acc[64];
        for (int kb = 0; kb < FIN_KB; kb++) {
            mbar_wait(bar + FB_B + 8 * kb, 0);
            if (h == 0) mbar_wait(bar + FB_A0 + 8 * (kb & 3), kb >> 2); else mbar_wait(bar + FB_A1 + 8 * kb, 0);
            const uint32_t sa = sbase + (h == 0 ? FIN_A0 + (kb & 3) * 8192 : FIN_A1 + kb * 8192), sb = sbase + kb * 16384;
            asm volatile("wgmma.fence.sync.aligned;" ::: "memory");
            #pragma unroll
            for (int kk = 0; kk < BK / 16; kk++)
                wgmma_m64n128k16(acc, make_desc(sa + kk * 32, 16, 1024), make_desc(sb + kk * 2048, 8192, 1024), (kb | kk) != 0);
            asm volatile("wgmma.commit_group.sync.aligned;" ::: "memory");
            asm volatile("wgmma.wait_group.sync.aligned 1;" ::: "memory");
            if (h == 0 && kb >= 1 && kb <= 4 && t128 == 0) mbar_arrive(bar + FB_E0 + 8 * (kb - 1));
        }
        asm volatile("wgmma.wait_group.sync.aligned 0;" ::: "memory");
        const uint32_t red = sbase + FIN_A0;
        auto ready = [&](int i) {
            named_bar_sync(1, 128);
            if (t128 < FIN_SPLIT)
                asm volatile("mbarrier.arrive.relaxed.cluster.shared::cluster.b64 _, [%0];" ::"r"(mapa(bar + FB_RDY + 8 * i, t128)) : "memory");
        };
        if (tid == 256) KMARK(16);
        if (tid == 128) KMARK(19);
        if (h == 0) ready(0);
        mbar_wait(bar + FB_RDY + 8 * h, 0);
        if (tid == 256) KMARK(17);
        #pragma unroll
        for (int q = 0; q < FIN_SPLIT; q++) {
            if (q != rank) {
                const uint32_t dst = mapa(red + (rank - (rank > q ? 1 : 0)) * 4096 + t128 * 16, q), rb = mapa(bar + FB_RED + 8 * h, q);
                #pragma unroll
                for (int j = 0; j < 2; j++)
                    asm volatile("st.async.weak.shared::cluster.mbarrier::complete_tx::bytes.v4.f32 [%0], {%1,%2,%3,%4}, [%5];"
                                 ::"r"(dst + j * 2048), "f"(acc[8 * q + 4 * j]), "f"(acc[8 * q + 4 * j + 1]),
                                   "f"(acc[8 * q + 4 * j + 2]), "f"(acc[8 * q + 4 * j + 3]), "r"(rb) : "memory");
            }
        }
        float o[8];
        #pragma unroll
        for (int q = 0; q < FIN_SPLIT; q++)
            if (q == rank) {
                #pragma unroll
                for (int e = 0; e < 8; e++) o[e] = acc[8 * q + e];
            }
        mbar_wait(bar + FB_RED + 8 * h, 0);
        if (tid == 256) KMARK(18);
        if (tid == 128) KMARK(20);
        #pragma unroll
        for (int sl = 0; sl < FIN_SPLIT - 1; sl++) {
            #pragma unroll
            for (int j = 0; j < 2; j++) {
                const uint4 v = lds128(red + sl * 4096 + j * 2048 + t128 * 16);
                o[4 * j] += __uint_as_float(v.x); o[4 * j + 1] += __uint_as_float(v.y);
                o[4 * j + 2] += __uint_as_float(v.z); o[4 * j + 3] += __uint_as_float(v.w);
            }
        }
        if (h == 0) ready(1);
        __nv_bfloat16* dst = p.out + (size_t)(p.mt * BM + h * 64 + wi * 16 + (lane >> 2)) * (2 * DM) + nt * 128 + rank * 16 + (lane & 3) * 2;
        #pragma unroll
        for (int j = 0; j < 2; j++) {
            *reinterpret_cast<uint32_t*>(dst + j * 8) = pack_bf16(o[4 * j], o[4 * j + 1]);
            *reinterpret_cast<uint32_t*>(dst + (size_t)8 * (2 * DM) + j * 8) = pack_bf16(o[4 * j + 2], o[4 * j + 3]);
        }
        if (t128 == 0) KEXIT(5);
    }
}

#define POLL_DELAY 2
#define FETCH_DELAY 450
#define AT_PF 7
#define AT_FIRST 4
#define SKIP3 3
#define V_FIRST 0
#define WO_PF 12
#define WO_PFA 6
#define WO_PFB_DELAY 60
#define V_EARLY 6
constexpr int REC_THREADS = 256;
constexpr uint32_t POLL_LIMIT = 1u << 16;
constexpr int NREG = 24;
__host__ __device__ constexpr int reg_idx(int j) { return ((j & 3) - 1) * 8 + (j >> 2); }
constexpr int SM_WQ = 0;
constexpr int SM_WO = 65536;
constexpr int SM_X = SM_WO + 11 * 8192;
constexpr int SM_PARK0 = SM_X, SM_PARK1 = SM_X + 8192;
constexpr int SM_MEM = SM_X + 4 * 4096;
constexpr int SM_RED = SM_X + 8 * 4096;
constexpr int SM_V = SM_X + 12 * 4096;
constexpr int SM_K = SM_X + 14 * 4096;
constexpr int SM_QS = SM_X + 15 * 4096;
constexpr int SM_QK = SM_X + 65536;
constexpr int SM_SP = SM_QK + 2048;
constexpr int SM_VM = SM_SP + 2560;
constexpr int SM_O = SM_VM + 2048;
constexpr int SM_SUM = SM_O + 2048;
constexpr int SM_TBL = SM_SUM + 128;
constexpr int SM_BAR = SM_TBL + 512;
constexpr int SM_STAMP = SM_BAR + 224;
constexpr int REC_SMEM = SM_STAMP;
static_assert(REC_SMEM <= 232448, "shared memory");
enum { BAR_V = 0, BAR_X = 8, BAR_P0 = 16, BAR_WQ = 40, BAR_WO = 48, BAR_XG = 56, BAR_F0 = 88, BAR_F3 = 96, BAR_VF = 104,
       BAR_M = 112, BAR_GO = 144, BAR_PK = 152, BAR_VM = 160, BAR_SELF = 168, BAR_TPUB = 176, BAR_MIN = 176, BAR_PUB = 192 };

template <int V> struct IntC { static constexpr int value = V; };
template <int I, int N, typename F> __device__ __forceinline__ void sfor(F&& f) {
    if constexpr (I < N) { f(IntC<I>{}); sfor<I + 1, N>(f); }
}

struct RecParams {
    CUtensorMap tmW[3];
    CUtensorMap tmWo;
    CUtensorMap tmX;
    const __nv_bfloat16* mem0;
    __nv_bfloat16* qkv_tok;
    __nv_bfloat16* kv_mem;
    uint8_t* xchg;
    uint32_t* flags;
    uint32_t one[2];
    uint32_t* arrivals;
};

__device__ __forceinline__ void mma_a(float* d, const uint32_t* a, uint32_t b0, uint32_t b1) {
    mma16816(d, a[0], a[1], a[2], a[3], b0, b1);
}
__device__ __forceinline__ void ldsm4(uint32_t addr, uint32_t* r) { ldsm_x4(addr, r[0], r[1], r[2], r[3]); }
__device__ __forceinline__ void ldsm4t(uint32_t addr, uint32_t* r) { ldsm_x4_t(addr, r[0], r[1], r[2], r[3]); }
template <int OFF> __device__ __forceinline__ void repoll_v2(uint2& v, const uint8_t* p) {
    asm volatile("{\n.reg .pred q;\nsetp.eq.u32 q, %1, 0xFFFFFFFF;\n@q ld.relaxed.gpu.global.v2.b32 {%0,%1}, [%2+%3];\n}"
                 : "+r"(v.x), "+r"(v.y) : "l"(p), "n"(OFF) : "memory");
}
__device__ __forceinline__ uint32_t max3(uint32_t a, uint32_t b, uint32_t c) { return max(max(a, b), c); }
__device__ __forceinline__ uint32_t pub_slot(int s) { return (s & 1) * XCHG_SLOT + ((s >> 1) & 1) * PUB_BYTES; }

__device__ __forceinline__ uint8_t* xaddr(uint32_t lo, uint32_t hi) {
    uint64_t a;
    asm("mov.b64 %0, {%1, %2};" : "=l"(a) : "r"(lo), "r"(hi));
    return reinterpret_cast<uint8_t*>(a);
}
template <int N> __device__ __forceinline__ uint32_t delay_zero(uint32_t a) {
    uint32_t x = a;
    #pragma unroll
    for (int i = 0; i < N; i++) x = lds32_volatile(x);
    return x - a;
}
__device__ __forceinline__ uint32_t fresh(uint32_t x) { asm volatile("" : "+r"(x)); return x; }

__device__ __forceinline__ void sched_fence(uint32_t& x, uint32_t zero) { x ^= clock32() & zero; }

template <int NT> __device__ __forceinline__ uint32_t wo_addr(uint32_t ao, uint32_t a3, int n) {
    return (n % NT == 2 ? a3 : ao + (n % NT) * 32768) + (n / NT) * 1024;
}
template <int NT>
__device__ __forceinline__ void wo_load(uint32_t ao, uint32_t a3, int n, uint32_t third, uint32_t* r, bool skip) {
    if (skip && n % NT == 2)
        asm volatile("{\n.reg .pred p;\nsetp.ne.u32 p, %5, 0;\nmov.b32 %0, 0;\nmov.b32 %1, 0;\nmov.b32 %2, 0;\nmov.b32 %3, 0;\n"
                     "@p ldmatrix.sync.aligned.m8n8.x4.trans.shared.b16 {%0,%1,%2,%3}, [%4];\n}"
                     : "=r"(r[0]), "=r"(r[1]), "=r"(r[2]), "=r"(r[3]) : "r"(wo_addr<NT>(ao, a3, n)), "r"(third) : "memory");
    else ldsm4t(wo_addr<NT>(ao, a3, n), r);
}
template <int NT, int PF>
__device__ __forceinline__ void wo_phase(uint32_t (&st)[8 * NT][4], uint32_t ao, uint32_t a3, uint32_t l16, uint32_t tbl, uint32_t sums,
                                         uint32_t slot, uint32_t xhi, uint32_t third, uint32_t xbar, uint32_t xpar, bool& x_ok, uint32_t wg, uint32_t zero, uint32_t& tok) {
    constexpr int AHEAD = PF > 0 ? PF - NT : 10;
    uint32_t of[4][4];
    uint2 sm;
    uint4 t;
    ldsm4t(l16 + SM_O, of[0]);
    #pragma unroll
    for (int n = PF; n < AHEAD; n++) {
        ldsm4t(wo_addr<NT>(ao, a3, n), st[n]);
        if (n == 2 * NT - 1) ldsm4t(l16 + SM_O + 512, of[1]);
    }
    if (PF >= 2 * NT) ldsm4t(l16 + SM_O + 512, of[1]);
    float acc[NT][4];
    #pragma unroll
    for (int i = 0; i < NT; i++) { acc[i][0] = acc[i][1] = acc[i][2] = acc[i][3] = 0.f; }
    #pragma unroll
    for (int kk = 0; kk < 8; kk++) {
        #pragma unroll
        for (int i = 0; i < NT; i++) {
            const int n = kk * NT + i;
            mma_a(acc[i], st[n], of[kk >> 1][(kk & 1) * 2], of[kk >> 1][(kk & 1) * 2 + 1]);
            if (n + AHEAD >= PF && n + AHEAD < 8 * NT) wo_load<NT>(ao, a3, n + AHEAD, third, st[n + AHEAD], SKIP3 & 1);
        }
        if (kk == 1 || kk == 3) ldsm4t(l16 + SM_O + ((kk >> 1) + 2) * 512, of[(kk >> 1) + 2]);
        if (kk == (NT == 3 ? 5 : 4)) {
            const uint32_t x = fresh(l16);
            sm = lds64(sums + ((x >> 1) & 0x18));
            t = lds128(tbl + ((x >> 3) & 0x30));
            x_ok = mbar_test_wait(xbar, xpar);
        }
    }
    if (NT == 3) {
        sched_fence(tok, zero);
        asm volatile("{\n.reg .pred p;\nsetp.ne.u32 p, %0, 0;\n@p bar.arrive 9, 256;\n}" ::"r"(wg) : "memory");
    }
    const float i0 = rcp(__uint_as_float(sm.x)), i1 = rcp(__uint_as_float(sm.y));
    const uint32_t d = slot + ((fresh(l16) >> 1) & 0x38);
    const uint32_t pl[3] = {t.x + d, t.y + d, t.z + d};
    #pragma unroll
    for (int i = 0; i < NT; i++)
        asm volatile("{\n.reg .pred p;\nsetp.ne.u32 p, %3, 0;\n@p st.relaxed.gpu.global.v2.b32 [%0], {%1,%2};\n}"
                     ::"l"(xaddr(pl[i], xhi)), "r"(pack_bf16(acc[i][0] * i0, acc[i][1] * i1)), "r"(pack_bf16(acc[i][2] * i0, acc[i][3] * i1)),
                       "r"(i < 2 ? 1u : third) : "memory");
}

constexpr uint32_t SMEM_ORIGIN = 1024;
constexpr uint64_t DESC_BASE = (1ull << 16) | (0x40000040ull << 32);
template <int OFFB, int SCALE_D>
__device__ __forceinline__ void wgmma_n32_rs(float (&d)[16], const uint32_t* a, uint32_t one) {
    asm volatile(
        "{\n.reg .b64 db;\nmad.wide.u32 db, %20, %21, %22;\n"
        "wgmma.mma_async.sync.aligned.m64n32k16.f32.bf16.bf16 {%0,%1,%2,%3,%4,%5,%6,%7,%8,%9,%10,%11,%12,%13,%14,%15}, "
        "{%16,%17,%18,%19}, db, %23, 1, 1, 0;\n}"
        : "+f"(d[0]), "+f"(d[1]), "+f"(d[2]), "+f"(d[3]), "+f"(d[4]), "+f"(d[5]), "+f"(d[6]), "+f"(d[7]),
          "+f"(d[8]), "+f"(d[9]), "+f"(d[10]), "+f"(d[11]), "+f"(d[12]), "+f"(d[13]), "+f"(d[14]), "+f"(d[15])
        : "r"(a[0]), "r"(a[1]), "r"(a[2]), "r"(a[3]), "r"(one), "n"((SMEM_ORIGIN + OFFB) >> 4), "l"(DESC_BASE), "n"(SCALE_D));
}
template <int OFFA, int OFFB, int SCALE_D>
__device__ __forceinline__ void wgmma_n32_ss(float (&d)[16], uint32_t one) {
    asm volatile(
        "{\n.reg .b64 da, db;\nmad.wide.u32 da, %16, %17, %19;\nmad.wide.u32 db, %16, %18, %19;\n"
        "wgmma.mma_async.sync.aligned.m64n32k16.f32.bf16.bf16 {%0,%1,%2,%3,%4,%5,%6,%7,%8,%9,%10,%11,%12,%13,%14,%15}, "
        "da, db, %20, 1, 1, 1, 0;\n}"
        : "+f"(d[0]), "+f"(d[1]), "+f"(d[2]), "+f"(d[3]), "+f"(d[4]), "+f"(d[5]), "+f"(d[6]), "+f"(d[7]),
          "+f"(d[8]), "+f"(d[9]), "+f"(d[10]), "+f"(d[11]), "+f"(d[12]), "+f"(d[13]), "+f"(d[14]), "+f"(d[15])
        : "r"(one), "n"((SMEM_ORIGIN + OFFA) >> 4), "n"((SMEM_ORIGIN + OFFB) >> 4), "l"(DESC_BASE), "n"(SCALE_D));
}
template <int WG, int J0, int J1, int I, bool ACC, bool FENCE = true>
__device__ __forceinline__ void token_mma(float (&ta)[2][16], const uint32_t (&wr)[NREG][2][4], uint32_t one) {
    if (FENCE) asm volatile("wgmma.fence.sync.aligned;" ::: "memory");
    sfor<J0, J1>([&](auto J) {
        constexpr int j = J.value, c = j >> 2, offb = SM_X + WG * 32768 + c * 4096 + (j & 3) * 32, sc = (ACC || j != J0) ? 1 : 0;
        if constexpr ((j & 3) != 0) wgmma_n32_rs<offb, sc>(ta[I], wr[reg_idx(j)][I], one);
        else if constexpr (WG == 0 || (I == 1 && c >= 4)) wgmma_n32_ss<SM_WQ + WG * 32768 + I * 16384 + c * 2048, offb, sc>(ta[I], one);
        constexpr int m = I ? c : c - 4;
        if constexpr (WG == 0 && (j & 3) == 1 && m >= 0)
            wgmma_n32_ss<SM_WQ + 32768 + (1 - I) * 16384 + m * 2048, SM_X + 32768 + m * 4096, 1>(ta[I], one);
    });
    asm volatile("wgmma.commit_group.sync.aligned;" ::: "memory");
}
__device__ __forceinline__ void warp_arrive(uint32_t bar) {
    __syncwarp();
    if (elect_one()) mbar_arrive(bar);
    __syncwarp();
}
__device__ __forceinline__ void remote_arrive(uint32_t bar, uint32_t rank) {
    asm volatile("mbarrier.arrive.relaxed.cluster.shared::cluster.b64 _, [%0];" ::"r"(mapa(bar, rank)) : "memory");
}
__device__ __forceinline__ void x_load(const RecParams& p, uint32_t sb, int sg, int g) {
    asm volatile("{\n.reg .pred p;\nelect.sync _|p, 0xFFFFFFFF;\n"
                 "@p cp.async.bulk.tensor.3d.shared::cluster.global.mbarrier::complete_tx::bytes.multicast::cluster [%0], [%1, {%3, %4, %5}], [%2], %6;\nbar.warp.sync 0xFFFFFFFF;\n}"
                 ::"r"(sb + SM_X + g * 16384), "l"(&p.tmX), "r"(sb + SM_BAR + BAR_XG + 8 * g), "r"(0), "r"(sg * SEG), "r"(g * 4), "h"((uint16_t)7) : "memory");
}

__device__ __forceinline__ void rec_steps(const RecParams& p, const uint32_t (&wr)[NREG][2][4], const uint32_t sb, const int warp,
                                          const int cta, const int head, const int rank) {
    const int wq = warp & 3, wg = warp >> 2;
    const uint32_t bar = sb + SM_BAR;
    const uint32_t xhi = (uint32_t)((uint64_t)p.xchg >> 32);
    const float sl2 = 0.08838834764831845f * 1.4426950408889634f;
    const bool has_unit = warp >= 5 && (warp < 7 || cta < 64);
    const bool qk = rank < 2;
    const uint32_t pa = rank == 2 ? 0 : rank + 1, pb = rank == 0 ? 2 : rank - 1;
    const uint32_t tbl = sb + SM_TBL + warp * 64;
    const bool att = (warp & 6) == 2;
    const int stile = warp < 5 ? warp : warp - 3;

    const uint32_t u_xa = uniform(sb + (qk ? SM_SP + rank * 1280 + stile * 256 : SM_VM + warp * 256));
    const uint32_t u_key = uniform(!qk || att || warp == 7 ? 0 : sb + (warp == 4 ? SM_QK + 1024 : SM_K + stile * 1024));
    const uint32_t u_bx = uniform(bar + (qk ? BAR_X : BAR_VM)), u_bra = uniform(mapa(u_bx, pa)), u_brb = uniform(mapa(u_bx, pb));
    const uint32_t u_src = uniform(lds32_volatile(tbl + 44));
    const uint32_t u_role = uniform((has_unit ? 1 : 0) | (att ? 2 : 0) | (wg == 1 || qk ? 4 : 0) | (rank != 1 && warp == 0 ? 8 : 0) | (rank != 0 && warp == 1 ? 16 : 0) |
                                    (warp == 5 || warp == 6 ? 32 : 0));
    uint32_t l16, aq, ao;
    {
        const int lane = threadIdx.x & 31, mi = lane >> 3, r8 = lane & 7, r16 = (mi >> 1) * 8 + r8;
        l16 = opaque(sb + lane * 16);
        aq = opaque(sb + SM_WQ + wg * 32768 + r16 * 128 + (((wq * 2 + (mi & 1)) ^ r8) << 4));
        ao = opaque(sb + SM_WO + (warp >> 1) * 8192 + r16 * 64 + ((((warp & 1) * 2 + (mi & 1)) ^ ((r8 >> 1) & 3)) << 4));
    }

    uint32_t mphase = 0;
    bool x0_ok = false;
    #pragma unroll 1
    for (int s = 0;; s++) {
        const uint32_t par = s & 1;
        uint32_t at[16][4];
        auto at_early = [](int i) { return i < 2 || ((i & 1) == 1 && (i >> 1) < AT_PF - 1); };
        auto at_prefetch = [&](bool first) {
            #pragma unroll
            for (int i = 0; i < 16; i++)
                if (at_early(i) && first == ((i & 1) == 1 && (i >> 1) < AT_FIRST)) ldsm4t(aq + (i & 1) * 16384 + (i >> 1) * 2048, at[i]);
        };
        auto att_stores = [&](bool tiles, bool rows) {
            if (warp == 4) {
                if (rows && !qk) mbar_wait_bounded(bar + BAR_VM, par);
                asm volatile("fence.proxy.async.shared::cta;" ::: "memory");
                if (elect_one()) {
                    if (tiles) {
                        __nv_bfloat16* dst = p.qkv_tok + ((size_t)s * NH + head) * (SEG * DH);
                        constexpr size_t MAT = (size_t)NSEG * NH * SEG * DH;
                        bulk_store(dst + (qk ? rank * (SEG * 64) : 2 * MAT), sb + (qk ? SM_QS : SM_V), 4096);
                        bulk_store(dst + (qk ? MAT + rank * (SEG * 64) : 2 * MAT + SEG * 64), sb + (qk ? SM_K : SM_V + 4096), 4096);
                    }
                    if (rows)
                        bulk_store(p.kv_mem + ((size_t)s * NH + head) * (MROWS * DH) + (qk ? rank * (MROWS * 64) : NSEG * NH * MROWS * DH),
                                   sb + (qk ? SM_QK + 1024 : SM_VM), qk ? 1024 : 2048);
                    bulk_commit();
                }
            }
        };
        uint32_t b[16][4];
        if (wg == 0) {
            float ta[2][16];
            if (!x0_ok) mbar_wait_bounded(bar + BAR_XG, par);
            STAMP(6);
            auto park = [&](int i, uint32_t dst) {
                #pragma unroll
                for (int e = 0; e < 16; e++) asm volatile("" : "+f"(ta[i][e]));
                #pragma unroll
                for (int j = 0; j < 4; j++)
                    sts128(l16 + dst + j * 2048 + wq * 512, __float_as_uint(ta[i][4 * j]), __float_as_uint(ta[i][4 * j + 1]),
                           __float_as_uint(ta[i][4 * j + 2]), __float_as_uint(ta[i][4 * j + 3]));
            };
            token_mma<0, 0, 16, 0, false>(ta, wr, 1);
            mbar_wait_bounded(bar + BAR_XG + 8, par);
            mbar_wait_bounded(bar + BAR_XG + 16, par);
            at_prefetch(true);
            token_mma<0, 16, 32, 0, true>(ta, wr, p.one[1]);
            token_mma<0, 0, 12, 1, false, false>(ta, wr, p.one[0]);
            token_mma<0, 12, 16, 1, true, false>(ta, wr, p.one[0]);
            mbar_wait_bounded(bar + BAR_XG + 24, par);
            asm volatile("wgmma.wait_group.sync.aligned 1;" ::: "memory");
            park(0, SM_PARK0);
            token_mma<0, 16, 32, 1, true>(ta, wr, 1);
            warp_arrive(bar + BAR_GO);
            mbar_wait_bounded(bar + BAR_PUB, par);
            const uint4 tp = lds128(bar + BAR_TPUB);
            const uint32_t tgo = tp.y + max(max((int)(tp.z - tp.y), (int)(tp.w - tp.y)), 0) + FETCH_DELAY;
            asm volatile("wgmma.wait_group.sync.aligned 0;" ::: "memory");
            park(1, SM_PARK1);
            warp_arrive(bar + BAR_PK);
            const uint8_t* src = xaddr(u_src + pub_slot(s), xhi);
            auto fetch = [&]() {
                if (elect_one()) {
                    mbar_arrive_expect_tx(bar + BAR_M + 8 * wq, 4096);
                    bulk_load(sb + SM_MEM + wq * 4096, src, 4096, bar + BAR_M + 8 * wq);
                }
            };
            while ((int)(clock_lo() - tgo) < 0) {}
            fetch();
            STAMP(12);
            if (warp == 0 && elect_one()) {
                if (qk) mbar_arrive_expect_tx(bar + BAR_V, 8192);
                mbar_arrive_expect_tx(bar + BAR_X, qk ? 1280 : 2560);
                mbar_arrive_expect_tx(bar + BAR_VM, qk ? 2048 : 0);
            }
            at_prefetch(false);
            const uint32_t x = fresh(l16) - sb;
            const uint32_t ca = sb + SM_MEM + wq * 4096 + x * 2 + ((x >> 4) & 0x1C);
            #pragma unroll 1
            for (uint32_t n = 0; n < POLL_LIMIT; n++) {
                mbar_wait_bounded(bar + BAR_M + 8 * wq, mphase);
                mphase ^= 1;
                const uint32_t c0 = lds32_volatile(ca), c1 = lds32_volatile(ca + 1024), c2 = lds32_volatile(ca + 2048), c3 = lds32_volatile(ca + 3072);
                if (!__any_sync(~0u, max(max3(c0, c1, c2), c3) == SENT)) break;
                fetch();
            }
            STAMP(0);
            named_bar_sync(10, 128);
            #pragma unroll
            for (int u = 0; u < 2; u++) ldsm4t(l16 + SM_MEM + u * 512, b[u]);
            if (!(u_role & 8) || s == NSEG - 1) {
                named_bar_sync(0, REC_THREADS);
            } else if (!qk) {
                const uint32_t d0 = mapa(sb + SM_V, 0), d1 = mapa(sb + SM_V, 1), b0 = mapa(bar + BAR_V, 0), b1 = mapa(bar + BAR_V, 1);
                named_bar_sync(0, REC_THREADS);
                const bool ok = mbar_test_wait(bar + BAR_VF, par);
                asm volatile("fence.proxy.async.shared::cta;" ::: "memory");
                if (!ok) mbar_wait_bounded(bar + BAR_VF, par);
                asm volatile("{\n.reg .pred p;\nelect.sync _|p, 0xFFFFFFFF;\n"
                             "@p cp.async.bulk.shared::cluster.shared::cta.mbarrier::complete_tx::bytes [%0], [%4], 8192, [%1];\n"
                             "@p cp.async.bulk.shared::cluster.shared::cta.mbarrier::complete_tx::bytes [%2], [%4], 8192, [%3];\nbar.warp.sync 0xFFFFFFFF;\n}"
                             ::"r"(d0), "r"(b0), "r"(d1), "r"(b1), "r"(sb + SM_V) : "memory");
            } else {
                named_bar_sync(0, REC_THREADS);
                mbar_wait_bounded(bar + BAR_F0, par);
                x_load(p, sb, s + 1, 0);
            }
        } else {
            at_prefetch(true);
            if (s > 0) {
                if (u_role & 1) {
                    const uint32_t ln = (fresh(l16) >> 4) & 31;
                    const uint32_t ibl = lds32_volatile(tbl + 12) + (par ^ 1) * XCHG_SLOT + ln * 8;
                    const uint32_t publ = lds32_volatile(tbl + 28) + pub_slot(s) + (ln & 16) * 256 + (ln & 8) * 16 + (ln & 7) * 4;
                    const bool odd = ln & 8;
                    const uint8_t* ib = xaddr(ibl + delay_zero<POLL_DELAY>(bar + BAR_SELF), xhi);
                    STAMP(8);
                    uint2 v[8];
                    #pragma unroll
                    for (int i = 0; i < 8; i++) v[i] = make_uint2(SENT, SENT);
                    #pragma unroll 1
                    for (uint32_t n = 0; n < POLL_LIMIT; n++) {
                        sfor<0, 8>([&](auto I) { repoll_v2<I.value * 256>(v[I.value], ib); });
                        const uint32_t mx = max(max3(v[0].y, v[1].y, v[2].y), max3(max3(v[3].y, v[4].y, v[5].y), v[6].y, v[7].y));
                        if (!__any_sync(~0u, mx == SENT)) break;
                    }
                    STAMP(9);
                    const float a0 = ((bf16_lo(v[0].x) + bf16_lo(v[1].x)) + (bf16_lo(v[2].x) + bf16_lo(v[3].x))) +
                                     ((bf16_lo(v[4].x) + bf16_lo(v[5].x)) + (bf16_lo(v[6].x) + bf16_lo(v[7].x)));
                    const float a1 = ((bf16_hi(v[0].x) + bf16_hi(v[1].x)) + (bf16_hi(v[2].x) + bf16_hi(v[3].x))) +
                                     ((bf16_hi(v[4].x) + bf16_hi(v[5].x)) + (bf16_hi(v[6].x) + bf16_hi(v[7].x)));
                    const float a2 = ((bf16_lo(v[0].y) + bf16_lo(v[1].y)) + (bf16_lo(v[2].y) + bf16_lo(v[3].y))) +
                                     ((bf16_lo(v[4].y) + bf16_lo(v[5].y)) + (bf16_lo(v[6].y) + bf16_lo(v[7].y)));
                    const float a3 = ((bf16_hi(v[0].y) + bf16_hi(v[1].y)) + (bf16_hi(v[2].y) + bf16_hi(v[3].y))) +
                                     ((bf16_hi(v[4].y) + bf16_hi(v[5].y)) + (bf16_hi(v[6].y) + bf16_hi(v[7].y)));
                    float k0 = odd ? a2 : a0, k1 = odd ? a3 : a1;
                    k0 += __shfl_xor_sync(~0u, odd ? a0 : a2, 8);
                    k1 += __shfl_xor_sync(~0u, odd ? a1 : a3, 8);
                    k0 += __shfl_xor_sync(~0u, k0, 16);
                    k1 += __shfl_xor_sync(~0u, k1, 16);
                    st_relaxed_b32(xaddr(publ, xhi), pack_bf16(k0, k1));
                    STAMP(11);
                } else if (warp == 4) {
                    bulk_wait_read_all();
                    if (elect_one()) remote_arrive(bar + BAR_F3, 2);
                    if (!qk) {
                        mbar_wait_bounded(bar + BAR_F3, par ^ 1);
                        x_load(p, sb, s, 3);
                    }
                    if (elect_one()) {
                        bulk_wait_all();
                        signal_bulk(p.flags + F_PROGRESS + s - 1);
                    }
                    __syncwarp();
                    STAMP(10);
                }
            }
            float ta[2][16];
            uint32_t w[8];
            auto unpark = [&](int i, uint32_t src) {
                mbar_wait_bounded(bar + (i ? BAR_GO : BAR_PK), par);
                #pragma unroll
                for (int j = 0; j < 4; j++) {
                    const uint4 v = lds128(l16 + src + j * 2048 + wq * 512);
                    ta[i][4 * j] = __uint_as_float(v.x); ta[i][4 * j + 1] = __uint_as_float(v.y);
                    ta[i][4 * j + 2] = __uint_as_float(v.z); ta[i][4 * j + 3] = __uint_as_float(v.w);
                }
            };
            sts32(bar + BAR_TPUB + 4 * wq, clock32());
            if (warp != 4) warp_arrive(bar + BAR_PUB);
            unpark(1, SM_PARK0);
            STAMP(6);
            token_mma<1, 0, 16, 1, true>(ta, wr, 1);
            unpark(0, SM_PARK1);
            token_mma<1, 16, 32, 1, true>(ta, wr, 1);
            token_mma<1, 16, 32, 0, true>(ta, wr, 1);
            token_mma<1, 0, 16, 0, true, false>(ta, wr, 1);
            auto put_tile = [&](int m, const uint32_t (&q)[8]) {
                #pragma unroll
                for (int h = 0; h < 2; h++) {
                    if (qk) asm volatile("stmatrix.sync.aligned.m8n8.x4.trans.shared.b16 [%0], {%1,%2,%3,%4};"
                                         ::"r"(aq - (SM_WQ + 32768) + (m ? SM_K : SM_QS) + h * 2048), "r"(q[4 * h]), "r"(q[4 * h + 1]),
                                           "r"(q[4 * h + 2]), "r"(q[4 * h + 3]) : "memory");
                    else sts128(l16 + SM_V + wq * 2048 + m * 1024 + h * 512, q[4 * h], q[4 * h + 1], q[4 * h + 2], q[4 * h + 3]);
                }
            };
            auto pack_tile = [&](int i) {
                #pragma unroll
                for (int e = 0; e < 16; e++) asm volatile("" : "+f"(ta[i][e]));
                #pragma unroll
                for (int j = 0; j < 8; j++) w[j] = pack_bf16(ta[i][2 * j], ta[i][2 * j + 1]);
            };
            asm volatile("wgmma.wait_group.sync.aligned 2;" ::: "memory");
            pack_tile(1);
            at_prefetch(false);
            asm volatile("wgmma.wait_group.sync.aligned 1;" ::: "memory");
            if (u_role & 32) {
                const uint32_t a_free = lds32_volatile(tbl + 60);
                if (elect_one()) asm volatile("mbarrier.arrive.relaxed.cluster.shared::cluster.b64 _, [%0];" ::"r"(a_free) : "memory");
            }
            put_tile(0, w);
            asm volatile("wgmma.wait_group.sync.aligned 0;" ::: "memory");
            pack_tile(0);
            put_tile(1, w);
            STAMP(0);
            named_bar_sync(0, REC_THREADS);
            #pragma unroll
            for (int u = 0; u < 2; u++) ldsm4t(l16 + SM_MEM + 8192 + u * 512, b[u]);
            if (s == NSEG - 1) att_stores(true, false);
            STAMP(14);
        }
        const uint32_t mb = l16 + SM_MEM + wg * 8192;
        float acc[2][2][4];
        {
            #pragma unroll
            for (int i = 0; i < 4; i++)
                if (!at_early(i)) ldsm4t(aq + (i & 1) * 16384 + (i >> 1) * 2048, at[i]);
            STAMPD(1, b[0][0]);
            #pragma unroll
            for (int i = 0; i < 4; i++) { for (int e = 0; e < 4; e++) acc[i >> 1][i & 1][e] = 0.f; }
            #pragma unroll
            for (int u = 0; u < 16; u++) {
                #pragma unroll
                for (int h = 0; h < 2; h++) {
                    const int j = 2 * u + h;
                    #pragma unroll
                    for (int m = 0; m < 2; m++) {
                        if ((j & 3) == 0) mma_a(acc[h][m], at[(j >> 2) * 2 + m], b[u][2 * h], b[u][2 * h + 1]);
                        else mma_a(acc[h][m], wr[reg_idx(j)][m], b[u][2 * h], b[u][2 * h + 1]);
                    }
                }
                #pragma unroll
                for (int v = u + 2 + (u > 2); v <= u + 2 + (u >= 2); v++)
                    if (v < 16) ldsm4t(mb + v * 512, b[v]);
                #pragma unroll
                for (int i = u + 4 + 2 * (u > 6); i <= u + 4 + 2 * (u >= 6); i++)
                    if (i < 16 && !at_early(i)) ldsm4t(aq + (i & 1) * 16384 + (i >> 1) * 2048, at[i]);
            }
        }
        sts128(l16 + SM_RED + warp * 512, __float_as_uint(acc[0][1][0] + acc[1][1][0]), __float_as_uint(acc[0][1][1] + acc[1][1][1]),
               __float_as_uint(acc[0][1][2] + acc[1][1][2]), __float_as_uint(acc[0][1][3] + acc[1][1][3]));
        #pragma unroll
        for (int e = 0; e < 4; e++) acc[0][0][e] += acc[1][0][e];
        const uint32_t x16 = fresh(l16);
        const uint32_t sa = fresh((x16 & 0x70) * 8 + ((((x16 >> 3) & 0x30) ^ x16) & 0x70));
        const uint32_t sq = fresh(sa ^ ((((x16 >> 7) ^ (x16 >> 8)) & 1) * 0x30));
        const uint32_t x8 = (x16 & 0x1F0) >> 1;
        const uint32_t ast = fresh(fresh(aq) - wg * (32768 - 1024)) + (SM_QK - SM_WQ);
        const uint32_t xra = fresh(x8 + __byte_perm(u_xa, u_bra, 0x7210)), xrb = fresh(x8 + __byte_perm(u_xa, u_brb, 0x7210));
        STAMP(2);
        named_bar_sync(1 + wq, 64);
        uint32_t p0, p1;
        {
            const uint4 v = lds128(l16 + SM_RED + (warp ^ 4) * 512);
            p0 = pack_bf16(acc[0][0][0] + __uint_as_float(v.x), acc[0][0][1] + __uint_as_float(v.y));
            p1 = pack_bf16(acc[0][0][2] + __uint_as_float(v.z), acc[0][0][3] + __uint_as_float(v.w));
        }
        auto send = [&](uint32_t y0, uint32_t y1) {
            st_async_v2(xra, y0, y1, u_bra);
            st_async_v2(xrb, y0, y1, u_brb);
            sts64(x8 + u_xa, y0, y1);
            warp_arrive(u_bx);
        };
        if (qk) {
            asm volatile("stmatrix.sync.aligned.m8n8.x2.trans.shared.b16 [%0], {%1,%2};" ::"r"(ast), "r"(p0), "r"(p1) : "memory");
            named_bar_sync(5, REC_THREADS);
            if (u_key != 0) {
                uint32_t qa[2][4], kf[2][4];
                ldsm4(sq + sb + SM_QK, qa[0]);
                ldsm4(sa + u_key, kf[0]);
                ldsm4((sq ^ 64) + sb + SM_QK, qa[1]);
                ldsm4((sa ^ 64) + u_key, kf[1]);
                float se[4] = {0.f, 0.f, 0.f, 0.f}, so[4] = {0.f, 0.f, 0.f, 0.f};
                #pragma unroll
                for (int u = 0; u < 2; u++) {
                    mma_a(se, qa[u], kf[u][0], kf[u][1]);
                    mma_a(so, qa[u], kf[u][2], kf[u][3]);
                }
                send(__float_as_uint(se[0] + so[2]), __float_as_uint(se[1] + so[3]));
            }
        } else if (!V_FIRST || !(u_role & 2) || s == NSEG - 1) {
            send(p0, p1);
        }
        STAMP(3);
        const uint32_t lane = (fresh(l16) >> 4) & 31;
        if (((s + 1) & 62) == 0) {
            if (s == NSEG - 1) { att_stores(false, true); break; }
            mbar_wait_bounded(bar + BAR_WO, 0);
            pdl_launch_dependents();
            PSTAMP(8);
        }
        const uint32_t slot = par * XCHG_SLOT;
        if (u_role & 2) {
            if (qk) mbar_wait_bounded(bar + BAR_V, par);
            uint32_t vt[2][4][4];
            auto v_load = [&](int i0, int i1) {
                #pragma unroll
                for (int i = i0; i < i1; i++) {
                    const uint4 v = lds128(l16 + SM_V + (warp & 1) * 1024 + (i & 3) * 2048 + (i >> 2) * 512);
                    vt[i >> 2][i & 3][0] = v.x; vt[i >> 2][i & 3][1] = v.y; vt[i >> 2][i & 3][2] = v.z; vt[i >> 2][i & 3][3] = v.w;
                }
            };
            v_load(0, V_EARLY);
            if (V_FIRST && !qk) send(p0, p1);
            const uint32_t l8 = fresh(sb + lane * 8);
            mbar_wait_bounded(bar + BAR_X, par);
            STAMP(4);
            float sv[10];
            #pragma unroll
            for (int j = 0; j < 5; j++) {
                const uint2 a = lds64(l8 + SM_SP + j * 256), b = lds64(l8 + SM_SP + 1280 + j * 256);
                sv[2 * j] = __uint_as_float(a.x) + __uint_as_float(b.x);
                sv[2 * j + 1] = __uint_as_float(a.y) + __uint_as_float(b.y);
            }
            float mx = fmaxf(fmaxf(fmaxf(sv[0], sv[1]), fmaxf(sv[2], sv[3])), fmaxf(fmaxf(sv[4], sv[5]), fmaxf(sv[6], sv[7])));
            mx = fmaxf(mx, fmaxf(sv[8], sv[9]));
            const float m1 = __shfl_xor_sync(~0u, mx, 1), m2 = __shfl_xor_sync(~0u, mx, 2), m3 = __shfl_xor_sync(~0u, mx, 3);
            __syncwarp();
            v_load(V_EARLY, 8);
            const bool vm_ok = mbar_test_wait(bar + BAR_VM, par);
            mx = fmaxf(fmaxf(mx, m1), fmaxf(m2, m3));
            const float mo = mx * sl2;
            #pragma unroll
            for (int j = 0; j < 10; j++) sv[j] = ex2(fmaf(sv[j], sl2, -mo));
            const uint32_t e0 = pack_bf16(sv[0], sv[1]), e1 = pack_bf16(sv[2], sv[3]);
            const uint32_t e2 = pack_bf16(sv[4], sv[5]), e3 = pack_bf16(sv[6], sv[7]), em = pack_bf16(sv[8], sv[9]);
            float o[4][4];
            #pragma unroll
            for (int i = 0; i < 4; i++) {
                o[i][0] = o[i][1] = o[i][2] = o[i][3] = 0.f;
                mma_a(o[i], vt[0][i], e0, e1);
            }
            const float sum = (((sv[0] + sv[1]) + (sv[2] + sv[3])) + ((sv[4] + sv[5]) + (sv[6] + sv[7]))) + (sv[8] + sv[9]);
            if (!vm_ok) mbar_wait_bounded(bar + BAR_VM, par);
            uint2 vm[4];
            #pragma unroll
            for (int i = 0; i < 4; i++) {
                vm[i] = lds64(l8 + SM_VM + (warp & 1) * 1024 + i * 256);
                mma_a(o[i], vt[1][i], e2, e3);
            }
            #pragma unroll
            for (int i = 0; i < 4; i++) mma1688(o[i], vm[i].x, vm[i].y, em);
            {
                const float s1 = __shfl_xor_sync(~0u, sum, 1), s2 = __shfl_xor_sync(~0u, sum, 2), s3 = __shfl_xor_sync(~0u, sum, 3);
                sts32(sb + SM_SUM + (lane & 28), __float_as_uint((sum + s1) + (s2 + s3)));
            }
            #pragma unroll
            for (int i = 0; i < 4; i += 2)
                stsm_x4(l16 + SM_O + (warp & 1) * 1024 + i * 256, pack_bf16(o[i][0], o[i][1]), pack_bf16(o[i][2], o[i][3]),
                        pack_bf16(o[i + 1][0], o[i + 1][1]), pack_bf16(o[i + 1][2], o[i + 1][3]));
            STAMP(5);
            uint32_t st[16][4];
            named_bar_sync(6, REC_THREADS);
            wo_phase<2, 0>(st, ao, 0, l16, tbl, sb + SM_SUM, slot, xhi, 0, bar + BAR_XG, par ^ 1, x0_ok, wg, p.one[0] - 1, aq);
        } else {
            const uint32_t a3 = fresh(ao) + (wg == 0 ? 10 : 6) * 8192;
            uint32_t st[24][4];
            #pragma unroll
            for (int n = 0; n < WO_PFA; n++) wo_load<3>(ao, a3, n, u_role & 4, st[n], SKIP3 & 2);
            if (u_role & 1) {
                const uint32_t ln = (fresh(l16) >> 4) & 31;
                uint8_t* ib = xaddr(lds32_volatile(tbl + 12) + (par ^ 1) * XCHG_SLOT + ln * 16, xhi);
                #pragma unroll
                for (int i = 0; i < 4; i++) st_relaxed_v4(ib + i * 512, SENT);
                st_relaxed_b32(xaddr(lds32_volatile(tbl + 28) + pub_slot(s + 3) + (ln & 16) * 256 + (ln & 8) * 16 + (ln & 7) * 4, xhi), SENT);
            }
            if (warp == 1) {
                if (elect_one()) {
                    #pragma unroll
                    for (int g = 0; g < 4; g++) mbar_arrive_expect_tx(bar + BAR_XG + 8 * g, 16384);
                }
                if (s + 2 < NSEG && cta < 4 && elect_one())
                    asm volatile("cp.async.bulk.prefetch.tensor.3d.L2.global [%0, {%1, %2, %3}];"
                                 ::"l"(&p.tmX), "r"(0), "r"((s + 2) * SEG), "r"(cta * 4) : "memory");
            }
            mbar_wait_bounded(bar + BAR_X, par);
            { const uint32_t t0 = clock_lo(); while (clock_lo() - t0 < WO_PFB_DELAY) {} }
            #pragma unroll
            for (int n = WO_PFA; n < WO_PF; n++) wo_load<3>(ao, a3, n, u_role & 4, st[n], SKIP3 & 2);
            att_stores(true, true);
            if (u_role & 16) {
                mbar_wait_bounded(bar + BAR_VM, par);
                x_load(p, sb, s + 1, rank);
            }
            named_bar_sync(6, REC_THREADS);
            wo_phase<3, WO_PF>(st, ao, a3, l16, tbl, sb + SM_SUM, slot, xhi, u_role & 4, bar + BAR_XG, par ^ 1, x0_ok, wg, p.one[0] - 1, aq);
        }
        STAMP(7);
        if (wg == 0) named_bar_sync(9, REC_THREADS);
    }
    if (threadIdx.x == 128) KMARK(8);
    if (warp == 4) {
        if (elect_one()) {
            asm volatile("cp.async.bulk.wait_group 1;" ::: "memory");
            signal_bulk(p.flags + F_LASTTOK);
            bulk_wait_all();
            signal_bulk(p.flags + F_PROGRESS + NSEG - 1);
            KMARK(9);
        }
    } else if (warp == 0) {
        mbar_wait(bar + BAR_X, 1);
        mbar_wait(bar + BAR_VM, 1);
        if (rank != 1) mbar_wait(bar + (qk ? BAR_F0 : BAR_VF), 1);
    }
}

__global__ void __launch_bounds__(REC_THREADS, 1) rec_kernel(const __grid_constant__ RecParams p) {
    extern __shared__ __align__(1024) uint8_t smem_raw[];
    const uint32_t sb = smem_u32(smem_raw);
    const int tid = threadIdx.x, lane = tid & 31;
    const int warp = __shfl_sync(~0u, tid >> 5, 0);
    const int cta = blockIdx.x, head = cta / 3, rank = cta % 3;
    const int wg = warp >> 2, wq = warp & 3;
    const uint32_t bar = sb + SM_BAR;
    uint8_t* const xb = p.xchg;
    const uint32_t xlo = (uint32_t)(uint64_t)xb;
    if ((sb & 0x3FFFF) != SMEM_ORIGIN) __trap();
    KENTER(1);
    auto w_box = [&](int part, int g, int i, uint32_t dst, uint32_t mb) {
        const int m = i ^ g;
        const CUtensorMap* tm = &p.tmW[rank == 2 ? 2 : m];
        const int col = head * DH + (rank == 2 ? m : rank) * 64, row = ((part + 1) & 3) * 16;
        tma_load_3d(dst, tm, col, row, g * 8, mb);
    };
    if (tid == 0) {
        mbar_init(bar + BAR_V, 1);
        for (int i = 0; i < 4; i++) { mbar_init(bar + BAR_XG + 8 * i, 1); mbar_init(bar + BAR_M + 8 * i, 1); }
        mbar_init(bar + BAR_GO, 4);
        mbar_init(bar + BAR_PUB, 3);
        mbar_init(bar + BAR_PK, 4);
        mbar_init(bar + BAR_VM, rank < 2 ? 1 : 9);
        mbar_init(bar + BAR_F0, 3);
        mbar_init(bar + BAR_F3, 3);
        mbar_init(bar + BAR_VF, 3);
        sts64(bar + BAR_MIN, ~0u, ~0u);
        mbar_init(bar + BAR_X, rank < 2 ? 6 : 1);
        for (int i = 0; i < 3; i++) mbar_init(bar + BAR_P0 + 8 * i, 1);
        mbar_init(bar + BAR_WQ, 1);
        mbar_init(bar + BAR_WO, 1);
        sts32(bar + BAR_SELF, bar + BAR_SELF);
        asm volatile("fence.mbarrier_init.release.cluster;" ::: "memory");
    }
    auto build_tables = [&](uint32_t av) {
        for (uint32_t n = 0; !__all_sync(~0u, (av >> 24) == 24); n++) {
            av = ld_acquire_b32(p.arrivals + (lane & 3));
            if (n > SPIN_LIMIT) __trap();
        }
        uint32_t cm[3];
        #pragma unroll
        for (int i = 0; i < 3; i++) {
            const int o = i * 32 + lane;
            cm[i] = __ballot_sync(~0u, __popc((__shfl_sync(~0u, av, o / 24) >> (o % 24 / 3 * 3)) & 7) >= 2);
        }
        auto color_of = [&](int o) { return ((o < 32 ? cm[0] : o < 64 ? cm[1] : cm[2]) >> (o & 31)) & 1u; };
        auto inbox = [&](int o, int byte) {
            uint32_t c = color_of(o);
            int ones = 0;
            #pragma unroll
            for (int i = 0; i < 3; i++) ones += __popc(o >= i * 32 + 32 ? cm[i] : (o > i * 32 ? cm[i] & ((1u << (o - i * 32)) - 1) : 0u));
            int idx = c ? ones : o - ones;
            if (idx >= INBOX_MAX) { idx = 2 * INBOX_MAX - 1 - idx; c ^= 1; }
            const uint32_t lin = idx * 6144 + byte, q = XCHG_INBOX + (lin >> 12) * 8192;
            return q + class_off(xlo + q, c) + (lin & 4095);
        };
        uint32_t off = 0;
        const int grp = (warp + 3) & 3;
        if (lane < 12) {
            const int i = lane >> 2, lt0 = rank * 6;
            const int o = i < 2 ? rank * 32 + warp * 4 + (lane & 3) : (lt0 + ((warp + 4) & 7)) * 4 + (lane & 3);
            off = inbox(min(o, 95), i * 2048 + head * 64);
        } else if (lane == 12) {
            off = inbox(cta, (grp % 3) * 2048);
        } else if (lane == 13) {
            int T;
            if (grp < 2) {
                T = (cta >> 5) * 22 + 8 * grp + ((cta & 31) >> 2);
            } else {
                const int tl = (cta & 63) >> 2;
                T = (tl / 6) * 22 + 16 + tl % 6;
            }
            off = XCHG_PUB + (T >> 4) * 8192 + (T & 15) * 256 + (cta & 3) * 32;
        } else if (lane == 14) {
            const uint32_t q = XCHG_PUB + wq * 8192;
            off = q + class_off(xlo + q, color_of(cta));
        }
        if (lane == 15) off = mapa(bar + (warp == 5 ? BAR_VF : BAR_F0), warp == 5 ? 2 : 0) - xlo;
        if (lane < 16) asm volatile("st.shared.b32 [%0], %1;" ::"r"(sb + SM_TBL + warp * 64 + (lane & 3) * 16 + (lane >> 2) * 4), "r"(xlo + off) : "memory");
    };
    if (tid >= 32 && tid < 37) asm volatile("prefetch.tensormap [%0];" ::"l"(&p.tmW[0] + (tid - 32)) : "memory");
    if (cta == 0) for (int i = tid; i < F_COUNT; i += REC_THREADS) p.flags[i] = 0;
    __syncthreads();
    auto stage = [](int part) { return ((part + 2) % 3) * 65536; };
    auto load_part = [&](int part) {
        mbar_arrive_expect_tx(bar + BAR_P0 + 8 * part, 65536);
        for (int u = 0; u < 4; u++) w_box(part, u >> 1, u & 1, sb + stage(part) + u * 16384, bar + BAR_P0 + 8 * part);
    };
    asm volatile("barrier.cluster.arrive.relaxed.aligned;" ::: "memory");
    uint4 img = make_uint4(SENT, SENT, SENT, SENT);
    if (cta >= 92) {
        const unsigned short* m = reinterpret_cast<const unsigned short*>(p.mem0) + (cta - 92) * 256 + tid;
        uint32_t w[4];
        #pragma unroll
        for (int i = 0; i < 4; i++) w[i] = (uint32_t)__ldg(m + 2 * i * DM) | ((uint32_t)__ldg(m + (2 * i + 1) * DM) << 16);
        img = make_uint4(w[0], w[1], w[2], w[3]);
    }
    {
        constexpr int NPAIR = (XCHG_SLOT + PUB_BYTES) / 8192;
        uint8_t* pr = xb + (4 + cta) * 8192;
        const uint32_t c0 = class_off(xlo + (4 + cta) * 8192, 0);
        #pragma unroll
        for (int c = 0; c < 2; c++) {
            const bool timed = lane == 0 || (lane == 8 && c == (warp & 1));
            reinterpret_cast<uint4*>(pr + (c0 ^ (c << 12)))[tid] = make_uint4(timed ? 0u : SENT, SENT, SENT, SENT);
        }
        __syncwarp();
        if (lane == 0) {
            uint32_t x = 0;
            for (int k = 0; k < 3; k++) {
                if (k == 0 && warp == 0) load_part(0);
                const uint32_t c = (k + warp) & 1, t0 = clock_after(x);
                x = atomicExch(reinterpret_cast<uint32_t*>(pr + (c0 ^ (c << 12)) + warp * 512 + (k >> 1) * 128 + x), SENT);
                const uint32_t lat = clock_after(x) - t0;
                asm volatile("red.shared.min.u32 [%0], %1;" ::"r"(bar + BAR_MIN + 4 * c), "r"(lat) : "memory");
            }
        }
        __syncwarp();
        if (cta >= 92 || 100 + cta < NPAIR) {
            if (cta >= 92) {
                if (img.x == SENT) img.x = 0x7FFF7FFFu;
                if (img.y == SENT) img.y = 0x7FFF7FFFu;
                if (img.z == SENT) img.z = 0x7FFF7FFFu;
                if (img.w == SENT) img.w = 0x7FFF7FFFu;
            }
            uint8_t* q = xb + (cta >= 92 ? cta - 92 : 100 + cta) * 8192;
            reinterpret_cast<uint4*>(q)[tid] = img;
            reinterpret_cast<uint4*>(q + 4096)[tid] = img;
        }
    }
    __syncthreads();
    PSTAMP(4);
    if (tid == 0) {
        for (int part = 1; part < 3; part++) load_part(part);
    }
    if (tid == 224) {
        const uint32_t c = lds32_volatile(bar + BAR_MIN) > lds32_volatile(bar + BAR_MIN + 4) ? 1 : 0;
        asm volatile("red.release.gpu.global.add.u32 [%0], %1;" ::"l"(p.arrivals + cta / 24), "r"((1u << 24) | (c << (cta % 24))) : "memory");
    }
    uint32_t wr[NREG][2][4];
    uint32_t arrived = 0;
    {
        const int mi = lane >> 3, r8 = lane & 7;
        const uint32_t a0 = sb + wg * 32768 + ((mi >> 1) * 8 + r8) * 128 + (((wq * 2 + (mi & 1)) ^ r8) << 4);
        #pragma unroll
        for (int part = 0; part < 3; part++) {
            mbar_wait_bounded(bar + BAR_P0 + 8 * part, 0);
            if (part == 0) arrived = ld_relaxed_b32(p.arrivals + (lane & 3));
            #pragma unroll
            for (int j = 0; j < 8; j++) {
                #pragma unroll
                for (int i = 0; i < 2; i++) ldsm4t(a0 + stage(part) + i * 16384 + j * 2048, wr[part * 8 + j][i]);
            }
            asm volatile("fence.proxy.async.shared::cta;" ::: "memory");
            __syncthreads();
            PSTAMP(5 + part);
            if (tid == 0) {
                if (part == 0) {
                    for (int g = 0; g < 4; g++) {
                        mbar_arrive_expect_tx(bar + BAR_XG + 8 * g, 16384);
                        tma_load_3d(sb + SM_X + g * 16384, &p.tmX, 0, 0, g * 4, bar + BAR_XG + 8 * g);
                    }
                } else if (part == 1) {
                    mbar_arrive_expect_tx(bar + BAR_WQ, 65536);
                    for (int u = 0; u < 4; u++) w_box(3, u >> 1, u & 1, sb + SM_WQ + u * 16384, bar + BAR_WQ);
                } else {
                    mbar_arrive_expect_tx(bar + BAR_WO, 11 * 8192);
                    tma_load_3d(sb + SM_WO, &p.tmWo, 0, head * DH, rank * 11, bar + BAR_WO);
                    if (cta < 4)
                        asm volatile("cp.async.bulk.prefetch.tensor.3d.L2.global [%0, {%1, %2, %3}];"
                                     ::"l"(&p.tmX), "r"(0), "r"(SEG), "r"(cta * 4) : "memory");
                }
            }
        }
    }
    build_tables(arrived);
    if (tid == 64) {
        uint32_t smid;
        asm volatile("mov.u32 %0, %%smid;" : "=r"(smid));
        if (smid < 384) atomicOr(p.flags + F_RECSM + (smid >> 5), 1u << (smid & 31));
    }
    __syncwarp();
    PSTAMP(9);
    mbar_wait(bar + BAR_WQ, 0);
    asm volatile("barrier.cluster.wait.aligned;" ::: "memory");

    rec_steps(p, wr, sb, warp, cta, head, rank);
    if (cta == 0 && tid < 4) p.arrivals[tid] = 0;
    if (tid == 128) KEXIT(1);
}

constexpr int ATT_SLOT = 28672;
constexpr int ATT_PAIRS = 8;
constexpr int ATT_BAR = ATT_PAIRS * ATT_SLOT;
constexpr int ATT_SMEM = ATT_BAR + ATT_PAIRS * 16;
constexpr int ATT_THREADS = ATT_PAIRS * 64;
struct AttnParams {
    CUtensorMap tmOa;
    CUtensorMap tmQb, tmKb;
    CUtensorMap tmOb;
    const __nv_bfloat16* qkv_tok;
    const __nv_bfloat16* kv_mem;
    uint32_t* flags;
};

__device__ __forceinline__ void tok_attn_warp(uint32_t base, int mh, int lane) {
    const uint32_t sq = base, sk = base + 8192, sv = base + 16384, skm = base + 24576, svm = skm + 2048;
    const int g = lane >> 2, c = lane & 3, mi = lane >> 3, r8 = lane & 7;
    const int ntile = mh ? 5 : 3;
    float sc[5][4];
    #pragma unroll
    for (int j = 0; j < 5; j++) { sc[j][0] = sc[j][1] = sc[j][2] = sc[j][3] = 0.f; }
    #pragma unroll
    for (int t2 = 0; t2 < 4; t2++) {
        uint32_t a[2][4];
        #pragma unroll
        for (int h = 0; h < 2; h++) {
            const int row = mh * 16 + (mi & 1) * 8 + r8, ch16 = 4 * t2 + 2 * h + (mi >> 1);
            ldsm_x4(sq + (ch16 >> 3) * 4096 + row * 128 + (((ch16 & 7) ^ r8) << 4), a[h][0], a[h][1], a[h][2], a[h][3]);
        }
        const int ch16 = 4 * t2 + mi;
        uint32_t b[5][4];
        #pragma unroll
        for (int j = 0; j < 5; j++) {
            if (j < ntile) {
                if (j == 0) ldsm_x4(skm + (ch16 >> 3) * 1024 + r8 * 128 + (((ch16 & 7) ^ r8) << 4), b[j][0], b[j][1], b[j][2], b[j][3]);
                else ldsm_x4(sk + (ch16 >> 3) * 4096 + ((j - 1) * 8 + r8) * 128 + (((ch16 & 7) ^ r8) << 4), b[j][0], b[j][1], b[j][2], b[j][3]);
            }
        }
        #pragma unroll
        for (int h = 0; h < 2; h++) {
            #pragma unroll
            for (int j = 0; j < 5; j++)
                if (j < ntile) mma16816(sc[j], a[h][0], a[h][1], a[h][2], a[h][3], b[j][2 * h], b[j][2 * h + 1]);
        }
    }
    const float sl2 = 0.08838834764831845f * 1.4426950408889634f;
    uint32_t pf[2][5];
    float inv[2];
    #pragma unroll
    for (int q = 0; q < 2; q++) {
        const int tok = mh * 16 + q * 8 + g;
        float v[10];
        #pragma unroll
        for (int j = 0; j < 5; j++) {
            #pragma unroll
            for (int e = 0; e < 2; e++) {
                const int key = (j - 1) * 8 + 2 * c + e;
                v[2 * j + e] = (j == 0 || key <= tok) ? sc[j][2 * q + e] : -INFINITY;
            }
        }
        float mx = v[0];
        #pragma unroll
        for (int j = 1; j < 10; j++) mx = fmaxf(mx, v[j]);
        mx = fmaxf(mx, __shfl_xor_sync(~0u, mx, 1));
        mx = fmaxf(mx, __shfl_xor_sync(~0u, mx, 2));
        const float mo = mx * sl2;
        float sum = 0.f;
        #pragma unroll
        for (int j = 0; j < 10; j++) { v[j] = ex2(fmaf(v[j], sl2, -mo)); sum += v[j]; }
        sum += __shfl_xor_sync(~0u, sum, 1);
        sum += __shfl_xor_sync(~0u, sum, 2);
        inv[q] = rcp(sum);
        #pragma unroll
        for (int j = 0; j < 5; j++) pf[q][j] = pack_bf16(v[2 * j], v[2 * j + 1]);
    }
    auto load_v = [&](int n4, uint32_t (&vm)[4], uint32_t (&vt)[4][4]) {
        const uint2 va = lds64(svm + n4 * 512 + lane * 8), vb = lds64(svm + n4 * 512 + 256 + lane * 8);
        vm[0] = va.x; vm[1] = va.y; vm[2] = vb.x; vm[3] = vb.y;
        #pragma unroll
        for (int u = 0; u < 4; u++) {
            const int dt = 2 * n4 + (u >> 1), kh = u & 1;
            const uint4 v = lds128(sv + (dt & 3) * 2048 + (dt >> 2) * 1024 + kh * 512 + lane * 16);
            vt[u & 2][2 * kh] = v.x; vt[u & 2][2 * kh + 1] = v.z;
            vt[(u & 2) + 1][2 * kh] = v.y; vt[(u & 2) + 1][2 * kh + 1] = v.w;
        }
    };
    uint32_t vm[2][4], vt[2][4][4];
    load_v(0, vm[0], vt[0]);
    #pragma unroll
    for (int n4 = 0; n4 < 4; n4++) {
        const int cur = n4 & 1;
        if (n4 + 1 < 4) load_v(n4 + 1, vm[cur ^ 1], vt[cur ^ 1]);
        float o[4][4];
        #pragma unroll
        for (int u = 0; u < 4; u++) {
            o[u][0] = o[u][1] = o[u][2] = o[u][3] = 0.f;
            mma16816(o[u], pf[0][1], pf[1][1], pf[0][2], pf[1][2], vt[cur][u][0], vt[cur][u][1]);
        }
        if (mh) {
            #pragma unroll
            for (int u = 0; u < 4; u++) mma16816(o[u], pf[0][3], pf[1][3], pf[0][4], pf[1][4], vt[cur][u][2], vt[cur][u][3]);
        }
        #pragma unroll
        for (int u = 0; u < 4; u++) mma1688(o[u], pf[0][0], pf[1][0], vm[cur][u]);
        #pragma unroll
        for (int u = 0; u < 4; u += 2) {
            const int row = mh * 16 + (mi & 1) * 8 + r8, nt = 4 * n4 + u + (mi >> 1);
            stsm_x4(sq + (nt >> 3) * 4096 + row * 128 + (((nt & 7) ^ r8) << 4),
                    pack_bf16(o[u][0] * inv[0], o[u][1] * inv[0]), pack_bf16(o[u][2] * inv[1], o[u][3] * inv[1]),
                    pack_bf16(o[u + 1][0] * inv[0], o[u + 1][1] * inv[0]), pack_bf16(o[u + 1][2] * inv[1], o[u + 1][3] * inv[1]));
        }
    }
}

__device__ __forceinline__ void b_attn_warp(uint32_t base, int hl, int idx0, int lane) {
    const uint32_t sq = base, sk = base + 8192, sv = base + 8192 + 9216;
    const int g = lane >> 2, c = lane & 3;
    auto addr = [&](uint32_t t, int row, int ch) { return t + row * 128 + ((ch ^ (row & 7)) << 4); };
    const float sl2 = 0.17677669529663687f * 1.4426950408889634f;
    #pragma unroll 2
    for (int blk = 0; blk < 4; blk++) {
        const int r0 = blk * 16;
        float sc[3][4];
        #pragma unroll
        for (int j = 0; j < 3; j++) { sc[j][0] = sc[j][1] = sc[j][2] = sc[j][3] = 0.f; }
        #pragma unroll
        for (int t = 0; t < 2; t++) {
            uint32_t a0, a1, a2, a3, b0, b1, b2, b3, d0, d1, d2, d3;
            const int mi = lane >> 3, r = lane & 7;
            ldsm_x4(addr(sq, r0 + (mi & 1) * 8 + r, hl * 4 + 2 * t + (mi >> 1)), a0, a1, a2, a3);
            ldsm_x4(addr(sk, r0 + (mi >> 1) * 8 + r, hl * 4 + 2 * t + (mi & 1)), b0, b1, b2, b3);
            ldsm_x4(addr(sk, r0 + 16 + r, hl * 4 + 2 * t + (mi & 1)), d0, d1, d2, d3);
            mma16816(sc[0], a0, a1, a2, a3, b0, b1);
            mma16816(sc[1], a0, a1, a2, a3, b2, b3);
            mma16816(sc[2], a0, a1, a2, a3, d0, d1);
        }
        uint32_t pf[2][3];
        float inv[2];
        #pragma unroll
        for (int r = 0; r < 2; r++) {
            const int u = r * 8 + g;
            float v[6];
            #pragma unroll
            for (int j = 0; j < 3; j++) {
                #pragma unroll
                for (int e = 0; e < 2; e++) {
                    const int key = j * 8 + 2 * c + e;
                    const bool ok = key > u && key <= u + 8 && idx0 + r0 - 8 + key >= 0;
                    v[2 * j + e] = ok ? sc[j][2 * r + e] : -INFINITY;
                }
            }
            float mx = fmaxf(fmaxf(fmaxf(v[0], v[1]), fmaxf(v[2], v[3])), fmaxf(v[4], v[5]));
            mx = fmaxf(mx, __shfl_xor_sync(~0u, mx, 1));
            mx = fmaxf(mx, __shfl_xor_sync(~0u, mx, 2));
            const float mo = mx * sl2;
            float sum = 0.f;
            #pragma unroll
            for (int j = 0; j < 6; j++) { v[j] = ex2(fmaf(v[j], sl2, -mo)); sum += v[j]; }
            sum += __shfl_xor_sync(~0u, sum, 1);
            sum += __shfl_xor_sync(~0u, sum, 2);
            inv[r] = rcp(sum);
            #pragma unroll
            for (int j = 0; j < 3; j++) pf[r][j] = pack_bf16(v[2 * j], v[2 * j + 1]);
        }
        uint32_t ow[4][2];
        {
            const int mi = lane >> 3, r = lane & 7;
            uint32_t vv[4][4];
            #pragma unroll
            for (int nt = 0; nt < 4; nt++)
                ldsm_x4_t(addr(sv, r0 + min(mi, 2) * 8 + r, hl * 4 + nt), vv[nt][0], vv[nt][1], vv[nt][2], vv[nt][3]);
            float o[4][4];
            #pragma unroll
            for (int nt = 0; nt < 4; nt++) {
                o[nt][0] = o[nt][1] = o[nt][2] = o[nt][3] = 0.f;
                mma16816(o[nt], pf[0][0], pf[1][0], pf[0][1], pf[1][1], vv[nt][0], vv[nt][1]);
            }
            #pragma unroll
            for (int nt = 0; nt < 4; nt++) mma1688(o[nt], pf[0][2], pf[1][2], vv[nt][2]);
            #pragma unroll
            for (int nt = 0; nt < 4; nt++) {
                ow[nt][0] = pack_bf16(o[nt][0] * inv[0], o[nt][1] * inv[0]);
                ow[nt][1] = pack_bf16(o[nt][2] * inv[1], o[nt][3] * inv[1]);
            }
        }
        #pragma unroll
        for (int u = 0; u < 4; u += 2) {
            const int mi = lane >> 3, r = lane & 7;
            stsm_x4(addr(sq, r0 + (mi & 1) * 8 + r, hl * 4 + u + (mi >> 1)), ow[u][0], ow[u][1], ow[u + 1][0], ow[u + 1][1]);
        }
    }
}

constexpr uint32_t QKVB_TARGET = 12 * 8;
constexpr uint32_t PROGRESS_TARGET = 96;
constexpr uint32_t OA_TARGET = 64, OB_TARGET = 32;
#define ATT_B0 8
#define ATT_BSTEP 2
constexpr int ATT_TASKS = (NSEG + 16) * 32;
static_assert(ATT_B0 + 16 * ATT_BSTEP <= NSEG, "order of the task groups");
__device__ __forceinline__ int att_group(int g, bool& isb) {
    constexpr int P = ATT_BSTEP + 1;
    const int q = g - ATT_B0;
    isb = q >= 0 && q < 16 * P && q % P == 0;
    return q < 0 ? g : q >= 16 * P ? g - 16 : isb ? q / P : g - q / P - 1;
}

__global__ void __launch_bounds__(ATT_THREADS, 1) attn_kernel(const __grid_constant__ AttnParams p) {
    extern __shared__ __align__(1024) uint8_t smem_raw[];
    const int tid = threadIdx.x, lane = tid & 31, warp = __shfl_sync(~0u, tid >> 5, 0);
    const int pair = warp >> 1, wi = warp & 1;
    const uint32_t base = smem_u32(smem_raw) + pair * ATT_SLOT, bar = smem_u32(smem_raw) + ATT_BAR + pair * 16;
    const bool leader = wi == 0 && lane == 0;
    if (tid == 0) pdl_launch_dependents();
    KENTER(3);
    uint32_t phase = 0;
    if (leader) {
        mbar_init(bar, 1);
        asm volatile("fence.mbarrier_init.release.cluster;" ::: "memory");
    }
    uint32_t* pending = nullptr;
    auto flush = [&]() {
        if (pending) {
            bulk_wait_all();
            signal_bulk(pending);
            if (pending == p.flags + F_OA + NSEG - 1) KMARK(14);
            pending = nullptr;
        }
    };
    int ready_a = -1, ready_b = -1;
    for (int task = pair * gridDim.x + blockIdx.x; task < ATT_TASKS; task += ATT_PAIRS * gridDim.x) {
        bool isb;
        const int grp = att_group(task >> 5, isb), i = task & 31;
        named_bar_sync(1 + pair, 64);
        if (leader) {
            {
                auto need = [&](const uint32_t* f, uint32_t target) {
                    if (ld_acquire_b32(f) < target) { flush(); wait_flag(f, target); }
                };
                if (isb) {
                    if (grp > ready_b) {
                        need(p.flags + F_QKVB + grp, QKVB_TARGET);
                        if (grp > 0) need(p.flags + F_QKVB + grp - 1, QKVB_TARGET);
                        asm volatile("fence.proxy.async.global;" ::: "memory");
                        ready_b = grp;
                    }
                    mbar_arrive_expect_tx(bar, 8192 + 2 * 9216);
                    tma_load_3d(base, &p.tmQb, (i >> 1) * 64, i & 1, grp * 64, bar);
                    tma_load_3d(base + 8192, &p.tmKb, DM + (i >> 1) * 64, i & 1, grp * 64 - 8, bar);
                    tma_load_3d(base + 8192 + 9216, &p.tmKb, 2 * DM + (i >> 1) * 64, i & 1, grp * 64 - 8, bar);
                } else {
                    if (grp > ready_a) {
                        need(p.flags + (grp == NSEG - 1 ? F_LASTTOK : F_PROGRESS + grp), PROGRESS_TARGET);
                        asm volatile("fence.proxy.async.global;" ::: "memory");
                        ready_a = grp;
                    }
                    if (grp == 63) KMARK(10);
                    mbar_arrive_expect_tx(bar, ATT_SLOT);
                    #pragma unroll
                    for (int w = 0; w < 3; w++)
                        bulk_load(base + w * 8192, p.qkv_tok + (((size_t)w * NSEG + grp) * NH + i) * (SEG * DH), 8192, bar);
                    if (grp == NSEG - 1) {
                        need(p.flags + F_PROGRESS + grp, PROGRESS_TARGET);
                        asm volatile("fence.proxy.async.global;" ::: "memory");
                    }
                    #pragma unroll
                    for (int w = 0; w < 2; w++)
                        bulk_load(base + 24576 + w * 2048, p.kv_mem + (((size_t)w * NSEG + grp) * NH + i) * (MROWS * DH), 2048, bar);
                }
            }
        }
        if (lane == 0) flush();
        __syncwarp();
        mbar_wait_sleep(bar, phase);
        phase ^= 1;
        if (isb) {
            b_attn_warp(base, wi, grp * 64, lane);
            asm volatile("fence.proxy.async.shared::cta;" ::: "memory");
            named_bar_sync(1 + pair, 64);
            if (wi == 1 && lane == 0) {
                asm volatile("cp.async.bulk.tensor.3d.global.shared::cta.bulk_group [%0, {%2, %3, %4}], [%1];"
                             ::"l"(&p.tmOb), "r"(base), "r"((i >> 1) * 64), "r"(i & 1), "r"(grp * 64) : "memory");
                pending = p.flags + F_OB + grp;
            }
        } else {
            if (grp == 63 && lane == 0) KMARK(11);
            tok_attn_warp(base, wi, lane);
            if (grp == 63 && lane == 0) KMARK(12);
            asm volatile("fence.proxy.async.shared::cta;" ::: "memory");
            __syncwarp();
            if (lane == 0) {
                #pragma unroll
                for (int h = 0; h < 2; h++) tma_store_2d(&p.tmOa, base + h * 4096 + wi * 2048, i * DH + h * 64, grp * SEG + wi * 16);
                pending = p.flags + F_OA + grp;
            }
        }
        if (lane == 0) { bulk_commit(); bulk_wait_read_all(); }
        __syncwarp();
    }
    if (lane == 0) { flush(); KEXIT(3); }
}

typedef CUresult (*EncodeFn)(CUtensorMap*, CUtensorMapDataType, cuuint32_t, void*, const cuuint64_t*, const cuuint64_t*,
                             const cuuint32_t*, const cuuint32_t*, CUtensorMapInterleave, CUtensorMapSwizzle,
                             CUtensorMapL2promotion, CUtensorMapFloatOOBfill);

void make_map_2d(EncodeFn enc, CUtensorMap* m, const void* ptr, uint64_t rows, uint64_t cols, uint32_t box_rows) {
    cuuint64_t dims[2] = {cols, rows};
    cuuint64_t strides[1] = {cols * 2};
    cuuint32_t box[2] = {64, box_rows};
    cuuint32_t es[2] = {1, 1};
    enc(m, CU_TENSOR_MAP_DATA_TYPE_BFLOAT16, 2, const_cast<void*>(ptr), dims, strides, box, es,
        CU_TENSOR_MAP_INTERLEAVE_NONE, CU_TENSOR_MAP_SWIZZLE_128B, CU_TENSOR_MAP_L2_PROMOTION_L2_256B,
        CU_TENSOR_MAP_FLOAT_OOB_FILL_NONE);
}
void make_map_b(EncodeFn enc, CUtensorMap* m, const void* ptr, uint64_t k, uint64_t n, uint32_t nblk, uint32_t box_rows = 64,
                uint32_t bc = 64) {
    cuuint64_t dims[3] = {bc, k, n / bc};
    cuuint64_t strides[2] = {n * 2, bc * 2};
    cuuint32_t box[3] = {bc, box_rows, nblk};
    cuuint32_t es[3] = {1, 1, 1};
    enc(m, CU_TENSOR_MAP_DATA_TYPE_BFLOAT16, 3, const_cast<void*>(ptr), dims, strides, box, es,
        CU_TENSOR_MAP_INTERLEAVE_NONE, bc == 64 ? CU_TENSOR_MAP_SWIZZLE_128B : CU_TENSOR_MAP_SWIZZLE_64B, CU_TENSOR_MAP_L2_PROMOTION_L2_256B,
        CU_TENSOR_MAP_FLOAT_OOB_FILL_NONE);
}

void make_map_parity(EncodeFn enc, CUtensorMap* m, const void* ptr, uint64_t cols, uint32_t box_rows) {
    cuuint64_t dims[3] = {cols, 2, S_TOK / 2};
    cuuint64_t strides[2] = {cols * 2, cols * 4};
    cuuint32_t box[3] = {64, 1, box_rows};
    cuuint32_t es[3] = {1, 1, 1};
    enc(m, CU_TENSOR_MAP_DATA_TYPE_BFLOAT16, 3, const_cast<void*>(ptr), dims, strides, box, es,
        CU_TENSOR_MAP_INTERLEAVE_NONE, CU_TENSOR_MAP_SWIZZLE_128B, CU_TENSOR_MAP_L2_PROMOTION_L2_128B,
        CU_TENSOR_MAP_FLOAT_OOB_FILL_NONE);
}
void make_map_w(EncodeFn enc, CUtensorMap* m, const void* ptr) {
    cuuint64_t dims[3] = {HD, 64, DM / 64};
    cuuint64_t strides[2] = {HD * 2, 64 * HD * 2};
    cuuint32_t box[3] = {64, 16, 8};
    cuuint32_t es[3] = {1, 1, 1};
    enc(m, CU_TENSOR_MAP_DATA_TYPE_BFLOAT16, 3, const_cast<void*>(ptr), dims, strides, box, es,
        CU_TENSOR_MAP_INTERLEAVE_NONE, CU_TENSOR_MAP_SWIZZLE_128B, CU_TENSOR_MAP_L2_PROMOTION_L2_256B,
        CU_TENSOR_MAP_FLOAT_OOB_FILL_NONE);
}

#define SIDE_ORDER 0
#define SERIAL_ATT_CTAS h.n_sm
#define N_TAIL_CTAS 28
#define N_SIDE_CTAS 28
#define N_ATT_CTAS 8
#define TAIL_BLOCK0 11

#define TAIL_SPARE 2
#define TAIL_KB2 30
#define TAIL_KB3 20
#define TAIL_BLOCK1 13
#define TAIL_BLOCK2 14

struct HostState {
    bool ready;
    bool overlap;
    int n_side, n_att, n_sm;
    SideParams seq_a, seq_b;
    const void* key[11];
    RecParams rec;
    SideParams side, tail;
    FinalParams fin;
    AttnParams attn;
    __nv_bfloat16 *qkv_tok, *kv_mem, *o_tok, *qkv_b, *o_b;
    uint8_t* xchg;
};
HostState g_host;

void setup(void* const* d_in, void* d_out) {
    HostState& h = g_host;
    void* fn = nullptr;
    cudaDriverEntryPointQueryResult qr;
    cudaGetDriverEntryPoint("cuTensorMapEncodeTiled", &fn, cudaEnableDefault, &qr);
    EncodeFn enc = reinterpret_cast<EncodeFn>(fn);
    void* ptr;
    cudaGetSymbolAddress(&ptr, g_qkv_tok); h.qkv_tok = (__nv_bfloat16*)ptr;
    cudaGetSymbolAddress(&ptr, g_kv_mem);  h.kv_mem = (__nv_bfloat16*)ptr;
    cudaGetSymbolAddress(&ptr, g_o_tok);   h.o_tok = (__nv_bfloat16*)ptr;
    cudaGetSymbolAddress(&ptr, g_qkv_b);   h.qkv_b = (__nv_bfloat16*)ptr;
    cudaGetSymbolAddress(&ptr, g_o_b);     h.o_b = (__nv_bfloat16*)ptr;
    cudaGetSymbolAddress(&ptr, g_xchg);    h.xchg = (uint8_t*)(((uint64_t)ptr + XCHG_BYTES - 1) & ~(uint64_t)(XCHG_BYTES - 1));
    cudaGetSymbolAddress(&ptr, g_flags);   uint32_t* flags = (uint32_t*)ptr;
    cudaGetSymbolAddress(&ptr, g_arrivals); uint32_t* arrivals = (uint32_t*)ptr;

    const void *xa = d_in[0], *mem0 = d_in[1], *wq = d_in[2], *wk = d_in[3], *wv = d_in[4], *wo = d_in[5];
    const void *xb = d_in[7], *wqkv = d_in[8], *wob = d_in[9];

    RecParams& r = h.rec;
    make_map_w(enc, &r.tmW[0], wq);
    make_map_w(enc, &r.tmW[1], wk);
    make_map_w(enc, &r.tmW[2], wv);
    make_map_b(enc, &r.tmWo, wo, HD, DM, 11, 128, 32);
    r.mem0 = (const __nv_bfloat16*)mem0;
    r.qkv_tok = h.qkv_tok; r.kv_mem = h.kv_mem; r.xchg = h.xchg;
    r.flags = flags; r.arrivals = arrivals; r.one[0] = r.one[1] = 1;
    make_map_b(enc, &r.tmX, xa, S_TOK, DM, 4, SEG);

    SideParams& sd = h.side;
    SideProb& p0 = sd.prob[0];
    make_map_2d(enc, &p0.tmA, xb, S_TOK, DM, BM);
    make_map_b(enc, &p0.tmB, wqkv, DM, 3 * DM, 4);
    make_map_2d(enc, &p0.tmC, h.qkv_b, S_TOK, 3 * DM, 16);
    p0.n_tiles = 3 * DM / 256; p0.k_blocks = DM / BK; p0.c_col0 = 0; p0.dep = nullptr; p0.dep_target = 0; p0.dep_n = 1; p0.sig = flags + F_QKVB;
    SideProb& p1 = sd.prob[1];
    make_map_2d(enc, &p1.tmA, h.o_tok, S_TOK, HD, BM);
    make_map_b(enc, &p1.tmB, wo, HD, DM, 4);
    make_map_2d(enc, &p1.tmC, d_out, S_TOK, 2 * DM, 16);
    p1.n_tiles = DM / 256; p1.k_blocks = HD / BK; p1.c_col0 = 0; p1.dep = flags + F_OA; p1.dep_target = OA_TARGET; p1.dep_n = 4; p1.sig = nullptr;
    SideProb& p2 = sd.prob[2];
    make_map_2d(enc, &p2.tmA, h.o_b, S_TOK, DM, BM);
    make_map_b(enc, &p2.tmB, wob, DM, DM, 4);
    p2.tmC = p1.tmC;
    p2.n_tiles = DM / 256; p2.k_blocks = DM / BK; p2.c_col0 = DM; p2.dep = flags + F_OB; p2.dep_target = OB_TARGET; p2.dep_n = 1; p2.sig = nullptr;
    p0.n_split = p0.n_tiles; p1.n_split = p1.n_tiles; p2.n_split = p2.n_tiles;
    p0.part = p1.part = p2.part = nullptr;
    p0.k_total = p0.k_blocks; p1.k_total = p1.k_blocks; p2.k_total = p2.k_blocks;
    if (SIDE_ORDER == 0) { sd.seg[0] = {0, 0, 16}; sd.seg[1] = {1, 0, TAIL_BLOCK0}; }
    else { sd.seg[0] = {1, 0, TAIL_BLOCK0}; sd.seg[1] = {0, 0, 16}; }
    sd.seg[2] = {2, 0, 16};
    sd.nseg = 3; sd.queue = flags + F_SIDEQ; sd.spare_seg = 3; sd.flags = flags;

    SideParams& tl = h.tail;
    tl.prob[0] = p1;
    make_map_b(enc, &tl.prob[0].tmB, wo, HD, DM, 2);
    cudaGetSymbolAddress(&ptr, g_part);
    for (int i = 0; i < 3; i++) {
        SideProb& q = tl.prob[i];
        q = tl.prob[0];
        q.n_tiles = (i + 1) * DM / 128; q.n_split = DM / 128; q.k_blocks = i == 0 ? HD / BK : i == 1 ? TAIL_KB2 : TAIL_KB3;
        q.part = i ? (float*)ptr : nullptr; q.part_flag = flags + F_PART;
    }
    tl.seg[0] = {0, TAIL_BLOCK0, TAIL_BLOCK1};
    tl.seg[1] = {1, TAIL_BLOCK1, TAIL_BLOCK2};
    tl.seg[2] = {2, TAIL_BLOCK2, 15};
    tl.nseg = 3; tl.queue = flags + F_TAILQ; tl.spare_seg = TAIL_SPARE; tl.flags = flags;

    make_map_2d(enc, &h.fin.tmA, h.o_tok, S_TOK, HD, SEG);
    h.fin.tmB = tl.prob[0].tmB; h.fin.out = (__nv_bfloat16*)d_out;
    h.fin.dep = flags + F_OA + 60; h.fin.dep_target = OA_TARGET; h.fin.mt = 15;

    make_map_2d(enc, &h.attn.tmOa, h.o_tok, S_TOK, HD, 16);
    make_map_parity(enc, &h.attn.tmQb, h.qkv_b, 3 * DM, 64);
    make_map_parity(enc, &h.attn.tmKb, h.qkv_b, 3 * DM, 72);
    make_map_parity(enc, &h.attn.tmOb, h.o_b, DM, 64);
    h.attn.qkv_tok = h.qkv_tok; h.attn.kv_mem = h.kv_mem; h.attn.flags = flags;

    int dev = 0, nsm = 0;
    cudaGetDevice(&dev);
    cudaDeviceGetAttribute(&nsm, cudaDevAttrMultiProcessorCount, dev);
    h.n_sm = nsm;
    h.overlap = nsm - 96 >= N_SIDE_CTAS + N_ATT_CTAS;
    h.n_side = N_SIDE_CTAS; h.n_att = N_ATT_CTAS;
    h.seq_a = sd;
    h.seq_a.seg[0] = {0, 0, 16};
    h.seq_a.nseg = 1;
    h.seq_b = sd;
    h.seq_b.seg[0] = {1, 0, 16};
    h.seq_b.seg[1] = {2, 0, 16};
    h.seq_b.nseg = 2; h.seq_b.queue = flags + F_TAILQ;

    cudaFuncSetAttribute(side_gemm_kernel<256>, cudaFuncAttributeMaxDynamicSharedMemorySize, GemmCfg<256>::SMEM);
    cudaFuncSetAttribute(side_gemm_kernel<128>, cudaFuncAttributeMaxDynamicSharedMemorySize, GemmCfg<128>::SMEM);
    cudaFuncSetAttribute(final_gemm_kernel, cudaFuncAttributeMaxDynamicSharedMemorySize, FIN_SMEM);
    cudaFuncSetAttribute(rec_kernel, cudaFuncAttributeMaxDynamicSharedMemorySize, REC_SMEM);
    cudaFuncSetAttribute(attn_kernel, cudaFuncAttributeMaxDynamicSharedMemorySize, ATT_SMEM);
    for (int i = 0; i < 10; i++) h.key[i] = d_in[i];
    h.key[10] = d_out;
    h.ready = true;
}

template <typename K, typename P>
void launch(K kernel, int grid, int block, int smem, cudaStream_t st, const P& prm, int cluster, bool pdl) {
    cudaLaunchConfig_t cfg = {};
    cfg.gridDim = dim3(grid); cfg.blockDim = dim3(block); cfg.dynamicSmemBytes = smem; cfg.stream = st;
    cudaLaunchAttribute at[2];
    int n = 0;
    if (cluster > 1) {
        at[n].id = cudaLaunchAttributeClusterDimension;
        at[n].val.clusterDim.x = cluster; at[n].val.clusterDim.y = 1; at[n].val.clusterDim.z = 1;
        n++;
    }
    if (pdl) {
        at[n].id = cudaLaunchAttributeProgrammaticStreamSerialization;
        at[n].val.programmaticStreamSerializationAllowed = 1;
        n++;
    }
    cfg.attrs = at; cfg.numAttrs = n;
    cudaLaunchKernelEx(&cfg, kernel, prm);
}

}

extern "C" void kernel_launch(void* const* d_in, const int* in_sizes, int n_in, void* d_out, int out_size) {
    HostState& h = g_host;
    bool same = h.ready;
    for (int i = 0; same && i < 10; i++) same = h.key[i] == d_in[i];
    if (!same || h.key[10] != d_out) setup(d_in, d_out);
    cudaStream_t st = cudaStreamPerThread;

    launch(rec_kernel, 96, REC_THREADS, REC_SMEM, st, h.rec, 3, false);
    {
        if (!h.overlap) {
            launch(side_gemm_kernel<256>, h.n_sm, 384, GemmCfg<256>::SMEM, st, h.seq_a, 1, false);
            launch(attn_kernel, SERIAL_ATT_CTAS, ATT_THREADS, ATT_SMEM, st, h.attn, 1, false);
            launch(side_gemm_kernel<256>, h.n_sm, 384, GemmCfg<256>::SMEM, st, h.seq_b, 1, false);
            return;
        }
    }
    launch(side_gemm_kernel<256>, h.n_side, 384, GemmCfg<256>::SMEM, st, h.side, 1, true);
    launch(attn_kernel, h.n_att, ATT_THREADS, ATT_SMEM, st, h.attn, 1, true);
    launch(side_gemm_kernel<128>, N_TAIL_CTAS, 384, GemmCfg<128>::SMEM, st, h.tail, 1, true);
    launch(final_gemm_kernel, 8 * FIN_SPLIT, 384, FIN_SMEM, st, h.fin, FIN_SPLIT, true);
}
```
